```python
import torch

def _softmax(x, axis=-1):
    return torch.softmax(x, dim=axis)
def _gelu(x):
    return torch.nn.functional.gelu(x, approximate="tanh")
def _silu(x):
    return torch.nn.functional.silu(x)
def _sigmoid(x):
    return torch.sigmoid(x)
def _layernorm(x, axis=-1, eps=1e-5):
    m = x.mean(dim=axis, keepdim=True)
    v = x.var(dim=axis, keepdim=True, unbiased=False)
    return (x - m) / torch.sqrt(v + eps)
def _scatter_add(tgt, idx, src, axis=0):
    return tgt.clone().index_add_(axis, idx, src)
def _segment_sum(src, seg, n):
    out = torch.zeros((n,) + src.shape[1:], dtype=src.dtype)
    return out.index_add_(0, seg, src)
def _pad(x, pw):
    flat = tuple(v for pair in reversed(pw) for v in pair)
    return torch.nn.functional.pad(x, flat)

kernel_name = 'parallel_sum__linear_attn_block__moe_arch_mod__prompt'

def setup_inputs():

    _w = (lambda a: (lambda t: t.to(torch.bfloat16) if t.is_floating_point() else t)(torch.as_tensor(a)))
    def _A_setup():
        B, S, D = 1, 2048, 1024
        return {
            "x": _w((lambda *s: torch.randn(*s, dtype=torch.bfloat16) * 0.05)(B, S, D)),
            "wqkv": _w((lambda *s: torch.randn(*s, dtype=torch.bfloat16) * 0.4)(D, 3 * D)),
            "wo": _w((lambda *s: torch.randn(*s, dtype=torch.bfloat16) * 0.2)(D, D)),
        }
    _A_in = _A_setup()

    def _B_setup():
        B, S, D, F, C = 1, 2048, 1024, 3584, 8
        return {
            "x": _w((lambda *s: torch.randn(*s, dtype=torch.bfloat16) * 0.05)(B, S, D)),
            "w_r": _w((lambda *s: torch.randn(*s, dtype=torch.bfloat16) * 0.05)(D)),
            "w_gate": _w((lambda *s: torch.randn(*s, dtype=torch.bfloat16) * 0.05)(D, F)),
            "w_up": _w((lambda *s: torch.randn(*s, dtype=torch.bfloat16) * 0.05)(D, F)),
            "w_down": _w((lambda *s: torch.randn(*s, dtype=torch.bfloat16) * 0.05)(F, D)),
        }
    _B_in = _B_setup()

    return {
        "A_x": _A_in["x"],
        "A_wqkv": _A_in["wqkv"],
        "A_wo": _A_in["wo"],
        "B_x": _B_in["x"],
        "B_w_r": _B_in["w_r"],
        "B_w_gate": _B_in["w_gate"],
        "B_w_up": _B_in["w_up"],
        "B_w_down": _B_in["w_down"],
    }

def reference(A_x, A_wqkv, A_wo, B_x, B_w_r, B_w_gate, B_w_up, B_w_down):
    def _A_ref(x, wqkv, wo):
        B, S, D = x.shape
        H = 32; Dh = D // H
        qkv = (lambda x, *d: x.permute(*d))((x @ wqkv).reshape(B, S, 3, H, Dh), 2, 0, 3, 1, 4)
        q, k, v = qkv[0], qkv[1], qkv[2]
        phi = lambda t: torch.where(t > 0, t + 1, torch.exp(t)) + 1e-6
        pq, pk = phi(q), phi(k)
        kv = torch.einsum("bhsd,bhse->bhde", pk, v)
        z = torch.einsum("bhsd->bhd", pk)
        num = torch.einsum("bhqd,bhde->bhqe", pq, kv)
        den = torch.einsum("bhqd,bhd->bhq", pq, z)[..., None] + 1e-6
        o = num / den
        return (lambda x, *d: x.permute(*d))(o, 0, 2, 1, 3).reshape(B, S, D) @ wo

    def _B_ref(x, w_r, w_gate, w_up, w_down):
        B, S, D = x.shape
        C = 8
        r = x @ w_r
        idx = torch.argsort(-r, axis=-1)[:, :C]
        idx_e = (lambda x, n, axis: torch.repeat_interleave(x, n, dim=axis))(idx.reshape(B, C, 1), D, axis=2)
        x_sel = (lambda x, i, axis: torch.take_along_dim(x, i, dim=axis))(x, idx_e, axis=1)
        g = _silu(x_sel @ w_gate)
        u = x_sel @ w_up
        y = (g * u) @ w_down
        r_sel = _sigmoid((lambda x, i, axis: torch.take_along_dim(x, i, dim=axis))(r, idx, axis=1))
        y = y * r_sel.reshape(B, C, 1)
        b_off = (torch.arange(B) * S).reshape(B, 1)
        flat_idx = (idx + b_off).reshape(B * C)
        zero = (x * 0.0).reshape(B * S, D)
        upd = _scatter_add(zero, flat_idx, y.reshape(B * C, D), axis=0)
        return x + upd.reshape(B, S, D)

    x = A_x
    xn = _layernorm(x, axis=-1)
    return x + _A_ref(xn, A_wqkv, A_wo) + _B_ref(xn, B_w_r, B_w_gate, B_w_up, B_w_down)
```

```cpp
#include <cuda_runtime.h>
#include <cuda.h>
#include <cuda_bf16.h>
#include <stdint.h>

namespace {

template <int TA, int TB>
__device__ __forceinline__ void wgmma_n8_ss(float (&d)[4], uint64_t da, uint64_t db, int sc) {
  asm volatile("{\n.reg .pred p;\nsetp.ne.b32 p, %6, 0;\n"
    "wgmma.mma_async.sync.aligned.m64n8k16.f32.bf16.bf16 {%0, %1, %2, %3}, %4, %5, p, 1, 1, %7, %8;\n}\n"
    : "+f"(d[0]), "+f"(d[1]), "+f"(d[2]), "+f"(d[3])
    : "l"(da), "l"(db), "r"(sc), "n"(TA), "n"(TB));
}
template <int TB>
__device__ __forceinline__ void wgmma_n40_rs(float (&d)[20], uint32_t a0, uint32_t a1, uint32_t a2, uint32_t a3, uint64_t db, int sc) {
  asm volatile("{\n.reg .pred p;\nsetp.ne.b32 p, %25, 0;\n"
    "wgmma.mma_async.sync.aligned.m64n40k16.f32.bf16.bf16 {%0, %1, %2, %3, %4, %5, %6, %7, %8, %9, %10, %11, %12, %13, %14, %15, %16, %17, %18, %19}, {%20,%21,%22,%23}, %24, p, 1, 1, %26;\n}\n"
    : "+f"(d[0]), "+f"(d[1]), "+f"(d[2]), "+f"(d[3]), "+f"(d[4]), "+f"(d[5]), "+f"(d[6]), "+f"(d[7]),
      "+f"(d[8]), "+f"(d[9]), "+f"(d[10]), "+f"(d[11]), "+f"(d[12]), "+f"(d[13]), "+f"(d[14]), "+f"(d[15]),
      "+f"(d[16]), "+f"(d[17]), "+f"(d[18]), "+f"(d[19])
    : "r"(a0), "r"(a1), "r"(a2), "r"(a3), "l"(db), "r"(sc), "n"(TB));
}
template <int TB>
__device__ __forceinline__ void wgmma_n64_rs(float (&d)[32], uint32_t a0, uint32_t a1, uint32_t a2, uint32_t a3, uint64_t db, int sc) {
  asm volatile("{\n.reg .pred p;\nsetp.ne.b32 p, %37, 0;\n"
    "wgmma.mma_async.sync.aligned.m64n64k16.f32.bf16.bf16 {%0, %1, %2, %3, %4, %5, %6, %7, %8, %9, %10, %11, %12, %13, %14, %15, %16, %17, %18, %19, %20, %21, %22, %23, %24, %25, %26, %27, %28, %29, %30, %31}, {%32,%33,%34,%35}, %36, p, 1, 1, %38;\n}\n"
    : "+f"(d[0]), "+f"(d[1]), "+f"(d[2]), "+f"(d[3]), "+f"(d[4]), "+f"(d[5]), "+f"(d[6]), "+f"(d[7]),
      "+f"(d[8]), "+f"(d[9]), "+f"(d[10]), "+f"(d[11]), "+f"(d[12]), "+f"(d[13]), "+f"(d[14]), "+f"(d[15]),
      "+f"(d[16]), "+f"(d[17]), "+f"(d[18]), "+f"(d[19]), "+f"(d[20]), "+f"(d[21]), "+f"(d[22]), "+f"(d[23]),
      "+f"(d[24]), "+f"(d[25]), "+f"(d[26]), "+f"(d[27]), "+f"(d[28]), "+f"(d[29]), "+f"(d[30]), "+f"(d[31])
    : "r"(a0), "r"(a1), "r"(a2), "r"(a3), "l"(db), "r"(sc), "n"(TB));
}
template <int TA, int TB>
__device__ __forceinline__ void wgmma_n128_ss(float (&d)[64], uint64_t da, uint64_t db, int sc) {
  asm volatile("{\n.reg .pred p;\nsetp.ne.b32 p, %66, 0;\n"
    "wgmma.mma_async.sync.aligned.m64n128k16.f32.bf16.bf16 {%0, %1, %2, %3, %4, %5, %6, %7, %8, %9, %10, %11, %12, %13, %14, %15, %16, %17, %18, %19, %20, %21, %22, %23, %24, %25, %26, %27, %28, %29, %30, %31, %32, %33, %34, %35, %36, %37, %38, %39, %40, %41, %42, %43, %44, %45, %46, %47, %48, %49, %50, %51, %52, %53, %54, %55, %56, %57, %58, %59, %60, %61, %62, %63}, %64, %65, p, 1, 1, %67, %68;\n}\n"
    : "+f"(d[0]), "+f"(d[1]), "+f"(d[2]), "+f"(d[3]), "+f"(d[4]), "+f"(d[5]), "+f"(d[6]), "+f"(d[7]),
      "+f"(d[8]), "+f"(d[9]), "+f"(d[10]), "+f"(d[11]), "+f"(d[12]), "+f"(d[13]), "+f"(d[14]), "+f"(d[15]),
      "+f"(d[16]), "+f"(d[17]), "+f"(d[18]), "+f"(d[19]), "+f"(d[20]), "+f"(d[21]), "+f"(d[22]), "+f"(d[23]),
      "+f"(d[24]), "+f"(d[25]), "+f"(d[26]), "+f"(d[27]), "+f"(d[28]), "+f"(d[29]), "+f"(d[30]), "+f"(d[31]),
      "+f"(d[32]), "+f"(d[33]), "+f"(d[34]), "+f"(d[35]), "+f"(d[36]), "+f"(d[37]), "+f"(d[38]), "+f"(d[39]),
      "+f"(d[40]), "+f"(d[41]), "+f"(d[42]), "+f"(d[43]), "+f"(d[44]), "+f"(d[45]), "+f"(d[46]), "+f"(d[47]),
      "+f"(d[48]), "+f"(d[49]), "+f"(d[50]), "+f"(d[51]), "+f"(d[52]), "+f"(d[53]), "+f"(d[54]), "+f"(d[55]),
      "+f"(d[56]), "+f"(d[57]), "+f"(d[58]), "+f"(d[59]), "+f"(d[60]), "+f"(d[61]), "+f"(d[62]), "+f"(d[63])
    : "l"(da), "l"(db), "r"(sc), "n"(TA), "n"(TB));
}
template <int TB>
__device__ __forceinline__ void wgmma_n128_rs(float (&d)[64], uint32_t a0, uint32_t a1, uint32_t a2, uint32_t a3, uint64_t db, int sc) {
  asm volatile("{\n.reg .pred p;\nsetp.ne.b32 p, %69, 0;\n"
    "wgmma.mma_async.sync.aligned.m64n128k16.f32.bf16.bf16 {%0, %1, %2, %3, %4, %5, %6, %7, %8, %9, %10, %11, %12, %13, %14, %15, %16, %17, %18, %19, %20, %21, %22, %23, %24, %25, %26, %27, %28, %29, %30, %31, %32, %33, %34, %35, %36, %37, %38, %39, %40, %41, %42, %43, %44, %45, %46, %47, %48, %49, %50, %51, %52, %53, %54, %55, %56, %57, %58, %59, %60, %61, %62, %63}, {%64,%65,%66,%67}, %68, p, 1, 1, %70;\n}\n"
    : "+f"(d[0]), "+f"(d[1]), "+f"(d[2]), "+f"(d[3]), "+f"(d[4]), "+f"(d[5]), "+f"(d[6]), "+f"(d[7]),
      "+f"(d[8]), "+f"(d[9]), "+f"(d[10]), "+f"(d[11]), "+f"(d[12]), "+f"(d[13]), "+f"(d[14]), "+f"(d[15]),
      "+f"(d[16]), "+f"(d[17]), "+f"(d[18]), "+f"(d[19]), "+f"(d[20]), "+f"(d[21]), "+f"(d[22]), "+f"(d[23]),
      "+f"(d[24]), "+f"(d[25]), "+f"(d[26]), "+f"(d[27]), "+f"(d[28]), "+f"(d[29]), "+f"(d[30]), "+f"(d[31]),
      "+f"(d[32]), "+f"(d[33]), "+f"(d[34]), "+f"(d[35]), "+f"(d[36]), "+f"(d[37]), "+f"(d[38]), "+f"(d[39]),
      "+f"(d[40]), "+f"(d[41]), "+f"(d[42]), "+f"(d[43]), "+f"(d[44]), "+f"(d[45]), "+f"(d[46]), "+f"(d[47]),
      "+f"(d[48]), "+f"(d[49]), "+f"(d[50]), "+f"(d[51]), "+f"(d[52]), "+f"(d[53]), "+f"(d[54]), "+f"(d[55]),
      "+f"(d[56]), "+f"(d[57]), "+f"(d[58]), "+f"(d[59]), "+f"(d[60]), "+f"(d[61]), "+f"(d[62]), "+f"(d[63])
    : "r"(a0), "r"(a1), "r"(a2), "r"(a3), "l"(db), "r"(sc), "n"(TB));
}

__device__ __align__(1024) __nv_bfloat16 g_xn[2048 * 1024];
__device__ __align__(1024) __nv_bfloat16 g_o[2048 * 1024];
__device__ __align__(128) float2 g_stats[2048];
__device__ __align__(128) uint32_t g_keys[2048];
__device__ __align__(128) float g_csum[16 * 1024];
__device__ __align__(128) float g_kv[33 * 1024];
__device__ __align__(128) __nv_bfloat16 g_h[8 * 3584];
__device__ __align__(128) float g_yp[8 * 8 * 1024];
__device__ __align__(128) uint32_t g_flagKV[128];
__device__ __align__(128) uint32_t g_flagO[256];
__device__ __align__(128) uint32_t g_flagH[128];
__device__ __align__(128) uint32_t g_flagY[128];
__device__ uint32_t g_epoch;

constexpr uint32_t NST = 5, SLOT = 32768;
constexpr uint32_t STG = 163840, AUX = 196608, FR = 212992, MISC = 229376, SMEM_BYTES = 232448;
constexpr uint32_t B_FULL = MISC, B_EMPTY = MISC + 40, B_XS = MISC + 80, B_WKB = MISC + 112, B_FR = MISC + 120,
                   B_XRES = MISC + 152, B_HOP = MISC + 160;
constexpr uint32_t S_EPOCH = MISC + 192, S_NCAND = MISC + 196, S_KEYS = MISC + 256, S_SEL = MISC + 320,
                   S_STAT = MISC + 384, S_KSTAT = MISC + 512, S_CSUM = MISC + 1536, S_XCH = MISC + 2048;
constexpr uint32_t KVB_P0 = AUX, KVB_Z = AUX + 4096, KVB_P1 = AUX + 5120, HOP = AUX + 9216;
enum { NB_KV = 1, NB_VQ = 2, NB_FRONT = 3, NB_FDONE = 4, NB_PK = 5, NB_KVB = 6, NB_WG1 = 7, NB_WG2 = 8, NB_XSEL = 9,
       NB_Y = 10, NB_ST = 11, NB_OWN0 = 12, NB_OWN1 = 13 };

constexpr float LOG2E = 1.4426950408889634f, LN2 = 0.6931471805599453f;

__device__ __forceinline__ void mbar_init(uint32_t b, uint32_t c) { asm volatile("mbarrier.init.shared::cta.b64 [%0], %1;" ::"r"(b), "r"(c) : "memory"); }
__device__ __forceinline__ void mbar_expect(uint32_t b, uint32_t n) { asm volatile("mbarrier.arrive.expect_tx.shared::cta.b64 _, [%0], %1;" ::"r"(b), "r"(n) : "memory"); }
__device__ __forceinline__ void mbar_arrive(uint32_t b) { asm volatile("mbarrier.arrive.shared::cta.b64 _, [%0];" ::"r"(b) : "memory"); }
__device__ __forceinline__ void mbar_wait(uint32_t b, uint32_t ph) {
  asm volatile("{\n.reg .pred p, q;\n.reg .u32 c;\nmov.u32 c, 0;\nLW:\nmbarrier.try_wait.parity.shared::cta.b64 p, [%0], %1;\n@p bra LD;\n"
               "add.u32 c, c, 1;\nsetp.lt.u32 q, c, 100000;\n@q bra LW;\ntrap;\nLD:\n}" ::"r"(b), "r"(ph) : "memory");
}
__device__ __forceinline__ void nb_sync(int id, int n) { asm volatile("bar.sync %0, %1;" ::"r"(id), "r"(n) : "memory"); }
__device__ __forceinline__ void nb_arrive(int id, int n) { asm volatile("bar.arrive %0, %1;" ::"r"(id), "r"(n) : "memory"); }
__device__ __forceinline__ void tma2d(uint32_t dst, const CUtensorMap* m, int c0, int c1, uint32_t bar) {
  asm volatile("cp.async.bulk.tensor.2d.shared::cluster.global.mbarrier::complete_tx::bytes [%0], [%1, {%3, %4}], [%2];"
               ::"r"(dst), "l"(m), "r"(bar), "r"(c0), "r"(c1) : "memory");
}
__device__ __forceinline__ void tma2d_ef(uint32_t dst, const CUtensorMap* m, int c0, int c1, uint32_t bar, uint64_t pol) {
  asm volatile("cp.async.bulk.tensor.2d.shared::cluster.global.mbarrier::complete_tx::bytes.L2::cache_hint [%0], [%1, {%3, %4}], [%2], %5;"
               ::"r"(dst), "l"(m), "r"(bar), "r"(c0), "r"(c1), "l"(pol) : "memory");
}
__device__ __forceinline__ void tma3d(uint32_t dst, const CUtensorMap* m, int c0, int c1, int c2, uint32_t bar) {
  asm volatile("cp.async.bulk.tensor.3d.shared::cluster.global.mbarrier::complete_tx::bytes [%0], [%1, {%3, %4, %5}], [%2];"
               ::"r"(dst), "l"(m), "r"(bar), "r"(c0), "r"(c1), "r"(c2) : "memory");
}
__device__ __forceinline__ void tma2d_store(const CUtensorMap* m, int c0, int c1, uint32_t src) {
  asm volatile("cp.async.bulk.tensor.2d.global.shared::cta.bulk_group [%0, {%2, %3}], [%1];" ::"l"(m), "r"(src), "r"(c0), "r"(c1) : "memory");
}
__device__ __forceinline__ void pf_map(const CUtensorMap* m) { asm volatile("prefetch.tensormap [%0];" ::"l"(m) : "memory"); }
__device__ __forceinline__ void wg_fence() { asm volatile("wgmma.fence.sync.aligned;" ::: "memory"); }
__device__ __forceinline__ void wg_commit() { asm volatile("wgmma.commit_group.sync.aligned;" ::: "memory"); }
template <int N> __device__ __forceinline__ void wg_wait() { asm volatile("wgmma.wait_group.sync.aligned %0;" ::"n"(N) : "memory"); }
template <int N> __device__ __forceinline__ void reg_fence(float (&a)[N]) {
#pragma unroll
  for (int i = 0; i < N; i++) asm volatile("" : "+f"(a[i])::"memory");
}
template <int N> __device__ __forceinline__ void reg_zero(float (&a)[N]) {
#pragma unroll
  for (int i = 0; i < N; i++) a[i] = 0.f;
}
__device__ __forceinline__ uint64_t mkdesc(uint32_t addr, uint32_t lbo, uint32_t sbo, uint32_t swz) {
  return (uint64_t)(addr >> 4) | ((uint64_t)(lbo >> 4) << 16) | ((uint64_t)(sbo >> 4) << 32) | ((uint64_t)swz << 62);
}
__device__ __forceinline__ void fence_async_smem() { asm volatile("fence.proxy.async.shared::cta;" ::: "memory"); }
__device__ __forceinline__ void fence_async_glob() { asm volatile("fence.proxy.async.global;" ::: "memory"); }
__device__ __forceinline__ void fence_acq() { asm volatile("fence.acquire.gpu;" ::: "memory"); }
__device__ __forceinline__ void bulk_store(void* dst, uint32_t src, uint32_t n) {
  asm volatile("cp.async.bulk.global.shared::cta.bulk_group [%0], [%1], %2;" ::"l"(dst), "r"(src), "r"(n) : "memory");
}
__device__ __forceinline__ void bulk_addf(void* dst, uint32_t src, uint32_t n) {
  asm volatile("cp.reduce.async.bulk.global.shared::cta.bulk_group.add.f32 [%0], [%1], %2;" ::"l"(dst), "r"(src), "r"(n) : "memory");
}
__device__ __forceinline__ void bulk_load(uint32_t dst, const void* src, uint32_t n, uint32_t bar) {
  asm volatile("cp.async.bulk.shared::cluster.global.mbarrier::complete_tx::bytes [%0], [%1], %2, [%3];" ::"r"(dst), "l"(src), "r"(n), "r"(bar) : "memory");
}
__device__ __forceinline__ void bulk_commit() { asm volatile("cp.async.bulk.commit_group;" ::: "memory"); }
__device__ __forceinline__ void bulk_wait_read() { asm volatile("cp.async.bulk.wait_group.read 0;" ::: "memory"); }
__device__ __forceinline__ void bulk_wait_done() {
  asm volatile("cp.async.bulk.wait_group 0;" ::: "memory");
}
__device__ __forceinline__ void st_relaxed(uint32_t* p, uint32_t v) { asm volatile("st.relaxed.gpu.global.u32 [%0], %1;" ::"l"(p), "r"(v) : "memory"); }
__device__ __forceinline__ uint32_t ld_relaxed(const uint32_t* p) { uint32_t v; asm volatile("ld.relaxed.gpu.global.u32 %0, [%1];" : "=r"(v) : "l"(p) : "memory"); return v; }
__device__ __forceinline__ uint4 ld_relaxed4(const uint32_t* p) {
  uint4 v; asm volatile("ld.relaxed.gpu.global.v4.u32 {%0,%1,%2,%3}, [%4];" : "=r"(v.x), "=r"(v.y), "=r"(v.z), "=r"(v.w) : "l"(p) : "memory"); return v;
}
__device__ __forceinline__ void poll_flag(const uint32_t* p, uint32_t e) {
  asm volatile("{\n.reg .pred p, q;\n.reg .u32 c, v;\nmov.u32 c, 0;\nLW:\nld.relaxed.gpu.global.u32 v, [%0];\nsetp.eq.u32 p, v, %1;\n@p bra LD;\n"
               "add.u32 c, c, 1;\nsetp.lt.u32 q, c, 1000000;\n@q bra LW;\ntrap;\nLD:\n}" ::"l"(p), "r"(e) : "memory");
}
__device__ __forceinline__ void spin_guard(int& c) {
  asm volatile("{\n.reg .pred q;\nadd.u32 %0, %0, 1;\nsetp.gt.u32 q, %0, 1000000;\n@q trap;\n}" : "+r"(c));
}
__device__ __forceinline__ uint4 lds128(uint32_t a) { uint4 v; asm volatile("ld.shared.v4.u32 {%0,%1,%2,%3}, [%4];" : "=r"(v.x), "=r"(v.y), "=r"(v.z), "=r"(v.w) : "r"(a)); return v; }
__device__ __forceinline__ float4 lds128f(uint32_t a) { float4 v; asm volatile("ld.shared.v4.f32 {%0,%1,%2,%3}, [%4];" : "=f"(v.x), "=f"(v.y), "=f"(v.z), "=f"(v.w) : "r"(a)); return v; }
__device__ __forceinline__ float2 lds64f(uint32_t a) { float2 v; asm volatile("ld.shared.v2.f32 {%0,%1}, [%2];" : "=f"(v.x), "=f"(v.y) : "r"(a)); return v; }
__device__ __forceinline__ uint32_t lds32(uint32_t a) { uint32_t v; asm volatile("ld.shared.u32 %0, [%1];" : "=r"(v) : "r"(a)); return v; }
__device__ __forceinline__ void sts128(uint32_t a, uint32_t x, uint32_t y, uint32_t z, uint32_t w) { asm volatile("st.shared.v4.u32 [%0], {%1,%2,%3,%4};" ::"r"(a), "r"(x), "r"(y), "r"(z), "r"(w) : "memory"); }
__device__ __forceinline__ void sts32(uint32_t a, uint32_t x) { asm volatile("st.shared.u32 [%0], %1;" ::"r"(a), "r"(x) : "memory"); }
__device__ __forceinline__ void stsm4(uint32_t a, uint32_t r0, uint32_t r1, uint32_t r2, uint32_t r3) {
  asm volatile("stmatrix.sync.aligned.m8n8.x4.shared.b16 [%0], {%1,%2,%3,%4};" ::"r"(a), "r"(r0), "r"(r1), "r"(r2), "r"(r3) : "memory");
}
__device__ __forceinline__ uint4 ldsm4(uint32_t a) {
  uint4 v; asm volatile("ldmatrix.sync.aligned.m8n8.x4.shared.b16 {%0,%1,%2,%3}, [%4];" : "=r"(v.x), "=r"(v.y), "=r"(v.z), "=r"(v.w) : "r"(a) : "memory"); return v;
}
__device__ __forceinline__ uint32_t pack(float lo, float hi) { uint32_t r; asm("cvt.rn.bf16x2.f32 %0, %1, %2;" : "=r"(r) : "f"(hi), "f"(lo)); return r; }
__device__ __forceinline__ float bf_lo(uint32_t w) { return __uint_as_float(w << 16); }
__device__ __forceinline__ float bf_hi(uint32_t w) { return __uint_as_float(w & 0xffff0000u); }
__device__ __forceinline__ float bf_round(float x) { return bf_lo(pack(x, x)); }
__device__ __forceinline__ float ex2(float x) { float v; asm("ex2.approx.ftz.f32 %0, %1;" : "=f"(v) : "f"(x)); return v; }
__device__ __forceinline__ float rcp(float x) { float v; asm("rcp.approx.ftz.f32 %0, %1;" : "=f"(v) : "f"(x)); return v; }
__device__ __forceinline__ float addsat(float a, float b) { float v; asm("add.sat.f32 %0, %1, %2;" : "=f"(v) : "f"(a), "f"(b)); return v; }
__device__ __forceinline__ float key_score(uint32_t key) { uint32_t u = key >> 16; u = (u & 0x8000u) ? (u & 0x7fffu) : (~u & 0xffffu); return __uint_as_float(u << 16); }
__device__ __forceinline__ int key_token(uint32_t key) { return 2047 - (int)((key >> 5) & 2047u); }

#define STAMP(id)
#define STAMP_IF(c, id)

template <bool TRANS>
__device__ __forceinline__ void mainloop(float (&a0)[64], float (&a1)[64], uint32_t base, int s, int ph, int handoff, bool leader) {
  int prev = -1;
#pragma unroll 1
  for (int kt = 0; kt < 16; kt++) {
    mbar_wait(base + B_FULL + 8 * s, ph);
    const uint32_t sa = base + s * SLOT;
    const uint64_t dw = mkdesc(sa, 8192, 1024, 1), dx = mkdesc(sa + 16384, 16, 1024, 1);
    wg_fence();
#pragma unroll
    for (int j = 0; j < 4; j++) {
      if (TRANS) {
        wgmma_n128_ss<1, 0>(a0, dw + j * 128, dx + j * 2, 1);
        wgmma_n128_ss<1, 0>(a1, dw + j * 128 + 512, dx + j * 2, 1);
      } else {
        wgmma_n128_ss<0, 1>(a0, dx + j * 2, dw + j * 128, 1);
        wgmma_n128_ss<0, 1>(a1, dx + j * 2 + 512, dw + j * 128, 1);
      }
    }
    wg_commit();
    if (handoff && kt == 15) nb_arrive(handoff, 256);
    wg_wait<1>();
    if (prev >= 0 && leader) mbar_arrive(base + B_EMPTY + 8 * prev);
    prev = s;
    if (++s == NST) { s = 0; ph ^= 1; }
  }
  wg_wait<0>();
  if (leader) mbar_arrive(base + B_EMPTY + 8 * prev);
  reg_fence(a0);
  reg_fence(a1);
}

__device__ __forceinline__ int out_kblock(int r, int tn) {
  if (r < 2) return 2 * tn + r;
  const int q = r - 2, half = q >= 7, pi = q - 7 * half;
  return 2 * (pi + (pi >= tn)) + half;
}

struct Maps {
  CUtensorMap wqkv, x, xn, o, wo, xs, gate, up, down, xns, out;
};

__global__ void __launch_bounds__(512, 1)
fused_kernel(const __grid_constant__ Maps mp, const __nv_bfloat16* __restrict__ w_r) {
  extern __shared__ __align__(1024) uint8_t smem_raw[];
  const uint32_t base = (uint32_t)__cvta_generic_to_shared(smem_raw);
  const int tid = threadIdx.x, lane = tid & 31;
  const int w = __shfl_sync(0xffffffffu, tid >> 5, 0);
  const int bid = blockIdx.x;
  const int tn = (bid & 3) + 4 * (bid >> 6), tm = (bid >> 2) & 15;

  if (tid == 384) {
    STAMP(0);
    pf_map(&mp.wqkv);
    pf_map(&mp.x);
#pragma unroll
    for (int s = 0; s < (int)NST; s++) { mbar_init(base + B_FULL + 8 * s, 2); mbar_init(base + B_EMPTY + 8 * s, 1); }
#pragma unroll
    for (int s = 0; s < 11; s++) mbar_init(base + B_XS + 8 * s, 1);
    sts32(base + S_NCAND, 0);
    asm volatile("fence.mbarrier_init.release.cluster;" ::: "memory");
#pragma unroll
    for (int s = 0; s < (int)NST; s++) {
      const uint32_t fb = base + B_FULL + 8 * s;
      mbar_expect(fb, 16384);
      tma3d(base + s * SLOT, &mp.wqkv, 0, s * 64, 16 + 2 * tn, fb);
      mbar_expect(fb, 16384);
      tma2d(base + s * SLOT + 16384, &mp.x, s * 64, tm * 128, fb);
    }
  }
  __syncthreads();

  if (w >= 12) {
    asm volatile("setmaxnreg.dec.sync.aligned.u32 40;");
    if (w == 12) {
      if (lane == 0) {
        int s = 0, ph = 0;
#pragma unroll 1
        for (int it = NST; it < 64; it++) {
          mbar_wait(base + B_EMPTY + 8 * s, ph);
          const uint32_t fb = base + B_FULL + 8 * s;
          mbar_expect(fb, 16384);
          if (it < 48) tma3d(base + s * SLOT, &mp.wqkv, 0, (it & 15) * 64, (it < 32 ? (it & 16) + 16 : 0) + 2 * tn, fb);
          else tma3d(base + s * SLOT, &mp.wo, 0, out_kblock(it - 48, tn) * 64, 2 * tn, fb);
          if (++s == NST) { s = 0; ph ^= 1; }
        }
      }
    } else if (w == 14) {
      const uint32_t ep = ld_relaxed(&g_epoch) + 1;
      int s = 0, ph = 0;
#pragma unroll 1
      for (int it = NST; it < 64; it++) {
        if (it == 16) {
          int c = 0;
          while (true) {
            const uint4 k = ld_relaxed4(g_keys + tm * 128 + lane * 4);
            const bool ok = (((k.x ^ ep) | (k.y ^ ep) | (k.z ^ ep) | (k.w ^ ep)) & 31u) == 0;
            if (__all_sync(0xffffffffu, ok)) break;
            spin_guard(c);
          }
          fence_acq();
          __syncwarp();
          fence_async_glob();
          STAMP_IF(lane == 0, 1);
        }
        if (lane == 0) {
          mbar_wait(base + B_EMPTY + 8 * s, ph);
          const uint32_t fb = base + B_FULL + 8 * s, dst = base + s * SLOT + 16384;
          if (it < 48) {
            mbar_expect(fb, 16384);
            tma2d(dst, it < 16 ? &mp.x : &mp.xn, (it & 15) * 64, tm * 128, fb);
          } else if (it < 50) {
            mbar_arrive(fb);
          } else {
            const int kb = out_kblock(it - 48, tn);
            poll_flag(g_flagO + tm * 16 + kb, ep);
            fence_acq();
            fence_async_glob();
            mbar_expect(fb, 16384);
            tma2d(dst, &mp.o, kb * 64, tm * 128, fb);
            STAMP_IF(it == 50, 2);
            STAMP_IF(it == 57, 3);
          }
        }
        __syncwarp();
        if (++s == NST) { s = 0; ph ^= 1; }
      }
    } else if (w == 13) {
      if (lane == 0) {
        pf_map(&mp.xs);
#pragma unroll 1
        for (int c = 0; c < 4; c++) {
          mbar_wait(base + B_FULL + 8 * c, 0);
          mbar_expect(base + B_XS + 8 * c, 8192);
          tma2d(base + STG + c * 8192, &mp.xs, c * 256, tm * 128 + tn * 16, base + B_XS + 8 * c);
        }
        mbar_wait(base + B_FULL + 8 * 4, 0);
        mbar_expect(base + B_WKB, 16384);
        tma3d(base + AUX, &mp.wqkv, 0, tm * 64, 16 + 2 * tn, base + B_WKB);
      }
      __syncwarp();
#pragma unroll 1
      for (int j = 0; j < 2; j++) {
        nb_sync(NB_OWN0 + j, 288);
        if (lane == 0) {
          tma2d_store(&mp.o, (2 * tn + j) * 64, tm * 128, base + STG + j * 16384);
          bulk_commit();
          const uint32_t ep = lds32(base + S_EPOCH);
          bulk_wait_done();
          st_relaxed(g_flagO + tm * 16 + 2 * tn + j, ep);
          STAMP(4 + j);
        }
        __syncwarp();
      }
      nb_arrive(NB_ST, 160);
    } else {
      if (lane == 0) { pf_map(&mp.xn); pf_map(&mp.gate); pf_map(&mp.up); pf_map(&mp.o); pf_map(&mp.wo); pf_map(&mp.down); pf_map(&mp.xns); pf_map(&mp.out); }
    }
  } else if (w >= 8) {
    asm volatile("setmaxnreg.dec.sync.aligned.u32 72;");
    const int t = tid - 256, ww = w - 8;
    const uint32_t ep = ld_relaxed(&g_epoch) + 1;
    if (t < 66) sts128(base + FR + 4096 + t * 16, 0u, 0u, 0u, 0u);
    {
      mbar_wait(base + B_WKB, 0);
      const int r0 = t >> 4;
      const uint32_t a = base + AUX + ((t >> 3) & 1) * 8192 + r0 * 128 + (((t & 7) ^ r0) << 4);
      float c[8];
#pragma unroll
      for (int i = 0; i < 8; i++) {
        const uint4 v = lds128(a + i * 1024);
        if (i == 0) {
          c[0] = bf_lo(v.x); c[1] = bf_hi(v.x); c[2] = bf_lo(v.y); c[3] = bf_hi(v.y);
          c[4] = bf_lo(v.z); c[5] = bf_hi(v.z); c[6] = bf_lo(v.w); c[7] = bf_hi(v.w);
        } else {
          c[0] += bf_lo(v.x); c[1] += bf_hi(v.x); c[2] += bf_lo(v.y); c[3] += bf_hi(v.y);
          c[4] += bf_lo(v.z); c[5] += bf_hi(v.z); c[6] += bf_lo(v.w); c[7] += bf_hi(v.w);
        }
      }
      const bool up = lane >= 16;
      float d[4];
#pragma unroll
      for (int i = 0; i < 4; i++) d[i] = (up ? c[4 + i] : c[i]) + __shfl_xor_sync(0xffffffffu, up ? c[i] : c[4 + i], 16);
      sts128(base + FR + ww * 512 + (lane & 15) * 32 + (up ? 16 : 0), __float_as_uint(d[0]), __float_as_uint(d[1]), __float_as_uint(d[2]), __float_as_uint(d[3]));
      nb_sync(NB_WG2, 128);
      const uint32_t b = base + FR + t * 4;
      const float sum = (__uint_as_float(lds32(b)) + __uint_as_float(lds32(b + 512))) + (__uint_as_float(lds32(b + 1024)) + __uint_as_float(lds32(b + 1536)));
      sts32(base + S_CSUM + t * 4, __float_as_uint(sum));
      fence_async_smem();
      nb_sync(NB_WG2, 128);
      if (t == 0) {
        bulk_store(g_csum + tm * 1024 + tn * 128, base + S_CSUM, 512);
        bulk_store(g_kv + bid * 264, base + FR + 4096, 1056);
        bulk_commit();
        bulk_wait_done();
      }
      __syncwarp();
    }
    STAMP_IF(t == 0, 8);
    if (ww == 0) nb_arrive(NB_FRONT, 64);
    const int NG = bid < 112 ? 32 : 0, ks = bid >> 4, nt = bid & 15;
    uint64_t pol;
    asm volatile("createpolicy.fractional.L2::evict_first.b64 %0, 1.0;" : "=l"(pol));
    auto issue = [&](int n) {
      const uint32_t bar = base + B_FR + 8 * (n & 3), dst = base + FR + (n & 3) * 4096;
      if (n < NG) {
        mbar_expect(bar, 4096);
        tma2d_ef(dst, &mp.gate, bid * 32, n * 32, bar, pol);
        tma2d_ef(dst + 2048, &mp.up, bid * 32, n * 32, bar, pol);
      } else if (n < NG + 14) {
        mbar_expect(bar, 4096);
        tma2d_ef(dst, &mp.down, nt * 64, ks * 448 + (n - NG) * 32, bar, pol);
      }
    };
    if (t == 0) {
#pragma unroll 1
      for (int n = 0; n < 4; n++) issue(n);
    }
    {
      uint32_t k[16];
      int c = 0;
      while (true) {
        uint32_t bad = 0;
#pragma unroll
        for (int q = 0; q < 4; q++) {
          const uint4 v = ld_relaxed4(g_keys + (q * 128 + t) * 4);
          k[q * 4] = v.x; k[q * 4 + 1] = v.y; k[q * 4 + 2] = v.z; k[q * 4 + 3] = v.w;
          bad |= (v.x ^ ep) | (v.y ^ ep) | (v.z ^ ep) | (v.w ^ ep);
        }
        if (__all_sync(0xffffffffu, (bad & 31u) == 0)) break;
        spin_guard(c);
        __nanosleep(64);
      }
      fence_acq();
      nb_sync(NB_WG2, 128);
      STAMP_IF(t == 0, 9);
      {
        const float2 st = __ldcg(g_stats + tm * 128 + t);
        float p[16];
#pragma unroll
        for (int i = 0; i < 16; i++) p[i] = __ldcg(g_csum + i * 1024 + tn * 128 + t);
        float sum = 0.f;
#pragma unroll
        for (int i = 0; i < 16; i += 4) sum += (p[i] + p[i + 1]) + (p[i + 2] + p[i + 3]);
        asm volatile("st.shared.v2.f32 [%0], {%1,%2};" ::"r"(base + S_KSTAT + t * 8), "f"(st.x), "f"(st.y * LOG2E) : "memory");
        sts32(base + S_CSUM + t * 4, __float_as_uint(sum));
        nb_arrive(NB_FDONE, 256);
      }
      uint32_t m = k[0];
#pragma unroll
      for (int i = 1; i < 16; i++) m = max(m, k[i]);
      uint32_t mm = m, T = 0;
#pragma unroll
      for (int r = 0; r < 8; r++) { T = __reduce_max_sync(0xffffffffu, mm); mm = mm == T ? 0u : mm; }
      if (m >= T) {
#pragma unroll
        for (int i = 0; i < 16; i++)
          if (k[i] >= T) {
            uint32_t pos;
            asm volatile("atom.shared.add.u32 %0, [%1], 1;" : "=r"(pos) : "r"(base + S_NCAND) : "memory");
            sts32(base + AUX + pos * 4, k[i]);
          }
      }
      nb_sync(NB_WG2, 128);
      const int n = (int)lds32(base + S_NCAND);
#pragma unroll 1
      for (int i = t; i < n; i += 128) {
        const uint32_t key = lds32(base + AUX + i * 4);
        int rank = 0;
#pragma unroll 4
        for (int j = 0; j < n; j++) rank += lds32(base + AUX + j * 4) > key;
        if (rank < 8) sts32(base + S_SEL + rank * 4, key);
      }
      nb_sync(NB_WG2, 128);
    }
    STAMP_IF(t == 0, 10);
    float fa[4] = {0.f, 0.f, 0.f, 0.f};
    if (NG) {
      {
        uint4 v[8];
#pragma unroll
        for (int j = 0; j < 8; j++) v[j] = __ldcg(reinterpret_cast<const uint4*>(g_xn + key_token(lds32(base + S_SEL + j * 4)) * 1024) + t);
#pragma unroll
        for (int j = 0; j < 8; j++) sts128(base + AUX + (t >> 3) * 1024 + j * 128 + (((t & 7) ^ j) << 4), v[j].x, v[j].y, v[j].z, v[j].w);
        fence_async_smem();
        nb_sync(NB_WG2, 128);
      }
      STAMP_IF(t == 0, 11);
#pragma unroll 1
      for (int n = 0; n < 32; n++) {
        mbar_wait(base + B_FR + 8 * (n & 3), (n >> 2) & 1);
        const uint64_t da = mkdesc(base + FR + (n & 3) * 4096, 2048, 512, 2);
        const uint64_t db = mkdesc(base + AUX + (n >> 1) * 1024 + (n & 1) * 64, 16, 1024, 1);
        wg_fence();
        wgmma_n8_ss<1, 0>(fa, da, db, n != 0);
        wgmma_n8_ss<1, 0>(fa, da + 64, db + 2, 1);
        wg_commit();
        wg_wait<1>();
        if (n && t == 0) issue(n + 3);
        if (n == 18) nb_arrive(NB_XSEL, 256);
      }
      wg_wait<0>();
      reg_fence(fa);
      if (t == 0) issue(35);
      STAMP_IF(t == 0, 12);
      if (ww >= 2) sts128(base + S_XCH + (t - 64) * 16, __float_as_uint(fa[0]), __float_as_uint(fa[1]), __float_as_uint(fa[2]), __float_as_uint(fa[3]));
      nb_sync(NB_WG2, 128);
      if (ww < 2) {
        const float4 u = lds128f(base + S_XCH + t * 16);
        const float uu[4] = {u.x, u.y, u.z, u.w};
#pragma unroll
        for (int i = 0; i < 4; i++) {
          const float g = fa[i], hv = g * rcp(1.f + ex2(-g * LOG2E)) * uu[i];
          asm volatile("st.shared.u16 [%0], %1;" ::"r"(base + HOP + ((lane & 3) * 2 + (i & 1)) * 64 + (((ww * 2 + (i >> 1)) ^ (lane & 3)) << 4) + (lane >> 2) * 2),
                       "h"((unsigned short)pack(hv, hv)) : "memory");
        }
        fence_async_smem();
      }
      nb_sync(NB_WG2, 128);
      if (t == 0) {
        bulk_store(g_h + bid * 256, base + HOP, 512);
        bulk_commit();
        bulk_wait_done();
        st_relaxed(g_flagH + bid, ep);
      }
      __syncwarp();
    } else {
      nb_arrive(NB_XSEL, 256);
    }
    if (ww == 0) {
      if (lane < 14) poll_flag(g_flagH + ks * 14 + lane, ep);
      fence_acq();
      __syncwarp();
      if (lane == 0) {
        fence_async_glob();
        mbar_expect(base + B_HOP, 7168);
        bulk_load(base + HOP, g_h + ks * 3584, 7168, base + B_HOP);
      }
    }
    mbar_wait(base + B_HOP, 0);
    STAMP_IF(t == 0, 13);
#pragma unroll 1
    for (int i = 0; i < 14; i++) {
      const int n = NG + i;
      mbar_wait(base + B_FR + 8 * (n & 3), (n >> 2) & 1);
      const uint64_t da = mkdesc(base + FR + (n & 3) * 4096, 4096, 1024, 1);
      const uint64_t db = mkdesc(base + HOP + i * 512, 16, 512, 2);
      wg_fence();
      wgmma_n8_ss<1, 0>(fa, da, db, i != 0);
      wgmma_n8_ss<1, 0>(fa, da + 128, db + 2, 1);
      wg_commit();
      wg_wait<1>();
      if (i && t == 0) issue(n + 3);
    }
    wg_wait<0>();
    reg_fence(fa);
    STAMP_IF(t == 0, 14);
    {
      const uint32_t yp = base + FR + 8192 + (lane & 3) * 512 + (ww * 16 + (lane >> 2)) * 4;
      sts32(yp, __float_as_uint(fa[0])); sts32(yp + 256, __float_as_uint(fa[1]));
      sts32(yp + 32, __float_as_uint(fa[2])); sts32(yp + 288, __float_as_uint(fa[3]));
      fence_async_smem();
    }
    nb_sync(NB_WG2, 128);
    if (t == 0) {
      bulk_store(g_yp + (nt * 8 + ks) * 512, base + FR + 8192, 2048);
      bulk_commit();
      bulk_wait_done();
      st_relaxed(g_flagY + nt * 8 + ks, ep);
    }
    __syncwarp();
    const uint32_t mykey = lds32(base + S_SEL + (lane & 7) * 4);
    const uint32_t inmask = __ballot_sync(0xffffffffu, (key_token(mykey) >> 7) == tm) & 0xffu;
    if (inmask) {
      if (ww == 0) {
        if (lane < 16) poll_flag(g_flagY + tn * 16 + lane, ep);
        fence_acq();
      }
      nb_sync(NB_WG2, 128);
      const float sg = rcp(1.f + ex2(-key_score(mykey) * LOG2E));
#pragma unroll 1
      for (int j = 0; j < 8; j++) {
        float y = 0.f;
        if ((inmask >> j) & 1) {
          float p[8];
#pragma unroll
          for (int q = 0; q < 8; q++) p[q] = __ldcg(g_yp + ((tn * 2 + (t >> 6)) * 8 + q) * 512 + j * 64 + (t & 63));
          y = ((p[0] + p[1]) + (p[2] + p[3])) + ((p[4] + p[5]) + (p[6] + p[7]));
        }
        y *= __shfl_sync(0xffffffffu, sg, j);
        asm volatile("st.shared.u16 [%0], %1;" ::"r"(base + FR + (t >> 6) * 1024 + j * 128 + ((((t >> 3) & 7) ^ j) << 4) + (t & 7) * 2),
                     "h"((unsigned short)pack(y, y)) : "memory");
      }
      fence_async_smem();
      nb_arrive(NB_Y, 256);
    }
    STAMP_IF(t == 0, 15);
  } else if (w >= 4) {
    asm volatile("setmaxnreg.inc.sync.aligned.u32 200;");
    const int t = tid - 128, ww = w - 4, g = lane >> 2, t4 = lane & 3;
    const bool leader = t == 0;
    const uint32_t ep = ld_relaxed(&g_epoch) + 1;
    {
      float wr[32], wsum = 0.f;
#pragma unroll
      for (int c = 0; c < 4; c++) {
        const uint4 v = __ldg(reinterpret_cast<const uint4*>(w_r) + c * 32 + lane);
        wr[c * 8 + 0] = bf_lo(v.x); wr[c * 8 + 1] = bf_hi(v.x); wr[c * 8 + 2] = bf_lo(v.y); wr[c * 8 + 3] = bf_hi(v.y);
        wr[c * 8 + 4] = bf_lo(v.z); wr[c * 8 + 5] = bf_hi(v.z); wr[c * 8 + 6] = bf_lo(v.w); wr[c * 8 + 7] = bf_hi(v.w);
      }
#pragma unroll
      for (int i = 0; i < 32; i++) wsum += wr[i];
#pragma unroll
      for (int o = 16; o; o >>= 1) wsum += __shfl_xor_sync(0xffffffffu, wsum, o);
      if (leader) sts32(base + S_EPOCH, ep);
      uint32_t xw[4][16];
      float s[4] = {0.f, 0.f, 0.f, 0.f}, q[4] = {0.f, 0.f, 0.f, 0.f}, d[4] = {0.f, 0.f, 0.f, 0.f};
#pragma unroll
      for (int c = 0; c < 4; c++) {
        mbar_wait(base + B_XS + 8 * c, 0);
#pragma unroll
        for (int r = 0; r < 4; r++) {
          const uint4 v = lds128(base + STG + c * 8192 + (ww * 4 + r) * 512 + lane * 16);
          xw[r][c * 4] = v.x; xw[r][c * 4 + 1] = v.y; xw[r][c * 4 + 2] = v.z; xw[r][c * 4 + 3] = v.w;
        }
#pragma unroll
        for (int r = 0; r < 4; r++)
#pragma unroll
          for (int i = 0; i < 4; i++) {
            const float lo = bf_lo(xw[r][c * 4 + i]), hi = bf_hi(xw[r][c * 4 + i]);
            s[r] += lo; q[r] = fmaf(lo, lo, q[r]); d[r] = fmaf(lo, wr[c * 8 + 2 * i], d[r]);
            s[r] += hi; q[r] = fmaf(hi, hi, q[r]); d[r] = fmaf(hi, wr[c * 8 + 2 * i + 1], d[r]);
          }
      }
      STAMP_IF(leader, 16);
      const bool u16 = lane & 16, u8 = lane & 8;
      float s2[2], q2[2], d2[2];
#pragma unroll
      for (int i = 0; i < 2; i++) {
        s2[i] = (u16 ? s[2 + i] : s[i]) + __shfl_xor_sync(0xffffffffu, u16 ? s[i] : s[2 + i], 16);
        q2[i] = (u16 ? q[2 + i] : q[i]) + __shfl_xor_sync(0xffffffffu, u16 ? q[i] : q[2 + i], 16);
        d2[i] = (u16 ? d[2 + i] : d[i]) + __shfl_xor_sync(0xffffffffu, u16 ? d[i] : d[2 + i], 16);
      }
      float s1 = (u8 ? s2[1] : s2[0]) + __shfl_xor_sync(0xffffffffu, u8 ? s2[0] : s2[1], 8);
      float q1 = (u8 ? q2[1] : q2[0]) + __shfl_xor_sync(0xffffffffu, u8 ? q2[0] : q2[1], 8);
      float d1 = (u8 ? d2[1] : d2[0]) + __shfl_xor_sync(0xffffffffu, u8 ? d2[0] : d2[1], 8);
#pragma unroll
      for (int o = 4; o; o >>= 1) {
        s1 += __shfl_xor_sync(0xffffffffu, s1, o);
        q1 += __shfl_xor_sync(0xffffffffu, q1, o);
        d1 += __shfl_xor_sync(0xffffffffu, d1, o);
      }
      const float mean = s1 * (1.f / 1024.f);
      const float var = fmaxf(fmaf(-mean, mean, q1 * (1.f / 1024.f)), 0.f);
      const float mb = bf_round(mean);
      float sd;
      asm("sqrt.approx.f32 %0, %1;" : "=f"(sd) : "f"(bf_round(bf_round(var) + 1e-5f)));
      const float rinv = rcp(bf_round(sd));
      const float rhi = bf_round(rinv);
      const uint32_t m2 = pack(mb, mb), hi2 = pack(rhi, rhi), lo2 = pack(rinv - rhi, rinv - rhi);
      const int row0 = tm * 128 + tn * 16 + ww * 4;
      if ((lane & 7) == 0) {
        const int row = row0 + (lane >> 3);
        asm volatile("st.shared.v2.f32 [%0], {%1,%2};" ::"r"(base + S_STAT + (ww * 4 + (lane >> 3)) * 8), "f"(mb), "f"(rinv) : "memory");
        const uint32_t rb = pack(fmaf(-mb, wsum, d1) * rinv, 0.f) & 0xffffu;
        const uint32_t mono = (rb & 0x8000u) ? (~rb & 0xffffu) : (rb | 0x8000u);
        sts32(base + S_KEYS + (ww * 4 + (lane >> 3)) * 4, (mono << 16) | ((2047 - row) << 5) | (ep & 31u));
      }
#pragma unroll
      for (int r = 0; r < 4; r++) {
        const uint32_t m = __shfl_sync(0xffffffffu, m2, r * 8), hi = __shfl_sync(0xffffffffu, hi2, r * 8), lo = __shfl_sync(0xffffffffu, lo2, r * 8);
#pragma unroll
        for (int c = 0; c < 4; c++) {
          uint32_t o[4];
#pragma unroll
          for (int i = 0; i < 4; i++)
            asm("{\n.reg .b32 d, e;\nsub.rn.bf16x2 d, %1, %2;\nmul.rn.bf16x2 e, d, %4;\nfma.rn.bf16x2 %0, d, %3, e;\n}"
                : "=r"(o[i]) : "r"(xw[r][c * 4 + i]), "r"(m), "r"(hi), "r"(lo));
          sts128(base + STG + c * 8192 + (ww * 4 + r) * 512 + lane * 16, o[0], o[1], o[2], o[3]);
        }
      }
      fence_async_smem();
      nb_sync(NB_WG1, 128);
      STAMP_IF(leader, 17);
      if (ww == 0) {
        if (leader) {
#pragma unroll
          for (int c = 0; c < 4; c++) tma2d_store(&mp.xns, c * 256, tm * 128 + tn * 16, base + STG + c * 8192);
          bulk_store(g_stats + tm * 128 + tn * 16, base + S_STAT, 128);
          bulk_commit();
          bulk_wait_done();
        }
        nb_sync(NB_FRONT, 64);
        if (t < 16) st_relaxed(g_keys + tm * 128 + tn * 16 + t, lds32(base + S_KEYS + t * 4));
      }
      STAMP_IF(leader, 18);
    }
    float a0[64], a1[64];
    reg_zero(a0); reg_zero(a1); reg_fence(a0); reg_fence(a1);
    nb_sync(NB_KV, 256);
    mainloop<true>(a0, a1, base, 1, 1, NB_VQ, leader);
    STAMP_IF(leader, 19);
    {
      uint32_t f0[32], f1[32];
#pragma unroll
      for (int i = 0; i < 32; i++) { f0[i] = pack(a0[2 * i], a0[2 * i + 1]); f1[i] = pack(a1[2 * i], a1[2 * i + 1]); }
      float c0[32], c1[32];
      reg_zero(c0); reg_zero(c1);
      nb_sync(NB_PK, 256);
      const uint64_t db = mkdesc(base + STG, 16, 1024, 1);
      wg_fence();
#pragma unroll
      for (int k = 0; k < 8; k++) {
        wgmma_n64_rs<0>(c0, f0[4 * k], f0[4 * k + 1], f0[4 * k + 2], f0[4 * k + 3], db + (k >> 2) * 1024 + (k & 3) * 2, k != 0);
        wgmma_n64_rs<0>(c1, f1[4 * k], f1[4 * k + 1], f1[4 * k + 2], f1[4 * k + 3], db + (k >> 2) * 1024 + (k & 3) * 2 + 512, k != 0);
      }
      wg_commit();
      wg_wait<0>();
      reg_fence(c0);
      reg_fence(c1);
      STAMP_IF(leader, 20);
      const bool hp = ww >> 1;
      nb_sync(NB_WG1, 128);
#pragma unroll
      for (int j = 0; j < 4; j++) {
        sts128(base + STG + 16384 + j * 2048 + t * 16, __float_as_uint(hp ? c0[16 + 4 * j] : c0[4 * j]), __float_as_uint(hp ? c0[17 + 4 * j] : c0[1 + 4 * j]),
               __float_as_uint(hp ? c0[18 + 4 * j] : c0[2 + 4 * j]), __float_as_uint(hp ? c0[19 + 4 * j] : c0[3 + 4 * j]));
        sts128(base + STG + 24576 + j * 2048 + t * 16, __float_as_uint(hp ? c1[16 + 4 * j] : c1[4 * j]), __float_as_uint(hp ? c1[17 + 4 * j] : c1[1 + 4 * j]),
               __float_as_uint(hp ? c1[18 + 4 * j] : c1[2 + 4 * j]), __float_as_uint(hp ? c1[19 + 4 * j] : c1[3 + 4 * j]));
      }
      fence_async_smem();
      nb_sync(NB_WG1, 128);
      if (leader) {
        bulk_addf(g_kv + tn * 4096, base + STG + 16384, 16384);
        bulk_addf(g_kv + 32768 + tn * 128, base + S_CSUM, 512);
        bulk_commit();
        mbar_expect(base + B_XRES, 32768);
        tma2d(base + STG, &mp.x, tn * 128, tm * 128, base + B_XRES);
        bulk_wait_read();
        tma2d(base + STG + 16384, &mp.x, tn * 128 + 64, tm * 128, base + B_XRES);
        bulk_wait_done();
        st_relaxed(g_flagKV + tn * 16 + tm, ep);
      }
      __syncwarp();
      STAMP_IF(leader, 21);
    }
    const uint32_t srow = (ww * 16 + (lane & 15)) * 128, sx = lane & 7, sc = lane >> 4;
    {
      float sa[4], sb[4];
#pragma unroll
      for (int i = 0; i < 4; i++) {
        const float2 st = lds64f(base + S_KSTAT + ((i >> 1) * 64 + ww * 16 + (i & 1) * 8 + g) * 8);
        const float r = st.y * LN2;
        sa[i] = 1.f + r; sb[i] = -st.x * r;
      }
      mbar_wait(base + B_XRES, 0);
#pragma unroll
      for (int j = 0; j < 8; j++) {
        const uint32_t a = base + STG + (j >> 2) * 16384 + srow + ((((j & 3) * 2 + sc) ^ sx) << 4);
        const uint4 v = ldsm4(a), u = ldsm4(a + 8192);
        a0[8 * j + 0] = fmaf(bf_lo(v.x), sa[0], sb[0]); a0[8 * j + 1] = fmaf(bf_hi(v.x), sa[0], sb[0]);
        a0[8 * j + 2] = fmaf(bf_lo(v.y), sa[1], sb[1]); a0[8 * j + 3] = fmaf(bf_hi(v.y), sa[1], sb[1]);
        a0[8 * j + 4] = fmaf(bf_lo(v.z), sa[0], sb[0]); a0[8 * j + 5] = fmaf(bf_hi(v.z), sa[0], sb[0]);
        a0[8 * j + 6] = fmaf(bf_lo(v.w), sa[1], sb[1]); a0[8 * j + 7] = fmaf(bf_hi(v.w), sa[1], sb[1]);
        a1[8 * j + 0] = fmaf(bf_lo(u.x), sa[2], sb[2]); a1[8 * j + 1] = fmaf(bf_hi(u.x), sa[2], sb[2]);
        a1[8 * j + 2] = fmaf(bf_lo(u.y), sa[3], sb[3]); a1[8 * j + 3] = fmaf(bf_hi(u.y), sa[3], sb[3]);
        a1[8 * j + 4] = fmaf(bf_lo(u.z), sa[2], sb[2]); a1[8 * j + 5] = fmaf(bf_hi(u.z), sa[2], sb[2]);
        a1[8 * j + 6] = fmaf(bf_lo(u.w), sa[3], sb[3]); a1[8 * j + 7] = fmaf(bf_hi(u.w), sa[3], sb[3]);
      }
      reg_fence(a0);
      reg_fence(a1);
    }
    STAMP_IF(leader, 22);
    {
      if (ww == 0) {
        if (lane < 16) poll_flag(g_flagKV + tn * 16 + lane, ep);
        fence_acq();
      }
      nb_sync(NB_XSEL, 256);
      STAMP_IF(leader, 23);
      const float4* kp = reinterpret_cast<const float4*>(g_kv + tn * 4096) + t;
      float4 v[8], z0, z1;
#pragma unroll
      for (int q = 0; q < 8; q++) v[q] = __ldcg(kp + q * 128);
      const float4* zp = reinterpret_cast<const float4*>(g_kv + 32768 + tn * 128 + (t & 15) * 8);
      z0 = __ldcg(zp); z1 = __ldcg(zp + 1);
#pragma unroll
      for (int q = 0; q < 8; q += 2)
        stsm4(base + (q < 4 ? KVB_P0 : KVB_P1) + ((ww & 1) * 16 + (lane & 15)) * 128 + ((((ww >> 1) * 4 + (q & 2) + sc) ^ sx) << 4),
              pack(v[q].x, v[q].y), pack(v[q].z, v[q].w), pack(v[q + 1].x, v[q + 1].y), pack(v[q + 1].z, v[q + 1].w));
      if (t < 64) sts128(base + KVB_Z + (t >> 3) * 128 + (((t & 7) ^ (t >> 3)) << 4), pack(z0.x, z0.y), pack(z0.z, z0.w), pack(z1.x, z1.y), pack(z1.z, z1.w));
      fence_async_smem();
      nb_arrive(NB_KVB, 256);
    }
    STAMP_IF(leader, 24);
    uint32_t oh[4];
    uint32_t inmask;
    {
      const int r0 = key_token(lds32(base + S_SEL + t4 * 8)) - tm * 128, r1 = key_token(lds32(base + S_SEL + t4 * 8 + 4)) - tm * 128;
#pragma unroll
      for (int i = 0; i < 4; i++) {
        const int row = (i >> 1) * 64 + ww * 16 + (i & 1) * 8 + g;
        oh[i] = (r0 == row ? 0x3f80u : 0u) | (r1 == row ? 0x3f800000u : 0u);
      }
      inmask = __ballot_sync(0xffffffffu, (unsigned)r0 < 128u || (unsigned)r1 < 128u);
    }
    {
      int s = 3, ph = 1, prev = -1;
#pragma unroll 1
      for (int r = 0; r < 16; r++) {
        if (r < 2) nb_sync(NB_OWN0 + r, 288);
        mbar_wait(base + B_FULL + 8 * s, ph);
        STAMP_IF(leader && r < 3, 25 + r);
        const uint32_t sa = base + s * SLOT;
        const uint64_t dw = mkdesc(sa, 8192, 1024, 1), dx = mkdesc(r < 2 ? base + STG + r * 16384 : sa + 16384, 16, 1024, 1);
        wg_fence();
#pragma unroll
        for (int j = 0; j < 4; j++) {
          wgmma_n128_ss<0, 1>(a0, dx + j * 2, dw + j * 128, 1);
          wgmma_n128_ss<0, 1>(a1, dx + j * 2 + 512, dw + j * 128, 1);
        }
        wg_commit();
        wg_wait<1>();
        if (prev >= 0 && leader) mbar_arrive(base + B_EMPTY + 8 * prev);
        prev = s;
        if (++s == NST) { s = 0; ph ^= 1; }
      }
      if (inmask) {
        nb_sync(NB_Y, 256);
        const uint64_t dy = mkdesc(base + FR, 1024, 0, 1);
        wg_fence();
        wgmma_n128_rs<1>(a0, oh[0], oh[1], 0u, 0u, dy, 1);
        wgmma_n128_rs<1>(a1, oh[2], oh[3], 0u, 0u, dy, 1);
        wg_commit();
      }
      nb_sync(NB_ST, 160);
      wg_wait<0>();
      reg_fence(a0);
      reg_fence(a1);
    }
    STAMP_IF(leader, 28);
#pragma unroll
    for (int c = 0; c < 2; c++) {
#pragma unroll
      for (int j = 4 * c; j < 4 * c + 4; j++) {
        const uint32_t a = base + STG + c * 16384 + srow + ((((j & 3) * 2 + sc) ^ sx) << 4);
        stsm4(a, pack(a0[8 * j], a0[8 * j + 1]), pack(a0[8 * j + 2], a0[8 * j + 3]), pack(a0[8 * j + 4], a0[8 * j + 5]), pack(a0[8 * j + 6], a0[8 * j + 7]));
        stsm4(a + 8192, pack(a1[8 * j], a1[8 * j + 1]), pack(a1[8 * j + 2], a1[8 * j + 3]), pack(a1[8 * j + 4], a1[8 * j + 5]), pack(a1[8 * j + 6], a1[8 * j + 7]));
      }
      fence_async_smem();
      __syncwarp();
      if (lane == 0) {
        tma2d_store(&mp.out, tn * 128 + c * 64, tm * 128 + ww * 16, base + STG + c * 16384 + ww * 2048);
        tma2d_store(&mp.out, tn * 128 + c * 64, tm * 128 + 64 + ww * 16, base + STG + c * 16384 + 8192 + ww * 2048);
      }
    }
    if (lane == 0) { bulk_commit(); bulk_wait_read(); }
    if (bid == 0 && leader) st_relaxed(&g_epoch, ep);
    STAMP_IF(leader, 29);
  } else {
    asm volatile("setmaxnreg.inc.sync.aligned.u32 200;");
    const int g = lane >> 2, t4 = lane & 3;
    const bool leader = tid == 0;
    const uint32_t srow = (w * 16 + (lane & 15)) * 128, sx = lane & 7, sc = lane >> 4;
    float a0[64], a1[64];
    reg_zero(a0); reg_zero(a1); reg_fence(a0); reg_fence(a1);
    mainloop<true>(a0, a1, base, 0, 0, NB_KV, leader);
    STAMP_IF(leader, 33);
    {
      nb_sync(NB_FDONE, 256);
      STAMP_IF(leader, 34);
      float c[4], z[4] = {0.f, 0.f, 0.f, 0.f};
#pragma unroll
      for (int i = 0; i < 4; i++) c[i] = -__uint_as_float(lds32(base + S_CSUM + ((i >> 1) * 64 + w * 16 + (i & 1) * 8 + g) * 4));
#pragma unroll
      for (int j = 0; j < 8; j++) {
        const float4 s0 = lds128f(base + S_KSTAT + (j * 16 + 2 * t4) * 8), s1 = lds128f(base + S_KSTAT + (j * 16 + 8 + 2 * t4) * 8);
        const float mu[4] = {s0.x, s0.z, s1.x, s1.z}, rl[4] = {s0.y, s0.w, s1.y, s1.w};
        const uint32_t a = base + STG + (j >> 2) * 16384 + srow + ((((j & 3) * 2 + sc) ^ sx) << 4);
#pragma unroll
        for (int m = 0; m < 2; m++) {
          float p[8];
#pragma unroll
          for (int i = 0; i < 8; i++) {
            const int r = m * 2 + ((i >> 1) & 1), cc = (i >> 2) * 2 + (i & 1);
            const float v = fmaf(c[r], mu[cc], m ? a1[8 * j + i] : a0[8 * j + i]) * rl[cc];
            p[i] = fmaf(fmaxf(v, 0.f), LN2, addsat(ex2(v), 1e-6f));
            z[r] += p[i];
          }
          stsm4(a + m * 8192, pack(p[0], p[1]), pack(p[2], p[3]), pack(p[4], p[5]), pack(p[6], p[7]));
        }
      }
#pragma unroll
      for (int i = 0; i < 4; i++) {
        z[i] += __shfl_xor_sync(0xffffffffu, z[i], 1);
        z[i] += __shfl_xor_sync(0xffffffffu, z[i], 2);
      }
      const float zz = t4 == 0 ? z[0] : t4 == 1 ? z[1] : t4 == 2 ? z[2] : z[3];
      sts32(base + S_CSUM + ((t4 >> 1) * 64 + w * 16 + (t4 & 1) * 8 + g) * 4, __float_as_uint(zz));
      fence_async_smem();
      nb_arrive(NB_PK, 256);
    }
    STAMP_IF(leader, 35);
    reg_zero(a0); reg_zero(a1); reg_fence(a0); reg_fence(a1);
    nb_sync(NB_VQ, 256);
    mainloop<false>(a0, a1, base, 2, 0, 0, leader);
    STAMP_IF(leader, 36);
    nb_sync(NB_KVB, 256);
    STAMP_IF(leader, 37);
    {
      uint32_t f[2][16];
      float oc[2][2][20];
      auto phi = [&](const float (&a)[64], int j, uint32_t (&o)[16]) {
#pragma unroll
        for (int i = 0; i < 16; i++) {
          const float x = a[32 * j + 2 * i], y = a[32 * j + 2 * i + 1];
          o[i] = pack(fmaxf(x, 0.f) + addsat(ex2(x * LOG2E), 1e-6f), fmaxf(y, 0.f) + addsat(ex2(y * LOG2E), 1e-6f));
        }
      };
      auto mma = [&](int j, const uint32_t (&a)[16], float (&o)[2][20]) {
        const uint64_t db = mkdesc(base + (j ? KVB_Z : KVB_P0), 16, 1024, 1);
        reg_zero(o[0]); reg_zero(o[1]);
        wg_fence();
        wgmma_n40_rs<0>(o[0], a[0], a[1], a[2], a[3], db, 0);
        wgmma_n40_rs<0>(o[1], a[8], a[9], a[10], a[11], db + 4, 0);
        wgmma_n40_rs<0>(o[0], a[4], a[5], a[6], a[7], db + 2, 1);
        wgmma_n40_rs<0>(o[1], a[12], a[13], a[14], a[15], db + 6, 1);
        wg_commit();
      };
      auto fin = [&](int j, int m, float (&o)[2][20]) {
        reg_fence(o[0]);
        reg_fence(o[1]);
#pragma unroll
        for (int h = 0; h < 2; h++) {
          const float r0 = rcp(o[h][j ? 1 : 16] + 1e-6f), r1 = rcp(o[h][j ? 3 : 18] + 1e-6f);
          const int b = j ? 4 : 0;
#pragma unroll
          for (int q = 0; q < 2; q++)
            stsm4(base + STG + j * 16384 + m * 8192 + srow + (((h * 4 + q * 2 + sc) ^ sx) << 4),
                  pack(o[h][b + 8 * q] * r0, o[h][b + 8 * q + 1] * r0), pack(o[h][b + 8 * q + 2] * r1, o[h][b + 8 * q + 3] * r1),
                  pack(o[h][b + 8 * q + 4] * r0, o[h][b + 8 * q + 5] * r0), pack(o[h][b + 8 * q + 6] * r1, o[h][b + 8 * q + 7] * r1));
        }
      };
      phi(a0, 0, f[0]);
      mma(0, f[0], oc[0]);
      phi(a1, 0, f[1]);
      wg_wait<0>();
      reg_fence(oc[0][0]);
      reg_fence(oc[0][1]);
      mma(0, f[1], oc[1]);
      fin(0, 0, oc[0]);
      wg_wait<0>();
      fin(0, 1, oc[1]);
      fence_async_smem();
      nb_arrive(NB_OWN0, 288);
      STAMP_IF(leader, 38);
      phi(a0, 1, f[0]);
      mma(1, f[0], oc[0]);
      phi(a1, 1, f[1]);
      wg_wait<0>();
      reg_fence(oc[0][0]);
      reg_fence(oc[0][1]);
      mma(1, f[1], oc[1]);
      fin(1, 0, oc[0]);
      wg_wait<0>();
      fin(1, 1, oc[1]);
      fence_async_smem();
      nb_arrive(NB_OWN1, 288);
      STAMP_IF(leader, 39);
    }
  }
}

typedef CUresult (*EncodeFn)(CUtensorMap*, CUtensorMapDataType, cuuint32_t, void*, const cuuint64_t*, const cuuint64_t*, const cuuint32_t*,
                             const cuuint32_t*, CUtensorMapInterleave, CUtensorMapSwizzle, CUtensorMapL2promotion, CUtensorMapFloatOOBfill);

void make_map(EncodeFn enc, CUtensorMap* m, const void* p, int rank, uint64_t d0, uint64_t d1, uint64_t d2, uint64_t s1, uint64_t s2,
              uint32_t b0, uint32_t b1, uint32_t b2, CUtensorMapSwizzle sw) {
  cuuint64_t gd[3] = {d0, d1, d2}, gs[2] = {s1, s2};
  cuuint32_t bd[3] = {b0, b1, b2}, es[3] = {1, 1, 1};
  enc(m, CU_TENSOR_MAP_DATA_TYPE_BFLOAT16, rank, const_cast<void*>(p), gd, gs, bd, es, CU_TENSOR_MAP_INTERLEAVE_NONE, sw,
      CU_TENSOR_MAP_L2_PROMOTION_L2_128B, CU_TENSOR_MAP_FLOAT_OOB_FILL_NONE);
}

}

extern "C" void kernel_launch(void* const* d_in, const int* in_sizes, int n_in, void* d_out, int out_size) {
  (void)in_sizes; (void)n_in; (void)out_size;
  void* fn = nullptr;
  cudaDriverEntryPointQueryResult qr;
  cudaGetDriverEntryPoint("cuTensorMapEncodeTiled", &fn, cudaEnableDefault, &qr);
  EncodeFn enc = (EncodeFn)fn;
  void *xn, *o;
  cudaGetSymbolAddress(&xn, g_xn);
  cudaGetSymbolAddress(&o, g_o);
  const CUtensorMapSwizzle S128 = CU_TENSOR_MAP_SWIZZLE_128B, S64 = CU_TENSOR_MAP_SWIZZLE_64B, S0 = CU_TENSOR_MAP_SWIZZLE_NONE;
  Maps mp;
  make_map(enc, &mp.wqkv, d_in[1], 3, 64, 1024, 48, 6144, 128, 64, 64, 2, S128);
  make_map(enc, &mp.x, d_in[0], 2, 1024, 2048, 1, 2048, 0, 64, 128, 1, S128);
  make_map(enc, &mp.xn, xn, 2, 1024, 2048, 1, 2048, 0, 64, 128, 1, S128);
  make_map(enc, &mp.o, o, 2, 1024, 2048, 1, 2048, 0, 64, 128, 1, S128);
  make_map(enc, &mp.wo, d_in[2], 3, 64, 1024, 16, 2048, 128, 64, 64, 2, S128);
  make_map(enc, &mp.xs, d_in[0], 2, 1024, 2048, 1, 2048, 0, 256, 16, 1, S0);
  make_map(enc, &mp.gate, d_in[5], 2, 3584, 1024, 1, 7168, 0, 32, 32, 1, S64);
  make_map(enc, &mp.up, d_in[6], 2, 3584, 1024, 1, 7168, 0, 32, 32, 1, S64);
  make_map(enc, &mp.down, d_in[7], 2, 1024, 3584, 1, 2048, 0, 64, 32, 1, S128);
  make_map(enc, &mp.xns, xn, 2, 1024, 2048, 1, 2048, 0, 256, 16, 1, S0);
  make_map(enc, &mp.out, d_out, 2, 1024, 2048, 1, 2048, 0, 64, 16, 1, S128);
  cudaFuncSetAttribute(fused_kernel, cudaFuncAttributeMaxDynamicSharedMemorySize, SMEM_BYTES);
  fused_kernel<<<128, 512, SMEM_BYTES>>>(mp, (const __nv_bfloat16*)d_in[4]);
}
```

```cpp
#include <cuda_runtime.h>
#include <cuda.h>
#include <cuda_bf16.h>
#include <stdint.h>

namespace {

template <int TA, int TB>
__device__ __forceinline__ void wgmma_n8_ss(float (&d)[4], uint64_t da, uint64_t db, int sc) {
  asm volatile("{\n.reg .pred p;\nsetp.ne.b32 p, %6, 0;\n"
    "wgmma.mma_async.sync.aligned.m64n8k16.f32.bf16.bf16 {%0, %1, %2, %3}, %4, %5, p, 1, 1, %7, %8;\n}\n"
    : "+f"(d[0]), "+f"(d[1]), "+f"(d[2]), "+f"(d[3])
    : "l"(da), "l"(db), "r"(sc), "n"(TA), "n"(TB));
}
template <int TB>
__device__ __forceinline__ void wgmma_n40_rs(float (&d)[20], uint32_t a0, uint32_t a1, uint32_t a2, uint32_t a3, uint64_t db, int sc) {
  asm volatile("{\n.reg .pred p;\nsetp.ne.b32 p, %25, 0;\n"
    "wgmma.mma_async.sync.aligned.m64n40k16.f32.bf16.bf16 {%0, %1, %2, %3, %4, %5, %6, %7, %8, %9, %10, %11, %12, %13, %14, %15, %16, %17, %18, %19}, {%20,%21,%22,%23}, %24, p, 1, 1, %26;\n}\n"
    : "+f"(d[0]), "+f"(d[1]), "+f"(d[2]), "+f"(d[3]), "+f"(d[4]), "+f"(d[5]), "+f"(d[6]), "+f"(d[7]),
      "+f"(d[8]), "+f"(d[9]), "+f"(d[10]), "+f"(d[11]), "+f"(d[12]), "+f"(d[13]), "+f"(d[14]), "+f"(d[15]),
      "+f"(d[16]), "+f"(d[17]), "+f"(d[18]), "+f"(d[19])
    : "r"(a0), "r"(a1), "r"(a2), "r"(a3), "l"(db), "r"(sc), "n"(TB));
}
template <int TB>
__device__ __forceinline__ void wgmma_n64_rs(float (&d)[32], uint32_t a0, uint32_t a1, uint32_t a2, uint32_t a3, uint64_t db, int sc) {
  asm volatile("{\n.reg .pred p;\nsetp.ne.b32 p, %37, 0;\n"
    "wgmma.mma_async.sync.aligned.m64n64k16.f32.bf16.bf16 {%0, %1, %2, %3, %4, %5, %6, %7, %8, %9, %10, %11, %12, %13, %14, %15, %16, %17, %18, %19, %20, %21, %22, %23, %24, %25, %26, %27, %28, %29, %30, %31}, {%32,%33,%34,%35}, %36, p, 1, 1, %38;\n}\n"
    : "+f"(d[0]), "+f"(d[1]), "+f"(d[2]), "+f"(d[3]), "+f"(d[4]), "+f"(d[5]), "+f"(d[6]), "+f"(d[7]),
      "+f"(d[8]), "+f"(d[9]), "+f"(d[10]), "+f"(d[11]), "+f"(d[12]), "+f"(d[13]), "+f"(d[14]), "+f"(d[15]),
      "+f"(d[16]), "+f"(d[17]), "+f"(d[18]), "+f"(d[19]), "+f"(d[20]), "+f"(d[21]), "+f"(d[22]), "+f"(d[23]),
      "+f"(d[24]), "+f"(d[25]), "+f"(d[26]), "+f"(d[27]), "+f"(d[28]), "+f"(d[29]), "+f"(d[30]), "+f"(d[31])
    : "r"(a0), "r"(a1), "r"(a2), "r"(a3), "l"(db), "r"(sc), "n"(TB));
}
template <int TA, int TB>
__device__ __forceinline__ void wgmma_n128_ss(float (&d)[64], uint64_t da, uint64_t db, int sc) {
  asm volatile("{\n.reg .pred p;\nsetp.ne.b32 p, %66, 0;\n"
    "wgmma.mma_async.sync.aligned.m64n128k16.f32.bf16.bf16 {%0, %1, %2, %3, %4, %5, %6, %7, %8, %9, %10, %11, %12, %13, %14, %15, %16, %17, %18, %19, %20, %21, %22, %23, %24, %25, %26, %27, %28, %29, %30, %31, %32, %33, %34, %35, %36, %37, %38, %39, %40, %41, %42, %43, %44, %45, %46, %47, %48, %49, %50, %51, %52, %53, %54, %55, %56, %57, %58, %59, %60, %61, %62, %63}, %64, %65, p, 1, 1, %67, %68;\n}\n"
    : "+f"(d[0]), "+f"(d[1]), "+f"(d[2]), "+f"(d[3]), "+f"(d[4]), "+f"(d[5]), "+f"(d[6]), "+f"(d[7]),
      "+f"(d[8]), "+f"(d[9]), "+f"(d[10]), "+f"(d[11]), "+f"(d[12]), "+f"(d[13]), "+f"(d[14]), "+f"(d[15]),
      "+f"(d[16]), "+f"(d[17]), "+f"(d[18]), "+f"(d[19]), "+f"(d[20]), "+f"(d[21]), "+f"(d[22]), "+f"(d[23]),
      "+f"(d[24]), "+f"(d[25]), "+f"(d[26]), "+f"(d[27]), "+f"(d[28]), "+f"(d[29]), "+f"(d[30]), "+f"(d[31]),
      "+f"(d[32]), "+f"(d[33]), "+f"(d[34]), "+f"(d[35]), "+f"(d[36]), "+f"(d[37]), "+f"(d[38]), "+f"(d[39]),
      "+f"(d[40]), "+f"(d[41]), "+f"(d[42]), "+f"(d[43]), "+f"(d[44]), "+f"(d[45]), "+f"(d[46]), "+f"(d[47]),
      "+f"(d[48]), "+f"(d[49]), "+f"(d[50]), "+f"(d[51]), "+f"(d[52]), "+f"(d[53]), "+f"(d[54]), "+f"(d[55]),
      "+f"(d[56]), "+f"(d[57]), "+f"(d[58]), "+f"(d[59]), "+f"(d[60]), "+f"(d[61]), "+f"(d[62]), "+f"(d[63])
    : "l"(da), "l"(db), "r"(sc), "n"(TA), "n"(TB));
}
template <int TB>
__device__ __forceinline__ void wgmma_n128_rs(float (&d)[64], uint32_t a0, uint32_t a1, uint32_t a2, uint32_t a3, uint64_t db, int sc) {
  asm volatile("{\n.reg .pred p;\nsetp.ne.b32 p, %69, 0;\n"
    "wgmma.mma_async.sync.aligned.m64n128k16.f32.bf16.bf16 {%0, %1, %2, %3, %4, %5, %6, %7, %8, %9, %10, %11, %12, %13, %14, %15, %16, %17, %18, %19, %20, %21, %22, %23, %24, %25, %26, %27, %28, %29, %30, %31, %32, %33, %34, %35, %36, %37, %38, %39, %40, %41, %42, %43, %44, %45, %46, %47, %48, %49, %50, %51, %52, %53, %54, %55, %56, %57, %58, %59, %60, %61, %62, %63}, {%64,%65,%66,%67}, %68, p, 1, 1, %70;\n}\n"
    : "+f"(d[0]), "+f"(d[1]), "+f"(d[2]), "+f"(d[3]), "+f"(d[4]), "+f"(d[5]), "+f"(d[6]), "+f"(d[7]),
      "+f"(d[8]), "+f"(d[9]), "+f"(d[10]), "+f"(d[11]), "+f"(d[12]), "+f"(d[13]), "+f"(d[14]), "+f"(d[15]),
      "+f"(d[16]), "+f"(d[17]), "+f"(d[18]), "+f"(d[19]), "+f"(d[20]), "+f"(d[21]), "+f"(d[22]), "+f"(d[23]),
      "+f"(d[24]), "+f"(d[25]), "+f"(d[26]), "+f"(d[27]), "+f"(d[28]), "+f"(d[29]), "+f"(d[30]), "+f"(d[31]),
      "+f"(d[32]), "+f"(d[33]), "+f"(d[34]), "+f"(d[35]), "+f"(d[36]), "+f"(d[37]), "+f"(d[38]), "+f"(d[39]),
      "+f"(d[40]), "+f"(d[41]), "+f"(d[42]), "+f"(d[43]), "+f"(d[44]), "+f"(d[45]), "+f"(d[46]), "+f"(d[47]),
      "+f"(d[48]), "+f"(d[49]), "+f"(d[50]), "+f"(d[51]), "+f"(d[52]), "+f"(d[53]), "+f"(d[54]), "+f"(d[55]),
      "+f"(d[56]), "+f"(d[57]), "+f"(d[58]), "+f"(d[59]), "+f"(d[60]), "+f"(d[61]), "+f"(d[62]), "+f"(d[63])
    : "r"(a0), "r"(a1), "r"(a2), "r"(a3), "l"(db), "r"(sc), "n"(TB));
}

__device__ __forceinline__ void poll1(uint32_t (&v)[1], const void* p, uint32_t tag, uint32_t mask) {
  asm volatile("{\n.reg .pred p, q;\n.reg .u32 c, b;\n.reg .b64 x, y;\n.reg .b128 z;\nmov.u32 c, 0;\nLW:\n"
               "ld.relaxed.gpu.global.u32 %0, [%1+0];\n"
               "xor.b32 b, %0, %2;\n"
               "and.b32 b, b, %3;\nsetp.eq.u32 p, b, 0;\nvote.sync.all.pred p, p, 0xffffffff;\n@p bra.uni LD;\n"
               "nanosleep.u32 150;\nadd.u32 c, c, 1;\nsetp.lt.u32 q, c, 1000000;\n@q bra.uni LW;\ntrap;\nLD:\n}"
               : "=&r"(v[0])
               : "l"(p), "r"(tag), "r"(mask) : "memory");
}
__device__ __forceinline__ void poll_pair(uint32_t (&v)[2], const void* p, uint32_t tag, uint32_t mask) {
  asm volatile("{\n.reg .pred p, q;\n.reg .u32 c, b;\n.reg .b64 x, y;\n.reg .b128 z;\nmov.u32 c, 0;\nLW:\n"
               "ld.relaxed.gpu.global.b64 x, [%2+0];\nmov.b64 {%0,%1}, x;\n"
               "xor.b32 b, %0, %3;\n"
               "and.b32 b, b, %4;\nsetp.eq.u32 p, b, 0;\nvote.sync.all.pred p, p, 0xffffffff;\n@p bra.uni LD;\n"
               "nanosleep.u32 100;\nadd.u32 c, c, 1;\nsetp.lt.u32 q, c, 1000000;\n@q bra.uni LW;\ntrap;\nLD:\n}"
               : "=&r"(v[0]), "=&r"(v[1])
               : "l"(p), "r"(tag), "r"(mask) : "memory");
}
__device__ __forceinline__ void poll_quad(uint32_t (&v)[4], const void* p, uint32_t tag, uint32_t mask) {
  asm volatile("{\n.reg .pred p, q;\n.reg .u32 c, b;\n.reg .b64 x, y;\n.reg .b128 z;\nmov.u32 c, 0;\nLW:\n"
               "ld.relaxed.gpu.global.v4.u32 {%0,%1,%2,%3}, [%4+0];\n"
               "xor.b32 b, %0, %5;\n"
               "lop3.b32 b, b, %1, %5, 0xf6;\nlop3.b32 b, b, %2, %5, 0xf6;\nlop3.b32 b, b, %3, %5, 0xf6;\n"
               "and.b32 b, b, %6;\nsetp.eq.u32 p, b, 0;\nvote.sync.all.pred p, p, 0xffffffff;\n@p bra.uni LD;\n"
               "nanosleep.u32 300;\nadd.u32 c, c, 1;\nsetp.lt.u32 q, c, 1000000;\n@q bra.uni LW;\ntrap;\nLD:\n}"
               : "=&r"(v[0]), "=&r"(v[1]), "=&r"(v[2]), "=&r"(v[3])
               : "l"(p), "r"(tag), "r"(mask) : "memory");
}
__device__ __forceinline__ void poll8(uint32_t (&v)[8], const void* p, uint32_t tag, uint32_t mask) {
  asm volatile("{\n.reg .pred p, q;\n.reg .u32 c, b;\n.reg .b64 x, y;\n.reg .b128 z;\nmov.u32 c, 0;\nLW:\n"
               "ld.relaxed.gpu.global.u32 %0, [%8+0];\n"
               "ld.relaxed.gpu.global.u32 %1, [%8+2048];\n"
               "ld.relaxed.gpu.global.u32 %2, [%8+4096];\n"
               "ld.relaxed.gpu.global.u32 %3, [%8+6144];\n"
               "ld.relaxed.gpu.global.u32 %4, [%8+8192];\n"
               "ld.relaxed.gpu.global.u32 %5, [%8+10240];\n"
               "ld.relaxed.gpu.global.u32 %6, [%8+12288];\n"
               "ld.relaxed.gpu.global.u32 %7, [%8+14336];\n"
               "xor.b32 b, %0, %9;\n"
               "lop3.b32 b, b, %1, %9, 0xf6;\nlop3.b32 b, b, %2, %9, 0xf6;\nlop3.b32 b, b, %3, %9, 0xf6;\nlop3.b32 b, b, %4, %9, 0xf6;\n"
               "lop3.b32 b, b, %5, %9, 0xf6;\nlop3.b32 b, b, %6, %9, 0xf6;\nlop3.b32 b, b, %7, %9, 0xf6;\n"
               "and.b32 b, b, %10;\nsetp.eq.u32 p, b, 0;\nvote.sync.all.pred p, p, 0xffffffff;\n@p bra.uni LD;\n"
               "nanosleep.u32 200;\nadd.u32 c, c, 1;\nsetp.lt.u32 q, c, 1000000;\n@q bra.uni LW;\ntrap;\nLD:\n}"
               : "=&r"(v[0]), "=&r"(v[1]), "=&r"(v[2]), "=&r"(v[3]), "=&r"(v[4]), "=&r"(v[5]), "=&r"(v[6]), "=&r"(v[7])
               : "l"(p), "r"(tag), "r"(mask) : "memory");
}
__device__ __forceinline__ void poll16(uint32_t (&v)[16], const void* p, uint32_t tag, uint32_t mask) {
  asm volatile("{\n.reg .pred p, q;\n.reg .u32 c, b;\n.reg .b64 x, y;\n.reg .b128 z;\nmov.u32 c, 0;\nLW:\n"
               "ld.relaxed.gpu.global.u32 %0, [%16+0];\n"
               "ld.relaxed.gpu.global.u32 %1, [%16+4096];\n"
               "ld.relaxed.gpu.global.u32 %2, [%16+8192];\n"
               "ld.relaxed.gpu.global.u32 %3, [%16+12288];\n"
               "ld.relaxed.gpu.global.u32 %4, [%16+16384];\n"
               "ld.relaxed.gpu.global.u32 %5, [%16+20480];\n"
               "ld.relaxed.gpu.global.u32 %6, [%16+24576];\n"
               "ld.relaxed.gpu.global.u32 %7, [%16+28672];\n"
               "ld.relaxed.gpu.global.u32 %8, [%16+32768];\n"
               "ld.relaxed.gpu.global.u32 %9, [%16+36864];\n"
               "ld.relaxed.gpu.global.u32 %10, [%16+40960];\n"
               "ld.relaxed.gpu.global.u32 %11, [%16+45056];\n"
               "ld.relaxed.gpu.global.u32 %12, [%16+49152];\n"
               "ld.relaxed.gpu.global.u32 %13, [%16+53248];\n"
               "ld.relaxed.gpu.global.u32 %14, [%16+57344];\n"
               "ld.relaxed.gpu.global.u32 %15, [%16+61440];\n"
               "xor.b32 b, %0, %17;\n"
               "lop3.b32 b, b, %1, %17, 0xf6;\nlop3.b32 b, b, %2, %17, 0xf6;\nlop3.b32 b, b, %3, %17, 0xf6;\nlop3.b32 b, b, %4, %17, 0xf6;\n"
               "lop3.b32 b, b, %5, %17, 0xf6;\nlop3.b32 b, b, %6, %17, 0xf6;\nlop3.b32 b, b, %7, %17, 0xf6;\nlop3.b32 b, b, %8, %17, 0xf6;\n"
               "lop3.b32 b, b, %9, %17, 0xf6;\nlop3.b32 b, b, %10, %17, 0xf6;\nlop3.b32 b, b, %11, %17, 0xf6;\nlop3.b32 b, b, %12, %17, 0xf6;\n"
               "lop3.b32 b, b, %13, %17, 0xf6;\nlop3.b32 b, b, %14, %17, 0xf6;\nlop3.b32 b, b, %15, %17, 0xf6;\n"
               "and.b32 b, b, %18;\nsetp.eq.u32 p, b, 0;\nvote.sync.all.pred p, p, 0xffffffff;\n@p bra.uni LD;\n"
               "nanosleep.u32 200;\nadd.u32 c, c, 1;\nsetp.lt.u32 q, c, 1000000;\n@q bra.uni LW;\ntrap;\nLD:\n}"
               : "=&r"(v[0]), "=&r"(v[1]), "=&r"(v[2]), "=&r"(v[3]), "=&r"(v[4]), "=&r"(v[5]), "=&r"(v[6]), "=&r"(v[7]), "=&r"(v[8]), "=&r"(v[9]), "=&r"(v[10]), "=&r"(v[11]), "=&r"(v[12]), "=&r"(v[13]), "=&r"(v[14]), "=&r"(v[15])
               : "l"(p), "r"(tag), "r"(mask) : "memory");
}
__device__ __forceinline__ void poll_keys(uint32_t (&v)[16], const void* p, uint32_t tag, uint32_t mask) {
  asm volatile("{\n.reg .pred p, q;\n.reg .u32 c, b;\n.reg .b64 x, y;\n.reg .b128 z;\nmov.u32 c, 0;\nLW:\n"
               "ld.relaxed.gpu.global.v2.b64 {x, y}, [%16+0];\nmov.b64 {%0,%1}, x;\nmov.b64 {%2,%3}, y;\n"
               "ld.relaxed.gpu.global.v2.b64 {x, y}, [%16+4096];\nmov.b64 {%4,%5}, x;\nmov.b64 {%6,%7}, y;\n"
               "ld.relaxed.gpu.global.v2.b64 {x, y}, [%16+8192];\nmov.b64 {%8,%9}, x;\nmov.b64 {%10,%11}, y;\n"
               "ld.relaxed.gpu.global.v2.b64 {x, y}, [%16+12288];\nmov.b64 {%12,%13}, x;\nmov.b64 {%14,%15}, y;\n"
               "xor.b32 b, %0, %17;\n"
               "lop3.b32 b, b, %2, %17, 0xf6;\nlop3.b32 b, b, %4, %17, 0xf6;\nlop3.b32 b, b, %6, %17, 0xf6;\nlop3.b32 b, b, %8, %17, 0xf6;\n"
               "lop3.b32 b, b, %10, %17, 0xf6;\nlop3.b32 b, b, %12, %17, 0xf6;\nlop3.b32 b, b, %14, %17, 0xf6;\n"
               "and.b32 b, b, %18;\nsetp.eq.u32 p, b, 0;\nvote.sync.all.pred p, p, 0xffffffff;\n@p bra.uni LD;\n"
               "nanosleep.u32 20;\nadd.u32 c, c, 1;\nsetp.lt.u32 q, c, 1000000;\n@q bra.uni LW;\ntrap;\nLD:\n}"
               : "=&r"(v[0]), "=&r"(v[1]), "=&r"(v[2]), "=&r"(v[3]), "=&r"(v[4]), "=&r"(v[5]), "=&r"(v[6]), "=&r"(v[7]), "=&r"(v[8]), "=&r"(v[9]), "=&r"(v[10]), "=&r"(v[11]), "=&r"(v[12]), "=&r"(v[13]), "=&r"(v[14]), "=&r"(v[15])
               : "l"(p), "r"(tag), "r"(mask) : "memory");
}
__device__ __forceinline__ void poll7x4(uint32_t (&v)[28], const void* p, uint32_t tag, uint32_t mask) {
  asm volatile("{\n.reg .pred p, q;\n.reg .u32 c, b;\n.reg .b64 x, y;\n.reg .b128 z;\nmov.u32 c, 0;\nLW:\n"
               "ld.relaxed.gpu.global.v4.u32 {%0,%1,%2,%3}, [%28+0];\n"
               "ld.relaxed.gpu.global.v4.u32 {%4,%5,%6,%7}, [%28+2048];\n"
               "ld.relaxed.gpu.global.v4.u32 {%8,%9,%10,%11}, [%28+4096];\n"
               "ld.relaxed.gpu.global.v4.u32 {%12,%13,%14,%15}, [%28+6144];\n"
               "ld.relaxed.gpu.global.v4.u32 {%16,%17,%18,%19}, [%28+8192];\n"
               "ld.relaxed.gpu.global.v4.u32 {%20,%21,%22,%23}, [%28+10240];\n"
               "ld.relaxed.gpu.global.v4.u32 {%24,%25,%26,%27}, [%28+12288];\n"
               "xor.b32 b, %0, %29;\n"
               "lop3.b32 b, b, %1, %29, 0xf6;\nlop3.b32 b, b, %2, %29, 0xf6;\nlop3.b32 b, b, %3, %29, 0xf6;\nlop3.b32 b, b, %4, %29, 0xf6;\n"
               "lop3.b32 b, b, %5, %29, 0xf6;\nlop3.b32 b, b, %6, %29, 0xf6;\nlop3.b32 b, b, %7, %29, 0xf6;\nlop3.b32 b, b, %8, %29, 0xf6;\n"
               "lop3.b32 b, b, %9, %29, 0xf6;\nlop3.b32 b, b, %10, %29, 0xf6;\nlop3.b32 b, b, %11, %29, 0xf6;\nlop3.b32 b, b, %12, %29, 0xf6;\n"
               "lop3.b32 b, b, %13, %29, 0xf6;\nlop3.b32 b, b, %14, %29, 0xf6;\nlop3.b32 b, b, %15, %29, 0xf6;\nlop3.b32 b, b, %16, %29, 0xf6;\n"
               "lop3.b32 b, b, %17, %29, 0xf6;\nlop3.b32 b, b, %18, %29, 0xf6;\nlop3.b32 b, b, %19, %29, 0xf6;\nlop3.b32 b, b, %20, %29, 0xf6;\n"
               "lop3.b32 b, b, %21, %29, 0xf6;\nlop3.b32 b, b, %22, %29, 0xf6;\nlop3.b32 b, b, %23, %29, 0xf6;\nlop3.b32 b, b, %24, %29, 0xf6;\n"
               "lop3.b32 b, b, %25, %29, 0xf6;\nlop3.b32 b, b, %26, %29, 0xf6;\nlop3.b32 b, b, %27, %29, 0xf6;\n"
               "and.b32 b, b, %30;\nsetp.eq.u32 p, b, 0;\nvote.sync.all.pred p, p, 0xffffffff;\n@p bra.uni LD;\n"
               "nanosleep.u32 200;\nadd.u32 c, c, 1;\nsetp.lt.u32 q, c, 1000000;\n@q bra.uni LW;\ntrap;\nLD:\n}"
               : "=&r"(v[0]), "=&r"(v[1]), "=&r"(v[2]), "=&r"(v[3]), "=&r"(v[4]), "=&r"(v[5]), "=&r"(v[6]), "=&r"(v[7]), "=&r"(v[8]), "=&r"(v[9]), "=&r"(v[10]), "=&r"(v[11]), "=&r"(v[12]), "=&r"(v[13]), "=&r"(v[14]), "=&r"(v[15]), "=&r"(v[16]), "=&r"(v[17]), "=&r"(v[18]), "=&r"(v[19]), "=&r"(v[20]), "=&r"(v[21]), "=&r"(v[22]), "=&r"(v[23]), "=&r"(v[24]), "=&r"(v[25]), "=&r"(v[26]), "=&r"(v[27])
               : "l"(p), "r"(tag), "r"(mask) : "memory");
}
__device__ __forceinline__ void poll_kvp(uint32_t (&v)[16], const void* p, uint32_t tag, uint32_t mask) {
  asm volatile("{\n.reg .pred p, q;\n.reg .u32 c, b;\n.reg .b64 x, y;\n.reg .b128 z;\nmov.u32 c, 0;\nLW:\n"
               "ld.relaxed.gpu.global.b128 z, [%16+0];\nmov.b128 {x, y}, z;\nmov.b64 {%0,%1}, x;\nmov.b64 {%2,%3}, y;\n"
               "ld.relaxed.gpu.global.b128 z, [%16+8192];\nmov.b128 {x, y}, z;\nmov.b64 {%4,%5}, x;\nmov.b64 {%6,%7}, y;\n"
               "ld.relaxed.gpu.global.b128 z, [%16+16384];\nmov.b128 {x, y}, z;\nmov.b64 {%8,%9}, x;\nmov.b64 {%10,%11}, y;\n"
               "ld.relaxed.gpu.global.b128 z, [%16+24576];\nmov.b128 {x, y}, z;\nmov.b64 {%12,%13}, x;\nmov.b64 {%14,%15}, y;\n"
               "xor.b32 b, %0, %17;\n"
               "lop3.b32 b, b, %4, %17, 0xf6;\nlop3.b32 b, b, %8, %17, 0xf6;\nlop3.b32 b, b, %12, %17, 0xf6;\n"
               "and.b32 b, b, %18;\nsetp.eq.u32 p, b, 0;\nvote.sync.all.pred p, p, 0xffffffff;\n@p bra.uni LD;\n"
               "nanosleep.u32 100;\nadd.u32 c, c, 1;\nsetp.lt.u32 q, c, 1000000;\n@q bra.uni LW;\ntrap;\nLD:\n}"
               : "=&r"(v[0]), "=&r"(v[1]), "=&r"(v[2]), "=&r"(v[3]), "=&r"(v[4]), "=&r"(v[5]), "=&r"(v[6]), "=&r"(v[7]), "=&r"(v[8]), "=&r"(v[9]), "=&r"(v[10]), "=&r"(v[11]), "=&r"(v[12]), "=&r"(v[13]), "=&r"(v[14]), "=&r"(v[15])
               : "l"(p), "r"(tag), "r"(mask) : "memory");
}
__device__ __forceinline__ void poll_kv(uint32_t (&v)[16], const void* p, uint32_t tag, uint32_t mask) {
  asm volatile("{\n.reg .pred p, q;\n.reg .u32 c, b;\n.reg .b64 x, y;\n.reg .b128 z;\nmov.u32 c, 0;\nLW:\n"
               "ld.relaxed.gpu.global.b128 z, [%16+0];\nmov.b128 {x, y}, z;\nmov.b64 {%0,%1}, x;\nmov.b64 {%2,%3}, y;\n"
               "ld.relaxed.gpu.global.b128 z, [%16+2048];\nmov.b128 {x, y}, z;\nmov.b64 {%4,%5}, x;\nmov.b64 {%6,%7}, y;\n"
               "ld.relaxed.gpu.global.b128 z, [%16+4096];\nmov.b128 {x, y}, z;\nmov.b64 {%8,%9}, x;\nmov.b64 {%10,%11}, y;\n"
               "ld.relaxed.gpu.global.b128 z, [%16+6144];\nmov.b128 {x, y}, z;\nmov.b64 {%12,%13}, x;\nmov.b64 {%14,%15}, y;\n"
               "xor.b32 b, %0, %17;\n"
               "lop3.b32 b, b, %4, %17, 0xf6;\nlop3.b32 b, b, %8, %17, 0xf6;\nlop3.b32 b, b, %12, %17, 0xf6;\n"
               "and.b32 b, b, %18;\nsetp.eq.u32 p, b, 0;\nvote.sync.all.pred p, p, 0xffffffff;\n@p bra.uni LD;\n"
               "nanosleep.u32 100;\nadd.u32 c, c, 1;\nsetp.lt.u32 q, c, 1000000;\n@q bra.uni LW;\ntrap;\nLD:\n}"
               : "=&r"(v[0]), "=&r"(v[1]), "=&r"(v[2]), "=&r"(v[3]), "=&r"(v[4]), "=&r"(v[5]), "=&r"(v[6]), "=&r"(v[7]), "=&r"(v[8]), "=&r"(v[9]), "=&r"(v[10]), "=&r"(v[11]), "=&r"(v[12]), "=&r"(v[13]), "=&r"(v[14]), "=&r"(v[15])
               : "l"(p), "r"(tag), "r"(mask) : "memory");
}

__device__ __align__(1024) __nv_bfloat16 g_o[2048 * 1024];
__device__ __align__(128) uint2 g_keys[2048];
__device__ __align__(128) uint32_t g_csum[18 * 1024];
__device__ __align__(128) uint32_t g_z[16 * 1024];
__device__ __align__(128) uint4 g_kvp[128 * 512];
__device__ __align__(128) uint4 g_kv[8 * 512];
__device__ __align__(128) uint32_t g_h[112 * 256];
__device__ __align__(128) uint32_t g_yp[128 * 512];
__device__ __align__(128) uint32_t g_xsel[4096 + 32];
__device__ __align__(128) uint32_t g_flagO[256 * 8];
__device__ __align__(128) uint32_t g_flagR[32];
__device__ uint32_t g_epoch;

constexpr uint32_t RING = 1024, SLOT = 32768, SMEM_BYTES = 232448;
constexpr int NST = 5, HST = 6;
constexpr uint32_t STG = RING + 163840, AUX = RING + 196608, FR = RING + 212992, MISC = RING + 229376;
constexpr uint32_t B_FULL = MISC, B_EMPTY = MISC + 48, B_XS = MISC + 96, B_SEL = MISC + 128, B_XRES = MISC + 136, B_WK = MISC + 144, B_CSDN = MISC + 152,
                   B_FR = MISC + 160, B_FE = MISC + 200, B_DR = MISC + 240, B_DE = MISC + 272, NBAR = 38;
constexpr uint32_t S_EPOCH = MISC + 304, S_NCAND = MISC + 308, S_SEL = MISC + 320, S_WMAX = MISC + 352,
                   S_KSTAT = MISC + 512, S_CSK = MISC + 1536, S_CSV = MISC + 2048, S_CSQ = MISC + 2560, S_ONES = MISC + 512;
constexpr uint32_t KVB_P0 = AUX, KVB_Z = AUX + 4096, KVB_P1 = AUX + 5120, HOP = AUX + 9216, GR = FR - 4096;
enum { NB_KVP = 0, NB_KV = 1, NB_VQ = 2, NB_WG0 = 3, NB_FDONE = 4, NB_PK = 5, NB_KVB = 6, NB_WG1 = 7, NB_WG2 = 8, NB_CSQ = 9,
       NB_Y = 10, NB_ST = 11, NB_OWN0 = 12, NB_OWN1 = 13, NB_Q0 = 14, NB_H1 = 15 };

#define XS_AT 0
#define XS_STEP 1
#define PFD 6
#define FFN_AT 12
constexpr float LOG2E = 1.4426950408889634f, LN2 = 0.6931471805599453f;

#define ELECT "{\n.reg .pred p;\nelect.sync _|p, 0xffffffff;\n"
#define TMA2D "cp.async.bulk.tensor.2d.shared::cluster.global.mbarrier::complete_tx::bytes"
#define TMA3D "cp.async.bulk.tensor.3d.shared::cluster.global.mbarrier::complete_tx::bytes"
__device__ __forceinline__ void e_expect(uint32_t b, uint32_t n) {
  asm volatile(ELECT "@p mbarrier.arrive.expect_tx.shared::cta.b64 _, [%0], %1;\n}" ::"r"(b), "r"(n) : "memory");
}
__device__ __forceinline__ void e_arrive(uint32_t b) { asm volatile(ELECT "@p mbarrier.arrive.shared::cta.b64 _, [%0];\n}" ::"r"(b) : "memory"); }
__device__ __forceinline__ void e_tma2d(uint32_t dst, const CUtensorMap* m, int c0, int c1, uint32_t bar) {
  asm volatile(ELECT "@p " TMA2D " [%0], [%1, {%3, %4}], [%2];\n}" ::"r"(dst), "l"(m), "r"(bar), "r"(c0), "r"(c1) : "memory");
}
__device__ __forceinline__ void e_tma2d_ef(uint32_t dst, const CUtensorMap* m, int c0, int c1, uint32_t bar, uint64_t pol) {
  asm volatile(ELECT "@p " TMA2D ".L2::cache_hint [%0], [%1, {%3, %4}], [%2], %5;\n}" ::"r"(dst), "l"(m), "r"(bar), "r"(c0), "r"(c1), "l"(pol) : "memory");
}
__device__ __forceinline__ void e_tma3d(uint32_t dst, const CUtensorMap* m, int c1, int c2, uint32_t bar) {
  asm volatile(ELECT "@p " TMA3D " [%0], [%1, {0, %3, %4}], [%2];\n}" ::"r"(dst), "l"(m), "r"(bar), "r"(c1), "r"(c2) : "memory");
}
__device__ __forceinline__ void e_store2d(const CUtensorMap* m, int c0, int c1, uint32_t src) {
  asm volatile(ELECT "@p cp.async.bulk.tensor.2d.global.shared::cta.bulk_group [%0, {%2, %3}], [%1];\n}" ::"l"(m), "r"(src), "r"(c0), "r"(c1) : "memory");
}
__device__ __forceinline__ void e_tma3d_ef(uint32_t dst, const CUtensorMap* m, int c0, int c1, uint32_t bar, uint64_t pol) {
  asm volatile(ELECT "@p " TMA3D ".L2::cache_hint [%0], [%1, {%3, %4, 0}], [%2], %5;\n}" ::"r"(dst), "l"(m), "r"(bar), "r"(c0), "r"(c1), "l"(pol) : "memory");
}
__device__ __forceinline__ void e_load(uint32_t dst, const void* src, uint32_t n, uint32_t bar) {
  asm volatile(ELECT "@p cp.async.bulk.shared::cluster.global.mbarrier::complete_tx::bytes [%0], [%1], %2, [%3];\n}" ::"r"(dst), "l"(src), "r"(n), "r"(bar) : "memory");
}
template <int I0, int I1> __device__ __forceinline__ void e_init() {
#pragma unroll
  for (int i = I0; i < I1; i++) asm volatile(ELECT "@p mbarrier.init.shared::cta.b64 [%0], %1;\n}" ::"r"(MISC + 8 * i), "r"(MISC + 8 * i == B_CSDN ? 4 : 1) : "memory");
  asm volatile("fence.mbarrier_init.release.cluster;" ::: "memory");
}
__device__ __forceinline__ void e_pfmap(const CUtensorMap* m) { asm volatile(ELECT "@p prefetch.tensormap [%0];\n}" ::"l"(m) : "memory"); }
__device__ __forceinline__ void bulk_wait_read() { asm volatile("cp.async.bulk.commit_group;\ncp.async.bulk.wait_group.read 0;" ::: "memory"); }
__device__ __forceinline__ void e_release(uint32_t* flag, uint32_t v, int lane) {
  asm volatile("cp.async.bulk.commit_group;\ncp.async.bulk.wait_group 0;\nfence.release.gpu;" ::: "memory");
  if (lane < 8) asm volatile("st.relaxed.gpu.global.u32 [%0], %1;" ::"l"(flag + lane), "r"(v) : "memory");
}

__device__ __forceinline__ void mbar_arrive(uint32_t b) { asm volatile("mbarrier.arrive.shared::cta.b64 _, [%0];" ::"r"(b) : "memory"); }
__device__ __forceinline__ void mbar_wait(uint32_t b, uint32_t ph) {
  asm volatile("{\n.reg .pred p, q;\n.reg .u32 c;\nmov.u32 c, 0;\nLW:\nmbarrier.try_wait.parity.shared::cta.b64 p, [%0], %1;\n@p bra LD;\n"
               "add.u32 c, c, 1;\nsetp.lt.u32 q, c, 100000;\n@q bra LW;\ntrap;\nLD:\n}" ::"r"(b), "r"(ph) : "memory");
}
__device__ __forceinline__ void nb_sync(int id, int n) { asm volatile("bar.sync %0, %1;" ::"r"(id), "r"(n) : "memory"); }
__device__ __forceinline__ void nb_arrive(int id, int n) { asm volatile("bar.arrive %0, %1;" ::"r"(id), "r"(n) : "memory"); }
__device__ __forceinline__ void wg_fence() { asm volatile("wgmma.fence.sync.aligned;" ::: "memory"); }
__device__ __forceinline__ void wg_commit() { asm volatile("wgmma.commit_group.sync.aligned;" ::: "memory"); }
template <int N> __device__ __forceinline__ void wg_wait() { asm volatile("wgmma.wait_group.sync.aligned %0;" ::"n"(N) : "memory"); }
template <int N> __device__ __forceinline__ void reg_fence(float (&a)[N]) {
#pragma unroll
  for (int i = 0; i < N; i++) asm volatile("" : "+f"(a[i])::"memory");
}
template <int N> __device__ __forceinline__ void reg_zero(float (&a)[N]) {
#pragma unroll
  for (int i = 0; i < N; i++) a[i] = 0.f;
}
__device__ __forceinline__ constexpr uint64_t mkdesc(uint32_t addr, uint32_t lbo, uint32_t sbo, uint32_t swz) {
  return (uint64_t)(addr >> 4) | ((uint64_t)(lbo >> 4) << 16) | ((uint64_t)(sbo >> 4) << 32) | ((uint64_t)swz << 62);
}
__device__ __forceinline__ void fence_async_smem() { asm volatile("fence.proxy.async.shared::cta;" ::: "memory"); }
__device__ __forceinline__ void fence_async_glob() { asm volatile("fence.proxy.async.global;" ::: "memory"); }
__device__ __forceinline__ void fence_acq() { asm volatile("fence.acquire.gpu;" ::: "memory"); }
__device__ __forceinline__ void st_relaxed(uint32_t* p, uint32_t v) { asm volatile("st.relaxed.gpu.global.u32 [%0], %1;" ::"l"(p), "r"(v) : "memory"); }
__device__ __forceinline__ uint32_t ld_relaxed(const uint32_t* p) { uint32_t v; asm volatile("ld.relaxed.gpu.global.u32 %0, [%1];" : "=r"(v) : "l"(p) : "memory"); return v; }
__device__ __forceinline__ void st_unit(uint4* p, uint32_t a, uint32_t b, uint32_t c, uint32_t d, uint32_t par) {
  asm volatile("{\n.reg .b64 x, y;\n.reg .b128 z;\nmov.b64 x, {%1,%2};\nmov.b64 y, {%3,%4};\nmov.b128 z, {x, y};\nst.relaxed.gpu.global.b128 [%0], z;\n}"
               ::"l"(p), "r"((a & ~1u) | par), "r"(b), "r"(c), "r"(d) : "memory");
}
__device__ __forceinline__ void spin_guard(int& c) {
  asm volatile("{\n.reg .pred q;\nadd.u32 %0, %0, 1;\nsetp.lt.u32 q, %0, 1000000;\n@q bra LOK;\ntrap;\nLOK:\n}" : "+r"(c));
}
__device__ __forceinline__ uint4 lds128(uint32_t a) { uint4 v; asm volatile("ld.shared.v4.u32 {%0,%1,%2,%3}, [%4];" : "=r"(v.x), "=r"(v.y), "=r"(v.z), "=r"(v.w) : "r"(a)); return v; }
__device__ __forceinline__ float4 lds128f(uint32_t a) { float4 v; asm volatile("ld.shared.v4.f32 {%0,%1,%2,%3}, [%4];" : "=f"(v.x), "=f"(v.y), "=f"(v.z), "=f"(v.w) : "r"(a)); return v; }
__device__ __forceinline__ float2 lds64f(uint32_t a) { float2 v; asm volatile("ld.shared.v2.f32 {%0,%1}, [%2];" : "=f"(v.x), "=f"(v.y) : "r"(a)); return v; }
__device__ __forceinline__ uint32_t lds32(uint32_t a) { uint32_t v; asm volatile("ld.shared.u32 %0, [%1];" : "=r"(v) : "r"(a)); return v; }
__device__ __forceinline__ void sts128(uint32_t a, uint32_t x, uint32_t y, uint32_t z, uint32_t w) { asm volatile("st.shared.v4.u32 [%0], {%1,%2,%3,%4};" ::"r"(a), "r"(x), "r"(y), "r"(z), "r"(w) : "memory"); }
__device__ __forceinline__ void sts128f(uint32_t a, float x, float y, float z, float w) { asm volatile("st.shared.v4.f32 [%0], {%1,%2,%3,%4};" ::"r"(a), "f"(x), "f"(y), "f"(z), "f"(w) : "memory"); }
__device__ __forceinline__ void sts32(uint32_t a, uint32_t x) { asm volatile("st.shared.u32 [%0], %1;" ::"r"(a), "r"(x) : "memory"); }
__device__ __forceinline__ void stsm4(uint32_t a, uint32_t r0, uint32_t r1, uint32_t r2, uint32_t r3) {
  asm volatile("stmatrix.sync.aligned.m8n8.x4.shared.b16 [%0], {%1,%2,%3,%4};" ::"r"(a), "r"(r0), "r"(r1), "r"(r2), "r"(r3) : "memory");
}
__device__ __forceinline__ uint4 ldsm4(uint32_t a) {
  uint4 v; asm volatile("ldmatrix.sync.aligned.m8n8.x4.shared.b16 {%0,%1,%2,%3}, [%4];" : "=r"(v.x), "=r"(v.y), "=r"(v.z), "=r"(v.w) : "r"(a) : "memory"); return v;
}
__device__ __forceinline__ uint32_t pack(float lo, float hi) { uint32_t r; asm("cvt.rn.bf16x2.f32 %0, %1, %2;" : "=r"(r) : "f"(hi), "f"(lo)); return r; }
__device__ __forceinline__ float bf_lo(uint32_t w) { return __uint_as_float(w << 16); }
__device__ __forceinline__ float bf_hi(uint32_t w) { return __uint_as_float(w & 0xffff0000u); }
__device__ __forceinline__ float bf_round(float x) { return bf_lo(pack(x, x)); }
__device__ __forceinline__ float ex2(float x) { float v; asm("ex2.approx.ftz.f32 %0, %1;" : "=f"(v) : "f"(x)); return v; }
__device__ __forceinline__ float rcp(float x) { float v; asm("rcp.approx.ftz.f32 %0, %1;" : "=f"(v) : "f"(x)); return v; }
__device__ __forceinline__ float addsat(float a, float b) { float v; asm("add.sat.f32 %0, %1, %2;" : "=f"(v) : "f"(a), "f"(b)); return v; }
__device__ __forceinline__ float phi2(float a) { return fmaf(fmaxf(a, 0.f), LN2, addsat(ex2(a), 1e-6f)); }
__device__ __forceinline__ uint32_t ln_bf16x2(uint32_t x, uint32_t m, uint32_t hi, uint32_t lo) {
  uint32_t o;
  asm("{\n.reg .b32 d, e;\nsub.rn.bf16x2 d, %1, %2;\nmul.rn.bf16x2 e, d, %4;\nfma.rn.bf16x2 %0, d, %3, e;\n}" : "=r"(o) : "r"(x), "r"(m), "r"(hi), "r"(lo));
  return o;
}
__device__ __forceinline__ float key_score(uint32_t key) { uint32_t u = key >> 16; u = (u & 0x8000u) ? (u & 0x7fffu) : (~u & 0xffffu); return __uint_as_float(u << 16); }
__device__ __forceinline__ int key_token(uint32_t key) { return 2047 - (int)((key >> 5) & 2047u); }
__device__ __forceinline__ uint32_t tagf(float v, uint32_t par) { return (__float_as_uint(v) & ~1u) | par; }
__device__ __forceinline__ float xred(float a, float b, bool up, int o) { return (up ? b : a) + __shfl_xor_sync(0xffffffffu, up ? a : b, o); }

#define STAMP(id)
#define STAMP_IF(c, id)
#define STAMP2(i)

template <bool TRANS>
__device__ __forceinline__ void mainloop(float (&a0)[64], float (&a1)[64], int s, int ph, int handoff, bool leader) {
  uint32_t prev = 0;
#pragma unroll 1
  for (int kt = 0; kt < 16; kt++) {
    mbar_wait(B_FULL + 8 * s, ph);
    const uint64_t dw = mkdesc(RING, 8192, 1024, 1) + s * (SLOT >> 4), dx = mkdesc(RING + 16384, 16, 1024, 1) + s * (SLOT >> 4);
    wg_fence();
#pragma unroll
    for (int j = 0; j < 4; j++) {
      if (TRANS) {
        wgmma_n128_ss<1, 0>(a0, dw + j * 128, dx + j * 2, 1);
        wgmma_n128_ss<1, 0>(a1, dw + j * 128 + 512, dx + j * 2, 1);
      } else {
        wgmma_n128_ss<0, 1>(a0, dx + j * 2, dw + j * 128, 1);
        wgmma_n128_ss<0, 1>(a1, dx + j * 2 + 512, dw + j * 128, 1);
      }
    }
    wg_commit();
    if (handoff && kt == 15) nb_arrive(handoff, 256);
    wg_wait<1>();
    if (prev && leader) mbar_arrive(prev);
    prev = B_EMPTY + 8 * s;
    if (++s == NST) { s = 0; ph ^= 1; }
  }
  wg_wait<0>();
  if (leader) mbar_arrive(prev);
  reg_fence(a0);
  reg_fence(a1);
}

__device__ __forceinline__ int out_kblock(int r, int tn) {
  const int q = r - 2, half = q >= 7, pi = q - 7 * half;
  return r < 2 ? 2 * tn + r : 2 * (pi + (pi >= tn)) + half;
}

struct Maps {
  CUtensorMap wqkv, x, o, os, wo, xs, gu, down, out;
};

__global__ void __launch_bounds__(512, 1)
fused_kernel(const __grid_constant__ Maps mp, const __nv_bfloat16* __restrict__ w_r, const __nv_bfloat16* __restrict__ xg,
             const char* __restrict__ wg, const char* __restrict__ wu, const char* __restrict__ wd) {
  extern __shared__ __align__(1024) uint8_t smem_raw[];
  const int tid = threadIdx.x, lane = tid & 31;
  const int w = __shfl_sync(0xffffffffu, tid >> 5, 0);
  const int rb = blockIdx.x;
  const int bid = (rb >> 1) == 44 ? rb + 40 : (rb >> 1) == 53 ? rb + 24 : rb - 2 * (rb > 89) - 2 * (rb > 107);
  const int tn = (bid & 3) + 4 * (bid >> 6), tm = (bid >> 2) & 15;

  if (w == 12) {
    STAMP_IF(lane == 0, 0);
    e_pfmap(&mp.wqkv);
    e_pfmap(&mp.x);
    e_init<0, 6>();
  } else {
    if (w == 13) e_init<6, 22>();
    if (w == 14) e_init<22, NBAR>();
    if (w == 15) {
      sts32(S_NCAND, 0);
      asm volatile("{\n.reg .pred q;\nsetp.eq.u32 q, %0, 1024;\n@q bra LOK;\ntrap;\nLOK:\n}" ::"r"((uint32_t)__cvta_generic_to_shared(smem_raw)));
    }
    nb_sync(0, 512);
  }

  if (bid >= 128) {
    if (w == 12) {
      int s = 0, ph = 1;
#pragma unroll 1
      for (int it = 0; it < 32; it++) {
        if (it == 16 && bid == 128) mbar_wait(B_SEL, 0);
        const int c = (it & 16) * 2 + 4 * (bid & 3);
        if (it == HST) nb_sync(0, 512);
        if (it >= HST) mbar_wait(B_EMPTY + 8 * s, ph);
        e_expect(B_FULL + 8 * s, 32768);
        e_tma3d(RING + s * SLOT, &mp.wqkv, (it & 15) * 64, c, B_FULL + 8 * s);
        e_tma3d(RING + s * SLOT + 16384, &mp.wqkv, (it & 15) * 64, c + 2, B_FULL + 8 * s);
        if (++s == HST) { s = 0; ph ^= 1; }
      }
    } else if (w < 4) {
      const uint32_t par = (ld_relaxed(&g_epoch) + 1) & 1u;
      sts32(S_ONES + tid * 4, 0x3f803f80u);
      fence_async_smem();
      nb_sync(NB_WG0, 128);
      int s = 0, ph = 0;
#pragma unroll 1
      for (int mtx = 0; mtx < 2; mtx++) {
        float c[4][4];
#pragma unroll
        for (int i = 0; i < 4; i++) reg_zero(c[i]);
        uint32_t prev = 0;
#pragma unroll 1
        for (int kt = 0; kt < 16; kt++) {
          mbar_wait(B_FULL + 8 * s, ph);
          const uint64_t dw = mkdesc(RING, 8192, 1024, 1) + s * (SLOT >> 4);
          wg_fence();
#pragma unroll
          for (int j = 0; j < 16; j++) wgmma_n8_ss<1, 0>(c[j & 3], dw + (j & 3) * 512 + (j >> 2) * 128, mkdesc(S_ONES, 128, 128, 0), 1);
          wg_commit();
          wg_wait<1>();
          if (prev && tid == 0) mbar_arrive(prev);
          prev = B_EMPTY + 8 * s;
          if (++s == HST) { s = 0; ph ^= 1; }
        }
        wg_wait<0>();
        if (tid == 0) mbar_arrive(prev);
#pragma unroll
        for (int i = 0; i < 4; i++) reg_fence(c[i]);
        const int q = lane & 3;
        uint32_t* cp = g_csum + mtx * 1024 + (bid & 3) * 256 + q * 64 + w * 16 + (lane >> 2);
        st_relaxed(cp, tagf(q == 0 ? c[0][0] : q == 1 ? c[1][0] : q == 2 ? c[2][0] : c[3][0], par));
        st_relaxed(cp + 8, tagf(q == 0 ? c[0][2] : q == 1 ? c[1][2] : q == 2 ? c[2][2] : c[3][2], par));
        STAMP_IF(tid == 0, mtx ? 6 : 30);
      }
    } else if (w < 12 && bid == 128) {
      const int t = tid - 128, j = w - 4;
      const uint32_t ep = ld_relaxed(&g_epoch) + 1;
      uint32_t kk[16];
      poll_keys(kk, g_keys + t * 2, ep, 31u);
      const uint32_t k[8] = {kk[0], kk[2], kk[4], kk[6], kk[8], kk[10], kk[12], kk[14]};
      STAMP_IF(t == 0, 42);
      const uint32_t m = __reduce_max_sync(0xffffffffu, max(max(max(k[0], k[1]), max(k[2], k[3])), max(max(k[4], k[5]), max(k[6], k[7]))));
      if (lane == 0) sts32(S_WMAX + j * 4, m);
      nb_sync(NB_WG1, 256);
      const uint32_t T = __reduce_min_sync(0xffffffffu, lds32(S_WMAX + (lane & 7) * 4));
      uint32_t cnt = 0;
#pragma unroll
      for (int i = 0; i < 8; i++) cnt += k[i] >= T;
      if (cnt) {
        uint32_t pos;
        asm volatile("atom.shared.add.u32 %0, [%1], %2;" : "=r"(pos) : "r"(S_NCAND), "r"(cnt * 4) : "memory");
#pragma unroll
        for (int i = 0; i < 8; i++)
          if (k[i] >= T) { sts32(AUX + pos, k[i]); pos += 4; }
      }
      nb_sync(NB_WG1, 256);
      const uint32_t n4 = lds32(S_NCAND);
#pragma unroll 1
      for (uint32_t i = t * 4; i < n4; i += 1024) {
        const uint32_t key = lds32(AUX + i);
        uint32_t rank = 0;
#pragma unroll 4
        for (uint32_t q = 0; q < n4; q += 4) rank += lds32(AUX + q) > key;
        if (rank < 8) sts32(S_SEL + rank * 4, key);
      }
      nb_sync(NB_WG1, 256);
      STAMP_IF(t == 0, 43);
      const uint32_t key = lds32(S_SEL + j * 4);
      const int tok = key_token(key);
      uint4 v[4];
#pragma unroll
      for (int q = 0; q < 4; q++) v[q] = __ldg(reinterpret_cast<const uint4*>(xg + tok * 1024) + q * 32 + lane);
      const uint32_t st = ld_relaxed(&g_keys[tok].y);
      const float rinv = rcp(bf_lo(st)), rhi = bf_round(rinv);
      const uint32_t m2 = __byte_perm(st, 0, 0x3232), hi = pack(rhi, rhi), lo = pack(rinv - rhi, rinv - rhi);
#pragma unroll
      for (int q = 0; q < 4; q++)
        *reinterpret_cast<uint4*>(g_xsel + (q * 8 + (lane >> 2)) * 128 + j * 16 + (((lane & 3) ^ (j >> 1)) << 2)) =
            make_uint4(ln_bf16x2(v[q].x, m2, hi, lo), ln_bf16x2(v[q].y, m2, hi, lo), ln_bf16x2(v[q].z, m2, hi, lo), ln_bf16x2(v[q].w, m2, hi, lo));
      if (lane == 0) g_xsel[4096 + j] = key;
      fence_async_glob();
      nb_sync(NB_WG1, 256);
      STAMP_IF(t == 0, 44);
      if (j == 0) { e_release(g_flagR, ep, lane); e_arrive(B_SEL); }
      STAMP_IF(t == 0, 45);
    }
  } else if (w >= 12) {
    asm volatile("setmaxnreg.dec.sync.aligned.u32 32;");
    if (w == 12) {
      int s = 0, ph = 1;
#pragma unroll 1
      for (int it = 0; it < 48; it++) {
        const int c = (it < 32 ? (it & 16) + 16 : 0) + 2 * tn;
        if (it == NST) nb_sync(0, 512);
        if (it >= NST) mbar_wait(B_EMPTY + 8 * s, ph);
        e_expect(B_FULL + 8 * s, 32768);
        e_tma3d(RING + s * SLOT, &mp.wqkv, (it & 15) * 64, c, B_FULL + 8 * s);
        e_tma2d(RING + s * SLOT + 16384, &mp.x, (it & 15) * 64, tm * 128, B_FULL + 8 * s);
        STAMP2(it >= NST ? it - NST : 63);
        if (++s == NST) { s = 0; ph ^= 1; }
      }
#pragma unroll 1
      for (int r = 0; r < 16; r++) {
        const int kb = out_kblock(r, tn);
        mbar_wait(B_EMPTY + 8 * s, ph);
        e_expect(B_FULL + 8 * s, r < 2 ? 16384 : 32768);
        e_tma3d(RING + s * SLOT, &mp.wo, kb * 64, 2 * tn, B_FULL + 8 * s);
        STAMP2(r + 48 - NST);
        if (++s == NST) { s = 0; ph ^= 1; }
      }
    } else if (w == 13) {
      e_pfmap(&mp.xs);
#pragma unroll
      for (int c = 0; c < 5; c++) {
        const int it = XS_AT + c * XS_STEP;
        if (it >= NST) mbar_wait(B_FULL + 8 * (it - NST), 0);
        mbar_wait(B_FULL + 8 * (it % NST), it / NST);
        if (c < 4) {
          e_expect(B_XS + 8 * c, 8192);
          e_tma2d(STG + c * 8192, &mp.xs, c * 256, tm * 128 + tn * 16, B_XS + 8 * c);
        } else {
          e_expect(B_WK, 16384);
          e_tma3d(FR, &mp.wqkv, tm * 64, 16 + 2 * tn, B_WK);
        }
      }
      nb_sync(NB_KVP, 160);
      const uint32_t ep = lds32(S_EPOCH);
      e_expect(B_XRES, 32768);
      e_tma2d(STG, &mp.x, tn * 128, tm * 128, B_XRES);
      e_tma2d(STG + 16384, &mp.x, tn * 128 + 64, tm * 128, B_XRES);
      nb_sync(NB_Q0, 192);
      e_store2d(&mp.os, tn * 128, tm * 128, STG);
      nb_sync(NB_OWN0, 288);
      e_store2d(&mp.os, tn * 128, tm * 128 + 64, STG + 8192);
      e_release(g_flagO + (tm * 16 + 2 * tn) * 8, ep, lane);
      STAMP_IF(lane == 0, 4);
      nb_sync(NB_H1, 160);
      e_store2d(&mp.os, tn * 128 + 64, tm * 128, STG + 16384);
      e_store2d(&mp.os, tn * 128 + 64, tm * 128 + 64, STG + 24576);
      e_release(g_flagO + (tm * 16 + 2 * tn + 1) * 8, ep, lane);
      STAMP_IF(lane == 0, 5);
      nb_arrive(NB_ST, 160);
    } else if (w == 14) {
      e_pfmap(&mp.gu); e_pfmap(&mp.o); e_pfmap(&mp.os); e_pfmap(&mp.wo); e_pfmap(&mp.down); e_pfmap(&mp.out);
      const uint32_t ep = ld_relaxed(&g_epoch) + 1;
      nb_sync(NB_FDONE, 416);
      {
        uint32_t c[4];
        poll_quad(c, g_csum + tn * 128 + lane * 4, ep, 1u);
        sts128(S_CSQ + lane * 16, c[0], c[1], c[2], c[3]);
        nb_arrive(NB_CSQ, 160);
        poll_quad(c, g_csum + 1024 + tn * 128 + lane * 4, ep, 1u);
        sts128(S_CSV + lane * 16, c[0], c[1], c[2], c[3]);
        nb_arrive(NB_PK, 288);
      }
      nb_sync(NB_Q0, 192);
      uint32_t ready = 0;
      int s = 0, ph = 1;
#pragma unroll 1
      for (int r = 2; r < 16; r++) {
        const int kb = out_kblock(r, tn);
        if (!((ready >> kb) & 1)) {
          int c = 0;
          do {
            spin_guard(c);
            ready = __ballot_sync(0xffffffffu, ld_relaxed(g_flagO + (tm * 16 + (lane & 15)) * 8) == ep);
          } while (!((ready >> kb) & 1));
          fence_acq();
          fence_async_glob();
        }
        mbar_wait(B_EMPTY + 8 * s, ph);
        e_tma2d(RING + s * SLOT + 16384, &mp.o, kb * 64, tm * 128, B_FULL + 8 * s);
        STAMP_IF(lane == 0 && r == 2, 2);
        STAMP_IF(lane == 0 && r == 9, 3);
        if (++s == NST) { s = 0; ph ^= 1; }
      }
    } else {
      const uint32_t ep = ld_relaxed(&g_epoch) + 1;
      uint64_t pol;
      asm volatile("createpolicy.fractional.L2::evict_first.b64 %0, 1.0;" : "=l"(pol));
      const char* pd = wd + (bid & 15) * 128 + ((bid >> 4) * 448 + lane) * 2048;
      const char* pf = ((bid & 1) ? wu : wg) + (bid >> 1) * 128 + lane * 7168;
#pragma unroll 1
      for (int it = FFN_AT % NST; it < FFN_AT + PFD; it += it < FFN_AT ? NST : 1) {
        mbar_wait(B_FULL + 8 * (it % NST), (it / NST) & 1);
        if (it >= FFN_AT && bid < 112) { asm volatile("prefetch.global.L2 [%0];" ::"l"(pf)); pf += 32 * 7168; }
      }
      mbar_wait(B_CSDN, 0);
      uint32_t f[1];
      poll1(f, g_flagR, ep, 0xffffffffu);
      fence_acq();
      fence_async_glob();
      e_expect(B_SEL, 32);
      e_load(S_SEL, g_xsel + 4096, 32, B_SEL);
      if (bid < 112) {
        int s = 0, ph = 1;
#pragma unroll 1
        for (int n = 0; n < 32; n++) {
          mbar_wait(B_FE + 8 * s, ph);
          e_expect(B_FR + 8 * s, 4608);
          e_tma3d_ef(GR + s * 4096, &mp.gu, bid * 32, n * 32, B_FR + 8 * s, pol);
          e_load(HOP + s * 512, g_xsel + n * 128, 512, B_FR + 8 * s);
          STAMP2(64 + n);
          if (PFD) {
            if (n == 32 - PFD) pf = pd;
            asm volatile("prefetch.global.L2 [%0];" ::"l"(pf));
            pf += n < 32 - PFD ? 32 * 7168 : 65536;
          }
          if (++s == 5) { s = 0; ph ^= 1; }
        }
      }
#pragma unroll 1
      for (int i = 0; i < 14; i++) {
        const int s = (i + 1) & 3;
        if (i >= 4) mbar_wait(B_DE + 8 * s, ((i >> 2) & 1) ^ 1);
        else if (bid < 112) mbar_wait(B_FE + 8 * (s + 1), s != 0);
        e_expect(B_DR + 8 * s, 4096);
        e_tma2d_ef(FR + s * 4096, &mp.down, (bid & 15) * 64, (bid >> 4) * 448 + i * 32, B_DR + 8 * s, pol);
        if (PFD && i + PFD < 14) asm volatile("prefetch.global.L2 [%0];" ::"l"(pd + (i + PFD) * 65536));
      }
    }
  } else if (w >= 8) {
    asm volatile("setmaxnreg.dec.sync.aligned.u32 64;");
    const int t = tid - 256, ww = w - 8;
    const uint32_t ep = ld_relaxed(&g_epoch) + 1, par = ep & 1u;
    {
      const int r0 = (lane >> 3) + (lane & 4);
      const uint32_t a = FR + (ww >> 1) * 8192 + r0 * 128 + ((((ww & 1) * 4 + (lane & 3)) ^ r0) << 4);
      float c[8];
      reg_zero(c);
      mbar_wait(B_WK, 0);
#pragma unroll 2
      for (int i = 0; i < 8; i++) {
        const uint4 v = lds128(a + i * 1024);
        c[0] += bf_lo(v.x); c[1] += bf_hi(v.x); c[2] += bf_lo(v.y); c[3] += bf_hi(v.y);
        c[4] += bf_lo(v.z); c[5] += bf_hi(v.z); c[6] += bf_lo(v.w); c[7] += bf_hi(v.w);
      }
      const bool u16 = lane & 16, u8 = lane & 8, u4 = lane & 4;
      const float d0 = xred(c[0], c[4], u16, 16), d1 = xred(c[1], c[5], u16, 16), d2 = xred(c[2], c[6], u16, 16), d3 = xred(c[3], c[7], u16, 16);
      fence_async_smem();
      e_arrive(B_CSDN);
      const float sum = xred(xred(d0, d2, u8, 8), xred(d1, d3, u8, 8), u4, 4);
      st_relaxed(g_csum + (2 + tm) * 1024 + tn * 128 + ww * 32 + (lane & 3) * 8 + (lane >> 2), tagf(sum, par));
      STAMP_IF(t == 0, 8);
      __nanosleep(500);
      uint32_t p[16];
      poll16(p, g_csum + 2048 + tn * 128 + t, par, 1u);
      float tot = 0.f;
#pragma unroll
      for (int i = 0; i < 16; i += 4) tot += (__uint_as_float(p[i]) + __uint_as_float(p[i + 1])) + (__uint_as_float(p[i + 2]) + __uint_as_float(p[i + 3]));
      sts32(S_CSK + t * 4, __float_as_uint(tot));
      nb_arrive(NB_FDONE, 416);
      STAMP_IF(t == 0, 9);
    }
    const int ks = bid >> 4, nt = bid & 15;
    mbar_wait(B_SEL, 0);
    STAMP_IF(t == 0, 11);
    float fa[4] = {0.f, 0.f, 0.f, 0.f};
    if (bid < 112) {
      int s = 0, ph = 0;
      uint32_t prev = 0;
#pragma unroll 1
      for (int n = 0; n < 32; n++) {
        mbar_wait(B_FR + 8 * s, ph);
        const uint64_t da = mkdesc(GR, 2048, 512, 2) + s * 256, db = mkdesc(HOP, 16, 512, 2) + s * 32;
        wg_fence();
        wgmma_n8_ss<1, 0>(fa, da, db, 1);
        wgmma_n8_ss<1, 0>(fa, da + 64, db + 2, 1);
        wg_commit();
        wg_wait<1>();
        if (prev && t == 0) mbar_arrive(prev);
        prev = B_FE + 8 * s;
        if (++s == 5) { s = 0; ph ^= 1; }
      }
      wg_wait<0>();
      reg_fence(fa);
      if (t == 0) mbar_arrive(prev);
      STAMP_IF(t == 0, 12);
      const bool isup = (ww >> 1) != (wu < wg);
      if (isup) sts128f(GR + (t & 63) * 16, fa[0], fa[1], fa[2], fa[3]);
      nb_sync(NB_WG2, 128);
      if (!isup) {
        const float4 u = lds128f(GR + (t & 63) * 16);
        const float uu[4] = {u.x, u.y, u.z, u.w};
        uint32_t* hp = g_h + bid * 256 + (lane & 3) * 64 + (ww & 1) * 16 + (lane >> 2);
#pragma unroll
        for (int i = 0; i < 4; i++) {
          const float g = fa[i], hv = g * rcp(1.f + ex2(-g * LOG2E)) * uu[i];
          st_relaxed(hp + (i & 1) * 32 + (i >> 1) * 8, __byte_perm(pack(hv, hv), ep, 0x3254));
        }
      }
      nb_sync(NB_WG2, 128);
      reg_zero(fa);
    } else {
      uint32_t f[1];
      poll1(f, g_h + ks * 3584 + 3583, ep, 0xffffu);
    }
    {
      uint32_t v[28];
      poll7x4(v, g_h + ks * 3584 + t * 4, ep, 0xffffu);
#pragma unroll
      for (int q = 0; q < 7; q++)
        asm volatile("st.shared.v2.u32 [%0], {%1,%2};" ::"r"(HOP + q * 1024 + (t >> 3) * 64 + ((((t >> 1) & 3) ^ ((t >> 4) & 3)) << 4) + (t & 1) * 8),
                     "r"(__byte_perm(v[4 * q], v[4 * q + 1], 0x7632)), "r"(__byte_perm(v[4 * q + 2], v[4 * q + 3], 0x7632)) : "memory");
      fence_async_smem();
      nb_sync(NB_WG2, 128);
    }
    STAMP_IF(t == 0, 13);
#pragma unroll 1
    for (int i = 0; i < 14; i++) {
      const int s = (i + 1) & 3;
      mbar_wait(B_DR + 8 * s, (i >> 2) & 1);
      const uint64_t da = mkdesc(FR, 4096, 1024, 1) + s * 256;
      const uint64_t db = mkdesc(HOP, 16, 512, 2) + i * 32;
      wg_fence();
      wgmma_n8_ss<1, 0>(fa, da, db, 1);
      wgmma_n8_ss<1, 0>(fa, da + 128, db + 2, 1);
      wg_commit();
      wg_wait<1>();
      if (i && t == 0) mbar_arrive(B_DE + 8 * (i & 3));
    }
    wg_wait<0>();
    reg_fence(fa);
    STAMP_IF(t == 0, 14);
    {
      uint32_t* yp = g_yp + (nt * 8 + ks) * 512 + (lane & 3) * 128 + ww * 16 + (lane >> 2);
#pragma unroll
      for (int i = 0; i < 4; i++) st_relaxed(yp + (i & 1) * 64 + (i >> 1) * 8, tagf(fa[i], par));
    }
    const uint32_t mykey = lds32(S_SEL + (lane & 7) * 4);
    const uint32_t inmask = __ballot_sync(0xffffffffu, (key_token(mykey) >> 7) == tm) & 0xffu;
    if (inmask) {
      nb_sync(NB_WG2, 128);
      const float sg = rcp(1.f + ex2(-key_score(mykey) * LOG2E));
#pragma unroll 1
      for (int j = 0; j < 8; j++) {
        float y = 0.f;
        if ((inmask >> j) & 1) {
          uint32_t p[8];
          poll8(p, g_yp + (tn * 2 + (t >> 6)) * 4096 + j * 64 + (t & 63), par, 1u);
          y = ((__uint_as_float(p[0]) + __uint_as_float(p[1])) + (__uint_as_float(p[2]) + __uint_as_float(p[3]))) +
              ((__uint_as_float(p[4]) + __uint_as_float(p[5])) + (__uint_as_float(p[6]) + __uint_as_float(p[7])));
        }
        y *= __shfl_sync(0xffffffffu, sg, j);
        asm volatile("st.shared.u16 [%0], %1;" ::"r"(FR + (t >> 6) * 1024 + j * 128 + ((((t >> 3) & 7) ^ j) << 4) + (t & 7) * 2),
                     "h"((unsigned short)pack(y, y)) : "memory");
      }
      fence_async_smem();
      nb_arrive(NB_Y, 256);
    }
    STAMP_IF(t == 0, 15);
  } else if (w >= 4) {
    asm volatile("setmaxnreg.inc.sync.aligned.u32 208;");
    const int t = tid - 128, ww = w - 4, g = lane >> 2, t4 = lane & 3;
    const bool leader = t == 0;
    const uint32_t ep = ld_relaxed(&g_epoch) + 1, par = ep & 1u;
    {
      const uint4* wp = reinterpret_cast<const uint4*>(w_r) + lane;
      uint4 w0 = __ldg(wp), w1 = __ldg(wp + 32), w2 = __ldg(wp + 64), w3 = __ldg(wp + 96);
      if (leader) sts32(S_EPOCH, ep);
      float s[4] = {0.f, 0.f, 0.f, 0.f}, q[4] = {0.f, 0.f, 0.f, 0.f}, d[4] = {0.f, 0.f, 0.f, 0.f}, wsum = 0.f;
#pragma unroll 1
      for (int c = 0; c < 4; c++) {
        const float wr[8] = {bf_lo(w0.x), bf_hi(w0.x), bf_lo(w0.y), bf_hi(w0.y), bf_lo(w0.z), bf_hi(w0.z), bf_lo(w0.w), bf_hi(w0.w)};
        w0 = w1; w1 = w2; w2 = w3;
        wsum += ((wr[0] + wr[1]) + (wr[2] + wr[3])) + ((wr[4] + wr[5]) + (wr[6] + wr[7]));
        mbar_wait(B_XS + 8 * c, 0);
#pragma unroll
        for (int r = 0; r < 4; r++) {
          const uint4 v = lds128(STG + c * 8192 + (ww * 4 + r) * 512 + lane * 16);
          const uint32_t xw[4] = {v.x, v.y, v.z, v.w};
#pragma unroll
          for (int i = 0; i < 4; i++) {
            const float lo = bf_lo(xw[i]), hi = bf_hi(xw[i]);
            s[r] += lo; q[r] = fmaf(lo, lo, q[r]); d[r] = fmaf(lo, wr[2 * i], d[r]);
            s[r] += hi; q[r] = fmaf(hi, hi, q[r]); d[r] = fmaf(hi, wr[2 * i + 1], d[r]);
          }
        }
      }
      STAMP_IF(leader, 16);
      const bool u16 = lane & 16, u8 = lane & 8, u4 = lane & 4, u2 = lane & 2;
      const float s1 = xred(xred(s[0], s[2], u16, 16), xred(s[1], s[3], u16, 16), u8, 8);
      const float q1 = xred(xred(q[0], q[2], u16, 16), xred(q[1], q[3], u16, 16), u8, 8);
      const float d1 = xred(xred(d[0], d[2], u16, 16), xred(d[1], d[3], u16, 16), u8, 8);
      wsum += __shfl_xor_sync(0xffffffffu, wsum, 16);
      wsum += __shfl_xor_sync(0xffffffffu, wsum, 8);
      float tot = xred(xred(s1, d1, u4, 4), xred(q1, wsum, u4, 4), u2, 2);
      tot += __shfl_xor_sync(0xffffffffu, tot, 1);
      const float qq = __shfl_down_sync(0xffffffffu, tot, 2), dd = __shfl_down_sync(0xffffffffu, tot, 4), ws = __shfl_down_sync(0xffffffffu, tot, 6);
      if ((lane & 7) == 0) {
        const float mean = tot * (1.f / 1024.f);
        const float var = fmaxf(fmaf(-mean, mean, qq * (1.f / 1024.f)), 0.f);
        float sd;
        asm("sqrt.approx.ftz.f32 %0, %1;" : "=f"(sd) : "f"(bf_round(bf_round(var) + 1e-5f)));
        const uint32_t ms = pack(sd, mean);
        const int row = tm * 128 + tn * 16 + ww * 4 + (lane >> 3);
        const uint32_t rbits = pack(0.f, fmaf(-bf_hi(ms), ws, dd) * rcp(bf_lo(ms)));
        const uint32_t key = (rbits ^ (((int)rbits >> 31 & 0x7fff0000u) | 0x80000000u)) | ((2047 - row) << 5) | (ep & 31u);
        asm volatile("{\n.reg .b64 x;\nmov.b64 x, {%1,%2};\nst.relaxed.gpu.global.b64 [%0], x;\n}" ::"l"(g_keys + row), "r"(key), "r"(ms) : "memory");
      }
      STAMP_IF(leader, 17);
      __nanosleep(400);
      uint32_t st[2];
      poll_pair(st, g_keys + tm * 128 + t, ep, 31u);
      asm volatile("st.shared.v2.f32 [%0], {%1,%2};" ::"r"(S_KSTAT + t * 8), "f"(bf_hi(st[1])), "f"(rcp(bf_lo(st[1])) * LOG2E) : "memory");
      nb_arrive(NB_FDONE, 416);
      STAMP_IF(leader, 10);
    }
    float a0[64], a1[64];
    reg_zero(a0); reg_zero(a1); reg_fence(a0); reg_fence(a1);
    STAMP_IF(leader, 18);
    nb_sync(NB_KV, 256);
    mainloop<true>(a0, a1, 1, 1, NB_VQ, leader);
    STAMP_IF(leader, 19);
    {
      nb_sync(NB_PK, 288);
      float c[4];
#pragma unroll
      for (int i = 0; i < 4; i++) c[i] = -__uint_as_float(lds32(S_CSV + ((i >> 1) * 64 + ww * 16 + (i & 1) * 8 + g) * 4));
      uint32_t f0[32], f1[32];
#pragma unroll
      for (int j = 0; j < 16; j++) {
        const float4 s0 = lds128f(S_KSTAT + (j * 8 + 2 * t4) * 8);
        f0[2 * j] = pack(fmaf(c[0], s0.x, a0[4 * j]), fmaf(c[0], s0.z, a0[4 * j + 1]));
        f0[2 * j + 1] = pack(fmaf(c[1], s0.x, a0[4 * j + 2]), fmaf(c[1], s0.z, a0[4 * j + 3]));
        f1[2 * j] = pack(fmaf(c[2], s0.x, a1[4 * j]), fmaf(c[2], s0.z, a1[4 * j + 1]));
        f1[2 * j + 1] = pack(fmaf(c[3], s0.x, a1[4 * j + 2]), fmaf(c[3], s0.z, a1[4 * j + 3]));
      }
      float c0[32], c1[32];
      reg_zero(c0); reg_zero(c1);
      constexpr uint64_t db = mkdesc(STG, 16, 1024, 1);
      wg_fence();
#pragma unroll
      for (int k = 0; k < 8; k++) {
        wgmma_n64_rs<0>(c0, f0[4 * k], f0[4 * k + 1], f0[4 * k + 2], f0[4 * k + 3], db + (k >> 2) * 1024 + (k & 3) * 2, k != 0);
        wgmma_n64_rs<0>(c1, f1[4 * k], f1[4 * k + 1], f1[4 * k + 2], f1[4 * k + 3], db + (k >> 2) * 1024 + (k & 3) * 2 + 512, k != 0);
      }
      wg_commit();
      wg_wait<0>();
      reg_fence(c0);
      reg_fence(c1);
      nb_arrive(NB_KVP, 160);
      STAMP_IF(leader, 20);
      uint4* pp = g_kvp + (tn * 16 + tm) * 512 + t;
      if (ww < 2) {
#pragma unroll
        for (int q = 0; q < 2; q++) {
          st_unit(pp + q * 128, pack(c0[8 * q], c0[8 * q + 1]), pack(c0[8 * q + 2], c0[8 * q + 3]), pack(c0[8 * q + 4], c0[8 * q + 5]), pack(c0[8 * q + 6], c0[8 * q + 7]), par);
          st_unit(pp + q * 128 + 256, pack(c1[8 * q], c1[8 * q + 1]), pack(c1[8 * q + 2], c1[8 * q + 3]), pack(c1[8 * q + 4], c1[8 * q + 5]), pack(c1[8 * q + 6], c1[8 * q + 7]), par);
        }
      } else {
#pragma unroll
        for (int q = 2; q < 4; q++) {
          st_unit(pp + q * 128 - 256, pack(c0[8 * q], c0[8 * q + 1]), pack(c0[8 * q + 2], c0[8 * q + 3]), pack(c0[8 * q + 4], c0[8 * q + 5]), pack(c0[8 * q + 6], c0[8 * q + 7]), par);
          st_unit(pp + q * 128, pack(c1[8 * q], c1[8 * q + 1]), pack(c1[8 * q + 2], c1[8 * q + 3]), pack(c1[8 * q + 4], c1[8 * q + 5]), pack(c1[8 * q + 6], c1[8 * q + 7]), par);
        }
      }
      STAMP_IF(leader, 47);
      {
        uint32_t p[16];
        poll16(p, g_z + tn * 128 + t, par, 1u);
        float tot = 0.f;
#pragma unroll
        for (int i = 0; i < 16; i += 4) tot += (__uint_as_float(p[i]) + __uint_as_float(p[i + 1])) + (__uint_as_float(p[i + 2]) + __uint_as_float(p[i + 3]));
        const unsigned short zb = (unsigned short)pack(tot, tot);
#pragma unroll
        for (int i = 0; i < 4; i++) {
          const int n = 2 * i + (t >> 6);
          asm volatile("st.shared.u16 [%0], %1;" ::"r"(KVB_Z + n * 128 + ((((t >> 3) & 7) ^ n) << 4) + (t & 7) * 2), "h"(zb) : "memory");
        }
      }
      STAMP_IF(leader, 46);
      {
        uint32_t p[16];
        poll_kvp(p, g_kvp + (tn * 16 + (lane >> 3) * 4) * 512 + tm * 32 + ww * 8 + (lane & 7), par, 1u);
        float r[8];
#pragma unroll
        for (int i = 0; i < 4; i++) {
          r[2 * i] = (bf_lo(p[i]) + bf_lo(p[4 + i])) + (bf_lo(p[8 + i]) + bf_lo(p[12 + i]));
          r[2 * i + 1] = (bf_hi(p[i]) + bf_hi(p[4 + i])) + (bf_hi(p[8 + i]) + bf_hi(p[12 + i]));
        }
#pragma unroll
        for (int i = 0; i < 8; i++) r[i] += __shfl_xor_sync(0xffffffffu, r[i], 8);
#pragma unroll
        for (int i = 0; i < 8; i++) r[i] += __shfl_xor_sync(0xffffffffu, r[i], 16);
        if (lane < 8) st_unit(g_kv + tn * 512 + tm * 32 + ww * 8 + lane, pack(r[0], r[1]), pack(r[2], r[3]), pack(r[4], r[5]), pack(r[6], r[7]), par);
      }
      STAMP_IF(leader, 21);
    }
    const uint32_t sx = lane & 7, sc = lane >> 4;
    const uint32_t sa = STG + (ww * 16 + (lane & 15)) * 128;
    const uint32_t sw[4] = {sa + ((sc ^ sx) << 4), sa + (((2 + sc) ^ sx) << 4), sa + (((4 + sc) ^ sx) << 4), sa + (((6 + sc) ^ sx) << 4)};
    {
      float ka[4], kb[4];
#pragma unroll
      for (int i = 0; i < 4; i++) {
        const float2 st = lds64f(S_KSTAT + ((i >> 1) * 64 + ww * 16 + (i & 1) * 8 + g) * 8);
        const float r = st.y * LN2;
        ka[i] = 1.f + r; kb[i] = -st.x * r;
      }
      mbar_wait(B_XRES, 0);
#pragma unroll
      for (int j = 0; j < 8; j++) {
        const uint4 v = ldsm4(sw[j & 3] + (j >> 2) * 16384), u = ldsm4(sw[j & 3] + (j >> 2) * 16384 + 8192);
        a0[8 * j + 0] = fmaf(bf_lo(v.x), ka[0], kb[0]); a0[8 * j + 1] = fmaf(bf_hi(v.x), ka[0], kb[0]);
        a0[8 * j + 2] = fmaf(bf_lo(v.y), ka[1], kb[1]); a0[8 * j + 3] = fmaf(bf_hi(v.y), ka[1], kb[1]);
        a0[8 * j + 4] = fmaf(bf_lo(v.z), ka[0], kb[0]); a0[8 * j + 5] = fmaf(bf_hi(v.z), ka[0], kb[0]);
        a0[8 * j + 6] = fmaf(bf_lo(v.w), ka[1], kb[1]); a0[8 * j + 7] = fmaf(bf_hi(v.w), ka[1], kb[1]);
        a1[8 * j + 0] = fmaf(bf_lo(u.x), ka[2], kb[2]); a1[8 * j + 1] = fmaf(bf_hi(u.x), ka[2], kb[2]);
        a1[8 * j + 2] = fmaf(bf_lo(u.y), ka[3], kb[3]); a1[8 * j + 3] = fmaf(bf_hi(u.y), ka[3], kb[3]);
        a1[8 * j + 4] = fmaf(bf_lo(u.z), ka[2], kb[2]); a1[8 * j + 5] = fmaf(bf_hi(u.z), ka[2], kb[2]);
        a1[8 * j + 6] = fmaf(bf_lo(u.w), ka[3], kb[3]); a1[8 * j + 7] = fmaf(bf_hi(u.w), ka[3], kb[3]);
      }
      reg_fence(a0);
      reg_fence(a1);
    }
    STAMP_IF(leader, 22);
    {
      uint32_t v[16];
      poll_kv(v, g_kv + tn * 512 + t, par, 1u);
      STAMP_IF(leader, 23);
#pragma unroll
      for (int q = 0; q < 4; q++)
        stsm4((q < 2 ? KVB_P0 : KVB_P1) + ((ww & 1) * 16 + (lane & 15)) * 128 + ((((ww >> 1) * 4 + (q & 1) * 2 + sc) ^ sx) << 4),
              v[4 * q], v[4 * q + 1], v[4 * q + 2], v[4 * q + 3]);
      fence_async_smem();
      nb_arrive(NB_KVB, 256);
    }
    STAMP_IF(leader, 24);
    uint32_t oh[4];
    uint32_t inmask;
    {
      mbar_wait(B_SEL, 0);
      const int r0 = key_token(lds32(S_SEL + t4 * 8)) - tm * 128, r1 = key_token(lds32(S_SEL + t4 * 8 + 4)) - tm * 128;
#pragma unroll
      for (int i = 0; i < 4; i++) {
        const int row = (i >> 1) * 64 + ww * 16 + (i & 1) * 8 + g;
        oh[i] = (r0 == row ? 0x3f80u : 0u) | (r1 == row ? 0x3f800000u : 0u);
      }
      inmask = __ballot_sync(0xffffffffu, (unsigned)r0 < 128u || (unsigned)r1 < 128u);
    }
    {
      int s = 3, ph = 1;
      uint32_t prev = 0;
#pragma unroll 1
      for (int r = 0; r < 16; r++) {
        if (r < 2) nb_sync(NB_OWN0 + r, r ? 256 : 288);
        mbar_wait(B_FULL + 8 * s, ph);
        STAMP_IF(leader && r < 3, 25 + r);
        const uint64_t dw = mkdesc(RING, 8192, 1024, 1) + s * (SLOT >> 4);
        const uint64_t dx = mkdesc(0, 16, 1024, 1) + (r < 2 ? (STG >> 4) + r * 1024 : ((RING + 16384) >> 4) + s * (SLOT >> 4));
        wg_fence();
#pragma unroll
        for (int j = 0; j < 4; j++) {
          wgmma_n128_ss<0, 1>(a0, dx + j * 2, dw + j * 128, 1);
          wgmma_n128_ss<0, 1>(a1, dx + j * 2 + 512, dw + j * 128, 1);
        }
        wg_commit();
        wg_wait<1>();
        if (prev && leader) mbar_arrive(prev);
        prev = B_EMPTY + 8 * s;
        if (++s == NST) { s = 0; ph ^= 1; }
      }
      if (inmask) {
        nb_sync(NB_Y, 256);
        wg_fence();
        wgmma_n128_rs<1>(a0, oh[0], oh[1], 0u, 0u, mkdesc(FR, 1024, 0, 1), 1);
        wgmma_n128_rs<1>(a1, oh[2], oh[3], 0u, 0u, mkdesc(FR, 1024, 0, 1), 1);
        wg_commit();
      }
      nb_sync(NB_ST, 160);
      wg_wait<0>();
      reg_fence(a0);
      reg_fence(a1);
    }
    STAMP_IF(leader, 28);
#pragma unroll
    for (int c = 0; c < 2; c++) {
#pragma unroll
      for (int j = 4 * c; j < 4 * c + 4; j++) {
        stsm4(sw[j & 3] + c * 16384, pack(a0[8 * j], a0[8 * j + 1]), pack(a0[8 * j + 2], a0[8 * j + 3]), pack(a0[8 * j + 4], a0[8 * j + 5]), pack(a0[8 * j + 6], a0[8 * j + 7]));
        stsm4(sw[j & 3] + c * 16384 + 8192, pack(a1[8 * j], a1[8 * j + 1]), pack(a1[8 * j + 2], a1[8 * j + 3]), pack(a1[8 * j + 4], a1[8 * j + 5]), pack(a1[8 * j + 6], a1[8 * j + 7]));
      }
      fence_async_smem();
      e_store2d(&mp.out, tn * 128 + c * 64, tm * 128 + ww * 16, STG + c * 16384 + ww * 2048);
      e_store2d(&mp.out, tn * 128 + c * 64, tm * 128 + 64 + ww * 16, STG + c * 16384 + 8192 + ww * 2048);
    }
    bulk_wait_read();
    if (bid == 0 && leader) st_relaxed(&g_epoch, ep);
    STAMP_IF(leader, 29);
  } else {
    asm volatile("setmaxnreg.inc.sync.aligned.u32 208;");
    const int g = lane >> 2, t4 = lane & 3;
    const bool leader = tid == 0;
    const uint32_t sx = lane & 7, sc = lane >> 4;
    const uint32_t sa = STG + (w * 16 + (lane & 15)) * 128;
    const uint32_t sw[4] = {sa + ((sc ^ sx) << 4), sa + (((2 + sc) ^ sx) << 4), sa + (((4 + sc) ^ sx) << 4), sa + (((6 + sc) ^ sx) << 4)};
    float a0[64], a1[64];
    reg_zero(a0); reg_zero(a1); reg_fence(a0); reg_fence(a1);
    mainloop<true>(a0, a1, 0, 0, NB_KV, leader);
    STAMP_IF(leader, 33);
    {
      nb_sync(NB_FDONE, 416);
      STAMP_IF(leader, 34);
      float c[4], z[4] = {0.f, 0.f, 0.f, 0.f};
#pragma unroll
      for (int i = 0; i < 4; i++) c[i] = -__uint_as_float(lds32(S_CSK + ((i >> 1) * 64 + w * 16 + (i & 1) * 8 + g) * 4));
#pragma unroll
      for (int j = 0; j < 8; j++) {
        const float4 s0 = lds128f(S_KSTAT + (j * 16 + 2 * t4) * 8), s1 = lds128f(S_KSTAT + (j * 16 + 8 + 2 * t4) * 8);
        const float mu[4] = {s0.x, s0.z, s1.x, s1.z}, rl[4] = {s0.y, s0.w, s1.y, s1.w};
#pragma unroll
        for (int m = 0; m < 2; m++) {
          float p[8];
#pragma unroll
          for (int i = 0; i < 8; i++) {
            const int r = m * 2 + ((i >> 1) & 1), cc = (i >> 2) * 2 + (i & 1);
            p[i] = phi2(fmaf(c[r], mu[cc], m ? a1[8 * j + i] : a0[8 * j + i]) * rl[cc]);
            z[r] += p[i];
            p[i] *= rl[cc];
          }
          stsm4(sw[j & 3] + (j >> 2) * 16384 + m * 8192, pack(p[0], p[1]), pack(p[2], p[3]), pack(p[4], p[5]), pack(p[6], p[7]));
        }
      }
      const bool u2 = lane & 2, u1 = lane & 1;
      const float zz = xred(xred(z[0], z[2], u2, 2), xred(z[1], z[3], u2, 2), u1, 1);
      fence_async_smem();
      nb_arrive(NB_PK, 288);
      st_relaxed(g_z + tm * 1024 + tn * 128 + (t4 >> 1) * 64 + w * 16 + (t4 & 1) * 8 + g, tagf(zz * LOG2E, lds32(S_EPOCH) & 1u));
    }
    STAMP_IF(leader, 35);
    float rl[4];
    {
      nb_sync(NB_CSQ, 160);
      float mu[4];
#pragma unroll
      for (int i = 0; i < 4; i++) {
        const float2 st = lds64f(S_KSTAT + ((i >> 1) * 64 + w * 16 + (i & 1) * 8 + g) * 8);
        mu[i] = -st.x; rl[i] = st.y;
      }
#pragma unroll
      for (int j = 0; j < 16; j++) {
        const float2 c = lds64f(S_CSQ + (j * 8 + 2 * t4) * 4);
        a0[4 * j] = mu[0] * c.x; a0[4 * j + 1] = mu[0] * c.y; a0[4 * j + 2] = mu[1] * c.x; a0[4 * j + 3] = mu[1] * c.y;
        a1[4 * j] = mu[2] * c.x; a1[4 * j + 1] = mu[2] * c.y; a1[4 * j + 2] = mu[3] * c.x; a1[4 * j + 3] = mu[3] * c.y;
      }
      reg_fence(a0); reg_fence(a1);
    }
    STAMP_IF(leader, 40);
    nb_sync(NB_VQ, 256);
    mainloop<false>(a0, a1, 2, 0, 0, leader);
    STAMP_IF(leader, 36);
    {
      uint32_t f[2][16];
      float oc[2][2][20];
      auto phi = [&](float (&a)[64], int j, int m, uint32_t (&o)[16]) {
#pragma unroll
        for (int i = 0; i < 32; i++) asm volatile("" : "+f"(a[32 * j + i])::"memory");
#pragma unroll
        for (int i = 0; i < 16; i++) o[i] = pack(phi2(a[32 * j + 2 * i] * rl[2 * m + (i & 1)]), phi2(a[32 * j + 2 * i + 1] * rl[2 * m + (i & 1)]));
      };
      auto mma = [&](int j, const uint32_t (&a)[16], float (&o)[2][20]) {
        const uint64_t db = mkdesc(j ? KVB_Z : KVB_P0, 16, 1024, 1);
        reg_zero(o[0]); reg_zero(o[1]);
        wg_fence();
        wgmma_n40_rs<0>(o[0], a[0], a[1], a[2], a[3], db, 0);
        wgmma_n40_rs<0>(o[1], a[8], a[9], a[10], a[11], db + 4, 0);
        wgmma_n40_rs<0>(o[0], a[4], a[5], a[6], a[7], db + 2, 1);
        wgmma_n40_rs<0>(o[1], a[12], a[13], a[14], a[15], db + 6, 1);
        wg_commit();
      };
      auto fin = [&](int j, int m, float (&o)[2][20]) {
#pragma unroll
        for (int h = 0; h < 2; h++) {
          const float r0 = rcp(o[h][j ? 1 : 16] + 1e-6f * LOG2E), r1 = rcp(o[h][j ? 3 : 18] + 1e-6f * LOG2E);
          const int b = j ? 4 : 0;
#pragma unroll
          for (int q = 0; q < 2; q++)
            stsm4(sw[h * 2 + q] + j * 16384 + m * 8192,
                  pack(o[h][b + 8 * q] * r0, o[h][b + 8 * q + 1] * r0), pack(o[h][b + 8 * q + 2] * r1, o[h][b + 8 * q + 3] * r1),
                  pack(o[h][b + 8 * q + 4] * r0, o[h][b + 8 * q + 5] * r0), pack(o[h][b + 8 * q + 6] * r1, o[h][b + 8 * q + 7] * r1));
        }
      };
#pragma unroll
      for (int j = 0; j < 2; j++) {
        phi(a0, j, 0, f[0]);
        if (j == 0) nb_sync(NB_KVB, 256);
        STAMP_IF(leader && j == 0, 37);
        mma(j, f[0], oc[0]);
        phi(a1, j, 1, f[1]);
        wg_wait<0>();
        reg_fence(oc[0][0]); reg_fence(oc[0][1]);
        mma(j, f[1], oc[1]);
        fin(j, 0, oc[0]);
        if (j == 0) { fence_async_smem(); nb_arrive(NB_Q0, 192); }
        wg_wait<0>();
        reg_fence(oc[1][0]); reg_fence(oc[1][1]);
        fin(j, 1, oc[1]);
        fence_async_smem();
        if (j == 0) nb_arrive(NB_OWN0, 288);
        else { nb_arrive(NB_OWN1, 256); nb_arrive(NB_H1, 160); }
        STAMP_IF(leader, 38 + j);
      }
    }
  }
}

typedef CUresult (*EncodeFn)(CUtensorMap*, CUtensorMapDataType, cuuint32_t, void*, const cuuint64_t*, const cuuint64_t*, const cuuint32_t*,
                             const cuuint32_t*, CUtensorMapInterleave, CUtensorMapSwizzle, CUtensorMapL2promotion, CUtensorMapFloatOOBfill);

void make_map(EncodeFn enc, CUtensorMap* m, const void* p, int rank, uint64_t d0, uint64_t d1, uint64_t d2, uint64_t s1, uint64_t s2,
              uint32_t b0, uint32_t b1, uint32_t b2, CUtensorMapSwizzle sw) {
  cuuint64_t gd[3] = {d0, d1, d2}, gs[2] = {s1, s2};
  cuuint32_t bd[3] = {b0, b1, b2}, es[3] = {1, 1, 1};
  enc(m, CU_TENSOR_MAP_DATA_TYPE_BFLOAT16, rank, const_cast<void*>(p), gd, gs, bd, es, CU_TENSOR_MAP_INTERLEAVE_NONE, sw,
      CU_TENSOR_MAP_L2_PROMOTION_L2_128B, CU_TENSOR_MAP_FLOAT_OOB_FILL_NONE);
}

}

extern "C" void kernel_launch(void* const* d_in, const int* in_sizes, int n_in, void* d_out, int out_size) {
  (void)in_sizes; (void)n_in; (void)out_size;
  void* fn = nullptr;
  cudaDriverEntryPointQueryResult qr;
  cudaGetDriverEntryPoint("cuTensorMapEncodeTiled", &fn, cudaEnableDefault, &qr);
  EncodeFn enc = (EncodeFn)fn;
  void* o;
  cudaGetSymbolAddress(&o, g_o);
  const CUtensorMapSwizzle S128 = CU_TENSOR_MAP_SWIZZLE_128B, S64 = CU_TENSOR_MAP_SWIZZLE_64B, S0 = CU_TENSOR_MAP_SWIZZLE_NONE;
  Maps mp;
  make_map(enc, &mp.wqkv, d_in[1], 3, 64, 1024, 48, 6144, 128, 64, 64, 2, S128);
  make_map(enc, &mp.x, d_in[0], 2, 1024, 2048, 1, 2048, 0, 64, 128, 1, S128);
  make_map(enc, &mp.os, o, 2, 1024, 2048, 1, 2048, 0, 64, 64, 1, S128);
  make_map(enc, &mp.o, o, 2, 1024, 2048, 1, 2048, 0, 64, 128, 1, S128);
  make_map(enc, &mp.wo, d_in[2], 3, 64, 1024, 16, 2048, 128, 64, 64, 2, S128);
  make_map(enc, &mp.xs, d_in[0], 2, 1024, 2048, 1, 2048, 0, 256, 16, 1, S0);
  const char *wg = (const char*)d_in[5], *wu = (const char*)d_in[6];
  make_map(enc, &mp.gu, wu < wg ? wu : wg, 3, 3584, 1024, 2, 7168, (uint64_t)(wu < wg ? wg - wu : wu - wg), 32, 32, 2, S64);
  make_map(enc, &mp.down, d_in[7], 2, 1024, 3584, 1, 2048, 0, 64, 32, 1, S128);
  make_map(enc, &mp.out, d_out, 2, 1024, 2048, 1, 2048, 0, 64, 16, 1, S128);
  cudaFuncSetAttribute(fused_kernel, cudaFuncAttributeMaxDynamicSharedMemorySize, SMEM_BYTES);
  fused_kernel<<<132, 512, SMEM_BYTES>>>(mp, (const __nv_bfloat16*)d_in[4], (const __nv_bfloat16*)d_in[0], (const char*)d_in[5],
                                         (const char*)d_in[6], (const char*)d_in[7]);
}
```

```cpp
#include <cuda_runtime.h>
#include <cuda.h>
#include <cuda_bf16.h>
#include <stdint.h>

namespace {

template <int TA, int TB>
__device__ __forceinline__ void wgmma_n8_ss(float (&d)[4], uint64_t da, uint64_t db, int sc) {
  asm volatile("{\n.reg .pred p;\nsetp.ne.b32 p, %6, 0;\n"
    "wgmma.mma_async.sync.aligned.m64n8k16.f32.bf16.bf16 {%0, %1, %2, %3}, %4, %5, p, 1, 1, %7, %8;\n}\n"
    : "+f"(d[0]), "+f"(d[1]), "+f"(d[2]), "+f"(d[3])
    : "l"(da), "l"(db), "r"(sc), "n"(TA), "n"(TB));
}
template <int TB>
__device__ __forceinline__ void wgmma_n40_rs(float (&d)[20], uint32_t a0, uint32_t a1, uint32_t a2, uint32_t a3, uint64_t db, int sc) {
  asm volatile("{\n.reg .pred p;\nsetp.ne.b32 p, %25, 0;\n"
    "wgmma.mma_async.sync.aligned.m64n40k16.f32.bf16.bf16 {%0, %1, %2, %3, %4, %5, %6, %7, %8, %9, %10, %11, %12, %13, %14, %15, %16, %17, %18, %19}, {%20,%21,%22,%23}, %24, p, 1, 1, %26;\n}\n"
    : "+f"(d[0]), "+f"(d[1]), "+f"(d[2]), "+f"(d[3]), "+f"(d[4]), "+f"(d[5]), "+f"(d[6]), "+f"(d[7]),
      "+f"(d[8]), "+f"(d[9]), "+f"(d[10]), "+f"(d[11]), "+f"(d[12]), "+f"(d[13]), "+f"(d[14]), "+f"(d[15]),
      "+f"(d[16]), "+f"(d[17]), "+f"(d[18]), "+f"(d[19])
    : "r"(a0), "r"(a1), "r"(a2), "r"(a3), "l"(db), "r"(sc), "n"(TB));
}
template <int TB>
__device__ __forceinline__ void wgmma_n64_rs(float (&d)[32], uint32_t a0, uint32_t a1, uint32_t a2, uint32_t a3, uint64_t db, int sc) {
  asm volatile("{\n.reg .pred p;\nsetp.ne.b32 p, %37, 0;\n"
    "wgmma.mma_async.sync.aligned.m64n64k16.f32.bf16.bf16 {%0, %1, %2, %3, %4, %5, %6, %7, %8, %9, %10, %11, %12, %13, %14, %15, %16, %17, %18, %19, %20, %21, %22, %23, %24, %25, %26, %27, %28, %29, %30, %31}, {%32,%33,%34,%35}, %36, p, 1, 1, %38;\n}\n"
    : "+f"(d[0]), "+f"(d[1]), "+f"(d[2]), "+f"(d[3]), "+f"(d[4]), "+f"(d[5]), "+f"(d[6]), "+f"(d[7]),
      "+f"(d[8]), "+f"(d[9]), "+f"(d[10]), "+f"(d[11]), "+f"(d[12]), "+f"(d[13]), "+f"(d[14]), "+f"(d[15]),
      "+f"(d[16]), "+f"(d[17]), "+f"(d[18]), "+f"(d[19]), "+f"(d[20]), "+f"(d[21]), "+f"(d[22]), "+f"(d[23]),
      "+f"(d[24]), "+f"(d[25]), "+f"(d[26]), "+f"(d[27]), "+f"(d[28]), "+f"(d[29]), "+f"(d[30]), "+f"(d[31])
    : "r"(a0), "r"(a1), "r"(a2), "r"(a3), "l"(db), "r"(sc), "n"(TB));
}
template <int TA, int TB>
__device__ __forceinline__ void wgmma_n128_ss(float (&d)[64], uint64_t da, uint64_t db, int sc) {
  asm volatile("{\n.reg .pred p;\nsetp.ne.b32 p, %66, 0;\n"
    "wgmma.mma_async.sync.aligned.m64n128k16.f32.bf16.bf16 {%0, %1, %2, %3, %4, %5, %6, %7, %8, %9, %10, %11, %12, %13, %14, %15, %16, %17, %18, %19, %20, %21, %22, %23, %24, %25, %26, %27, %28, %29, %30, %31, %32, %33, %34, %35, %36, %37, %38, %39, %40, %41, %42, %43, %44, %45, %46, %47, %48, %49, %50, %51, %52, %53, %54, %55, %56, %57, %58, %59, %60, %61, %62, %63}, %64, %65, p, 1, 1, %67, %68;\n}\n"
    : "+f"(d[0]), "+f"(d[1]), "+f"(d[2]), "+f"(d[3]), "+f"(d[4]), "+f"(d[5]), "+f"(d[6]), "+f"(d[7]),
      "+f"(d[8]), "+f"(d[9]), "+f"(d[10]), "+f"(d[11]), "+f"(d[12]), "+f"(d[13]), "+f"(d[14]), "+f"(d[15]),
      "+f"(d[16]), "+f"(d[17]), "+f"(d[18]), "+f"(d[19]), "+f"(d[20]), "+f"(d[21]), "+f"(d[22]), "+f"(d[23]),
      "+f"(d[24]), "+f"(d[25]), "+f"(d[26]), "+f"(d[27]), "+f"(d[28]), "+f"(d[29]), "+f"(d[30]), "+f"(d[31]),
      "+f"(d[32]), "+f"(d[33]), "+f"(d[34]), "+f"(d[35]), "+f"(d[36]), "+f"(d[37]), "+f"(d[38]), "+f"(d[39]),
      "+f"(d[40]), "+f"(d[41]), "+f"(d[42]), "+f"(d[43]), "+f"(d[44]), "+f"(d[45]), "+f"(d[46]), "+f"(d[47]),
      "+f"(d[48]), "+f"(d[49]), "+f"(d[50]), "+f"(d[51]), "+f"(d[52]), "+f"(d[53]), "+f"(d[54]), "+f"(d[55]),
      "+f"(d[56]), "+f"(d[57]), "+f"(d[58]), "+f"(d[59]), "+f"(d[60]), "+f"(d[61]), "+f"(d[62]), "+f"(d[63])
    : "l"(da), "l"(db), "r"(sc), "n"(TA), "n"(TB));
}
template <int TB>
__device__ __forceinline__ void wgmma_n128_rs(float (&d)[64], uint32_t a0, uint32_t a1, uint32_t a2, uint32_t a3, uint64_t db, int sc) {
  asm volatile("{\n.reg .pred p;\nsetp.ne.b32 p, %69, 0;\n"
    "wgmma.mma_async.sync.aligned.m64n128k16.f32.bf16.bf16 {%0, %1, %2, %3, %4, %5, %6, %7, %8, %9, %10, %11, %12, %13, %14, %15, %16, %17, %18, %19, %20, %21, %22, %23, %24, %25, %26, %27, %28, %29, %30, %31, %32, %33, %34, %35, %36, %37, %38, %39, %40, %41, %42, %43, %44, %45, %46, %47, %48, %49, %50, %51, %52, %53, %54, %55, %56, %57, %58, %59, %60, %61, %62, %63}, {%64,%65,%66,%67}, %68, p, 1, 1, %70;\n}\n"
    : "+f"(d[0]), "+f"(d[1]), "+f"(d[2]), "+f"(d[3]), "+f"(d[4]), "+f"(d[5]), "+f"(d[6]), "+f"(d[7]),
      "+f"(d[8]), "+f"(d[9]), "+f"(d[10]), "+f"(d[11]), "+f"(d[12]), "+f"(d[13]), "+f"(d[14]), "+f"(d[15]),
      "+f"(d[16]), "+f"(d[17]), "+f"(d[18]), "+f"(d[19]), "+f"(d[20]), "+f"(d[21]), "+f"(d[22]), "+f"(d[23]),
      "+f"(d[24]), "+f"(d[25]), "+f"(d[26]), "+f"(d[27]), "+f"(d[28]), "+f"(d[29]), "+f"(d[30]), "+f"(d[31]),
      "+f"(d[32]), "+f"(d[33]), "+f"(d[34]), "+f"(d[35]), "+f"(d[36]), "+f"(d[37]), "+f"(d[38]), "+f"(d[39]),
      "+f"(d[40]), "+f"(d[41]), "+f"(d[42]), "+f"(d[43]), "+f"(d[44]), "+f"(d[45]), "+f"(d[46]), "+f"(d[47]),
      "+f"(d[48]), "+f"(d[49]), "+f"(d[50]), "+f"(d[51]), "+f"(d[52]), "+f"(d[53]), "+f"(d[54]), "+f"(d[55]),
      "+f"(d[56]), "+f"(d[57]), "+f"(d[58]), "+f"(d[59]), "+f"(d[60]), "+f"(d[61]), "+f"(d[62]), "+f"(d[63])
    : "r"(a0), "r"(a1), "r"(a2), "r"(a3), "l"(db), "r"(sc), "n"(TB));
}

__device__ __forceinline__ void poll1(uint32_t (&v)[1], const void* p, uint32_t tag, uint32_t mask) {
  asm volatile("{\n.reg .pred p, q;\n.reg .u32 c, b;\n.reg .b64 x, y;\n.reg .b128 z;\nmov.u32 c, 0;\nLW:\n"
               "ld.relaxed.gpu.global.u32 %0, [%1+0];\n"
               "xor.b32 b, %0, %2;\n"
               "and.b32 b, b, %3;\nsetp.eq.u32 p, b, 0;\nvote.sync.all.pred p, p, 0xffffffff;\n@p bra.uni LD;\n"
               "nanosleep.u32 150;\nadd.u32 c, c, 1;\nsetp.lt.u32 q, c, 1000000;\n@q bra.uni LW;\ntrap;\nLD:\n}"
               : "=&r"(v[0])
               : "l"(p), "r"(tag), "r"(mask) : "memory");
}
__device__ __forceinline__ void poll_pair(uint32_t (&v)[2], const void* p, uint32_t tag, uint32_t mask) {
  asm volatile("{\n.reg .pred p, q;\n.reg .u32 c, b;\n.reg .b64 x, y;\n.reg .b128 z;\nmov.u32 c, 0;\nLW:\n"
               "ld.relaxed.gpu.global.b64 x, [%2+0];\nmov.b64 {%0,%1}, x;\n"
               "xor.b32 b, %0, %3;\n"
               "and.b32 b, b, %4;\nsetp.eq.u32 p, b, 0;\nvote.sync.all.pred p, p, 0xffffffff;\n@p bra.uni LD;\n"
               "nanosleep.u32 100;\nadd.u32 c, c, 1;\nsetp.lt.u32 q, c, 1000000;\n@q bra.uni LW;\ntrap;\nLD:\n}"
               : "=&r"(v[0]), "=&r"(v[1])
               : "l"(p), "r"(tag), "r"(mask) : "memory");
}
__device__ __forceinline__ void poll_quad(uint32_t (&v)[4], const void* p, uint32_t tag, uint32_t mask) {
  asm volatile("{\n.reg .pred p, q;\n.reg .u32 c, b;\n.reg .b64 x, y;\n.reg .b128 z;\nmov.u32 c, 0;\nLW:\n"
               "ld.relaxed.gpu.global.v4.u32 {%0,%1,%2,%3}, [%4+0];\n"
               "xor.b32 b, %0, %5;\n"
               "lop3.b32 b, b, %1, %5, 0xf6;\nlop3.b32 b, b, %2, %5, 0xf6;\nlop3.b32 b, b, %3, %5, 0xf6;\n"
               "and.b32 b, b, %6;\nsetp.eq.u32 p, b, 0;\nvote.sync.all.pred p, p, 0xffffffff;\n@p bra.uni LD;\n"
               "nanosleep.u32 300;\nadd.u32 c, c, 1;\nsetp.lt.u32 q, c, 1000000;\n@q bra.uni LW;\ntrap;\nLD:\n}"
               : "=&r"(v[0]), "=&r"(v[1]), "=&r"(v[2]), "=&r"(v[3])
               : "l"(p), "r"(tag), "r"(mask) : "memory");
}
__device__ __forceinline__ void poll8(uint32_t (&v)[8], const void* p, uint32_t tag, uint32_t mask) {
  asm volatile("{\n.reg .pred p, q;\n.reg .u32 c, b;\n.reg .b64 x, y;\n.reg .b128 z;\nmov.u32 c, 0;\nLW:\n"
               "ld.relaxed.gpu.global.u32 %0, [%8+0];\n"
               "ld.relaxed.gpu.global.u32 %1, [%8+2048];\n"
               "ld.relaxed.gpu.global.u32 %2, [%8+4096];\n"
               "ld.relaxed.gpu.global.u32 %3, [%8+6144];\n"
               "ld.relaxed.gpu.global.u32 %4, [%8+8192];\n"
               "ld.relaxed.gpu.global.u32 %5, [%8+10240];\n"
               "ld.relaxed.gpu.global.u32 %6, [%8+12288];\n"
               "ld.relaxed.gpu.global.u32 %7, [%8+14336];\n"
               "xor.b32 b, %0, %9;\n"
               "lop3.b32 b, b, %1, %9, 0xf6;\nlop3.b32 b, b, %2, %9, 0xf6;\nlop3.b32 b, b, %3, %9, 0xf6;\nlop3.b32 b, b, %4, %9, 0xf6;\n"
               "lop3.b32 b, b, %5, %9, 0xf6;\nlop3.b32 b, b, %6, %9, 0xf6;\nlop3.b32 b, b, %7, %9, 0xf6;\n"
               "and.b32 b, b, %10;\nsetp.eq.u32 p, b, 0;\nvote.sync.all.pred p, p, 0xffffffff;\n@p bra.uni LD;\n"
               "nanosleep.u32 200;\nadd.u32 c, c, 1;\nsetp.lt.u32 q, c, 1000000;\n@q bra.uni LW;\ntrap;\nLD:\n}"
               : "=&r"(v[0]), "=&r"(v[1]), "=&r"(v[2]), "=&r"(v[3]), "=&r"(v[4]), "=&r"(v[5]), "=&r"(v[6]), "=&r"(v[7])
               : "l"(p), "r"(tag), "r"(mask) : "memory");
}
__device__ __forceinline__ void poll16(uint32_t (&v)[16], const void* p, uint32_t tag, uint32_t mask) {
  asm volatile("{\n.reg .pred p, q;\n.reg .u32 c, b;\n.reg .b64 x, y;\n.reg .b128 z;\nmov.u32 c, 0;\nLW:\n"
               "ld.relaxed.gpu.global.u32 %0, [%16+0];\n"
               "ld.relaxed.gpu.global.u32 %1, [%16+4096];\n"
               "ld.relaxed.gpu.global.u32 %2, [%16+8192];\n"
               "ld.relaxed.gpu.global.u32 %3, [%16+12288];\n"
               "ld.relaxed.gpu.global.u32 %4, [%16+16384];\n"
               "ld.relaxed.gpu.global.u32 %5, [%16+20480];\n"
               "ld.relaxed.gpu.global.u32 %6, [%16+24576];\n"
               "ld.relaxed.gpu.global.u32 %7, [%16+28672];\n"
               "ld.relaxed.gpu.global.u32 %8, [%16+32768];\n"
               "ld.relaxed.gpu.global.u32 %9, [%16+36864];\n"
               "ld.relaxed.gpu.global.u32 %10, [%16+40960];\n"
               "ld.relaxed.gpu.global.u32 %11, [%16+45056];\n"
               "ld.relaxed.gpu.global.u32 %12, [%16+49152];\n"
               "ld.relaxed.gpu.global.u32 %13, [%16+53248];\n"
               "ld.relaxed.gpu.global.u32 %14, [%16+57344];\n"
               "ld.relaxed.gpu.global.u32 %15, [%16+61440];\n"
               "xor.b32 b, %0, %17;\n"
               "lop3.b32 b, b, %1, %17, 0xf6;\nlop3.b32 b, b, %2, %17, 0xf6;\nlop3.b32 b, b, %3, %17, 0xf6;\nlop3.b32 b, b, %4, %17, 0xf6;\n"
               "lop3.b32 b, b, %5, %17, 0xf6;\nlop3.b32 b, b, %6, %17, 0xf6;\nlop3.b32 b, b, %7, %17, 0xf6;\nlop3.b32 b, b, %8, %17, 0xf6;\n"
               "lop3.b32 b, b, %9, %17, 0xf6;\nlop3.b32 b, b, %10, %17, 0xf6;\nlop3.b32 b, b, %11, %17, 0xf6;\nlop3.b32 b, b, %12, %17, 0xf6;\n"
               "lop3.b32 b, b, %13, %17, 0xf6;\nlop3.b32 b, b, %14, %17, 0xf6;\nlop3.b32 b, b, %15, %17, 0xf6;\n"
               "and.b32 b, b, %18;\nsetp.eq.u32 p, b, 0;\nvote.sync.all.pred p, p, 0xffffffff;\n@p bra.uni LD;\n"
               "nanosleep.u32 200;\nadd.u32 c, c, 1;\nsetp.lt.u32 q, c, 1000000;\n@q bra.uni LW;\ntrap;\nLD:\n}"
               : "=&r"(v[0]), "=&r"(v[1]), "=&r"(v[2]), "=&r"(v[3]), "=&r"(v[4]), "=&r"(v[5]), "=&r"(v[6]), "=&r"(v[7]), "=&r"(v[8]), "=&r"(v[9]), "=&r"(v[10]), "=&r"(v[11]), "=&r"(v[12]), "=&r"(v[13]), "=&r"(v[14]), "=&r"(v[15])
               : "l"(p), "r"(tag), "r"(mask) : "memory");
}
__device__ __forceinline__ void poll_keys(uint32_t (&v)[16], const void* p, uint32_t tag, uint32_t mask) {
  asm volatile("{\n.reg .pred p, q;\n.reg .u32 c, b;\n.reg .b64 x, y;\n.reg .b128 z;\nmov.u32 c, 0;\nLW:\n"
               "ld.relaxed.gpu.global.v2.b64 {x, y}, [%16+0];\nmov.b64 {%0,%1}, x;\nmov.b64 {%2,%3}, y;\n"
               "ld.relaxed.gpu.global.v2.b64 {x, y}, [%16+4096];\nmov.b64 {%4,%5}, x;\nmov.b64 {%6,%7}, y;\n"
               "ld.relaxed.gpu.global.v2.b64 {x, y}, [%16+8192];\nmov.b64 {%8,%9}, x;\nmov.b64 {%10,%11}, y;\n"
               "ld.relaxed.gpu.global.v2.b64 {x, y}, [%16+12288];\nmov.b64 {%12,%13}, x;\nmov.b64 {%14,%15}, y;\n"
               "xor.b32 b, %0, %17;\n"
               "lop3.b32 b, b, %2, %17, 0xf6;\nlop3.b32 b, b, %4, %17, 0xf6;\nlop3.b32 b, b, %6, %17, 0xf6;\nlop3.b32 b, b, %8, %17, 0xf6;\n"
               "lop3.b32 b, b, %10, %17, 0xf6;\nlop3.b32 b, b, %12, %17, 0xf6;\nlop3.b32 b, b, %14, %17, 0xf6;\n"
               "and.b32 b, b, %18;\nsetp.eq.u32 p, b, 0;\nvote.sync.all.pred p, p, 0xffffffff;\n@p bra.uni LD;\n"
               "nanosleep.u32 20;\nadd.u32 c, c, 1;\nsetp.lt.u32 q, c, 1000000;\n@q bra.uni LW;\ntrap;\nLD:\n}"
               : "=&r"(v[0]), "=&r"(v[1]), "=&r"(v[2]), "=&r"(v[3]), "=&r"(v[4]), "=&r"(v[5]), "=&r"(v[6]), "=&r"(v[7]), "=&r"(v[8]), "=&r"(v[9]), "=&r"(v[10]), "=&r"(v[11]), "=&r"(v[12]), "=&r"(v[13]), "=&r"(v[14]), "=&r"(v[15])
               : "l"(p), "r"(tag), "r"(mask) : "memory");
}
__device__ __forceinline__ void poll_z(uint32_t (&v)[16], const void* p, uint32_t tag, uint32_t mask) {
  asm volatile("{\n.reg .pred p, q;\n.reg .u32 c, b;\n.reg .b64 x, y;\n.reg .b128 z;\nmov.u32 c, 0;\nLW:\n"
               "ld.relaxed.gpu.global.v4.u32 {%0,%1,%2,%3}, [%16+0];\n"
               "ld.relaxed.gpu.global.v4.u32 {%4,%5,%6,%7}, [%16+4096];\n"
               "ld.relaxed.gpu.global.v4.u32 {%8,%9,%10,%11}, [%16+8192];\n"
               "ld.relaxed.gpu.global.v4.u32 {%12,%13,%14,%15}, [%16+12288];\n"
               "xor.b32 b, %0, %17;\n"
               "lop3.b32 b, b, %1, %17, 0xf6;\nlop3.b32 b, b, %2, %17, 0xf6;\nlop3.b32 b, b, %3, %17, 0xf6;\nlop3.b32 b, b, %4, %17, 0xf6;\n"
               "lop3.b32 b, b, %5, %17, 0xf6;\nlop3.b32 b, b, %6, %17, 0xf6;\nlop3.b32 b, b, %7, %17, 0xf6;\nlop3.b32 b, b, %8, %17, 0xf6;\n"
               "lop3.b32 b, b, %9, %17, 0xf6;\nlop3.b32 b, b, %10, %17, 0xf6;\nlop3.b32 b, b, %11, %17, 0xf6;\nlop3.b32 b, b, %12, %17, 0xf6;\n"
               "lop3.b32 b, b, %13, %17, 0xf6;\nlop3.b32 b, b, %14, %17, 0xf6;\nlop3.b32 b, b, %15, %17, 0xf6;\n"
               "and.b32 b, b, %18;\nsetp.eq.u32 p, b, 0;\nvote.sync.all.pred p, p, 0xffffffff;\n@p bra.uni LD;\n"
               "nanosleep.u32 300;\nadd.u32 c, c, 1;\nsetp.lt.u32 q, c, 1000000;\n@q bra.uni LW;\ntrap;\nLD:\n}"
               : "=&r"(v[0]), "=&r"(v[1]), "=&r"(v[2]), "=&r"(v[3]), "=&r"(v[4]), "=&r"(v[5]), "=&r"(v[6]), "=&r"(v[7]), "=&r"(v[8]), "=&r"(v[9]), "=&r"(v[10]), "=&r"(v[11]), "=&r"(v[12]), "=&r"(v[13]), "=&r"(v[14]), "=&r"(v[15])
               : "l"(p), "r"(tag), "r"(mask) : "memory");
}
__device__ __forceinline__ void poll7x4(uint32_t (&v)[28], const void* p, uint32_t tag, uint32_t mask) {
  asm volatile("{\n.reg .pred p, q;\n.reg .u32 c, b;\n.reg .b64 x, y;\n.reg .b128 z;\nmov.u32 c, 0;\nLW:\n"
               "ld.relaxed.gpu.global.v4.u32 {%0,%1,%2,%3}, [%28+0];\n"
               "ld.relaxed.gpu.global.v4.u32 {%4,%5,%6,%7}, [%28+2048];\n"
               "ld.relaxed.gpu.global.v4.u32 {%8,%9,%10,%11}, [%28+4096];\n"
               "ld.relaxed.gpu.global.v4.u32 {%12,%13,%14,%15}, [%28+6144];\n"
               "ld.relaxed.gpu.global.v4.u32 {%16,%17,%18,%19}, [%28+8192];\n"
               "ld.relaxed.gpu.global.v4.u32 {%20,%21,%22,%23}, [%28+10240];\n"
               "ld.relaxed.gpu.global.v4.u32 {%24,%25,%26,%27}, [%28+12288];\n"
               "xor.b32 b, %0, %29;\n"
               "lop3.b32 b, b, %1, %29, 0xf6;\nlop3.b32 b, b, %2, %29, 0xf6;\nlop3.b32 b, b, %3, %29, 0xf6;\nlop3.b32 b, b, %4, %29, 0xf6;\n"
               "lop3.b32 b, b, %5, %29, 0xf6;\nlop3.b32 b, b, %6, %29, 0xf6;\nlop3.b32 b, b, %7, %29, 0xf6;\nlop3.b32 b, b, %8, %29, 0xf6;\n"
               "lop3.b32 b, b, %9, %29, 0xf6;\nlop3.b32 b, b, %10, %29, 0xf6;\nlop3.b32 b, b, %11, %29, 0xf6;\nlop3.b32 b, b, %12, %29, 0xf6;\n"
               "lop3.b32 b, b, %13, %29, 0xf6;\nlop3.b32 b, b, %14, %29, 0xf6;\nlop3.b32 b, b, %15, %29, 0xf6;\nlop3.b32 b, b, %16, %29, 0xf6;\n"
               "lop3.b32 b, b, %17, %29, 0xf6;\nlop3.b32 b, b, %18, %29, 0xf6;\nlop3.b32 b, b, %19, %29, 0xf6;\nlop3.b32 b, b, %20, %29, 0xf6;\n"
               "lop3.b32 b, b, %21, %29, 0xf6;\nlop3.b32 b, b, %22, %29, 0xf6;\nlop3.b32 b, b, %23, %29, 0xf6;\nlop3.b32 b, b, %24, %29, 0xf6;\n"
               "lop3.b32 b, b, %25, %29, 0xf6;\nlop3.b32 b, b, %26, %29, 0xf6;\nlop3.b32 b, b, %27, %29, 0xf6;\n"
               "and.b32 b, b, %30;\nsetp.eq.u32 p, b, 0;\nvote.sync.all.pred p, p, 0xffffffff;\n@p bra.uni LD;\n"
               "nanosleep.u32 200;\nadd.u32 c, c, 1;\nsetp.lt.u32 q, c, 1000000;\n@q bra.uni LW;\ntrap;\nLD:\n}"
               : "=&r"(v[0]), "=&r"(v[1]), "=&r"(v[2]), "=&r"(v[3]), "=&r"(v[4]), "=&r"(v[5]), "=&r"(v[6]), "=&r"(v[7]), "=&r"(v[8]), "=&r"(v[9]), "=&r"(v[10]), "=&r"(v[11]), "=&r"(v[12]), "=&r"(v[13]), "=&r"(v[14]), "=&r"(v[15]), "=&r"(v[16]), "=&r"(v[17]), "=&r"(v[18]), "=&r"(v[19]), "=&r"(v[20]), "=&r"(v[21]), "=&r"(v[22]), "=&r"(v[23]), "=&r"(v[24]), "=&r"(v[25]), "=&r"(v[26]), "=&r"(v[27])
               : "l"(p), "r"(tag), "r"(mask) : "memory");
}
__device__ __forceinline__ void poll_kvp(uint32_t (&v)[16], const void* p, uint32_t tag, uint32_t mask) {
  asm volatile("{\n.reg .pred p, q;\n.reg .u32 c, b;\n.reg .b64 x, y;\n.reg .b128 z;\nmov.u32 c, 0;\nLW:\n"
               "ld.relaxed.gpu.global.b128 z, [%16+0];\nmov.b128 {x, y}, z;\nmov.b64 {%0,%1}, x;\nmov.b64 {%2,%3}, y;\n"
               "ld.relaxed.gpu.global.b128 z, [%16+8192];\nmov.b128 {x, y}, z;\nmov.b64 {%4,%5}, x;\nmov.b64 {%6,%7}, y;\n"
               "ld.relaxed.gpu.global.b128 z, [%16+16384];\nmov.b128 {x, y}, z;\nmov.b64 {%8,%9}, x;\nmov.b64 {%10,%11}, y;\n"
               "ld.relaxed.gpu.global.b128 z, [%16+24576];\nmov.b128 {x, y}, z;\nmov.b64 {%12,%13}, x;\nmov.b64 {%14,%15}, y;\n"
               "xor.b32 b, %0, %17;\n"
               "lop3.b32 b, b, %4, %17, 0xf6;\nlop3.b32 b, b, %8, %17, 0xf6;\nlop3.b32 b, b, %12, %17, 0xf6;\n"
               "and.b32 b, b, %18;\nsetp.eq.u32 p, b, 0;\nvote.sync.all.pred p, p, 0xffffffff;\n@p bra.uni LD;\n"
               "nanosleep.u32 100;\nadd.u32 c, c, 1;\nsetp.lt.u32 q, c, 1000000;\n@q bra.uni LW;\ntrap;\nLD:\n}"
               : "=&r"(v[0]), "=&r"(v[1]), "=&r"(v[2]), "=&r"(v[3]), "=&r"(v[4]), "=&r"(v[5]), "=&r"(v[6]), "=&r"(v[7]), "=&r"(v[8]), "=&r"(v[9]), "=&r"(v[10]), "=&r"(v[11]), "=&r"(v[12]), "=&r"(v[13]), "=&r"(v[14]), "=&r"(v[15])
               : "l"(p), "r"(tag), "r"(mask) : "memory");
}
__device__ __forceinline__ void poll_kv(uint32_t (&v)[16], const void* p, uint32_t tag, uint32_t mask) {
  asm volatile("{\n.reg .pred p, q;\n.reg .u32 c, b;\n.reg .b64 x, y;\n.reg .b128 z;\nmov.u32 c, 0;\nLW:\n"
               "ld.relaxed.gpu.global.b128 z, [%16+0];\nmov.b128 {x, y}, z;\nmov.b64 {%0,%1}, x;\nmov.b64 {%2,%3}, y;\n"
               "ld.relaxed.gpu.global.b128 z, [%16+2048];\nmov.b128 {x, y}, z;\nmov.b64 {%4,%5}, x;\nmov.b64 {%6,%7}, y;\n"
               "ld.relaxed.gpu.global.b128 z, [%16+4096];\nmov.b128 {x, y}, z;\nmov.b64 {%8,%9}, x;\nmov.b64 {%10,%11}, y;\n"
               "ld.relaxed.gpu.global.b128 z, [%16+6144];\nmov.b128 {x, y}, z;\nmov.b64 {%12,%13}, x;\nmov.b64 {%14,%15}, y;\n"
               "xor.b32 b, %0, %17;\n"
               "lop3.b32 b, b, %4, %17, 0xf6;\nlop3.b32 b, b, %8, %17, 0xf6;\nlop3.b32 b, b, %12, %17, 0xf6;\n"
               "and.b32 b, b, %18;\nsetp.eq.u32 p, b, 0;\nvote.sync.all.pred p, p, 0xffffffff;\n@p bra.uni LD;\n"
               "nanosleep.u32 100;\nadd.u32 c, c, 1;\nsetp.lt.u32 q, c, 1000000;\n@q bra.uni LW;\ntrap;\nLD:\n}"
               : "=&r"(v[0]), "=&r"(v[1]), "=&r"(v[2]), "=&r"(v[3]), "=&r"(v[4]), "=&r"(v[5]), "=&r"(v[6]), "=&r"(v[7]), "=&r"(v[8]), "=&r"(v[9]), "=&r"(v[10]), "=&r"(v[11]), "=&r"(v[12]), "=&r"(v[13]), "=&r"(v[14]), "=&r"(v[15])
               : "l"(p), "r"(tag), "r"(mask) : "memory");
}

__device__ __align__(1024) __nv_bfloat16 g_o[2048 * 1024];
__device__ __align__(128) uint2 g_keys[2048];
__device__ __align__(128) uint32_t g_csum[18 * 1024];
__device__ __align__(128) uint32_t g_z[16 * 1024];
__device__ __align__(128) uint4 g_kvp[128 * 512];
__device__ __align__(128) uint4 g_kv[8 * 512];
__device__ __align__(128) uint32_t g_h[112 * 256];
__device__ __align__(128) uint32_t g_yp[128 * 512];
__device__ __align__(128) uint32_t g_xsel[4096 + 32];
__device__ __align__(128) uint32_t g_flagO[256 * 8];
__device__ __align__(128) uint32_t g_flagR[32];
__device__ uint32_t g_epoch;

constexpr uint32_t RING = 1024, SLOT = 32768, SMEM_BYTES = 232448;
constexpr int NST = 5, HST = 7;
constexpr uint32_t STG = RING + 163840, AUX = RING + 196608, FR = RING + 212992, MISC = RING + 229376;
constexpr uint32_t B_FULL = MISC, B_EMPTY = MISC + 56, B_XS = MISC + 112, B_SEL = MISC + 144, B_XRES = MISC + 152, B_WK = MISC + 160, B_CSDN = MISC + 168,
                   B_FR = MISC + 176, B_FE = MISC + 216, B_DR = MISC + 256, B_DE = MISC + 288, NBAR = 40;
constexpr uint32_t S_EPOCH = MISC + 320, S_NCAND = MISC + 324, S_SEL = MISC + 336, S_WMAX = MISC + 368,
                   S_KSTAT = MISC + 512, S_CSK = MISC + 1536, S_CSV = MISC + 2048, S_CSQ = MISC + 2560, S_ONES = MISC + 512;
constexpr uint32_t KVB_P0 = AUX, KVB_Z = AUX + 4096, KVB_P1 = AUX + 5120, HOP = AUX + 9216, GR = FR - 4096;
enum { NB_Z = 0, NB_KV = 1, NB_VQ = 2, NB_WG0 = 3, NB_FDONE = 4, NB_PK = 5, NB_KVB = 6, NB_WG1 = 7, NB_WG2 = 8, NB_CSQ = 9,
       NB_Y = 10, NB_ST = 11, NB_OWN0 = 12, NB_OWN1 = 13, NB_Q0 = 14, NB_H1 = 15 };

#define XS_AT 0
#define XS_STEP 1
#define PFD 6
#define FFN_AT 12
constexpr float LOG2E = 1.4426950408889634f, LN2 = 0.6931471805599453f;

#define ELECT "{\n.reg .pred p;\nelect.sync _|p, 0xffffffff;\n"
#define TMA2D "cp.async.bulk.tensor.2d.shared::cluster.global.mbarrier::complete_tx::bytes"
#define TMA3D "cp.async.bulk.tensor.3d.shared::cluster.global.mbarrier::complete_tx::bytes"
__device__ __forceinline__ void e_expect(uint32_t b, uint32_t n) {
  asm volatile(ELECT "@p mbarrier.arrive.expect_tx.shared::cta.b64 _, [%0], %1;\n}" ::"r"(b), "r"(n) : "memory");
}
__device__ __forceinline__ void e_arrive(uint32_t b) { asm volatile(ELECT "@p mbarrier.arrive.shared::cta.b64 _, [%0];\n}" ::"r"(b) : "memory"); }
__device__ __forceinline__ void e_tma2d(uint32_t dst, const CUtensorMap* m, int c0, int c1, uint32_t bar) {
  asm volatile(ELECT "@p " TMA2D " [%0], [%1, {%3, %4}], [%2];\n}" ::"r"(dst), "l"(m), "r"(bar), "r"(c0), "r"(c1) : "memory");
}
__device__ __forceinline__ void e_tma2d_ef(uint32_t dst, const CUtensorMap* m, int c0, int c1, uint32_t bar, uint64_t pol) {
  asm volatile(ELECT "@p " TMA2D ".L2::cache_hint [%0], [%1, {%3, %4}], [%2], %5;\n}" ::"r"(dst), "l"(m), "r"(bar), "r"(c0), "r"(c1), "l"(pol) : "memory");
}
__device__ __forceinline__ void e_tma3d(uint32_t dst, const CUtensorMap* m, int c1, int c2, uint32_t bar) {
  asm volatile(ELECT "@p " TMA3D " [%0], [%1, {0, %3, %4}], [%2];\n}" ::"r"(dst), "l"(m), "r"(bar), "r"(c1), "r"(c2) : "memory");
}
__device__ __forceinline__ void e_store2d(const CUtensorMap* m, int c0, int c1, uint32_t src) {
  asm volatile(ELECT "@p cp.async.bulk.tensor.2d.global.shared::cta.bulk_group [%0, {%2, %3}], [%1];\n}" ::"l"(m), "r"(src), "r"(c0), "r"(c1) : "memory");
}
__device__ __forceinline__ void e_tma3d_ef(uint32_t dst, const CUtensorMap* m, int c0, int c1, uint32_t bar, uint64_t pol) {
  asm volatile(ELECT "@p " TMA3D ".L2::cache_hint [%0], [%1, {%3, %4, 0}], [%2], %5;\n}" ::"r"(dst), "l"(m), "r"(bar), "r"(c0), "r"(c1), "l"(pol) : "memory");
}
__device__ __forceinline__ void e_load(uint32_t dst, const void* src, uint32_t n, uint32_t bar) {
  asm volatile(ELECT "@p cp.async.bulk.shared::cluster.global.mbarrier::complete_tx::bytes [%0], [%1], %2, [%3];\n}" ::"r"(dst), "l"(src), "r"(n), "r"(bar) : "memory");
}
template <int I0, int I1> __device__ __forceinline__ void e_init() {
#pragma unroll
  for (int i = I0; i < I1; i++) asm volatile(ELECT "@p mbarrier.init.shared::cta.b64 [%0], %1;\n}" ::"r"(MISC + 8 * i), "r"(MISC + 8 * i == B_CSDN ? 4 : 1) : "memory");
  asm volatile("fence.mbarrier_init.release.cluster;" ::: "memory");
}
__device__ __forceinline__ void e_pfmap(const CUtensorMap* m) { asm volatile(ELECT "@p prefetch.tensormap [%0];\n}" ::"l"(m) : "memory"); }
__device__ __forceinline__ void bulk_wait_read() { asm volatile("cp.async.bulk.commit_group;\ncp.async.bulk.wait_group.read 0;" ::: "memory"); }
__device__ __forceinline__ void e_release(uint32_t* flag, uint32_t v, int lane) {
  asm volatile("cp.async.bulk.commit_group;\ncp.async.bulk.wait_group 0;\nfence.release.gpu;" ::: "memory");
  if (lane < 8) asm volatile("st.relaxed.gpu.global.u32 [%0], %1;" ::"l"(flag + lane), "r"(v) : "memory");
}

__device__ __forceinline__ void mbar_arrive(uint32_t b) { asm volatile("mbarrier.arrive.shared::cta.b64 _, [%0];" ::"r"(b) : "memory"); }
__device__ __forceinline__ void mbar_wait(uint32_t b, uint32_t ph) {
  asm volatile("{\n.reg .pred p, q;\n.reg .u32 c;\nmov.u32 c, 0;\nLW:\nmbarrier.try_wait.parity.shared::cta.b64 p, [%0], %1;\n@p bra LD;\n"
               "add.u32 c, c, 1;\nsetp.lt.u32 q, c, 100000;\n@q bra LW;\ntrap;\nLD:\n}" ::"r"(b), "r"(ph) : "memory");
}
__device__ __forceinline__ void nb_sync(int id, int n) { asm volatile("bar.sync %0, %1;" ::"r"(id), "r"(n) : "memory"); }
__device__ __forceinline__ void nb_arrive(int id, int n) { asm volatile("bar.arrive %0, %1;" ::"r"(id), "r"(n) : "memory"); }
__device__ __forceinline__ void wg_fence() { asm volatile("wgmma.fence.sync.aligned;" ::: "memory"); }
__device__ __forceinline__ void wg_commit() { asm volatile("wgmma.commit_group.sync.aligned;" ::: "memory"); }
template <int N> __device__ __forceinline__ void wg_wait() { asm volatile("wgmma.wait_group.sync.aligned %0;" ::"n"(N) : "memory"); }
template <int N> __device__ __forceinline__ void reg_fence(float (&a)[N]) {
#pragma unroll
  for (int i = 0; i < N; i++) asm volatile("" : "+f"(a[i])::"memory");
}
template <int N> __device__ __forceinline__ void reg_zero(float (&a)[N]) {
#pragma unroll
  for (int i = 0; i < N; i++) a[i] = 0.f;
}
__device__ __forceinline__ constexpr uint64_t mkdesc(uint32_t addr, uint32_t lbo, uint32_t sbo, uint32_t swz) {
  return (uint64_t)(addr >> 4) | ((uint64_t)(lbo >> 4) << 16) | ((uint64_t)(sbo >> 4) << 32) | ((uint64_t)swz << 62);
}
__device__ __forceinline__ void fence_async_smem() { asm volatile("fence.proxy.async.shared::cta;" ::: "memory"); }
__device__ __forceinline__ void fence_async_glob() { asm volatile("fence.proxy.async.global;" ::: "memory"); }
__device__ __forceinline__ void fence_acq() { asm volatile("fence.acquire.gpu;" ::: "memory"); }
__device__ __forceinline__ void st_relaxed(uint32_t* p, uint32_t v) { asm volatile("st.relaxed.gpu.global.u32 [%0], %1;" ::"l"(p), "r"(v) : "memory"); }
__device__ __forceinline__ uint32_t ld_relaxed(const uint32_t* p) { uint32_t v; asm volatile("ld.relaxed.gpu.global.u32 %0, [%1];" : "=r"(v) : "l"(p) : "memory"); return v; }
__device__ __forceinline__ void st_unit(uint4* p, uint32_t a, uint32_t b, uint32_t c, uint32_t d, uint32_t par) {
  asm volatile("{\n.reg .b64 x, y;\n.reg .b128 z;\nmov.b64 x, {%1,%2};\nmov.b64 y, {%3,%4};\nmov.b128 z, {x, y};\nst.relaxed.gpu.global.b128 [%0], z;\n}"
               ::"l"(p), "r"((a & ~1u) | par), "r"(b), "r"(c), "r"(d) : "memory");
}
__device__ __forceinline__ void spin_guard(int& c) {
  asm volatile("{\n.reg .pred q;\nadd.u32 %0, %0, 1;\nsetp.lt.u32 q, %0, 1000000;\n@q bra LOK;\ntrap;\nLOK:\n}" : "+r"(c));
}
__device__ __forceinline__ uint4 lds128(uint32_t a) { uint4 v; asm volatile("ld.shared.v4.u32 {%0,%1,%2,%3}, [%4];" : "=r"(v.x), "=r"(v.y), "=r"(v.z), "=r"(v.w) : "r"(a)); return v; }
__device__ __forceinline__ float4 lds128f(uint32_t a) { float4 v; asm volatile("ld.shared.v4.f32 {%0,%1,%2,%3}, [%4];" : "=f"(v.x), "=f"(v.y), "=f"(v.z), "=f"(v.w) : "r"(a)); return v; }
__device__ __forceinline__ float2 lds64f(uint32_t a) { float2 v; asm volatile("ld.shared.v2.f32 {%0,%1}, [%2];" : "=f"(v.x), "=f"(v.y) : "r"(a)); return v; }
__device__ __forceinline__ uint32_t lds32(uint32_t a) { uint32_t v; asm volatile("ld.shared.u32 %0, [%1];" : "=r"(v) : "r"(a)); return v; }
__device__ __forceinline__ void sts128(uint32_t a, uint32_t x, uint32_t y, uint32_t z, uint32_t w) { asm volatile("st.shared.v4.u32 [%0], {%1,%2,%3,%4};" ::"r"(a), "r"(x), "r"(y), "r"(z), "r"(w) : "memory"); }
__device__ __forceinline__ void sts128f(uint32_t a, float x, float y, float z, float w) { asm volatile("st.shared.v4.f32 [%0], {%1,%2,%3,%4};" ::"r"(a), "f"(x), "f"(y), "f"(z), "f"(w) : "memory"); }
__device__ __forceinline__ void sts32(uint32_t a, uint32_t x) { asm volatile("st.shared.u32 [%0], %1;" ::"r"(a), "r"(x) : "memory"); }
__device__ __forceinline__ void stsm4(uint32_t a, uint32_t r0, uint32_t r1, uint32_t r2, uint32_t r3) {
  asm volatile("stmatrix.sync.aligned.m8n8.x4.shared.b16 [%0], {%1,%2,%3,%4};" ::"r"(a), "r"(r0), "r"(r1), "r"(r2), "r"(r3) : "memory");
}
__device__ __forceinline__ uint4 ldsm4(uint32_t a) {
  uint4 v; asm volatile("ldmatrix.sync.aligned.m8n8.x4.shared.b16 {%0,%1,%2,%3}, [%4];" : "=r"(v.x), "=r"(v.y), "=r"(v.z), "=r"(v.w) : "r"(a) : "memory"); return v;
}
__device__ __forceinline__ uint32_t pack(float lo, float hi) { uint32_t r; asm("cvt.rn.bf16x2.f32 %0, %1, %2;" : "=r"(r) : "f"(hi), "f"(lo)); return r; }
__device__ __forceinline__ float bf_lo(uint32_t w) { return __uint_as_float(w << 16); }
__device__ __forceinline__ float bf_hi(uint32_t w) { return __uint_as_float(w & 0xffff0000u); }
__device__ __forceinline__ float bf_round(float x) { return bf_lo(pack(x, x)); }
__device__ __forceinline__ float ex2(float x) { float v; asm("ex2.approx.ftz.f32 %0, %1;" : "=f"(v) : "f"(x)); return v; }
__device__ __forceinline__ float rcp(float x) { float v; asm("rcp.approx.ftz.f32 %0, %1;" : "=f"(v) : "f"(x)); return v; }
__device__ __forceinline__ float addsat(float a, float b) { float v; asm("add.sat.f32 %0, %1, %2;" : "=f"(v) : "f"(a), "f"(b)); return v; }
__device__ __forceinline__ float phi2(float a) { return fmaf(fmaxf(a, 0.f), LN2, addsat(ex2(a), 1e-6f)); }
__device__ __forceinline__ uint32_t ln_bf16x2(uint32_t x, uint32_t m, uint32_t hi, uint32_t lo) {
  uint32_t o;
  asm("{\n.reg .b32 d, e;\nsub.rn.bf16x2 d, %1, %2;\nmul.rn.bf16x2 e, d, %4;\nfma.rn.bf16x2 %0, d, %3, e;\n}" : "=r"(o) : "r"(x), "r"(m), "r"(hi), "r"(lo));
  return o;
}
__device__ __forceinline__ float key_score(uint32_t key) { uint32_t u = key >> 16; u = (u & 0x8000u) ? (u & 0x7fffu) : (~u & 0xffffu); return __uint_as_float(u << 16); }
__device__ __forceinline__ int key_token(uint32_t key) { return 2047 - (int)((key >> 5) & 2047u); }
__device__ __forceinline__ uint32_t tagf(float v, uint32_t par) { return (__float_as_uint(v) & ~1u) | par; }
__device__ __forceinline__ float xred(float a, float b, bool up, int o) { return (up ? b : a) + __shfl_xor_sync(0xffffffffu, up ? a : b, o); }

#define STAMP(id)
#define STAMP_IF(c, id)
#define STAMP2(i)

template <bool TRANS>
__device__ __forceinline__ void mainloop(float (&a0)[64], float (&a1)[64], int s, int ph, int handoff, bool leader) {
  uint32_t prev = 0;
#pragma unroll 1
  for (int kt = 0; kt < 16; kt++) {
    mbar_wait(B_FULL + 8 * s, ph);
    const uint64_t dw = mkdesc(RING, 8192, 1024, 1) + s * (SLOT >> 4), dx = mkdesc(RING + 16384, 16, 1024, 1) + s * (SLOT >> 4);
    wg_fence();
#pragma unroll
    for (int j = 0; j < 4; j++) {
      if (TRANS) {
        wgmma_n128_ss<1, 0>(a0, dw + j * 128, dx + j * 2, 1);
        wgmma_n128_ss<1, 0>(a1, dw + j * 128 + 512, dx + j * 2, 1);
      } else {
        wgmma_n128_ss<0, 1>(a0, dx + j * 2, dw + j * 128, 1);
        wgmma_n128_ss<0, 1>(a1, dx + j * 2 + 512, dw + j * 128, 1);
      }
    }
    wg_commit();
    if (handoff && kt == 15) nb_arrive(handoff, 256);
    wg_wait<1>();
    if (prev && leader) mbar_arrive(prev);
    prev = B_EMPTY + 8 * s;
    if (++s == NST) { s = 0; ph ^= 1; }
  }
  wg_wait<0>();
  if (leader) mbar_arrive(prev);
  reg_fence(a0);
  reg_fence(a1);
}

__device__ __forceinline__ int out_kblock(int r, int tn) {
  const int q = r - 2, half = q >= 7, pi = q - 7 * half;
  return r < 2 ? 2 * tn + r : 2 * (pi + (pi >= tn)) + half;
}

struct Maps {
  CUtensorMap wqkv, x, o, os, wo, xs, gu, down, out;
};

__global__ void __launch_bounds__(512, 1)
fused_kernel(const __grid_constant__ Maps mp, const __nv_bfloat16* __restrict__ w_r, const __nv_bfloat16* __restrict__ xg,
             const char* __restrict__ wg, const char* __restrict__ wu, const char* __restrict__ wd) {
  extern __shared__ __align__(1024) uint8_t smem_raw[];
  const int tid = threadIdx.x, lane = tid & 31;
  const int w = __shfl_sync(0xffffffffu, tid >> 5, 0);
  int bid = blockIdx.x;
  {
    uint32_t sm, nsm;
    asm volatile("mov.u32 %0, %%smid;" : "=r"(sm));
    asm volatile("mov.u32 %0, %%nsmid;" : "=r"(nsm));
    const uint32_t p = sm >> 1, q = ((p - 32) * 37) >> 8;
    const uint32_t gpc = p < 32 ? p & 7 : p < 60 ? p - 31 - 7 * q : 0, tpc = p < 32 ? p >> 3 : p < 60 ? 4 + q : p - 58;
    const int id = (p >> 1) == 30 ? 128 + ((0x9cu >> (2 * (sm & 3))) & 3) : ((0x75143620u >> (4 * gpc)) & 7) * 16 + tpc * 2 + (sm & 1);
    if (nsm == 132) bid = id;
  }
  const int tn = (bid & 3) + 4 * (bid >> 6), tm = (bid >> 2) & 15;

  if (w == 12) {
    STAMP_IF(lane == 0, 0);
    e_pfmap(&mp.wqkv);
    e_pfmap(&mp.x);
    e_init<0, 7>();
  } else {
    if (w == 13) e_init<7, 23>();
    if (w == 14) e_init<23, NBAR>();
    if (w == 15) {
      sts32(S_NCAND, 0);
      asm volatile("{\n.reg .pred q;\nsetp.eq.u32 q, %0, 1024;\n@q bra LOK;\ntrap;\nLOK:\n}" ::"r"((uint32_t)__cvta_generic_to_shared(smem_raw)));
    }
    nb_sync(0, 512);
  }

  if (bid >= 128) {
    const int h0 = bid == 128 ? 14 : bid - 129, hs = bid == 128 ? 1 : 3, h1 = bid == 128 ? 16 : 14;
    if (w == 12) {
      int s = 0, ph = 1, n = 0;
      if (bid == 128) { nb_sync(0, 512); mbar_wait(B_SEL, 0); n = HST + 1; }
#pragma unroll 1
      for (int h = h0; h < h1; h += hs) {
        const int c = 2 * h + (h & 8) * 2;
#pragma unroll 1
        for (int kt = 0; kt < 16; kt += 2, n++) {
          if (n == HST) nb_sync(0, 512);
          if (n >= HST) mbar_wait(B_EMPTY + 8 * s, ph);
          e_expect(B_FULL + 8 * s, 32768);
          e_tma3d(RING + s * SLOT, &mp.wqkv, kt * 64, c, B_FULL + 8 * s);
          e_tma3d(RING + s * SLOT + 16384, &mp.wqkv, kt * 64 + 64, c, B_FULL + 8 * s);
          if (++s == HST) { s = 0; ph ^= 1; }
        }
      }
    } else if (w < 4) {
      const uint32_t par = (ld_relaxed(&g_epoch) + 1) & 1u;
      sts32(S_ONES + tid * 4, 0x3f803f80u);
      fence_async_smem();
      nb_sync(NB_WG0, 128);
      int s = 0, ph = 0;
#pragma unroll 1
      for (int h = h0; h < h1; h += hs) {
        float c[4][4];
#pragma unroll
        for (int i = 0; i < 4; i++) reg_zero(c[i]);
        uint32_t prev = 0;
#pragma unroll 1
        for (int kt = 0; kt < 8; kt++) {
          mbar_wait(B_FULL + 8 * s, ph);
          const uint64_t dw = mkdesc(RING, 8192, 1024, 1) + s * (SLOT >> 4);
          wg_fence();
#pragma unroll
          for (int j = 0; j < 16; j++) wgmma_n8_ss<1, 0>(c[j & 3], dw + (j & 3) * 512 + (j >> 2) * 128, mkdesc(S_ONES, 128, 128, 0), 1);
          wg_commit();
          wg_wait<1>();
          if (prev && tid == 0) mbar_arrive(prev);
          prev = B_EMPTY + 8 * s;
          if (++s == HST) { s = 0; ph ^= 1; }
        }
        wg_wait<0>();
        if (tid == 0) mbar_arrive(prev);
#pragma unroll
        for (int i = 0; i < 4; i++) reg_fence(c[i]);
        const bool u2 = lane & 2, u1 = lane & 1;
        const float lo = u2 ? c[1][0] + c[3][0] : c[0][0] + c[2][0], hi = u2 ? c[1][2] + c[3][2] : c[0][2] + c[2][2];
        st_relaxed(g_csum + h * 128 + (lane & 2) * 32 + w * 16 + (lane & 1) * 8 + (lane >> 2), tagf(u1 ? hi : lo, par));
        STAMP_IF(tid == 0, h >= 8 ? 6 : 30);
      }
    } else if (w < 12 && bid == 128) {
      const int t = tid - 128, j = w - 4;
      const uint32_t ep = ld_relaxed(&g_epoch) + 1;
      uint32_t kk[16];
      poll_keys(kk, g_keys + t * 2, ep, 31u);
      const uint32_t k[8] = {kk[0], kk[2], kk[4], kk[6], kk[8], kk[10], kk[12], kk[14]};
      STAMP_IF(t == 0, 42);
      const uint32_t m = __reduce_max_sync(0xffffffffu, max(max(max(k[0], k[1]), max(k[2], k[3])), max(max(k[4], k[5]), max(k[6], k[7]))));
      if (lane == 0) sts32(S_WMAX + j * 4, m);
      nb_sync(NB_WG1, 256);
      const uint32_t T = __reduce_min_sync(0xffffffffu, lds32(S_WMAX + (lane & 7) * 4));
      uint32_t cnt = 0;
#pragma unroll
      for (int i = 0; i < 8; i++) cnt += k[i] >= T;
      if (cnt) {
        uint32_t pos;
        asm volatile("atom.shared.add.u32 %0, [%1], %2;" : "=r"(pos) : "r"(S_NCAND), "r"(cnt * 4) : "memory");
#pragma unroll
        for (int i = 0; i < 8; i++)
          if (k[i] >= T) { sts32(AUX + pos, k[i]); pos += 4; }
      }
      nb_sync(NB_WG1, 256);
      const uint32_t n4 = lds32(S_NCAND);
#pragma unroll 1
      for (uint32_t i = t * 4; i < n4; i += 1024) {
        const uint32_t key = lds32(AUX + i);
        uint32_t rank = 0;
#pragma unroll 4
        for (uint32_t q = 0; q < n4; q += 4) rank += lds32(AUX + q) > key;
        if (rank < 8) sts32(S_SEL + rank * 4, key);
      }
      nb_sync(NB_WG1, 256);
      STAMP_IF(t == 0, 43);
      const uint32_t key = lds32(S_SEL + j * 4);
      const int tok = key_token(key);
      uint4 v[4];
#pragma unroll
      for (int q = 0; q < 4; q++) v[q] = __ldg(reinterpret_cast<const uint4*>(xg + tok * 1024) + q * 32 + lane);
      const uint32_t st = ld_relaxed(&g_keys[tok].y);
      const float rinv = rcp(bf_lo(st)), rhi = bf_round(rinv);
      const uint32_t m2 = __byte_perm(st, 0, 0x3232), hi = pack(rhi, rhi), lo = pack(rinv - rhi, rinv - rhi);
#pragma unroll
      for (int q = 0; q < 4; q++)
        *reinterpret_cast<uint4*>(g_xsel + (q * 8 + (lane >> 2)) * 128 + j * 16 + (((lane & 3) ^ (j >> 1)) << 2)) =
            make_uint4(ln_bf16x2(v[q].x, m2, hi, lo), ln_bf16x2(v[q].y, m2, hi, lo), ln_bf16x2(v[q].z, m2, hi, lo), ln_bf16x2(v[q].w, m2, hi, lo));
      if (lane == 0) g_xsel[4096 + j] = key;
      fence_async_glob();
      fence_async_smem();
      nb_sync(NB_WG1, 256);
      STAMP_IF(t == 0, 44);
      if (j == 0) { e_release(g_flagR, ep, lane); e_arrive(B_SEL); }
      STAMP_IF(t == 0, 45);
    }
  } else if (w >= 12) {
    asm volatile("setmaxnreg.dec.sync.aligned.u32 32;");
    if (w == 12) {
      int s = 0, ph = 1;
#pragma unroll 1
      for (int it = 0; it < 48; it++) {
        const int c = (it < 32 ? (it & 16) + 16 : 0) + 2 * tn;
        if (it == NST) nb_sync(0, 512);
        if (it >= NST) mbar_wait(B_EMPTY + 8 * s, ph);
        e_expect(B_FULL + 8 * s, 32768);
        e_tma3d(RING + s * SLOT, &mp.wqkv, (it & 15) * 64, c, B_FULL + 8 * s);
        e_tma2d(RING + s * SLOT + 16384, &mp.x, (it & 15) * 64, tm * 128, B_FULL + 8 * s);
        STAMP2(it >= NST ? it - NST : 63);
        if (++s == NST) { s = 0; ph ^= 1; }
      }
#pragma unroll 1
      for (int r = 0; r < 16; r++) {
        const int kb = out_kblock(r, tn);
        mbar_wait(B_EMPTY + 8 * s, ph);
        e_expect(B_FULL + 8 * s, r < 2 ? 16384 : 32768);
        e_tma3d(RING + s * SLOT, &mp.wo, kb * 64, 2 * tn, B_FULL + 8 * s);
        if (r < 2) {
          if (r == 0) e_expect(B_XRES, 32768);
          e_tma2d(RING + s * SLOT + 16384, &mp.x, kb * 64, tm * 128, B_XRES);
        }
        STAMP2(r + 48 - NST);
        if (++s == NST) { s = 0; ph ^= 1; }
      }
    } else if (w == 13) {
      e_pfmap(&mp.xs);
#pragma unroll
      for (int c = 0; c < 5; c++) {
        const int it = XS_AT + c * XS_STEP;
        if (it >= NST) mbar_wait(B_FULL + 8 * (it - NST), 0);
        mbar_wait(B_FULL + 8 * (it % NST), it / NST);
        if (c < 4) {
          e_expect(B_XS + 8 * c, 8192);
          e_tma2d(STG + c * 8192, &mp.xs, c * 256, tm * 128 + tn * 16, B_XS + 8 * c);
        } else {
          e_expect(B_WK, 16384);
          e_tma3d(FR, &mp.wqkv, tm * 64, 16 + 2 * tn, B_WK);
        }
      }
      nb_sync(NB_Z, 160);
      const uint32_t ep = lds32(S_EPOCH);
      {
        float z[4] = {0.f, 0.f, 0.f, 0.f};
        __nanosleep(500);
#pragma unroll 1
        for (int i = 0; i < 4; i++) {
          uint32_t p[16];
          poll_z(p, g_z + i * 4096 + tn * 128 + lane * 4, ep, 1u);
#pragma unroll
          for (int q = 0; q < 4; q++) z[q] += (__uint_as_float(p[q]) + __uint_as_float(p[4 + q])) + (__uint_as_float(p[8 + q]) + __uint_as_float(p[12 + q]));
        }
        const uint32_t z01 = pack(z[0], z[1]), z23 = pack(z[2], z[3]);
#pragma unroll
        for (int i = 0; i < 4; i++) {
          const int n = 2 * i + (lane >> 4);
          asm volatile("st.shared.v2.u32 [%0], {%1,%2};" ::"r"(KVB_Z + n * 128 + ((((lane >> 1) & 7) ^ n) << 4) + (lane & 1) * 8), "r"(z01), "r"(z23) : "memory");
        }
        fence_async_smem();
        nb_arrive(NB_KVB, 288);
        STAMP_IF(lane == 0, 46);
      }
      nb_sync(NB_Q0, 192);
      e_store2d(&mp.os, tn * 128, tm * 128, STG);
      nb_sync(NB_OWN0, 288);
      e_store2d(&mp.os, tn * 128, tm * 128 + 64, STG + 8192);
      e_release(g_flagO + (tm * 16 + 2 * tn) * 8, ep, lane);
      STAMP_IF(lane == 0, 4);
      nb_sync(NB_H1, 160);
      e_store2d(&mp.os, tn * 128 + 64, tm * 128, STG + 16384);
      e_store2d(&mp.os, tn * 128 + 64, tm * 128 + 64, STG + 24576);
      e_release(g_flagO + (tm * 16 + 2 * tn + 1) * 8, ep, lane);
      STAMP_IF(lane == 0, 5);
      nb_arrive(NB_ST, 160);
    } else if (w == 14) {
      e_pfmap(&mp.gu); e_pfmap(&mp.o); e_pfmap(&mp.os); e_pfmap(&mp.wo); e_pfmap(&mp.down); e_pfmap(&mp.out);
      const uint32_t ep = ld_relaxed(&g_epoch) + 1;
      nb_sync(NB_FDONE, 416);
      {
        uint32_t c[4];
        poll_quad(c, g_csum + tn * 128 + lane * 4, ep, 1u);
        sts128(S_CSQ + lane * 16, c[0], c[1], c[2], c[3]);
        nb_arrive(NB_CSQ, 160);
        poll_quad(c, g_csum + 1024 + tn * 128 + lane * 4, ep, 1u);
        sts128(S_CSV + lane * 16, c[0], c[1], c[2], c[3]);
        nb_arrive(NB_PK, 288);
      }
      nb_sync(NB_Q0, 192);
      uint32_t ready = 0;
      int s = 0, ph = 1;
#pragma unroll 1
      for (int r = 2; r < 16; r++) {
        const int kb = out_kblock(r, tn);
        if (!((ready >> kb) & 1)) {
          int c = 0;
          do {
            spin_guard(c);
            ready = __ballot_sync(0xffffffffu, ld_relaxed(g_flagO + (tm * 16 + (lane & 15)) * 8) == ep);
          } while (!((ready >> kb) & 1));
          fence_acq();
          fence_async_glob();
        }
        mbar_wait(B_EMPTY + 8 * s, ph);
        e_tma2d(RING + s * SLOT + 16384, &mp.o, kb * 64, tm * 128, B_FULL + 8 * s);
        STAMP_IF(lane == 0 && r == 2, 2);
        STAMP_IF(lane == 0 && r == 9, 3);
        if (++s == NST) { s = 0; ph ^= 1; }
      }
    } else {
      const uint32_t ep = ld_relaxed(&g_epoch) + 1;
      uint64_t pol;
      asm volatile("createpolicy.fractional.L2::evict_first.b64 %0, 1.0;" : "=l"(pol));
      const char* pd = wd + (bid & 15) * 128 + ((bid >> 4) * 448 + lane) * 2048;
      const char* pf = ((bid & 1) ? wu : wg) + (bid >> 1) * 128 + lane * 7168;
#pragma unroll 1
      for (int it = FFN_AT % NST; it < FFN_AT + PFD; it += it < FFN_AT ? NST : 1) {
        mbar_wait(B_FULL + 8 * (it % NST), (it / NST) & 1);
        if (it >= FFN_AT && bid < 112) { asm volatile("prefetch.global.L2 [%0];" ::"l"(pf)); pf += 32 * 7168; }
      }
      mbar_wait(B_CSDN, 0);
      uint32_t f[1];
      poll1(f, g_flagR, ep, 0xffffffffu);
      fence_acq();
      fence_async_glob();
      e_expect(B_SEL, 32);
      e_load(S_SEL, g_xsel + 4096, 32, B_SEL);
      if (bid < 112) {
        int s = 0, ph = 1;
#pragma unroll 1
        for (int n = 0; n < 32; n++) {
          mbar_wait(B_FE + 8 * s, ph);
          e_expect(B_FR + 8 * s, 4608);
          e_tma3d_ef(GR + s * 4096, &mp.gu, bid * 32, n * 32, B_FR + 8 * s, pol);
          e_load(HOP + s * 512, g_xsel + n * 128, 512, B_FR + 8 * s);
          STAMP2(64 + n);
          if (PFD) {
            if (n == 32 - PFD) pf = pd;
            asm volatile("prefetch.global.L2 [%0];" ::"l"(pf));
            pf += n < 32 - PFD ? 32 * 7168 : 65536;
          }
          if (++s == 5) { s = 0; ph ^= 1; }
        }
      }
#pragma unroll 1
      for (int i = 0; i < 14; i++) {
        const int s = (i + 1) & 3;
        if (i >= 4) mbar_wait(B_DE + 8 * s, ((i >> 2) & 1) ^ 1);
        else if (bid < 112) mbar_wait(B_FE + 8 * (s + 1), s != 0);
        e_expect(B_DR + 8 * s, 4096);
        e_tma2d_ef(FR + s * 4096, &mp.down, (bid & 15) * 64, (bid >> 4) * 448 + i * 32, B_DR + 8 * s, pol);
        if (PFD && i + PFD < 14) asm volatile("prefetch.global.L2 [%0];" ::"l"(pd + (i + PFD) * 65536));
      }
    }
  } else if (w >= 8) {
    asm volatile("setmaxnreg.dec.sync.aligned.u32 64;");
    const int t = tid - 256, ww = w - 8;
    const uint32_t ep = ld_relaxed(&g_epoch) + 1, par = ep & 1u;
    {
      const int r0 = (lane >> 3) + (lane & 4);
      const uint32_t a = FR + (ww >> 1) * 8192 + r0 * 128 + ((((ww & 1) * 4 + (lane & 3)) ^ r0) << 4);
      float c[8];
      reg_zero(c);
      mbar_wait(B_WK, 0);
#pragma unroll 2
      for (int i = 0; i < 8; i++) {
        const uint4 v = lds128(a + i * 1024);
        c[0] += bf_lo(v.x); c[1] += bf_hi(v.x); c[2] += bf_lo(v.y); c[3] += bf_hi(v.y);
        c[4] += bf_lo(v.z); c[5] += bf_hi(v.z); c[6] += bf_lo(v.w); c[7] += bf_hi(v.w);
      }
      const bool u16 = lane & 16, u8 = lane & 8, u4 = lane & 4;
      const float d0 = xred(c[0], c[4], u16, 16), d1 = xred(c[1], c[5], u16, 16), d2 = xred(c[2], c[6], u16, 16), d3 = xred(c[3], c[7], u16, 16);
      fence_async_smem();
      e_arrive(B_CSDN);
      const float sum = xred(xred(d0, d2, u8, 8), xred(d1, d3, u8, 8), u4, 4);
      st_relaxed(g_csum + (2 + tm) * 1024 + tn * 128 + ww * 32 + (lane & 3) * 8 + (lane >> 2), tagf(sum, par));
      STAMP_IF(t == 0, 8);
      __nanosleep(500);
      uint32_t p[16];
      poll16(p, g_csum + 2048 + tn * 128 + t, par, 1u);
      float tot = 0.f;
#pragma unroll
      for (int i = 0; i < 16; i += 4) tot += (__uint_as_float(p[i]) + __uint_as_float(p[i + 1])) + (__uint_as_float(p[i + 2]) + __uint_as_float(p[i + 3]));
      sts32(S_CSK + t * 4, __float_as_uint(tot));
      nb_arrive(NB_FDONE, 416);
      STAMP_IF(t == 0, 9);
    }
    const int ks = bid >> 4, nt = bid & 15;
    mbar_wait(B_SEL, 0);
    STAMP_IF(t == 0, 11);
    float fa[4] = {0.f, 0.f, 0.f, 0.f};
    if (bid < 112) {
      int s = 0, ph = 0;
      uint32_t prev = 0;
#pragma unroll 1
      for (int n = 0; n < 32; n++) {
        mbar_wait(B_FR + 8 * s, ph);
        const uint64_t da = mkdesc(GR, 2048, 512, 2) + s * 256, db = mkdesc(HOP, 16, 512, 2) + s * 32;
        wg_fence();
        wgmma_n8_ss<1, 0>(fa, da, db, 1);
        wgmma_n8_ss<1, 0>(fa, da + 64, db + 2, 1);
        wg_commit();
        wg_wait<1>();
        if (prev && t == 0) mbar_arrive(prev);
        prev = B_FE + 8 * s;
        if (++s == 5) { s = 0; ph ^= 1; }
      }
      wg_wait<0>();
      reg_fence(fa);
      if (t == 0) mbar_arrive(prev);
      STAMP_IF(t == 0, 12);
      const bool isup = (ww >> 1) != (wu < wg);
      if (isup) sts128f(GR + (t & 63) * 16, fa[0], fa[1], fa[2], fa[3]);
      nb_sync(NB_WG2, 128);
      if (!isup) {
        const float4 u = lds128f(GR + (t & 63) * 16);
        const float uu[4] = {u.x, u.y, u.z, u.w};
        uint32_t* hp = g_h + bid * 256 + (lane & 3) * 64 + (ww & 1) * 16 + (lane >> 2);
#pragma unroll
        for (int i = 0; i < 4; i++) {
          const float g = fa[i], hv = g * rcp(1.f + ex2(-g * LOG2E)) * uu[i];
          st_relaxed(hp + (i & 1) * 32 + (i >> 1) * 8, __byte_perm(pack(hv, hv), ep, 0x3254));
        }
      }
      nb_sync(NB_WG2, 128);
      reg_zero(fa);
    } else {
      uint32_t f[1];
      poll1(f, g_h + ks * 3584 + 3583, ep, 0xffffu);
    }
    {
      uint32_t v[28];
      poll7x4(v, g_h + ks * 3584 + t * 4, ep, 0xffffu);
#pragma unroll
      for (int q = 0; q < 7; q++)
        asm volatile("st.shared.v2.u32 [%0], {%1,%2};" ::"r"(HOP + q * 1024 + (t >> 3) * 64 + ((((t >> 1) & 3) ^ ((t >> 4) & 3)) << 4) + (t & 1) * 8),
                     "r"(__byte_perm(v[4 * q], v[4 * q + 1], 0x7632)), "r"(__byte_perm(v[4 * q + 2], v[4 * q + 3], 0x7632)) : "memory");
      fence_async_smem();
      nb_sync(NB_WG2, 128);
    }
    STAMP_IF(t == 0, 13);
#pragma unroll 1
    for (int i = 0; i < 14; i++) {
      const int s = (i + 1) & 3;
      mbar_wait(B_DR + 8 * s, (i >> 2) & 1);
      const uint64_t da = mkdesc(FR, 4096, 1024, 1) + s * 256;
      const uint64_t db = mkdesc(HOP, 16, 512, 2) + i * 32;
      wg_fence();
      wgmma_n8_ss<1, 0>(fa, da, db, 1);
      wgmma_n8_ss<1, 0>(fa, da + 128, db + 2, 1);
      wg_commit();
      wg_wait<1>();
      if (i && t == 0) mbar_arrive(B_DE + 8 * (i & 3));
    }
    wg_wait<0>();
    reg_fence(fa);
    STAMP_IF(t == 0, 14);
    {
      uint32_t* yp = g_yp + (nt * 8 + ks) * 512 + (lane & 3) * 128 + ww * 16 + (lane >> 2);
#pragma unroll
      for (int i = 0; i < 4; i++) st_relaxed(yp + (i & 1) * 64 + (i >> 1) * 8, tagf(fa[i], par));
    }
    const uint32_t mykey = lds32(S_SEL + (lane & 7) * 4);
    const uint32_t inmask = __ballot_sync(0xffffffffu, (key_token(mykey) >> 7) == tm) & 0xffu;
    if (inmask) {
      nb_sync(NB_WG2, 128);
      const float sg = rcp(1.f + ex2(-key_score(mykey) * LOG2E));
#pragma unroll 1
      for (int j = 0; j < 8; j++) {
        float y = 0.f;
        if ((inmask >> j) & 1) {
          uint32_t p[8];
          poll8(p, g_yp + (tn * 2 + (t >> 6)) * 4096 + j * 64 + (t & 63), par, 1u);
          y = ((__uint_as_float(p[0]) + __uint_as_float(p[1])) + (__uint_as_float(p[2]) + __uint_as_float(p[3]))) +
              ((__uint_as_float(p[4]) + __uint_as_float(p[5])) + (__uint_as_float(p[6]) + __uint_as_float(p[7])));
        }
        y *= __shfl_sync(0xffffffffu, sg, j);
        asm volatile("st.shared.u16 [%0], %1;" ::"r"(FR + (t >> 6) * 1024 + j * 128 + ((((t >> 3) & 7) ^ j) << 4) + (t & 7) * 2),
                     "h"((unsigned short)pack(y, y)) : "memory");
      }
      fence_async_smem();
      nb_arrive(NB_Y, 256);
    }
    STAMP_IF(t == 0, 15);
  } else if (w >= 4) {
    asm volatile("setmaxnreg.inc.sync.aligned.u32 208;");
    const int t = tid - 128, ww = w - 4, g = lane >> 2, t4 = lane & 3;
    const bool leader = t == 0;
    const uint32_t ep = ld_relaxed(&g_epoch) + 1, par = ep & 1u;
    {
      const uint4* wp = reinterpret_cast<const uint4*>(w_r) + lane;
      uint4 w0 = __ldg(wp), w1 = __ldg(wp + 32), w2 = __ldg(wp + 64), w3 = __ldg(wp + 96);
      if (leader) sts32(S_EPOCH, ep);
      float s[4] = {0.f, 0.f, 0.f, 0.f}, q[4] = {0.f, 0.f, 0.f, 0.f}, d[4] = {0.f, 0.f, 0.f, 0.f}, wsum = 0.f;
#pragma unroll 1
      for (int c = 0; c < 4; c++) {
        const float wr[8] = {bf_lo(w0.x), bf_hi(w0.x), bf_lo(w0.y), bf_hi(w0.y), bf_lo(w0.z), bf_hi(w0.z), bf_lo(w0.w), bf_hi(w0.w)};
        w0 = w1; w1 = w2; w2 = w3;
        wsum += ((wr[0] + wr[1]) + (wr[2] + wr[3])) + ((wr[4] + wr[5]) + (wr[6] + wr[7]));
        mbar_wait(B_XS + 8 * c, 0);
#pragma unroll
        for (int r = 0; r < 4; r++) {
          const uint4 v = lds128(STG + c * 8192 + (ww * 4 + r) * 512 + lane * 16);
          const uint32_t xw[4] = {v.x, v.y, v.z, v.w};
#pragma unroll
          for (int i = 0; i < 4; i++) {
            const float lo = bf_lo(xw[i]), hi = bf_hi(xw[i]);
            s[r] += lo; q[r] = fmaf(lo, lo, q[r]); d[r] = fmaf(lo, wr[2 * i], d[r]);
            s[r] += hi; q[r] = fmaf(hi, hi, q[r]); d[r] = fmaf(hi, wr[2 * i + 1], d[r]);
          }
        }
      }
      STAMP_IF(leader, 16);
      const bool u16 = lane & 16, u8 = lane & 8, u4 = lane & 4, u2 = lane & 2;
      const float s1 = xred(xred(s[0], s[2], u16, 16), xred(s[1], s[3], u16, 16), u8, 8);
      const float q1 = xred(xred(q[0], q[2], u16, 16), xred(q[1], q[3], u16, 16), u8, 8);
      const float d1 = xred(xred(d[0], d[2], u16, 16), xred(d[1], d[3], u16, 16), u8, 8);
      wsum += __shfl_xor_sync(0xffffffffu, wsum, 16);
      wsum += __shfl_xor_sync(0xffffffffu, wsum, 8);
      float tot = xred(xred(s1, d1, u4, 4), xred(q1, wsum, u4, 4), u2, 2);
      tot += __shfl_xor_sync(0xffffffffu, tot, 1);
      const float qq = __shfl_down_sync(0xffffffffu, tot, 2), dd = __shfl_down_sync(0xffffffffu, tot, 4), ws = __shfl_down_sync(0xffffffffu, tot, 6);
      if ((lane & 7) == 0) {
        const float mean = tot * (1.f / 1024.f);
        const float var = fmaxf(fmaf(-mean, mean, qq * (1.f / 1024.f)), 0.f);
        float sd;
        asm("sqrt.approx.ftz.f32 %0, %1;" : "=f"(sd) : "f"(bf_round(bf_round(var) + 1e-5f)));
        const uint32_t ms = pack(sd, mean);
        const int row = tm * 128 + tn * 16 + ww * 4 + (lane >> 3);
        const uint32_t rbits = pack(0.f, fmaf(-bf_hi(ms), ws, dd) * rcp(bf_lo(ms)));
        const uint32_t key = (rbits ^ (((int)rbits >> 31 & 0x7fff0000u) | 0x80000000u)) | ((2047 - row) << 5) | (ep & 31u);
        asm volatile("{\n.reg .b64 x;\nmov.b64 x, {%1,%2};\nst.relaxed.gpu.global.b64 [%0], x;\n}" ::"l"(g_keys + row), "r"(key), "r"(ms) : "memory");
      }
      STAMP_IF(leader, 17);
      __nanosleep(400);
      uint32_t st[2];
      poll_pair(st, g_keys + tm * 128 + t, ep, 31u);
      asm volatile("st.shared.v2.f32 [%0], {%1,%2};" ::"r"(S_KSTAT + t * 8), "f"(bf_hi(st[1])), "f"(rcp(bf_lo(st[1])) * LOG2E) : "memory");
      nb_arrive(NB_FDONE, 416);
      STAMP_IF(leader, 10);
    }
    float a0[64], a1[64];
    reg_zero(a0); reg_zero(a1); reg_fence(a0); reg_fence(a1);
    STAMP_IF(leader, 18);
    nb_sync(NB_KV, 256);
    mainloop<true>(a0, a1, 1, 1, NB_VQ, leader);
    STAMP_IF(leader, 19);
    {
      nb_sync(NB_PK, 288);
      float c[4];
#pragma unroll
      for (int i = 0; i < 4; i++) c[i] = -__uint_as_float(lds32(S_CSV + ((i >> 1) * 64 + ww * 16 + (i & 1) * 8 + g) * 4));
      float mu[32];
#pragma unroll
      for (int j = 0; j < 16; j++) {
        const float4 s0 = lds128f(S_KSTAT + (j * 8 + 2 * t4) * 8);
        mu[2 * j] = s0.x; mu[2 * j + 1] = s0.z;
      }
      uint32_t f0[32], f1[32];
      float c0[32], c1[32];
      constexpr uint64_t db = mkdesc(STG, 16, 1024, 1);
#pragma unroll
      for (int i = 0; i < 32; i++) f0[i] = pack(fmaf(c[i & 1], mu[i & ~1], a0[2 * i]), fmaf(c[i & 1], mu[i | 1], a0[2 * i + 1]));
      reg_zero(c0);
      wg_fence();
#pragma unroll
      for (int k = 0; k < 8; k++) wgmma_n64_rs<0>(c0, f0[4 * k], f0[4 * k + 1], f0[4 * k + 2], f0[4 * k + 3], db + (k >> 2) * 1024 + (k & 3) * 2, k != 0);
      wg_commit();
      reg_fence(a1);
#pragma unroll
      for (int i = 0; i < 32; i++) f1[i] = pack(fmaf(c[2 + (i & 1)], mu[i & ~1], a1[2 * i]), fmaf(c[2 + (i & 1)], mu[i | 1], a1[2 * i + 1]));
      wg_wait<0>();
      reg_fence(c0);
      reg_zero(c1);
      wg_fence();
#pragma unroll
      for (int k = 0; k < 8; k++) wgmma_n64_rs<0>(c1, f1[4 * k], f1[4 * k + 1], f1[4 * k + 2], f1[4 * k + 3], db + (k >> 2) * 1024 + (k & 3) * 2 + 512, k != 0);
      wg_commit();
      uint4* pp = g_kvp + (tn * 16 + tm) * 512 + t;
      const bool hp = ww >> 1;
      auto put = [&](uint4* p, const float (&c)[32]) {
        if (!hp) {
          st_unit(p, pack(c[0], c[1]), pack(c[2], c[3]), pack(c[4], c[5]), pack(c[6], c[7]), par);
          st_unit(p + 128, pack(c[8], c[9]), pack(c[10], c[11]), pack(c[12], c[13]), pack(c[14], c[15]), par);
        } else {
          st_unit(p, pack(c[16], c[17]), pack(c[18], c[19]), pack(c[20], c[21]), pack(c[22], c[23]), par);
          st_unit(p + 128, pack(c[24], c[25]), pack(c[26], c[27]), pack(c[28], c[29]), pack(c[30], c[31]), par);
        }
      };
      put(pp, c0);
      wg_wait<0>();
      reg_fence(c1);
      STAMP_IF(leader, 20);
      put(pp + 256, c1);
      STAMP_IF(leader, 47);
      {
        uint32_t p[16];
        if (ww == 0) poll1(*reinterpret_cast<uint32_t(*)[1]>(p), g_kvp + (tn * 16 + (lane & 15)) * 512 + 384 + (lane >> 4) * 127, par, 1u);
        nb_sync(NB_WG1, 128);
        poll_kvp(p, g_kvp + (tn * 16 + (lane >> 3) * 4) * 512 + tm * 32 + ww * 8 + (lane & 7), par, 1u);
        float r[8];
#pragma unroll
        for (int i = 0; i < 4; i++) {
          r[2 * i] = (bf_lo(p[i]) + bf_lo(p[4 + i])) + (bf_lo(p[8 + i]) + bf_lo(p[12 + i]));
          r[2 * i + 1] = (bf_hi(p[i]) + bf_hi(p[4 + i])) + (bf_hi(p[8 + i]) + bf_hi(p[12 + i]));
        }
#pragma unroll
        for (int i = 0; i < 8; i++) r[i] += __shfl_xor_sync(0xffffffffu, r[i], 8);
#pragma unroll
        for (int i = 0; i < 8; i++) r[i] += __shfl_xor_sync(0xffffffffu, r[i], 16);
        if (lane < 8) st_unit(g_kv + tn * 512 + tm * 32 + ww * 8 + lane, pack(r[0], r[1]), pack(r[2], r[3]), pack(r[4], r[5]), pack(r[6], r[7]), par);
      }
      STAMP_IF(leader, 21);
    }
    const uint32_t sx = lane & 7, sc = lane >> 4;
    const uint32_t sa = STG + (ww * 16 + (lane & 15)) * 128;
    const uint32_t sw[4] = {sa + ((sc ^ sx) << 4), sa + (((2 + sc) ^ sx) << 4), sa + (((4 + sc) ^ sx) << 4), sa + (((6 + sc) ^ sx) << 4)};
    {
      uint32_t v[16];
      if (ww == 0) poll1(*reinterpret_cast<uint32_t(*)[1]>(v), g_kv + tn * 512 + lane * 16, par, 1u);
      nb_sync(NB_WG1, 128);
      poll_kv(v, g_kv + tn * 512 + t, par, 1u);
      STAMP_IF(leader, 23);
#pragma unroll
      for (int q = 0; q < 4; q++)
        stsm4((q < 2 ? KVB_P0 : KVB_P1) + ((ww & 1) * 16 + (lane & 15)) * 128 + ((((ww >> 1) * 4 + (q & 1) * 2 + sc) ^ sx) << 4),
              v[4 * q], v[4 * q + 1], v[4 * q + 2], v[4 * q + 3]);
      fence_async_smem();
      nb_arrive(NB_KVB, 288);
    }
    STAMP_IF(leader, 24);
    uint32_t oh[4];
    uint32_t inmask;
    {
      mbar_wait(B_SEL, 0);
      const int r0 = key_token(lds32(S_SEL + t4 * 8)) - tm * 128, r1 = key_token(lds32(S_SEL + t4 * 8 + 4)) - tm * 128;
#pragma unroll
      for (int i = 0; i < 4; i++) {
        const int row = (i >> 1) * 64 + ww * 16 + (i & 1) * 8 + g;
        oh[i] = (r0 == row ? 0x3f80u : 0u) | (r1 == row ? 0x3f800000u : 0u);
      }
      inmask = __ballot_sync(0xffffffffu, (unsigned)r0 < 128u || (unsigned)r1 < 128u);
    }
    {
      float ka[4], kb[4];
#pragma unroll
      for (int i = 0; i < 4; i++) {
        const float2 st = lds64f(S_KSTAT + ((i >> 1) * 64 + ww * 16 + (i & 1) * 8 + g) * 8);
        const float r = st.y * LN2;
        ka[i] = 1.f + r; kb[i] = -st.x * r;
      }
      constexpr uint32_t XOFF = RING + 3 * SLOT + 16384 - STG;
      mbar_wait(B_XRES, 0);
#pragma unroll
      for (int j = 0; j < 8; j++) {
        const uint4 v = ldsm4(sw[j & 3] + XOFF + (j >> 2) * SLOT), u = ldsm4(sw[j & 3] + XOFF + (j >> 2) * SLOT + 8192);
        a0[8 * j + 0] = fmaf(bf_lo(v.x), ka[0], kb[0]); a0[8 * j + 1] = fmaf(bf_hi(v.x), ka[0], kb[0]);
        a0[8 * j + 2] = fmaf(bf_lo(v.y), ka[1], kb[1]); a0[8 * j + 3] = fmaf(bf_hi(v.y), ka[1], kb[1]);
        a0[8 * j + 4] = fmaf(bf_lo(v.z), ka[0], kb[0]); a0[8 * j + 5] = fmaf(bf_hi(v.z), ka[0], kb[0]);
        a0[8 * j + 6] = fmaf(bf_lo(v.w), ka[1], kb[1]); a0[8 * j + 7] = fmaf(bf_hi(v.w), ka[1], kb[1]);
        a1[8 * j + 0] = fmaf(bf_lo(u.x), ka[2], kb[2]); a1[8 * j + 1] = fmaf(bf_hi(u.x), ka[2], kb[2]);
        a1[8 * j + 2] = fmaf(bf_lo(u.y), ka[3], kb[3]); a1[8 * j + 3] = fmaf(bf_hi(u.y), ka[3], kb[3]);
        a1[8 * j + 4] = fmaf(bf_lo(u.z), ka[2], kb[2]); a1[8 * j + 5] = fmaf(bf_hi(u.z), ka[2], kb[2]);
        a1[8 * j + 6] = fmaf(bf_lo(u.w), ka[3], kb[3]); a1[8 * j + 7] = fmaf(bf_hi(u.w), ka[3], kb[3]);
      }
      reg_fence(a0);
      reg_fence(a1);
      fence_async_smem();
    }
    STAMP_IF(leader, 22);
    {
      int s = 3, ph = 1;
      uint32_t prev = 0;
#pragma unroll 1
      for (int r = 0; r < 16; r++) {
        if (r < 2) nb_sync(NB_OWN0 + r, r ? 256 : 288);
        mbar_wait(B_FULL + 8 * s, ph);
        STAMP_IF(leader && r < 3, 25 + r);
        const uint64_t dw = mkdesc(RING, 8192, 1024, 1) + s * (SLOT >> 4);
        const uint64_t dx = mkdesc(0, 16, 1024, 1) + (r < 2 ? (STG >> 4) + r * 1024 : ((RING + 16384) >> 4) + s * (SLOT >> 4));
        wg_fence();
#pragma unroll
        for (int j = 0; j < 4; j++) {
          wgmma_n128_ss<0, 1>(a0, dx + j * 2, dw + j * 128, 1);
          wgmma_n128_ss<0, 1>(a1, dx + j * 2 + 512, dw + j * 128, 1);
        }
        wg_commit();
        wg_wait<1>();
        if (prev && leader) mbar_arrive(prev);
        prev = B_EMPTY + 8 * s;
        if (++s == NST) { s = 0; ph ^= 1; }
      }
      if (inmask) {
        nb_sync(NB_Y, 256);
        wg_fence();
        wgmma_n128_rs<1>(a0, oh[0], oh[1], 0u, 0u, mkdesc(FR, 1024, 0, 1), 1);
        wgmma_n128_rs<1>(a1, oh[2], oh[3], 0u, 0u, mkdesc(FR, 1024, 0, 1), 1);
        wg_commit();
      }
      nb_sync(NB_ST, 160);
      wg_wait<0>();
      reg_fence(a0);
      reg_fence(a1);
    }
    STAMP_IF(leader, 28);
#pragma unroll
    for (int c = 0; c < 2; c++) {
#pragma unroll
      for (int j = 4 * c; j < 4 * c + 4; j++) {
        stsm4(sw[j & 3] + c * 16384, pack(a0[8 * j], a0[8 * j + 1]), pack(a0[8 * j + 2], a0[8 * j + 3]), pack(a0[8 * j + 4], a0[8 * j + 5]), pack(a0[8 * j + 6], a0[8 * j + 7]));
        stsm4(sw[j & 3] + c * 16384 + 8192, pack(a1[8 * j], a1[8 * j + 1]), pack(a1[8 * j + 2], a1[8 * j + 3]), pack(a1[8 * j + 4], a1[8 * j + 5]), pack(a1[8 * j + 6], a1[8 * j + 7]));
      }
      fence_async_smem();
      e_store2d(&mp.out, tn * 128 + c * 64, tm * 128 + ww * 16, STG + c * 16384 + ww * 2048);
      e_store2d(&mp.out, tn * 128 + c * 64, tm * 128 + 64 + ww * 16, STG + c * 16384 + 8192 + ww * 2048);
    }
    bulk_wait_read();
    if (bid == 0 && leader) st_relaxed(&g_epoch, ep);
    STAMP_IF(leader, 29);
  } else {
    asm volatile("setmaxnreg.inc.sync.aligned.u32 208;");
    const int g = lane >> 2, t4 = lane & 3;
    const bool leader = tid == 0;
    const uint32_t sx = lane & 7, sc = lane >> 4;
    const uint32_t sa = STG + (w * 16 + (lane & 15)) * 128;
    const uint32_t sw[4] = {sa + ((sc ^ sx) << 4), sa + (((2 + sc) ^ sx) << 4), sa + (((4 + sc) ^ sx) << 4), sa + (((6 + sc) ^ sx) << 4)};
    float a0[64], a1[64];
    reg_zero(a0); reg_zero(a1); reg_fence(a0); reg_fence(a1);
    mainloop<true>(a0, a1, 0, 0, NB_KV, leader);
    STAMP_IF(leader, 33);
    {
      nb_sync(NB_FDONE, 416);
      STAMP_IF(leader, 34);
      float c[4], z[4] = {0.f, 0.f, 0.f, 0.f};
#pragma unroll
      for (int i = 0; i < 4; i++) c[i] = -__uint_as_float(lds32(S_CSK + ((i >> 1) * 64 + w * 16 + (i & 1) * 8 + g) * 4));
#pragma unroll
      for (int j = 0; j < 8; j++) {
        const float4 s0 = lds128f(S_KSTAT + (j * 16 + 2 * t4) * 8), s1 = lds128f(S_KSTAT + (j * 16 + 8 + 2 * t4) * 8);
        const float mu[4] = {s0.x, s0.z, s1.x, s1.z}, rl[4] = {s0.y, s0.w, s1.y, s1.w};
#pragma unroll
        for (int m = 0; m < 2; m++) {
          float p[8];
#pragma unroll
          for (int i = 0; i < 8; i++) {
            const int r = m * 2 + ((i >> 1) & 1), cc = (i >> 2) * 2 + (i & 1);
            p[i] = phi2(fmaf(c[r], mu[cc], m ? a1[8 * j + i] : a0[8 * j + i]) * rl[cc]);
            z[r] += p[i];
            p[i] *= rl[cc];
          }
          stsm4(sw[j & 3] + (j >> 2) * 16384 + m * 8192, pack(p[0], p[1]), pack(p[2], p[3]), pack(p[4], p[5]), pack(p[6], p[7]));
        }
      }
      const bool u2 = lane & 2, u1 = lane & 1;
      const float zz = xred(xred(z[0], z[2], u2, 2), xred(z[1], z[3], u2, 2), u1, 1);
      fence_async_smem();
      nb_arrive(NB_PK, 288);
      st_relaxed(g_z + tm * 1024 + tn * 128 + (t4 >> 1) * 64 + w * 16 + (t4 & 1) * 8 + g, tagf(zz * LOG2E, lds32(S_EPOCH) & 1u));
      nb_arrive(NB_Z, 160);
    }
    STAMP_IF(leader, 35);
    float rl[4];
    {
      nb_sync(NB_CSQ, 160);
      float mu[4];
#pragma unroll
      for (int i = 0; i < 4; i++) {
        const float2 st = lds64f(S_KSTAT + ((i >> 1) * 64 + w * 16 + (i & 1) * 8 + g) * 8);
        mu[i] = -st.x; rl[i] = st.y;
      }
#pragma unroll
      for (int j = 0; j < 16; j++) {
        const float2 c = lds64f(S_CSQ + (j * 8 + 2 * t4) * 4);
        a0[4 * j] = mu[0] * c.x; a0[4 * j + 1] = mu[0] * c.y; a0[4 * j + 2] = mu[1] * c.x; a0[4 * j + 3] = mu[1] * c.y;
        a1[4 * j] = mu[2] * c.x; a1[4 * j + 1] = mu[2] * c.y; a1[4 * j + 2] = mu[3] * c.x; a1[4 * j + 3] = mu[3] * c.y;
      }
      reg_fence(a0); reg_fence(a1);
    }
    STAMP_IF(leader, 40);
    nb_sync(NB_VQ, 256);
    mainloop<false>(a0, a1, 2, 0, 0, leader);
    STAMP_IF(leader, 36);
    {
      uint32_t f[2][16];
      float oc[2][2][20];
      auto phi = [&](float (&a)[64], int j, int m, uint32_t (&o)[16]) {
#pragma unroll
        for (int i = 0; i < 32; i++) asm volatile("" : "+f"(a[32 * j + i])::"memory");
#pragma unroll
        for (int i = 0; i < 16; i++) o[i] = pack(phi2(a[32 * j + 2 * i] * rl[2 * m + (i & 1)]), phi2(a[32 * j + 2 * i + 1] * rl[2 * m + (i & 1)]));
      };
      auto mma = [&](int j, const uint32_t (&a)[16], float (&o)[2][20]) {
        const uint64_t db = mkdesc(j ? KVB_Z : KVB_P0, 16, 1024, 1);
        reg_zero(o[0]); reg_zero(o[1]);
        wg_fence();
        wgmma_n40_rs<0>(o[0], a[0], a[1], a[2], a[3], db, 0);
        wgmma_n40_rs<0>(o[1], a[8], a[9], a[10], a[11], db + 4, 0);
        wgmma_n40_rs<0>(o[0], a[4], a[5], a[6], a[7], db + 2, 1);
        wgmma_n40_rs<0>(o[1], a[12], a[13], a[14], a[15], db + 6, 1);
        wg_commit();
      };
      auto fin = [&](int j, int m, float (&o)[2][20]) {
#pragma unroll
        for (int h = 0; h < 2; h++) {
          const float r0 = rcp(o[h][j ? 1 : 16] + 1e-6f * LOG2E), r1 = rcp(o[h][j ? 3 : 18] + 1e-6f * LOG2E);
          const int b = j ? 4 : 0;
#pragma unroll
          for (int q = 0; q < 2; q++)
            stsm4(sw[h * 2 + q] + j * 16384 + m * 8192,
                  pack(o[h][b + 8 * q] * r0, o[h][b + 8 * q + 1] * r0), pack(o[h][b + 8 * q + 2] * r1, o[h][b + 8 * q + 3] * r1),
                  pack(o[h][b + 8 * q + 4] * r0, o[h][b + 8 * q + 5] * r0), pack(o[h][b + 8 * q + 6] * r1, o[h][b + 8 * q + 7] * r1));
        }
      };
#pragma unroll
      for (int j = 0; j < 2; j++) {
        phi(a0, j, 0, f[0]);
        if (j == 0) nb_sync(NB_KVB, 288);
        STAMP_IF(leader && j == 0, 37);
        mma(j, f[0], oc[0]);
        phi(a1, j, 1, f[1]);
        wg_wait<0>();
        reg_fence(oc[0][0]); reg_fence(oc[0][1]);
        mma(j, f[1], oc[1]);
        fin(j, 0, oc[0]);
        if (j == 0) { fence_async_smem(); nb_arrive(NB_Q0, 192); }
        wg_wait<0>();
        reg_fence(oc[1][0]); reg_fence(oc[1][1]);
        fin(j, 1, oc[1]);
        fence_async_smem();
        if (j == 0) nb_arrive(NB_OWN0, 288);
        else { nb_arrive(NB_OWN1, 256); nb_arrive(NB_H1, 160); }
        STAMP_IF(leader, 38 + j);
      }
    }
  }
}

typedef CUresult (*EncodeFn)(CUtensorMap*, CUtensorMapDataType, cuuint32_t, void*, const cuuint64_t*, const cuuint64_t*, const cuuint32_t*,
                             const cuuint32_t*, CUtensorMapInterleave, CUtensorMapSwizzle, CUtensorMapL2promotion, CUtensorMapFloatOOBfill);

void make_map(EncodeFn enc, CUtensorMap* m, const void* p, int rank, uint64_t d0, uint64_t d1, uint64_t d2, uint64_t s1, uint64_t s2,
              uint32_t b0, uint32_t b1, uint32_t b2, CUtensorMapSwizzle sw) {
  cuuint64_t gd[3] = {d0, d1, d2}, gs[2] = {s1, s2};
  cuuint32_t bd[3] = {b0, b1, b2}, es[3] = {1, 1, 1};
  enc(m, CU_TENSOR_MAP_DATA_TYPE_BFLOAT16, rank, const_cast<void*>(p), gd, gs, bd, es, CU_TENSOR_MAP_INTERLEAVE_NONE, sw,
      CU_TENSOR_MAP_L2_PROMOTION_L2_128B, CU_TENSOR_MAP_FLOAT_OOB_FILL_NONE);
}

}

extern "C" void kernel_launch(void* const* d_in, const int* in_sizes, int n_in, void* d_out, int out_size) {
  (void)in_sizes; (void)n_in; (void)out_size;
  void* fn = nullptr;
  cudaDriverEntryPointQueryResult qr;
  cudaGetDriverEntryPoint("cuTensorMapEncodeTiled", &fn, cudaEnableDefault, &qr);
  EncodeFn enc = (EncodeFn)fn;
  void* o;
  cudaGetSymbolAddress(&o, g_o);
  const CUtensorMapSwizzle S128 = CU_TENSOR_MAP_SWIZZLE_128B, S64 = CU_TENSOR_MAP_SWIZZLE_64B, S0 = CU_TENSOR_MAP_SWIZZLE_NONE;
  Maps mp;
  make_map(enc, &mp.wqkv, d_in[1], 3, 64, 1024, 48, 6144, 128, 64, 64, 2, S128);
  make_map(enc, &mp.x, d_in[0], 2, 1024, 2048, 1, 2048, 0, 64, 128, 1, S128);
  make_map(enc, &mp.os, o, 2, 1024, 2048, 1, 2048, 0, 64, 64, 1, S128);
  make_map(enc, &mp.o, o, 2, 1024, 2048, 1, 2048, 0, 64, 128, 1, S128);
  make_map(enc, &mp.wo, d_in[2], 3, 64, 1024, 16, 2048, 128, 64, 64, 2, S128);
  make_map(enc, &mp.xs, d_in[0], 2, 1024, 2048, 1, 2048, 0, 256, 16, 1, S0);
  const char *wg = (const char*)d_in[5], *wu = (const char*)d_in[6];
  make_map(enc, &mp.gu, wu < wg ? wu : wg, 3, 3584, 1024, 2, 7168, (uint64_t)(wu < wg ? wg - wu : wu - wg), 32, 32, 2, S64);
  make_map(enc, &mp.down, d_in[7], 2, 1024, 3584, 1, 2048, 0, 64, 32, 1, S128);
  make_map(enc, &mp.out, d_out, 2, 1024, 2048, 1, 2048, 0, 64, 16, 1, S128);
  cudaFuncSetAttribute(fused_kernel, cudaFuncAttributeMaxDynamicSharedMemorySize, SMEM_BYTES);
  fused_kernel<<<132, 512, SMEM_BYTES>>>(mp, (const __nv_bfloat16*)d_in[4], (const __nv_bfloat16*)d_in[0], (const char*)d_in[5],
                                         (const char*)d_in[6], (const char*)d_in[7]);
}
```

```cpp
#include <cuda_runtime.h>
#include <cuda.h>
#include <cuda_bf16.h>
#include <stdint.h>

namespace {

template <int TA, int TB>
__device__ __forceinline__ void wgmma_n8_ss(float (&d)[4], uint64_t da, uint64_t db, int sc) {
  asm volatile("{\n.reg .pred p;\nsetp.ne.b32 p, %6, 0;\n"
    "wgmma.mma_async.sync.aligned.m64n8k16.f32.bf16.bf16 {%0, %1, %2, %3}, %4, %5, p, 1, 1, %7, %8;\n}\n"
    : "+f"(d[0]), "+f"(d[1]), "+f"(d[2]), "+f"(d[3])
    : "l"(da), "l"(db), "r"(sc), "n"(TA), "n"(TB));
}
template <int TB>
__device__ __forceinline__ void wgmma_n40_rs(float (&d)[20], uint32_t a0, uint32_t a1, uint32_t a2, uint32_t a3, uint64_t db, int sc) {
  asm volatile("{\n.reg .pred p;\nsetp.ne.b32 p, %25, 0;\n"
    "wgmma.mma_async.sync.aligned.m64n40k16.f32.bf16.bf16 {%0, %1, %2, %3, %4, %5, %6, %7, %8, %9, %10, %11, %12, %13, %14, %15, %16, %17, %18, %19}, {%20,%21,%22,%23}, %24, p, 1, 1, %26;\n}\n"
    : "+f"(d[0]), "+f"(d[1]), "+f"(d[2]), "+f"(d[3]), "+f"(d[4]), "+f"(d[5]), "+f"(d[6]), "+f"(d[7]),
      "+f"(d[8]), "+f"(d[9]), "+f"(d[10]), "+f"(d[11]), "+f"(d[12]), "+f"(d[13]), "+f"(d[14]), "+f"(d[15]),
      "+f"(d[16]), "+f"(d[17]), "+f"(d[18]), "+f"(d[19])
    : "r"(a0), "r"(a1), "r"(a2), "r"(a3), "l"(db), "r"(sc), "n"(TB));
}
template <int TB>
__device__ __forceinline__ void wgmma_n64_rs(float (&d)[32], uint32_t a0, uint32_t a1, uint32_t a2, uint32_t a3, uint64_t db, int sc) {
  asm volatile("{\n.reg .pred p;\nsetp.ne.b32 p, %37, 0;\n"
    "wgmma.mma_async.sync.aligned.m64n64k16.f32.bf16.bf16 {%0, %1, %2, %3, %4, %5, %6, %7, %8, %9, %10, %11, %12, %13, %14, %15, %16, %17, %18, %19, %20, %21, %22, %23, %24, %25, %26, %27, %28, %29, %30, %31}, {%32,%33,%34,%35}, %36, p, 1, 1, %38;\n}\n"
    : "+f"(d[0]), "+f"(d[1]), "+f"(d[2]), "+f"(d[3]), "+f"(d[4]), "+f"(d[5]), "+f"(d[6]), "+f"(d[7]),
      "+f"(d[8]), "+f"(d[9]), "+f"(d[10]), "+f"(d[11]), "+f"(d[12]), "+f"(d[13]), "+f"(d[14]), "+f"(d[15]),
      "+f"(d[16]), "+f"(d[17]), "+f"(d[18]), "+f"(d[19]), "+f"(d[20]), "+f"(d[21]), "+f"(d[22]), "+f"(d[23]),
      "+f"(d[24]), "+f"(d[25]), "+f"(d[26]), "+f"(d[27]), "+f"(d[28]), "+f"(d[29]), "+f"(d[30]), "+f"(d[31])
    : "r"(a0), "r"(a1), "r"(a2), "r"(a3), "l"(db), "r"(sc), "n"(TB));
}
template <int TA, int TB>
__device__ __forceinline__ void wgmma_n128_ss(float (&d)[64], uint64_t da, uint64_t db, int sc) {
  asm volatile("{\n.reg .pred p;\nsetp.ne.b32 p, %66, 0;\n"
    "wgmma.mma_async.sync.aligned.m64n128k16.f32.bf16.bf16 {%0, %1, %2, %3, %4, %5, %6, %7, %8, %9, %10, %11, %12, %13, %14, %15, %16, %17, %18, %19, %20, %21, %22, %23, %24, %25, %26, %27, %28, %29, %30, %31, %32, %33, %34, %35, %36, %37, %38, %39, %40, %41, %42, %43, %44, %45, %46, %47, %48, %49, %50, %51, %52, %53, %54, %55, %56, %57, %58, %59, %60, %61, %62, %63}, %64, %65, p, 1, 1, %67, %68;\n}\n"
    : "+f"(d[0]), "+f"(d[1]), "+f"(d[2]), "+f"(d[3]), "+f"(d[4]), "+f"(d[5]), "+f"(d[6]), "+f"(d[7]),
      "+f"(d[8]), "+f"(d[9]), "+f"(d[10]), "+f"(d[11]), "+f"(d[12]), "+f"(d[13]), "+f"(d[14]), "+f"(d[15]),
      "+f"(d[16]), "+f"(d[17]), "+f"(d[18]), "+f"(d[19]), "+f"(d[20]), "+f"(d[21]), "+f"(d[22]), "+f"(d[23]),
      "+f"(d[24]), "+f"(d[25]), "+f"(d[26]), "+f"(d[27]), "+f"(d[28]), "+f"(d[29]), "+f"(d[30]), "+f"(d[31]),
      "+f"(d[32]), "+f"(d[33]), "+f"(d[34]), "+f"(d[35]), "+f"(d[36]), "+f"(d[37]), "+f"(d[38]), "+f"(d[39]),
      "+f"(d[40]), "+f"(d[41]), "+f"(d[42]), "+f"(d[43]), "+f"(d[44]), "+f"(d[45]), "+f"(d[46]), "+f"(d[47]),
      "+f"(d[48]), "+f"(d[49]), "+f"(d[50]), "+f"(d[51]), "+f"(d[52]), "+f"(d[53]), "+f"(d[54]), "+f"(d[55]),
      "+f"(d[56]), "+f"(d[57]), "+f"(d[58]), "+f"(d[59]), "+f"(d[60]), "+f"(d[61]), "+f"(d[62]), "+f"(d[63])
    : "l"(da), "l"(db), "r"(sc), "n"(TA), "n"(TB));
}
template <int TB>
__device__ __forceinline__ void wgmma_n128_rs(float (&d)[64], uint32_t a0, uint32_t a1, uint32_t a2, uint32_t a3, uint64_t db, int sc) {
  asm volatile("{\n.reg .pred p;\nsetp.ne.b32 p, %69, 0;\n"
    "wgmma.mma_async.sync.aligned.m64n128k16.f32.bf16.bf16 {%0, %1, %2, %3, %4, %5, %6, %7, %8, %9, %10, %11, %12, %13, %14, %15, %16, %17, %18, %19, %20, %21, %22, %23, %24, %25, %26, %27, %28, %29, %30, %31, %32, %33, %34, %35, %36, %37, %38, %39, %40, %41, %42, %43, %44, %45, %46, %47, %48, %49, %50, %51, %52, %53, %54, %55, %56, %57, %58, %59, %60, %61, %62, %63}, {%64,%65,%66,%67}, %68, p, 1, 1, %70;\n}\n"
    : "+f"(d[0]), "+f"(d[1]), "+f"(d[2]), "+f"(d[3]), "+f"(d[4]), "+f"(d[5]), "+f"(d[6]), "+f"(d[7]),
      "+f"(d[8]), "+f"(d[9]), "+f"(d[10]), "+f"(d[11]), "+f"(d[12]), "+f"(d[13]), "+f"(d[14]), "+f"(d[15]),
      "+f"(d[16]), "+f"(d[17]), "+f"(d[18]), "+f"(d[19]), "+f"(d[20]), "+f"(d[21]), "+f"(d[22]), "+f"(d[23]),
      "+f"(d[24]), "+f"(d[25]), "+f"(d[26]), "+f"(d[27]), "+f"(d[28]), "+f"(d[29]), "+f"(d[30]), "+f"(d[31]),
      "+f"(d[32]), "+f"(d[33]), "+f"(d[34]), "+f"(d[35]), "+f"(d[36]), "+f"(d[37]), "+f"(d[38]), "+f"(d[39]),
      "+f"(d[40]), "+f"(d[41]), "+f"(d[42]), "+f"(d[43]), "+f"(d[44]), "+f"(d[45]), "+f"(d[46]), "+f"(d[47]),
      "+f"(d[48]), "+f"(d[49]), "+f"(d[50]), "+f"(d[51]), "+f"(d[52]), "+f"(d[53]), "+f"(d[54]), "+f"(d[55]),
      "+f"(d[56]), "+f"(d[57]), "+f"(d[58]), "+f"(d[59]), "+f"(d[60]), "+f"(d[61]), "+f"(d[62]), "+f"(d[63])
    : "r"(a0), "r"(a1), "r"(a2), "r"(a3), "l"(db), "r"(sc), "n"(TB));
}

__device__ __forceinline__ void poll1(uint32_t (&v)[1], const void* p, uint32_t tag, uint32_t mask) {
  asm volatile("{\n.reg .pred p, q;\n.reg .u32 c, b;\n.reg .b64 x, y;\n.reg .b128 z;\nmov.u32 c, 0;\nLW:\n"
               "ld.relaxed.gpu.global.u32 %0, [%1+0];\n"
               "xor.b32 b, %0, %2;\n"
               "and.b32 b, b, %3;\nsetp.eq.u32 p, b, 0;\nvote.sync.all.pred p, p, 0xffffffff;\n@p bra.uni LD;\n"
               "nanosleep.u32 100;\nadd.u32 c, c, 1;\nsetp.lt.u32 q, c, 1000000;\n@q bra.uni LW;\ntrap;\nLD:\n}"
               : "=&r"(v[0])
               : "l"(p), "r"(tag), "r"(mask) : "memory");
}
__device__ __forceinline__ void poll_pair(uint32_t (&v)[2], const void* p, uint32_t tag, uint32_t mask) {
  asm volatile("{\n.reg .pred p, q;\n.reg .u32 c, b;\n.reg .b64 x, y;\n.reg .b128 z;\nmov.u32 c, 0;\nLW:\n"
               "ld.relaxed.gpu.global.b64 x, [%2+0];\nmov.b64 {%0,%1}, x;\n"
               "xor.b32 b, %0, %3;\n"
               "and.b32 b, b, %4;\nsetp.eq.u32 p, b, 0;\nvote.sync.all.pred p, p, 0xffffffff;\n@p bra.uni LD;\n"
               "nanosleep.u32 100;\nadd.u32 c, c, 1;\nsetp.lt.u32 q, c, 1000000;\n@q bra.uni LW;\ntrap;\nLD:\n}"
               : "=&r"(v[0]), "=&r"(v[1])
               : "l"(p), "r"(tag), "r"(mask) : "memory");
}
__device__ __forceinline__ void poll_quad(uint32_t (&v)[4], const void* p, uint32_t tag, uint32_t mask) {
  asm volatile("{\n.reg .pred p, q;\n.reg .u32 c, b;\n.reg .b64 x, y;\n.reg .b128 z;\nmov.u32 c, 0;\nLW:\n"
               "ld.relaxed.gpu.global.v4.u32 {%0,%1,%2,%3}, [%4+0];\n"
               "xor.b32 b, %0, %5;\n"
               "lop3.b32 b, b, %1, %5, 0xf6;\nlop3.b32 b, b, %2, %5, 0xf6;\nlop3.b32 b, b, %3, %5, 0xf6;\n"
               "and.b32 b, b, %6;\nsetp.eq.u32 p, b, 0;\nvote.sync.all.pred p, p, 0xffffffff;\n@p bra.uni LD;\n"
               "nanosleep.u32 200;\nadd.u32 c, c, 1;\nsetp.lt.u32 q, c, 1000000;\n@q bra.uni LW;\ntrap;\nLD:\n}"
               : "=&r"(v[0]), "=&r"(v[1]), "=&r"(v[2]), "=&r"(v[3])
               : "l"(p), "r"(tag), "r"(mask) : "memory");
}
__device__ __forceinline__ void poll8(uint32_t (&v)[8], const void* p, uint32_t tag, uint32_t mask) {
  asm volatile("{\n.reg .pred p, q;\n.reg .u32 c, b;\n.reg .b64 x, y;\n.reg .b128 z;\nmov.u32 c, 0;\nLW:\n"
               "ld.relaxed.gpu.global.u32 %0, [%8+0];\n"
               "ld.relaxed.gpu.global.u32 %1, [%8+2048];\n"
               "ld.relaxed.gpu.global.u32 %2, [%8+4096];\n"
               "ld.relaxed.gpu.global.u32 %3, [%8+6144];\n"
               "ld.relaxed.gpu.global.u32 %4, [%8+8192];\n"
               "ld.relaxed.gpu.global.u32 %5, [%8+10240];\n"
               "ld.relaxed.gpu.global.u32 %6, [%8+12288];\n"
               "ld.relaxed.gpu.global.u32 %7, [%8+14336];\n"
               "xor.b32 b, %0, %9;\n"
               "lop3.b32 b, b, %1, %9, 0xf6;\nlop3.b32 b, b, %2, %9, 0xf6;\nlop3.b32 b, b, %3, %9, 0xf6;\nlop3.b32 b, b, %4, %9, 0xf6;\n"
               "lop3.b32 b, b, %5, %9, 0xf6;\nlop3.b32 b, b, %6, %9, 0xf6;\nlop3.b32 b, b, %7, %9, 0xf6;\n"
               "and.b32 b, b, %10;\nsetp.eq.u32 p, b, 0;\nvote.sync.all.pred p, p, 0xffffffff;\n@p bra.uni LD;\n"
               "nanosleep.u32 50;\nadd.u32 c, c, 1;\nsetp.lt.u32 q, c, 1000000;\n@q bra.uni LW;\ntrap;\nLD:\n}"
               : "=&r"(v[0]), "=&r"(v[1]), "=&r"(v[2]), "=&r"(v[3]), "=&r"(v[4]), "=&r"(v[5]), "=&r"(v[6]), "=&r"(v[7])
               : "l"(p), "r"(tag), "r"(mask) : "memory");
}
__device__ __forceinline__ void poll16(uint32_t (&v)[16], const void* p, uint32_t tag, uint32_t mask) {
  asm volatile("{\n.reg .pred p, q;\n.reg .u32 c, b;\n.reg .b64 x, y;\n.reg .b128 z;\nmov.u32 c, 0;\nLW:\n"
               "ld.relaxed.gpu.global.u32 %0, [%16+0];\n"
               "ld.relaxed.gpu.global.u32 %1, [%16+4096];\n"
               "ld.relaxed.gpu.global.u32 %2, [%16+8192];\n"
               "ld.relaxed.gpu.global.u32 %3, [%16+12288];\n"
               "ld.relaxed.gpu.global.u32 %4, [%16+16384];\n"
               "ld.relaxed.gpu.global.u32 %5, [%16+20480];\n"
               "ld.relaxed.gpu.global.u32 %6, [%16+24576];\n"
               "ld.relaxed.gpu.global.u32 %7, [%16+28672];\n"
               "ld.relaxed.gpu.global.u32 %8, [%16+32768];\n"
               "ld.relaxed.gpu.global.u32 %9, [%16+36864];\n"
               "ld.relaxed.gpu.global.u32 %10, [%16+40960];\n"
               "ld.relaxed.gpu.global.u32 %11, [%16+45056];\n"
               "ld.relaxed.gpu.global.u32 %12, [%16+49152];\n"
               "ld.relaxed.gpu.global.u32 %13, [%16+53248];\n"
               "ld.relaxed.gpu.global.u32 %14, [%16+57344];\n"
               "ld.relaxed.gpu.global.u32 %15, [%16+61440];\n"
               "xor.b32 b, %0, %17;\n"
               "lop3.b32 b, b, %1, %17, 0xf6;\nlop3.b32 b, b, %2, %17, 0xf6;\nlop3.b32 b, b, %3, %17, 0xf6;\nlop3.b32 b, b, %4, %17, 0xf6;\n"
               "lop3.b32 b, b, %5, %17, 0xf6;\nlop3.b32 b, b, %6, %17, 0xf6;\nlop3.b32 b, b, %7, %17, 0xf6;\nlop3.b32 b, b, %8, %17, 0xf6;\n"
               "lop3.b32 b, b, %9, %17, 0xf6;\nlop3.b32 b, b, %10, %17, 0xf6;\nlop3.b32 b, b, %11, %17, 0xf6;\nlop3.b32 b, b, %12, %17, 0xf6;\n"
               "lop3.b32 b, b, %13, %17, 0xf6;\nlop3.b32 b, b, %14, %17, 0xf6;\nlop3.b32 b, b, %15, %17, 0xf6;\n"
               "and.b32 b, b, %18;\nsetp.eq.u32 p, b, 0;\nvote.sync.all.pred p, p, 0xffffffff;\n@p bra.uni LD;\n"
               "nanosleep.u32 200;\nadd.u32 c, c, 1;\nsetp.lt.u32 q, c, 1000000;\n@q bra.uni LW;\ntrap;\nLD:\n}"
               : "=&r"(v[0]), "=&r"(v[1]), "=&r"(v[2]), "=&r"(v[3]), "=&r"(v[4]), "=&r"(v[5]), "=&r"(v[6]), "=&r"(v[7]), "=&r"(v[8]), "=&r"(v[9]), "=&r"(v[10]), "=&r"(v[11]), "=&r"(v[12]), "=&r"(v[13]), "=&r"(v[14]), "=&r"(v[15])
               : "l"(p), "r"(tag), "r"(mask) : "memory");
}
__device__ __forceinline__ void poll_keys(uint32_t (&v)[16], const void* p, uint32_t tag, uint32_t mask) {
  asm volatile("{\n.reg .pred p, q;\n.reg .u32 c, b;\n.reg .b64 x, y;\n.reg .b128 z;\nmov.u32 c, 0;\nLW:\n"
               "ld.relaxed.gpu.global.v2.b64 {x, y}, [%16+0];\nmov.b64 {%0,%1}, x;\nmov.b64 {%2,%3}, y;\n"
               "ld.relaxed.gpu.global.v2.b64 {x, y}, [%16+4096];\nmov.b64 {%4,%5}, x;\nmov.b64 {%6,%7}, y;\n"
               "ld.relaxed.gpu.global.v2.b64 {x, y}, [%16+8192];\nmov.b64 {%8,%9}, x;\nmov.b64 {%10,%11}, y;\n"
               "ld.relaxed.gpu.global.v2.b64 {x, y}, [%16+12288];\nmov.b64 {%12,%13}, x;\nmov.b64 {%14,%15}, y;\n"
               "xor.b32 b, %0, %17;\n"
               "lop3.b32 b, b, %2, %17, 0xf6;\nlop3.b32 b, b, %4, %17, 0xf6;\nlop3.b32 b, b, %6, %17, 0xf6;\nlop3.b32 b, b, %8, %17, 0xf6;\n"
               "lop3.b32 b, b, %10, %17, 0xf6;\nlop3.b32 b, b, %12, %17, 0xf6;\nlop3.b32 b, b, %14, %17, 0xf6;\n"
               "and.b32 b, b, %18;\nsetp.eq.u32 p, b, 0;\nvote.sync.all.pred p, p, 0xffffffff;\n@p bra.uni LD;\n"
               "nanosleep.u32 20;\nadd.u32 c, c, 1;\nsetp.lt.u32 q, c, 1000000;\n@q bra.uni LW;\ntrap;\nLD:\n}"
               : "=&r"(v[0]), "=&r"(v[1]), "=&r"(v[2]), "=&r"(v[3]), "=&r"(v[4]), "=&r"(v[5]), "=&r"(v[6]), "=&r"(v[7]), "=&r"(v[8]), "=&r"(v[9]), "=&r"(v[10]), "=&r"(v[11]), "=&r"(v[12]), "=&r"(v[13]), "=&r"(v[14]), "=&r"(v[15])
               : "l"(p), "r"(tag), "r"(mask) : "memory");
}
__device__ __forceinline__ void poll_z(uint32_t (&v)[16], const void* p, uint32_t tag, uint32_t mask) {
  asm volatile("{\n.reg .pred p, q;\n.reg .u32 c, b;\n.reg .b64 x, y;\n.reg .b128 z;\nmov.u32 c, 0;\nLW:\n"
               "ld.relaxed.gpu.global.v4.u32 {%0,%1,%2,%3}, [%16+0];\n"
               "ld.relaxed.gpu.global.v4.u32 {%4,%5,%6,%7}, [%16+4096];\n"
               "ld.relaxed.gpu.global.v4.u32 {%8,%9,%10,%11}, [%16+8192];\n"
               "ld.relaxed.gpu.global.v4.u32 {%12,%13,%14,%15}, [%16+12288];\n"
               "xor.b32 b, %0, %17;\n"
               "lop3.b32 b, b, %1, %17, 0xf6;\nlop3.b32 b, b, %2, %17, 0xf6;\nlop3.b32 b, b, %3, %17, 0xf6;\nlop3.b32 b, b, %4, %17, 0xf6;\n"
               "lop3.b32 b, b, %5, %17, 0xf6;\nlop3.b32 b, b, %6, %17, 0xf6;\nlop3.b32 b, b, %7, %17, 0xf6;\nlop3.b32 b, b, %8, %17, 0xf6;\n"
               "lop3.b32 b, b, %9, %17, 0xf6;\nlop3.b32 b, b, %10, %17, 0xf6;\nlop3.b32 b, b, %11, %17, 0xf6;\nlop3.b32 b, b, %12, %17, 0xf6;\n"
               "lop3.b32 b, b, %13, %17, 0xf6;\nlop3.b32 b, b, %14, %17, 0xf6;\nlop3.b32 b, b, %15, %17, 0xf6;\n"
               "and.b32 b, b, %18;\nsetp.eq.u32 p, b, 0;\nvote.sync.all.pred p, p, 0xffffffff;\n@p bra.uni LD;\n"
               "nanosleep.u32 300;\nadd.u32 c, c, 1;\nsetp.lt.u32 q, c, 1000000;\n@q bra.uni LW;\ntrap;\nLD:\n}"
               : "=&r"(v[0]), "=&r"(v[1]), "=&r"(v[2]), "=&r"(v[3]), "=&r"(v[4]), "=&r"(v[5]), "=&r"(v[6]), "=&r"(v[7]), "=&r"(v[8]), "=&r"(v[9]), "=&r"(v[10]), "=&r"(v[11]), "=&r"(v[12]), "=&r"(v[13]), "=&r"(v[14]), "=&r"(v[15])
               : "l"(p), "r"(tag), "r"(mask) : "memory");
}
__device__ __forceinline__ void poll7x4(uint32_t (&v)[28], const void* p, uint32_t tag, uint32_t mask) {
  asm volatile("{\n.reg .pred p, q;\n.reg .u32 c, b;\n.reg .b64 x, y;\n.reg .b128 z;\nmov.u32 c, 0;\nLW:\n"
               "ld.relaxed.gpu.global.v4.u32 {%0,%1,%2,%3}, [%28+0];\n"
               "ld.relaxed.gpu.global.v4.u32 {%4,%5,%6,%7}, [%28+2048];\n"
               "ld.relaxed.gpu.global.v4.u32 {%8,%9,%10,%11}, [%28+4096];\n"
               "ld.relaxed.gpu.global.v4.u32 {%12,%13,%14,%15}, [%28+6144];\n"
               "ld.relaxed.gpu.global.v4.u32 {%16,%17,%18,%19}, [%28+8192];\n"
               "ld.relaxed.gpu.global.v4.u32 {%20,%21,%22,%23}, [%28+10240];\n"
               "ld.relaxed.gpu.global.v4.u32 {%24,%25,%26,%27}, [%28+12288];\n"
               "xor.b32 b, %0, %29;\n"
               "lop3.b32 b, b, %1, %29, 0xf6;\nlop3.b32 b, b, %2, %29, 0xf6;\nlop3.b32 b, b, %3, %29, 0xf6;\nlop3.b32 b, b, %4, %29, 0xf6;\n"
               "lop3.b32 b, b, %5, %29, 0xf6;\nlop3.b32 b, b, %6, %29, 0xf6;\nlop3.b32 b, b, %7, %29, 0xf6;\nlop3.b32 b, b, %8, %29, 0xf6;\n"
               "lop3.b32 b, b, %9, %29, 0xf6;\nlop3.b32 b, b, %10, %29, 0xf6;\nlop3.b32 b, b, %11, %29, 0xf6;\nlop3.b32 b, b, %12, %29, 0xf6;\n"
               "lop3.b32 b, b, %13, %29, 0xf6;\nlop3.b32 b, b, %14, %29, 0xf6;\nlop3.b32 b, b, %15, %29, 0xf6;\nlop3.b32 b, b, %16, %29, 0xf6;\n"
               "lop3.b32 b, b, %17, %29, 0xf6;\nlop3.b32 b, b, %18, %29, 0xf6;\nlop3.b32 b, b, %19, %29, 0xf6;\nlop3.b32 b, b, %20, %29, 0xf6;\n"
               "lop3.b32 b, b, %21, %29, 0xf6;\nlop3.b32 b, b, %22, %29, 0xf6;\nlop3.b32 b, b, %23, %29, 0xf6;\nlop3.b32 b, b, %24, %29, 0xf6;\n"
               "lop3.b32 b, b, %25, %29, 0xf6;\nlop3.b32 b, b, %26, %29, 0xf6;\nlop3.b32 b, b, %27, %29, 0xf6;\n"
               "and.b32 b, b, %30;\nsetp.eq.u32 p, b, 0;\nvote.sync.all.pred p, p, 0xffffffff;\n@p bra.uni LD;\n"
               "nanosleep.u32 50;\nadd.u32 c, c, 1;\nsetp.lt.u32 q, c, 1000000;\n@q bra.uni LW;\ntrap;\nLD:\n}"
               : "=&r"(v[0]), "=&r"(v[1]), "=&r"(v[2]), "=&r"(v[3]), "=&r"(v[4]), "=&r"(v[5]), "=&r"(v[6]), "=&r"(v[7]), "=&r"(v[8]), "=&r"(v[9]), "=&r"(v[10]), "=&r"(v[11]), "=&r"(v[12]), "=&r"(v[13]), "=&r"(v[14]), "=&r"(v[15]), "=&r"(v[16]), "=&r"(v[17]), "=&r"(v[18]), "=&r"(v[19]), "=&r"(v[20]), "=&r"(v[21]), "=&r"(v[22]), "=&r"(v[23]), "=&r"(v[24]), "=&r"(v[25]), "=&r"(v[26]), "=&r"(v[27])
               : "l"(p), "r"(tag), "r"(mask) : "memory");
}
__device__ __forceinline__ void poll_kvp(uint32_t (&v)[16], const void* p, uint32_t tag, uint32_t mask) {
  asm volatile("{\n.reg .pred p, q;\n.reg .u32 c, b;\n.reg .b64 x, y;\n.reg .b128 z;\nmov.u32 c, 0;\nLW:\n"
               "ld.relaxed.gpu.global.b128 z, [%16+0];\nmov.b128 {x, y}, z;\nmov.b64 {%0,%1}, x;\nmov.b64 {%2,%3}, y;\n"
               "ld.relaxed.gpu.global.b128 z, [%16+8192];\nmov.b128 {x, y}, z;\nmov.b64 {%4,%5}, x;\nmov.b64 {%6,%7}, y;\n"
               "ld.relaxed.gpu.global.b128 z, [%16+16384];\nmov.b128 {x, y}, z;\nmov.b64 {%8,%9}, x;\nmov.b64 {%10,%11}, y;\n"
               "ld.relaxed.gpu.global.b128 z, [%16+24576];\nmov.b128 {x, y}, z;\nmov.b64 {%12,%13}, x;\nmov.b64 {%14,%15}, y;\n"
               "xor.b32 b, %0, %17;\n"
               "lop3.b32 b, b, %4, %17, 0xf6;\nlop3.b32 b, b, %8, %17, 0xf6;\nlop3.b32 b, b, %12, %17, 0xf6;\n"
               "and.b32 b, b, %18;\nsetp.eq.u32 p, b, 0;\nvote.sync.all.pred p, p, 0xffffffff;\n@p bra.uni LD;\n"
               "nanosleep.u32 50;\nadd.u32 c, c, 1;\nsetp.lt.u32 q, c, 1000000;\n@q bra.uni LW;\ntrap;\nLD:\n}"
               : "=&r"(v[0]), "=&r"(v[1]), "=&r"(v[2]), "=&r"(v[3]), "=&r"(v[4]), "=&r"(v[5]), "=&r"(v[6]), "=&r"(v[7]), "=&r"(v[8]), "=&r"(v[9]), "=&r"(v[10]), "=&r"(v[11]), "=&r"(v[12]), "=&r"(v[13]), "=&r"(v[14]), "=&r"(v[15])
               : "l"(p), "r"(tag), "r"(mask) : "memory");
}
__device__ __forceinline__ void poll_kv(uint32_t (&v)[16], const void* p, uint32_t tag, uint32_t mask) {
  asm volatile("{\n.reg .pred p, q;\n.reg .u32 c, b;\n.reg .b64 x, y;\n.reg .b128 z;\nmov.u32 c, 0;\nLW:\n"
               "ld.relaxed.gpu.global.b128 z, [%16+0];\nmov.b128 {x, y}, z;\nmov.b64 {%0,%1}, x;\nmov.b64 {%2,%3}, y;\n"
               "ld.relaxed.gpu.global.b128 z, [%16+2048];\nmov.b128 {x, y}, z;\nmov.b64 {%4,%5}, x;\nmov.b64 {%6,%7}, y;\n"
               "ld.relaxed.gpu.global.b128 z, [%16+4096];\nmov.b128 {x, y}, z;\nmov.b64 {%8,%9}, x;\nmov.b64 {%10,%11}, y;\n"
               "ld.relaxed.gpu.global.b128 z, [%16+6144];\nmov.b128 {x, y}, z;\nmov.b64 {%12,%13}, x;\nmov.b64 {%14,%15}, y;\n"
               "xor.b32 b, %0, %17;\n"
               "lop3.b32 b, b, %4, %17, 0xf6;\nlop3.b32 b, b, %8, %17, 0xf6;\nlop3.b32 b, b, %12, %17, 0xf6;\n"
               "and.b32 b, b, %18;\nsetp.eq.u32 p, b, 0;\nvote.sync.all.pred p, p, 0xffffffff;\n@p bra.uni LD;\n"
               "nanosleep.u32 50;\nadd.u32 c, c, 1;\nsetp.lt.u32 q, c, 1000000;\n@q bra.uni LW;\ntrap;\nLD:\n}"
               : "=&r"(v[0]), "=&r"(v[1]), "=&r"(v[2]), "=&r"(v[3]), "=&r"(v[4]), "=&r"(v[5]), "=&r"(v[6]), "=&r"(v[7]), "=&r"(v[8]), "=&r"(v[9]), "=&r"(v[10]), "=&r"(v[11]), "=&r"(v[12]), "=&r"(v[13]), "=&r"(v[14]), "=&r"(v[15])
               : "l"(p), "r"(tag), "r"(mask) : "memory");
}

__device__ __align__(1024) __nv_bfloat16 g_o[2048 * 1024];
__device__ __align__(128) uint2 g_keys[2048];
__device__ __align__(128) uint32_t g_csum[18 * 1024];
__device__ __align__(128) uint32_t g_z[16 * 1024];
__device__ __align__(128) uint4 g_kvp[128 * 512];
__device__ __align__(128) uint4 g_kv[8 * 512];
__device__ __align__(128) uint32_t g_h[112 * 256];
__device__ __align__(128) uint32_t g_yp[128 * 512];
__device__ __align__(128) uint32_t g_xsel[4096 + 32];
__device__ __align__(128) uint32_t g_flagO[256 * 8];
__device__ __align__(128) uint32_t g_flagR[32];
__device__ uint32_t g_epoch;

constexpr uint32_t RING = 1024, SLOT = 32768, SMEM_BYTES = 232448;
constexpr int NST = 5, HST = 7;
constexpr uint32_t STG = RING + 163840, AUX = RING + 196608, FR = RING + 212992, MISC = RING + 229376;
constexpr uint32_t B_FULL = MISC, B_EMPTY = MISC + 56, B_XS = MISC + 112, B_SEL = MISC + 144, B_XRES = MISC + 152, B_WK = MISC + 160, B_CSDN = MISC + 168,
                   B_FR = MISC + 176, B_FE = MISC + 216, B_DR = MISC + 256, B_DE = MISC + 288,
                   B_P1 = MISC + 320, B_P2 = MISC + 328, B_PH = MISC + 336, B_PY = MISC + 344, NBAR = 44;
constexpr uint32_t S_EPOCH = MISC + 352, S_NCAND = MISC + 356, S_SEL = MISC + 368, S_WMAX = MISC + 400,
                   S_KSTAT = MISC + 512, S_CSK = MISC + 1536, S_CSV = MISC + 2048, S_CSQ = MISC + 2560, S_ONES = MISC + 512;
constexpr uint32_t KVB_P0 = AUX, KVB_Z = AUX + 4096, KVB_P1 = AUX + 5120, HOP = AUX + 9216, GR = FR - 4096;
enum { NB_Z = 0, NB_KV = 1, NB_VQ = 2, NB_WG0 = 3, NB_FDONE = 4, NB_PK = 5, NB_KVB = 6, NB_WG1 = 7, NB_WG2 = 8, NB_CSQ = 9,
       NB_Y = 10, NB_ST = 11, NB_OWN0 = 12, NB_OWN1 = 13, NB_Q0 = 14, NB_H1 = 15 };

#define XS_AT 0
#define XS_STEP 1
#define PFD 6
#define FFN_AT 12
#define EXP_A 1
#define EXP_B 1
constexpr float LOG2E = 1.4426950408889634f, LN2 = 0.6931471805599453f;

#define ELECT "{\n.reg .pred p;\nelect.sync _|p, 0xffffffff;\n"
#define TMA2D "cp.async.bulk.tensor.2d.shared::cluster.global.mbarrier::complete_tx::bytes"
#define TMA3D "cp.async.bulk.tensor.3d.shared::cluster.global.mbarrier::complete_tx::bytes"
__device__ __forceinline__ void e_expect(uint32_t b, uint32_t n) {
  asm volatile(ELECT "@p mbarrier.arrive.expect_tx.shared::cta.b64 _, [%0], %1;\n}" ::"r"(b), "r"(n) : "memory");
}
__device__ __forceinline__ void e_arrive(uint32_t b) { asm volatile(ELECT "@p mbarrier.arrive.shared::cta.b64 _, [%0];\n}" ::"r"(b) : "memory"); }
__device__ __forceinline__ void e_tma2d(uint32_t dst, const CUtensorMap* m, int c0, int c1, uint32_t bar) {
  asm volatile(ELECT "@p " TMA2D " [%0], [%1, {%3, %4}], [%2];\n}" ::"r"(dst), "l"(m), "r"(bar), "r"(c0), "r"(c1) : "memory");
}
__device__ __forceinline__ void e_tma2d_ef(uint32_t dst, const CUtensorMap* m, int c0, int c1, uint32_t bar, uint64_t pol) {
  asm volatile(ELECT "@p " TMA2D ".L2::cache_hint [%0], [%1, {%3, %4}], [%2], %5;\n}" ::"r"(dst), "l"(m), "r"(bar), "r"(c0), "r"(c1), "l"(pol) : "memory");
}
__device__ __forceinline__ void e_tma3d(uint32_t dst, const CUtensorMap* m, int c1, int c2, uint32_t bar) {
  asm volatile(ELECT "@p " TMA3D " [%0], [%1, {0, %3, %4}], [%2];\n}" ::"r"(dst), "l"(m), "r"(bar), "r"(c1), "r"(c2) : "memory");
}
__device__ __forceinline__ void e_store2d(const CUtensorMap* m, int c0, int c1, uint32_t src) {
  asm volatile(ELECT "@p cp.async.bulk.tensor.2d.global.shared::cta.bulk_group [%0, {%2, %3}], [%1];\n}" ::"l"(m), "r"(src), "r"(c0), "r"(c1) : "memory");
}
__device__ __forceinline__ void e_tma3d_ef(uint32_t dst, const CUtensorMap* m, int c0, int c1, uint32_t bar, uint64_t pol) {
  asm volatile(ELECT "@p " TMA3D ".L2::cache_hint [%0], [%1, {%3, %4, 0}], [%2], %5;\n}" ::"r"(dst), "l"(m), "r"(bar), "r"(c0), "r"(c1), "l"(pol) : "memory");
}
__device__ __forceinline__ void e_load(uint32_t dst, const void* src, uint32_t n, uint32_t bar) {
  asm volatile(ELECT "@p cp.async.bulk.shared::cluster.global.mbarrier::complete_tx::bytes [%0], [%1], %2, [%3];\n}" ::"r"(dst), "l"(src), "r"(n), "r"(bar) : "memory");
}
template <int I0, int I1> __device__ __forceinline__ void e_init() {
#pragma unroll
  for (int i = I0; i < I1; i++) asm volatile(ELECT "@p mbarrier.init.shared::cta.b64 [%0], %1;\n}" ::"r"(MISC + 8 * i), "r"(MISC + 8 * i == B_CSDN ? 4 : 1) : "memory");
  asm volatile("fence.mbarrier_init.release.cluster;" ::: "memory");
}
__device__ __forceinline__ void e_pfmap(const CUtensorMap* m) { asm volatile(ELECT "@p prefetch.tensormap [%0];\n}" ::"l"(m) : "memory"); }
__device__ __forceinline__ void bulk_wait_read() { asm volatile("cp.async.bulk.commit_group;\ncp.async.bulk.wait_group.read 0;" ::: "memory"); }
__device__ __forceinline__ void e_release(uint32_t* flag, uint32_t v, int lane) {
  asm volatile("cp.async.bulk.commit_group;\ncp.async.bulk.wait_group 0;\nfence.release.gpu;" ::: "memory");
  if (lane < 8) asm volatile("st.relaxed.gpu.global.u32 [%0], %1;" ::"l"(flag + lane), "r"(v) : "memory");
}

__device__ __forceinline__ void mbar_arrive(uint32_t b) { asm volatile("mbarrier.arrive.shared::cta.b64 _, [%0];" ::"r"(b) : "memory"); }
__device__ __forceinline__ void mbar_wait(uint32_t b, uint32_t ph) {
  asm volatile("{\n.reg .pred p, q;\n.reg .u32 c;\nmov.u32 c, 0;\nLW:\nmbarrier.try_wait.parity.shared::cta.b64 p, [%0], %1;\n@p bra LD;\n"
               "add.u32 c, c, 1;\nsetp.lt.u32 q, c, 100000;\n@q bra LW;\ntrap;\nLD:\n}" ::"r"(b), "r"(ph) : "memory");
}
__device__ __forceinline__ void nb_sync(int id, int n) { asm volatile("bar.sync %0, %1;" ::"r"(id), "r"(n) : "memory"); }
__device__ __forceinline__ void nb_arrive(int id, int n) { asm volatile("bar.arrive %0, %1;" ::"r"(id), "r"(n) : "memory"); }
__device__ __forceinline__ void wg_fence() { asm volatile("wgmma.fence.sync.aligned;" ::: "memory"); }
__device__ __forceinline__ void wg_commit() { asm volatile("wgmma.commit_group.sync.aligned;" ::: "memory"); }
template <int N> __device__ __forceinline__ void wg_wait() { asm volatile("wgmma.wait_group.sync.aligned %0;" ::"n"(N) : "memory"); }
template <int N> __device__ __forceinline__ void reg_fence(float (&a)[N]) {
#pragma unroll
  for (int i = 0; i < N; i++) asm volatile("" : "+f"(a[i])::"memory");
}
template <int N> __device__ __forceinline__ void reg_zero(float (&a)[N]) {
#pragma unroll
  for (int i = 0; i < N; i++) a[i] = 0.f;
}
__device__ __forceinline__ constexpr uint64_t mkdesc(uint32_t addr, uint32_t lbo, uint32_t sbo, uint32_t swz) {
  return (uint64_t)(addr >> 4) | ((uint64_t)(lbo >> 4) << 16) | ((uint64_t)(sbo >> 4) << 32) | ((uint64_t)swz << 62);
}
__device__ __forceinline__ void fence_async_smem() { asm volatile("fence.proxy.async.shared::cta;" ::: "memory"); }
__device__ __forceinline__ void fence_async_glob() { asm volatile("fence.proxy.async.global;" ::: "memory"); }
__device__ __forceinline__ void fence_acq() { asm volatile("fence.acquire.gpu;" ::: "memory"); }
__device__ __forceinline__ void st_relaxed(uint32_t* p, uint32_t v) { asm volatile("st.relaxed.gpu.global.u32 [%0], %1;" ::"l"(p), "r"(v) : "memory"); }
__device__ __forceinline__ uint32_t ld_relaxed(const uint32_t* p) { uint32_t v; asm volatile("ld.relaxed.gpu.global.u32 %0, [%1];" : "=r"(v) : "l"(p) : "memory"); return v; }
__device__ __forceinline__ void st_unit(uint4* p, uint32_t a, uint32_t b, uint32_t c, uint32_t d, uint32_t par) {
  asm volatile("{\n.reg .b64 x, y;\n.reg .b128 z;\nmov.b64 x, {%1,%2};\nmov.b64 y, {%3,%4};\nmov.b128 z, {x, y};\nst.relaxed.gpu.global.b128 [%0], z;\n}"
               ::"l"(p), "r"((a & ~1u) | par), "r"(b), "r"(c), "r"(d) : "memory");
}
__device__ __forceinline__ void spin_guard(int& c) {
  asm volatile("{\n.reg .pred q;\nadd.u32 %0, %0, 1;\nsetp.lt.u32 q, %0, 1000000;\n@q bra LOK;\ntrap;\nLOK:\n}" : "+r"(c));
}
__device__ __forceinline__ uint4 lds128(uint32_t a) { uint4 v; asm volatile("ld.shared.v4.u32 {%0,%1,%2,%3}, [%4];" : "=r"(v.x), "=r"(v.y), "=r"(v.z), "=r"(v.w) : "r"(a)); return v; }
__device__ __forceinline__ float4 lds128f(uint32_t a) { float4 v; asm volatile("ld.shared.v4.f32 {%0,%1,%2,%3}, [%4];" : "=f"(v.x), "=f"(v.y), "=f"(v.z), "=f"(v.w) : "r"(a)); return v; }
__device__ __forceinline__ float2 lds64f(uint32_t a) { float2 v; asm volatile("ld.shared.v2.f32 {%0,%1}, [%2];" : "=f"(v.x), "=f"(v.y) : "r"(a)); return v; }
__device__ __forceinline__ uint32_t lds32(uint32_t a) { uint32_t v; asm volatile("ld.shared.u32 %0, [%1];" : "=r"(v) : "r"(a)); return v; }
__device__ __forceinline__ void sts128(uint32_t a, uint32_t x, uint32_t y, uint32_t z, uint32_t w) { asm volatile("st.shared.v4.u32 [%0], {%1,%2,%3,%4};" ::"r"(a), "r"(x), "r"(y), "r"(z), "r"(w) : "memory"); }
__device__ __forceinline__ void sts128f(uint32_t a, float x, float y, float z, float w) { asm volatile("st.shared.v4.f32 [%0], {%1,%2,%3,%4};" ::"r"(a), "f"(x), "f"(y), "f"(z), "f"(w) : "memory"); }
__device__ __forceinline__ void sts32(uint32_t a, uint32_t x) { asm volatile("st.shared.u32 [%0], %1;" ::"r"(a), "r"(x) : "memory"); }
__device__ __forceinline__ void stsm4(uint32_t a, uint32_t r0, uint32_t r1, uint32_t r2, uint32_t r3) {
  asm volatile("stmatrix.sync.aligned.m8n8.x4.shared.b16 [%0], {%1,%2,%3,%4};" ::"r"(a), "r"(r0), "r"(r1), "r"(r2), "r"(r3) : "memory");
}
__device__ __forceinline__ uint4 ldsm4(uint32_t a) {
  uint4 v; asm volatile("ldmatrix.sync.aligned.m8n8.x4.shared.b16 {%0,%1,%2,%3}, [%4];" : "=r"(v.x), "=r"(v.y), "=r"(v.z), "=r"(v.w) : "r"(a) : "memory"); return v;
}
__device__ __forceinline__ uint32_t pack(float lo, float hi) { uint32_t r; asm("cvt.rn.bf16x2.f32 %0, %1, %2;" : "=r"(r) : "f"(hi), "f"(lo)); return r; }
__device__ __forceinline__ float bf_lo(uint32_t w) { return __uint_as_float(w << 16); }
__device__ __forceinline__ float bf_hi(uint32_t w) { return __uint_as_float(w & 0xffff0000u); }
__device__ __forceinline__ float bf_round(float x) { return bf_lo(pack(x, x)); }
__device__ __forceinline__ float ex2(float x) { float v; asm("ex2.approx.ftz.f32 %0, %1;" : "=f"(v) : "f"(x)); return v; }
__device__ __forceinline__ float rcp(float x) { float v; asm("rcp.approx.ftz.f32 %0, %1;" : "=f"(v) : "f"(x)); return v; }
__device__ __forceinline__ float addsat(float a, float b) { float v; asm("add.sat.f32 %0, %1, %2;" : "=f"(v) : "f"(a), "f"(b)); return v; }
__device__ __forceinline__ float phi2(float a) { return fmaf(fmaxf(a, 0.f), LN2, addsat(ex2(a), 1e-6f)); }
__device__ __forceinline__ uint32_t ln_bf16x2(uint32_t x, uint32_t m, uint32_t hi, uint32_t lo) {
  uint32_t o;
  asm("{\n.reg .b32 d, e;\nsub.rn.bf16x2 d, %1, %2;\nmul.rn.bf16x2 e, d, %4;\nfma.rn.bf16x2 %0, d, %3, e;\n}" : "=r"(o) : "r"(x), "r"(m), "r"(hi), "r"(lo));
  return o;
}
__device__ __forceinline__ float key_score(uint32_t key) { uint32_t u = key >> 16; u = (u & 0x8000u) ? (u & 0x7fffu) : (~u & 0xffffu); return __uint_as_float(u << 16); }
__device__ __forceinline__ int key_token(uint32_t key) { return 2047 - (int)((key >> 5) & 2047u); }
__device__ __forceinline__ uint32_t tagf(float v, uint32_t par) { return (__float_as_uint(v) & ~1u) | par; }
__device__ __forceinline__ float xred(float a, float b, bool up, int o) { return (up ? b : a) + __shfl_xor_sync(0xffffffffu, up ? a : b, o); }

#define STAMP(id)
#define STAMP_IF(c, id)
#define STAMP2(i)

template <bool TRANS>
__device__ __forceinline__ void mainloop(float (&a0)[64], float (&a1)[64], int s, int ph, int handoff, bool leader) {
  uint32_t prev = 0;
#pragma unroll 1
  for (int kt = 0; kt < 16; kt++) {
    mbar_wait(B_FULL + 8 * s, ph);
    const uint64_t dw = mkdesc(RING, 8192, 1024, 1) + s * (SLOT >> 4), dx = mkdesc(RING + 16384, 16, 1024, 1) + s * (SLOT >> 4);
    wg_fence();
#pragma unroll
    for (int j = 0; j < 4; j++) {
      if (TRANS) {
        wgmma_n128_ss<1, 0>(a0, dw + j * 128, dx + j * 2, 1);
        wgmma_n128_ss<1, 0>(a1, dw + j * 128 + 512, dx + j * 2, 1);
      } else {
        wgmma_n128_ss<0, 1>(a0, dx + j * 2, dw + j * 128, 1);
        wgmma_n128_ss<0, 1>(a1, dx + j * 2 + 512, dw + j * 128, 1);
      }
    }
    wg_commit();
    if (handoff && kt == 15) nb_arrive(handoff, 256);
    wg_wait<1>();
    if (prev && leader) mbar_arrive(prev);
    prev = B_EMPTY + 8 * s;
    if (++s == NST) { s = 0; ph ^= 1; }
  }
  wg_wait<0>();
  if (leader) mbar_arrive(prev);
  reg_fence(a0);
  reg_fence(a1);
}

__device__ __forceinline__ int out_kblock(int r, int tn) {
  const int q = r - 2, half = q >= 7, pi = q - 7 * half;
  return r < 2 ? 2 * tn + r : 2 * (pi + (pi >= tn)) + half;
}

struct Maps {
  CUtensorMap wqkv, x, o, os, wo, xs, gu, down, out;
};

__global__ void __launch_bounds__(512, 1)
fused_kernel(const __grid_constant__ Maps mp, const __nv_bfloat16* __restrict__ w_r, const __nv_bfloat16* __restrict__ xg,
             const char* __restrict__ wg, const char* __restrict__ wu, const char* __restrict__ wd) {
  extern __shared__ __align__(1024) uint8_t smem_raw[];
  const int tid = threadIdx.x, lane = tid & 31;
  const int w = __shfl_sync(0xffffffffu, tid >> 5, 0);
  int bid = blockIdx.x;
  {
    uint32_t sm, nsm;
    asm volatile("mov.u32 %0, %%smid;" : "=r"(sm));
    asm volatile("mov.u32 %0, %%nsmid;" : "=r"(nsm));
    const uint32_t p = sm >> 1, q = ((p - 32) * 37) >> 8;
    const uint32_t gpc = p < 32 ? p & 7 : p < 60 ? p - 31 - 7 * q : 0, tpc = p < 32 ? p >> 3 : p < 60 ? 4 + q : p - 58;
    const int id = (p >> 1) == 30 ? 128 + ((0x9cu >> (2 * (sm & 3))) & 3) : ((0x75143620u >> (4 * gpc)) & 7) * 16 + tpc * 2 + (sm & 1);
    if (nsm == 132) bid = id;
  }
  const int tn = (bid & 3) + 4 * (bid >> 6), tm = (bid >> 2) & 15;

  if (w == 12) {
    STAMP_IF(lane == 0, 0);
    e_pfmap(&mp.wqkv);
    e_pfmap(&mp.x);
    e_init<0, 7>();
  } else {
    if (w == 13) e_init<7, 25>();
    if (w == 14) e_init<25, NBAR>();
    if (w == 15) {
      sts32(S_NCAND, 0);
      asm volatile("{\n.reg .pred q;\nsetp.eq.u32 q, %0, 1024;\n@q bra LOK;\ntrap;\nLOK:\n}" ::"r"((uint32_t)__cvta_generic_to_shared(smem_raw)));
    }
    nb_sync(0, 512);
  }

  if (bid >= 128) {
    const int h0 = bid == 128 ? 14 : bid - 129, hs = bid == 128 ? 1 : 3, h1 = bid == 128 ? 16 : 14;
    if (w == 12) {
      int s = 0, ph = 1, n = 0;
      if (bid == 128) { nb_sync(0, 512); mbar_wait(B_SEL, 0); n = HST + 1; }
#pragma unroll 1
      for (int h = h0; h < h1; h += hs) {
        const int c = 2 * h + (h & 8) * 2;
#pragma unroll 1
        for (int kt = 0; kt < 16; kt += 2, n++) {
          if (n == HST) nb_sync(0, 512);
          if (n >= HST) mbar_wait(B_EMPTY + 8 * s, ph);
          e_expect(B_FULL + 8 * s, 32768);
          e_tma3d(RING + s * SLOT, &mp.wqkv, kt * 64, c, B_FULL + 8 * s);
          e_tma3d(RING + s * SLOT + 16384, &mp.wqkv, kt * 64 + 64, c, B_FULL + 8 * s);
          if (++s == HST) { s = 0; ph ^= 1; }
        }
      }
    } else if (w < 4) {
      const uint32_t par = (ld_relaxed(&g_epoch) + 1) & 1u;
      sts32(S_ONES + tid * 4, 0x3f803f80u);
      fence_async_smem();
      nb_sync(NB_WG0, 128);
      int s = 0, ph = 0;
#pragma unroll 1
      for (int h = h0; h < h1; h += hs) {
        float c[4][4];
#pragma unroll
        for (int i = 0; i < 4; i++) reg_zero(c[i]);
        uint32_t prev = 0;
#pragma unroll 1
        for (int kt = 0; kt < 8; kt++) {
          mbar_wait(B_FULL + 8 * s, ph);
          const uint64_t dw = mkdesc(RING, 8192, 1024, 1) + s * (SLOT >> 4);
          wg_fence();
#pragma unroll
          for (int j = 0; j < 16; j++) wgmma_n8_ss<1, 0>(c[j & 3], dw + (j & 3) * 512 + (j >> 2) * 128, mkdesc(S_ONES, 128, 128, 0), 1);
          wg_commit();
          wg_wait<1>();
          if (prev && tid == 0) mbar_arrive(prev);
          prev = B_EMPTY + 8 * s;
          if (++s == HST) { s = 0; ph ^= 1; }
        }
        wg_wait<0>();
        if (tid == 0) mbar_arrive(prev);
#pragma unroll
        for (int i = 0; i < 4; i++) reg_fence(c[i]);
        const bool u2 = lane & 2, u1 = lane & 1;
        const float lo = u2 ? c[1][0] + c[3][0] : c[0][0] + c[2][0], hi = u2 ? c[1][2] + c[3][2] : c[0][2] + c[2][2];
        st_relaxed(g_csum + h * 128 + (lane & 2) * 32 + w * 16 + (lane & 1) * 8 + (lane >> 2), tagf(u1 ? hi : lo, par));
        STAMP_IF(tid == 0, h >= 8 ? 6 : 30);
      }
    } else if (w < 12 && bid == 128) {
      const int t = tid - 128, j = w - 4;
      const uint32_t ep = ld_relaxed(&g_epoch) + 1;
      uint32_t kk[16];
      poll_keys(kk, g_keys + t * 2, ep, 31u);
      const uint32_t k[8] = {kk[0], kk[2], kk[4], kk[6], kk[8], kk[10], kk[12], kk[14]};
      STAMP_IF(t == 0, 42);
      const uint32_t m = __reduce_max_sync(0xffffffffu, max(max(max(k[0], k[1]), max(k[2], k[3])), max(max(k[4], k[5]), max(k[6], k[7]))));
      if (lane == 0) sts32(S_WMAX + j * 4, m);
      nb_sync(NB_WG1, 256);
      const uint32_t T = __reduce_min_sync(0xffffffffu, lds32(S_WMAX + (lane & 7) * 4));
      uint32_t cnt = 0;
#pragma unroll
      for (int i = 0; i < 8; i++) cnt += k[i] >= T;
      if (cnt) {
        uint32_t pos;
        asm volatile("atom.shared.add.u32 %0, [%1], %2;" : "=r"(pos) : "r"(S_NCAND), "r"(cnt * 4) : "memory");
#pragma unroll
        for (int i = 0; i < 8; i++)
          if (k[i] >= T) { sts32(AUX + pos, k[i]); pos += 4; }
      }
      nb_sync(NB_WG1, 256);
      const uint32_t n4 = lds32(S_NCAND);
#pragma unroll 1
      for (uint32_t i = t * 4; i < n4; i += 1024) {
        const uint32_t key = lds32(AUX + i);
        uint32_t rank = 0;
#pragma unroll 4
        for (uint32_t q = 0; q < n4; q += 4) rank += lds32(AUX + q) > key;
        if (rank < 8) sts32(S_SEL + rank * 4, key);
      }
      nb_sync(NB_WG1, 256);
      STAMP_IF(t == 0, 43);
      const uint32_t key = lds32(S_SEL + j * 4);
      const int tok = key_token(key);
      uint4 v[4];
#pragma unroll
      for (int q = 0; q < 4; q++) v[q] = __ldg(reinterpret_cast<const uint4*>(xg + tok * 1024) + q * 32 + lane);
      const uint32_t st = ld_relaxed(&g_keys[tok].y);
      const float rinv = rcp(bf_lo(st)), rhi = bf_round(rinv);
      const uint32_t m2 = __byte_perm(st, 0, 0x3232), hi = pack(rhi, rhi), lo = pack(rinv - rhi, rinv - rhi);
#pragma unroll
      for (int q = 0; q < 4; q++)
        *reinterpret_cast<uint4*>(g_xsel + (q * 8 + (lane >> 2)) * 128 + j * 16 + (((lane & 3) ^ (j >> 1)) << 2)) =
            make_uint4(ln_bf16x2(v[q].x, m2, hi, lo), ln_bf16x2(v[q].y, m2, hi, lo), ln_bf16x2(v[q].z, m2, hi, lo), ln_bf16x2(v[q].w, m2, hi, lo));
      if (lane == 0) g_xsel[4096 + j] = key;
      fence_async_glob();
      fence_async_smem();
      nb_sync(NB_WG1, 256);
      STAMP_IF(t == 0, 44);
      if (j == 0) { e_release(g_flagR, ep, lane); e_arrive(B_SEL); }
      STAMP_IF(t == 0, 45);
    }
  } else if (w >= 12) {
    asm volatile("setmaxnreg.dec.sync.aligned.u32 32;");
    if (w == 12) {
      int s = 0, ph = 1;
#pragma unroll 1
      for (int it = 0; it < 48; it++) {
        const int c = (it < 32 ? (it & 16) + 16 : 0) + 2 * tn;
        if (it == NST) nb_sync(0, 512);
        if (it >= NST) mbar_wait(B_EMPTY + 8 * s, ph);
        e_expect(B_FULL + 8 * s, 32768);
        e_tma3d(RING + s * SLOT, &mp.wqkv, (it & 15) * 64, c, B_FULL + 8 * s);
        e_tma2d(RING + s * SLOT + 16384, &mp.x, (it & 15) * 64, tm * 128, B_FULL + 8 * s);
        STAMP2(it >= NST ? it - NST : 63);
        if (++s == NST) { s = 0; ph ^= 1; }
      }
#pragma unroll 1
      for (int r = 0; r < 16; r++) {
        const int kb = out_kblock(r, tn);
        mbar_wait(B_EMPTY + 8 * s, ph);
        e_expect(B_FULL + 8 * s, r < 2 ? 16384 : 32768);
        e_tma3d(RING + s * SLOT, &mp.wo, kb * 64, 2 * tn, B_FULL + 8 * s);
        if (r < 2) {
          if (r == 0) e_expect(B_XRES, 32768);
          e_tma2d(RING + s * SLOT + 16384, &mp.x, kb * 64, tm * 128, B_XRES);
        }
        STAMP2(r + 48 - NST);
        if (++s == NST) { s = 0; ph ^= 1; }
      }
    } else if (w == 13) {
      e_pfmap(&mp.xs);
#pragma unroll
      for (int c = 0; c < 5; c++) {
        const int it = XS_AT + c * XS_STEP;
        if (it >= NST) mbar_wait(B_FULL + 8 * (it - NST), 0);
        mbar_wait(B_FULL + 8 * (it % NST), it / NST);
        if (c < 4) {
          e_expect(B_XS + 8 * c, 8192);
          e_tma2d(STG + c * 8192, &mp.xs, c * 256, tm * 128 + tn * 16, B_XS + 8 * c);
        } else {
          e_expect(B_WK, 16384);
          e_tma3d(FR, &mp.wqkv, tm * 64, 16 + 2 * tn, B_WK);
        }
      }
      nb_sync(NB_Z, 160);
      const uint32_t ep = lds32(S_EPOCH);
      {
        float z[4] = {0.f, 0.f, 0.f, 0.f};
        __nanosleep(500);
#pragma unroll 1
        for (int i = 0; i < 4; i++) {
          uint32_t p[16];
          poll_z(p, g_z + i * 4096 + tn * 128 + lane * 4, ep, 1u);
#pragma unroll
          for (int q = 0; q < 4; q++) z[q] += (__uint_as_float(p[q]) + __uint_as_float(p[4 + q])) + (__uint_as_float(p[8 + q]) + __uint_as_float(p[12 + q]));
        }
        const uint32_t z01 = pack(z[0], z[1]), z23 = pack(z[2], z[3]);
#pragma unroll
        for (int i = 0; i < 4; i++) {
          const int n = 2 * i + (lane >> 4);
          asm volatile("st.shared.v2.u32 [%0], {%1,%2};" ::"r"(KVB_Z + n * 128 + ((((lane >> 1) & 7) ^ n) << 4) + (lane & 1) * 8), "r"(z01), "r"(z23) : "memory");
        }
        fence_async_smem();
        nb_arrive(NB_KVB, 288);
        STAMP_IF(lane == 0, 46);
      }
      nb_sync(NB_Q0, 192);
      e_store2d(&mp.os, tn * 128, tm * 128, STG);
      nb_sync(NB_OWN0, 288);
      e_store2d(&mp.os, tn * 128, tm * 128 + 64, STG + 8192);
      e_release(g_flagO + (tm * 16 + 2 * tn) * 8, ep, lane);
      STAMP_IF(lane == 0, 4);
      nb_sync(NB_H1, 160);
      e_store2d(&mp.os, tn * 128 + 64, tm * 128, STG + 16384);
      e_store2d(&mp.os, tn * 128 + 64, tm * 128 + 64, STG + 24576);
      e_release(g_flagO + (tm * 16 + 2 * tn + 1) * 8, ep, lane);
      STAMP_IF(lane == 0, 5);
      nb_arrive(NB_ST, 160);
    } else if (w == 14) {
      e_pfmap(&mp.gu); e_pfmap(&mp.o); e_pfmap(&mp.os); e_pfmap(&mp.wo); e_pfmap(&mp.down); e_pfmap(&mp.out);
      const uint32_t ep = ld_relaxed(&g_epoch) + 1;
      nb_sync(NB_FDONE, 416);
      {
        uint32_t c[4];
        poll_quad(c, g_csum + tn * 128 + lane * 4, ep, 1u);
        sts128(S_CSQ + lane * 16, c[0], c[1], c[2], c[3]);
        nb_arrive(NB_CSQ, 160);
        poll_quad(c, g_csum + 1024 + tn * 128 + lane * 4, ep, 1u);
        sts128(S_CSV + lane * 16, c[0], c[1], c[2], c[3]);
        nb_arrive(NB_PK, 288);
      }
      {
        const uint32_t* p = reinterpret_cast<const uint32_t*>(lane < 16 ? g_kvp + (tn * 16 + lane) * 512 + 511 : g_kv + tn * 512 + (lane - 16) * 32 + 31);
        uint32_t need = 0xffffu;
        int c = 0;
        while (true) {
          const uint32_t ok = __ballot_sync(0xffffffffu, ((ld_relaxed(p) ^ ep) & 1u) == 0);
          if ((ok & need) == need) {
            e_arrive(need == 0xffffu ? B_P1 : B_P2);
            if (need != 0xffffu) break;
            need = 0xffff0000u;
          }
          spin_guard(c);
          __nanosleep(50);
        }
      }
      nb_sync(NB_Q0, 192);
      uint32_t ready = 0;
      int s = 0, ph = 1;
#pragma unroll 1
      for (int r = 2; r < 16; r++) {
        const int kb = out_kblock(r, tn);
        if (!((ready >> kb) & 1)) {
          int c = 0;
          do {
            spin_guard(c);
            ready = __ballot_sync(0xffffffffu, ld_relaxed(g_flagO + (tm * 16 + (lane & 15)) * 8) == ep);
          } while (!((ready >> kb) & 1));
          fence_acq();
          fence_async_glob();
        }
        mbar_wait(B_EMPTY + 8 * s, ph);
        e_tma2d(RING + s * SLOT + 16384, &mp.o, kb * 64, tm * 128, B_FULL + 8 * s);
        STAMP_IF(lane == 0 && r == 2, 2);
        STAMP_IF(lane == 0 && r == 9, 3);
        if (++s == NST) { s = 0; ph ^= 1; }
      }
    } else {
      const uint32_t ep = ld_relaxed(&g_epoch) + 1;
      uint64_t pol;
      asm volatile("createpolicy.fractional.L2::evict_first.b64 %0, 1.0;" : "=l"(pol));
      const char* pd = wd + (bid & 15) * 128 + ((bid >> 4) * 448 + lane) * 2048;
      const char* pf = ((bid & 1) ? wu : wg) + (bid >> 1) * 128 + lane * 7168;
#pragma unroll 1
      for (int it = FFN_AT % NST; it < FFN_AT + PFD; it += it < FFN_AT ? NST : 1) {
        mbar_wait(B_FULL + 8 * (it % NST), (it / NST) & 1);
        if (it >= FFN_AT && bid < 112) { asm volatile("prefetch.global.L2 [%0];" ::"l"(pf)); pf += 32 * 7168; }
      }
      mbar_wait(B_CSDN, 0);
      uint32_t f[1];
      poll1(f, g_flagR, ep, 0xffffffffu);
      fence_acq();
      fence_async_glob();
      e_expect(B_SEL, 32);
      e_load(S_SEL, g_xsel + 4096, 32, B_SEL);
      if (bid < 112) {
        int s = 0, ph = 1;
#pragma unroll 1
        for (int n = 0; n < 32; n++) {
          mbar_wait(B_FE + 8 * s, ph);
          e_expect(B_FR + 8 * s, 4608);
          e_tma3d_ef(GR + s * 4096, &mp.gu, bid * 32 * EXP_A, n * 32 * EXP_B, B_FR + 8 * s, pol);
          e_load(HOP + s * 512, g_xsel + n * 128, 512, B_FR + 8 * s);
          STAMP2(64 + n);
          if (PFD) {
            if (n == 32 - PFD) pf = pd;
            asm volatile("prefetch.global.L2 [%0];" ::"l"(pf));
            pf += n < 32 - PFD ? 32 * 7168 : 65536;
          }
          if (++s == 5) { s = 0; ph ^= 1; }
        }
      }
      const uint32_t* hw = g_h + ((bid >> 4) * 14 + min(lane >> 1, 13)) * 256 + 239 + (lane & 1) * 16;
#pragma unroll 1
      for (int i = 0; i < 14; i++) {
        const int s = (i + 1) & 3;
        if (i >= 4) mbar_wait(B_DE + 8 * s, ((i >> 2) & 1) ^ 1);
        else if (bid < 112) mbar_wait(B_FE + 8 * (s + 1), s != 0);
        e_expect(B_DR + 8 * s, 4096);
        e_tma2d_ef(FR + s * 4096, &mp.down, (bid & 15) * 64, (bid >> 4) * 448 + i * 32 * EXP_B, B_DR + 8 * s, pol);
        if (PFD && i + PFD < 14) asm volatile("prefetch.global.L2 [%0];" ::"l"(pd + (i + PFD) * 65536));
        if (i == 2) ld_relaxed(hw);
        if (i == 3) { poll1(f, hw, ep, 0xffffu); e_arrive(B_PH); }
      }
      mbar_wait(B_SEL, 0);
      if (__any_sync(0xffffffffu, (key_token(lds32(S_SEL + (lane & 7) * 4)) >> 7) == tm)) {
        poll1(f, g_yp + (tn * 16 + (lane & 15)) * 512 + 495 + (lane & 16), ep, 1u);
        e_arrive(B_PY);
      }
    }
  } else if (w >= 8) {
    asm volatile("setmaxnreg.dec.sync.aligned.u32 64;");
    const int t = tid - 256, ww = w - 8;
    const uint32_t ep = ld_relaxed(&g_epoch) + 1, par = ep & 1u;
    {
      const int r0 = (lane >> 3) + (lane & 4);
      const uint32_t a = FR + (ww >> 1) * 8192 + r0 * 128 + ((((ww & 1) * 4 + (lane & 3)) ^ r0) << 4);
      float c[8];
      reg_zero(c);
      mbar_wait(B_WK, 0);
#pragma unroll 2
      for (int i = 0; i < 8; i++) {
        const uint4 v = lds128(a + i * 1024);
        c[0] += bf_lo(v.x); c[1] += bf_hi(v.x); c[2] += bf_lo(v.y); c[3] += bf_hi(v.y);
        c[4] += bf_lo(v.z); c[5] += bf_hi(v.z); c[6] += bf_lo(v.w); c[7] += bf_hi(v.w);
      }
      const bool u16 = lane & 16, u8 = lane & 8, u4 = lane & 4;
      const float d0 = xred(c[0], c[4], u16, 16), d1 = xred(c[1], c[5], u16, 16), d2 = xred(c[2], c[6], u16, 16), d3 = xred(c[3], c[7], u16, 16);
      fence_async_smem();
      e_arrive(B_CSDN);
      const float sum = xred(xred(d0, d2, u8, 8), xred(d1, d3, u8, 8), u4, 4);
      st_relaxed(g_csum + (2 + tm) * 1024 + tn * 128 + ww * 32 + (lane & 3) * 8 + (lane >> 2), tagf(sum, par));
      STAMP_IF(t == 0, 8);
      __nanosleep(500);
      uint32_t p[16];
      poll16(p, g_csum + 2048 + tn * 128 + t, par, 1u);
      float tot = 0.f;
#pragma unroll
      for (int i = 0; i < 16; i += 4) tot += (__uint_as_float(p[i]) + __uint_as_float(p[i + 1])) + (__uint_as_float(p[i + 2]) + __uint_as_float(p[i + 3]));
      sts32(S_CSK + t * 4, __float_as_uint(tot));
      nb_arrive(NB_FDONE, 416);
      STAMP_IF(t == 0, 9);
    }
    const int ks = bid >> 4, nt = bid & 15;
    mbar_wait(B_SEL, 0);
    STAMP_IF(t == 0, 11);
    float fa[4] = {0.f, 0.f, 0.f, 0.f};
    if (bid < 112) {
      int s = 0, ph = 0;
      uint32_t prev = 0;
#pragma unroll 1
      for (int n = 0; n < 32; n++) {
        mbar_wait(B_FR + 8 * s, ph);
        const uint64_t da = mkdesc(GR, 2048, 512, 2) + s * 256, db = mkdesc(HOP, 16, 512, 2) + s * 32;
        wg_fence();
        wgmma_n8_ss<1, 0>(fa, da, db, 1);
        wgmma_n8_ss<1, 0>(fa, da + 64, db + 2, 1);
        wg_commit();
        wg_wait<1>();
        if (prev && t == 0) mbar_arrive(prev);
        prev = B_FE + 8 * s;
        if (++s == 5) { s = 0; ph ^= 1; }
      }
      wg_wait<0>();
      reg_fence(fa);
      if (t == 0) mbar_arrive(prev);
      STAMP_IF(t == 0, 12);
      const bool isup = (ww >> 1) != (wu < wg);
      if (isup) sts128f(GR + (t & 63) * 16, fa[0], fa[1], fa[2], fa[3]);
      nb_sync(NB_WG2, 128);
      if (!isup) {
        const float4 u = lds128f(GR + (t & 63) * 16);
        const float uu[4] = {u.x, u.y, u.z, u.w};
        uint32_t* hp = g_h + bid * 256 + (lane & 3) * 64 + (ww & 1) * 16 + (lane >> 2);
#pragma unroll
        for (int i = 0; i < 4; i++) {
          const float g = fa[i], hv = g * rcp(1.f + ex2(-g * LOG2E)) * uu[i];
          st_relaxed(hp + (i & 1) * 32 + (i >> 1) * 8, __byte_perm(pack(hv, hv), ep, 0x3254));
        }
      }
      nb_sync(NB_WG2, 128);
      reg_zero(fa);
    }
    {
      uint32_t v[28];
      mbar_wait(B_PH, 0);
      poll7x4(v, g_h + ks * 3584 + t * 4, ep, 0xffffu);
#pragma unroll
      for (int q = 0; q < 7; q++)
        asm volatile("st.shared.v2.u32 [%0], {%1,%2};" ::"r"(HOP + q * 1024 + (t >> 3) * 64 + ((((t >> 1) & 3) ^ ((t >> 4) & 3)) << 4) + (t & 1) * 8),
                     "r"(__byte_perm(v[4 * q], v[4 * q + 1], 0x7632)), "r"(__byte_perm(v[4 * q + 2], v[4 * q + 3], 0x7632)) : "memory");
      fence_async_smem();
      nb_sync(NB_WG2, 128);
    }
    STAMP_IF(t == 0, 13);
#pragma unroll 1
    for (int i = 0; i < 14; i++) {
      const int s = (i + 1) & 3;
      mbar_wait(B_DR + 8 * s, (i >> 2) & 1);
      const uint64_t da = mkdesc(FR, 4096, 1024, 1) + s * 256;
      const uint64_t db = mkdesc(HOP, 16, 512, 2) + i * 32;
      wg_fence();
      wgmma_n8_ss<1, 0>(fa, da, db, 1);
      wgmma_n8_ss<1, 0>(fa, da + 128, db + 2, 1);
      wg_commit();
      wg_wait<1>();
      if (i && t == 0) mbar_arrive(B_DE + 8 * (i & 3));
    }
    wg_wait<0>();
    reg_fence(fa);
    STAMP_IF(t == 0, 14);
    {
      uint32_t* yp = g_yp + (nt * 8 + ks) * 512 + (lane & 3) * 128 + ww * 16 + (lane >> 2);
#pragma unroll
      for (int i = 0; i < 4; i++) st_relaxed(yp + (i & 1) * 64 + (i >> 1) * 8, tagf(fa[i], par));
    }
    const uint32_t mykey = lds32(S_SEL + (lane & 7) * 4);
    const uint32_t inmask = __ballot_sync(0xffffffffu, (key_token(mykey) >> 7) == tm) & 0xffu;
    if (inmask) {
      mbar_wait(B_PY, 0);
      nb_sync(NB_WG2, 128);
      const float sg = rcp(1.f + ex2(-key_score(mykey) * LOG2E));
#pragma unroll 1
      for (int j = 0; j < 8; j++) {
        float y = 0.f;
        if ((inmask >> j) & 1) {
          uint32_t p[8];
          poll8(p, g_yp + (tn * 2 + (t >> 6)) * 4096 + j * 64 + (t & 63), par, 1u);
          y = ((__uint_as_float(p[0]) + __uint_as_float(p[1])) + (__uint_as_float(p[2]) + __uint_as_float(p[3]))) +
              ((__uint_as_float(p[4]) + __uint_as_float(p[5])) + (__uint_as_float(p[6]) + __uint_as_float(p[7])));
        }
        y *= __shfl_sync(0xffffffffu, sg, j);
        asm volatile("st.shared.u16 [%0], %1;" ::"r"(FR + (t >> 6) * 1024 + j * 128 + ((((t >> 3) & 7) ^ j) << 4) + (t & 7) * 2),
                     "h"((unsigned short)pack(y, y)) : "memory");
      }
      fence_async_smem();
      nb_arrive(NB_Y, 256);
    }
    STAMP_IF(t == 0, 15);
  } else if (w >= 4) {
    asm volatile("setmaxnreg.inc.sync.aligned.u32 208;");
    const int t = tid - 128, ww = w - 4, g = lane >> 2, t4 = lane & 3;
    const bool leader = t == 0;
    const uint32_t ep = ld_relaxed(&g_epoch) + 1, par = ep & 1u;
    {
      const uint4* wp = reinterpret_cast<const uint4*>(w_r) + lane;
      uint4 w0 = __ldg(wp), w1 = __ldg(wp + 32), w2 = __ldg(wp + 64), w3 = __ldg(wp + 96);
      if (leader) sts32(S_EPOCH, ep);
      float s[4] = {0.f, 0.f, 0.f, 0.f}, q[4] = {0.f, 0.f, 0.f, 0.f}, d[4] = {0.f, 0.f, 0.f, 0.f}, wsum = 0.f;
#pragma unroll 1
      for (int c = 0; c < 4; c++) {
        const float wr[8] = {bf_lo(w0.x), bf_hi(w0.x), bf_lo(w0.y), bf_hi(w0.y), bf_lo(w0.z), bf_hi(w0.z), bf_lo(w0.w), bf_hi(w0.w)};
        w0 = w1; w1 = w2; w2 = w3;
        wsum += ((wr[0] + wr[1]) + (wr[2] + wr[3])) + ((wr[4] + wr[5]) + (wr[6] + wr[7]));
        mbar_wait(B_XS + 8 * c, 0);
#pragma unroll
        for (int r = 0; r < 4; r++) {
          const uint4 v = lds128(STG + c * 8192 + (ww * 4 + r) * 512 + lane * 16);
          const uint32_t xw[4] = {v.x, v.y, v.z, v.w};
#pragma unroll
          for (int i = 0; i < 4; i++) {
            const float lo = bf_lo(xw[i]), hi = bf_hi(xw[i]);
            s[r] += lo; q[r] = fmaf(lo, lo, q[r]); d[r] = fmaf(lo, wr[2 * i], d[r]);
            s[r] += hi; q[r] = fmaf(hi, hi, q[r]); d[r] = fmaf(hi, wr[2 * i + 1], d[r]);
          }
        }
      }
      STAMP_IF(leader, 16);
      const bool u16 = lane & 16, u8 = lane & 8, u4 = lane & 4, u2 = lane & 2;
      const float s1 = xred(xred(s[0], s[2], u16, 16), xred(s[1], s[3], u16, 16), u8, 8);
      const float q1 = xred(xred(q[0], q[2], u16, 16), xred(q[1], q[3], u16, 16), u8, 8);
      const float d1 = xred(xred(d[0], d[2], u16, 16), xred(d[1], d[3], u16, 16), u8, 8);
      wsum += __shfl_xor_sync(0xffffffffu, wsum, 16);
      wsum += __shfl_xor_sync(0xffffffffu, wsum, 8);
      float tot = xred(xred(s1, d1, u4, 4), xred(q1, wsum, u4, 4), u2, 2);
      tot += __shfl_xor_sync(0xffffffffu, tot, 1);
      const float qq = __shfl_down_sync(0xffffffffu, tot, 2), dd = __shfl_down_sync(0xffffffffu, tot, 4), ws = __shfl_down_sync(0xffffffffu, tot, 6);
      if ((lane & 7) == 0) {
        const float mean = tot * (1.f / 1024.f);
        const float var = fmaxf(fmaf(-mean, mean, qq * (1.f / 1024.f)), 0.f);
        float sd;
        asm("sqrt.approx.ftz.f32 %0, %1;" : "=f"(sd) : "f"(bf_round(bf_round(var) + 1e-5f)));
        const uint32_t ms = pack(sd, mean);
        const int row = tm * 128 + tn * 16 + ww * 4 + (lane >> 3);
        const uint32_t rbits = pack(0.f, fmaf(-bf_hi(ms), ws, dd) * rcp(bf_lo(ms)));
        const uint32_t key = (rbits ^ (((int)rbits >> 31 & 0x7fff0000u) | 0x80000000u)) | ((2047 - row) << 5) | (ep & 31u);
        asm volatile("{\n.reg .b64 x;\nmov.b64 x, {%1,%2};\nst.relaxed.gpu.global.b64 [%0], x;\n}" ::"l"(g_keys + row), "r"(key), "r"(ms) : "memory");
      }
      STAMP_IF(leader, 17);
      __nanosleep(400);
      uint32_t st[2];
      poll_pair(st, g_keys + tm * 128 + t, ep, 31u);
      asm volatile("st.shared.v2.f32 [%0], {%1,%2};" ::"r"(S_KSTAT + t * 8), "f"(bf_hi(st[1])), "f"(rcp(bf_lo(st[1])) * LOG2E) : "memory");
      nb_arrive(NB_FDONE, 416);
      STAMP_IF(leader, 10);
    }
    float a0[64], a1[64];
    reg_zero(a0); reg_zero(a1); reg_fence(a0); reg_fence(a1);
    STAMP_IF(leader, 18);
    nb_sync(NB_KV, 256);
    mainloop<true>(a0, a1, 1, 1, NB_VQ, leader);
    STAMP_IF(leader, 19);
    {
      nb_sync(NB_PK, 288);
      float c[4];
#pragma unroll
      for (int i = 0; i < 4; i++) c[i] = -__uint_as_float(lds32(S_CSV + ((i >> 1) * 64 + ww * 16 + (i & 1) * 8 + g) * 4));
      float mu[32];
#pragma unroll
      for (int j = 0; j < 16; j++) {
        const float4 s0 = lds128f(S_KSTAT + (j * 8 + 2 * t4) * 8);
        mu[2 * j] = s0.x; mu[2 * j + 1] = s0.z;
      }
      uint32_t f0[32], f1[32];
      float c0[32], c1[32];
      constexpr uint64_t db = mkdesc(STG, 16, 1024, 1);
#pragma unroll
      for (int i = 0; i < 32; i++) f0[i] = pack(fmaf(c[i & 1], mu[i & ~1], a0[2 * i]), fmaf(c[i & 1], mu[i | 1], a0[2 * i + 1]));
      reg_zero(c0);
      wg_fence();
#pragma unroll
      for (int k = 0; k < 8; k++) wgmma_n64_rs<0>(c0, f0[4 * k], f0[4 * k + 1], f0[4 * k + 2], f0[4 * k + 3], db + (k >> 2) * 1024 + (k & 3) * 2, k != 0);
      wg_commit();
      reg_fence(a1);
#pragma unroll
      for (int i = 0; i < 32; i++) f1[i] = pack(fmaf(c[2 + (i & 1)], mu[i & ~1], a1[2 * i]), fmaf(c[2 + (i & 1)], mu[i | 1], a1[2 * i + 1]));
      wg_wait<0>();
      reg_fence(c0);
      reg_zero(c1);
      wg_fence();
#pragma unroll
      for (int k = 0; k < 8; k++) wgmma_n64_rs<0>(c1, f1[4 * k], f1[4 * k + 1], f1[4 * k + 2], f1[4 * k + 3], db + (k >> 2) * 1024 + (k & 3) * 2 + 512, k != 0);
      wg_commit();
      uint4* pp = g_kvp + (tn * 16 + tm) * 512 + t;
      const bool hp = ww >> 1;
      auto put = [&](uint4* p, const float (&c)[32]) {
        if (!hp) {
          st_unit(p, pack(c[0], c[1]), pack(c[2], c[3]), pack(c[4], c[5]), pack(c[6], c[7]), par);
          st_unit(p + 128, pack(c[8], c[9]), pack(c[10], c[11]), pack(c[12], c[13]), pack(c[14], c[15]), par);
        } else {
          st_unit(p, pack(c[16], c[17]), pack(c[18], c[19]), pack(c[20], c[21]), pack(c[22], c[23]), par);
          st_unit(p + 128, pack(c[24], c[25]), pack(c[26], c[27]), pack(c[28], c[29]), pack(c[30], c[31]), par);
        }
      };
      put(pp, c0);
      wg_wait<0>();
      reg_fence(c1);
      STAMP_IF(leader, 20);
      put(pp + 256, c1);
      STAMP_IF(leader, 47);
      {
        uint32_t p[16];
        mbar_wait(B_P1, 0);
        STAMP_IF(leader, 1);
        poll_kvp(p, g_kvp + (tn * 16 + (lane >> 3) * 4) * 512 + tm * 32 + ww * 8 + (lane & 7), par, 1u);
        float r[8];
#pragma unroll
        for (int i = 0; i < 4; i++) {
          r[2 * i] = (bf_lo(p[i]) + bf_lo(p[4 + i])) + (bf_lo(p[8 + i]) + bf_lo(p[12 + i]));
          r[2 * i + 1] = (bf_hi(p[i]) + bf_hi(p[4 + i])) + (bf_hi(p[8 + i]) + bf_hi(p[12 + i]));
        }
#pragma unroll
        for (int i = 0; i < 8; i++) r[i] += __shfl_xor_sync(0xffffffffu, r[i], 8);
#pragma unroll
        for (int i = 0; i < 8; i++) r[i] += __shfl_xor_sync(0xffffffffu, r[i], 16);
        if (lane < 8) st_unit(g_kv + tn * 512 + tm * 32 + ww * 8 + lane, pack(r[0], r[1]), pack(r[2], r[3]), pack(r[4], r[5]), pack(r[6], r[7]), par);
      }
      STAMP_IF(leader, 21);
    }
    const uint32_t sx = lane & 7, sc = lane >> 4;
    const uint32_t sa = STG + (ww * 16 + (lane & 15)) * 128;
    const uint32_t sw[4] = {sa + ((sc ^ sx) << 4), sa + (((2 + sc) ^ sx) << 4), sa + (((4 + sc) ^ sx) << 4), sa + (((6 + sc) ^ sx) << 4)};
    {
      uint32_t v[16];
      mbar_wait(B_P2, 0);
      STAMP_IF(leader, 7);
      poll_kv(v, g_kv + tn * 512 + t, par, 1u);
      STAMP_IF(leader, 23);
#pragma unroll
      for (int q = 0; q < 4; q++)
        stsm4((q < 2 ? KVB_P0 : KVB_P1) + ((ww & 1) * 16 + (lane & 15)) * 128 + ((((ww >> 1) * 4 + (q & 1) * 2 + sc) ^ sx) << 4),
              v[4 * q], v[4 * q + 1], v[4 * q + 2], v[4 * q + 3]);
      fence_async_smem();
      nb_arrive(NB_KVB, 288);
    }
    STAMP_IF(leader, 24);
    uint32_t oh[4];
    uint32_t inmask;
    {
      mbar_wait(B_SEL, 0);
      const int r0 = key_token(lds32(S_SEL + t4 * 8)) - tm * 128, r1 = key_token(lds32(S_SEL + t4 * 8 + 4)) - tm * 128;
#pragma unroll
      for (int i = 0; i < 4; i++) {
        const int row = (i >> 1) * 64 + ww * 16 + (i & 1) * 8 + g;
        oh[i] = (r0 == row ? 0x3f80u : 0u) | (r1 == row ? 0x3f800000u : 0u);
      }
      inmask = __ballot_sync(0xffffffffu, (unsigned)r0 < 128u || (unsigned)r1 < 128u);
    }
    {
      float ka[4], kb[4];
#pragma unroll
      for (int i = 0; i < 4; i++) {
        const float2 st = lds64f(S_KSTAT + ((i >> 1) * 64 + ww * 16 + (i & 1) * 8 + g) * 8);
        const float r = st.y * LN2;
        ka[i] = 1.f + r; kb[i] = -st.x * r;
      }
      constexpr uint32_t XOFF = RING + 3 * SLOT + 16384 - STG;
      mbar_wait(B_XRES, 0);
#pragma unroll
      for (int j = 0; j < 8; j++) {
        const uint4 v = ldsm4(sw[j & 3] + XOFF + (j >> 2) * SLOT), u = ldsm4(sw[j & 3] + XOFF + (j >> 2) * SLOT + 8192);
        a0[8 * j + 0] = fmaf(bf_lo(v.x), ka[0], kb[0]); a0[8 * j + 1] = fmaf(bf_hi(v.x), ka[0], kb[0]);
        a0[8 * j + 2] = fmaf(bf_lo(v.y), ka[1], kb[1]); a0[8 * j + 3] = fmaf(bf_hi(v.y), ka[1], kb[1]);
        a0[8 * j + 4] = fmaf(bf_lo(v.z), ka[0], kb[0]); a0[8 * j + 5] = fmaf(bf_hi(v.z), ka[0], kb[0]);
        a0[8 * j + 6] = fmaf(bf_lo(v.w), ka[1], kb[1]); a0[8 * j + 7] = fmaf(bf_hi(v.w), ka[1], kb[1]);
        a1[8 * j + 0] = fmaf(bf_lo(u.x), ka[2], kb[2]); a1[8 * j + 1] = fmaf(bf_hi(u.x), ka[2], kb[2]);
        a1[8 * j + 2] = fmaf(bf_lo(u.y), ka[3], kb[3]); a1[8 * j + 3] = fmaf(bf_hi(u.y), ka[3], kb[3]);
        a1[8 * j + 4] = fmaf(bf_lo(u.z), ka[2], kb[2]); a1[8 * j + 5] = fmaf(bf_hi(u.z), ka[2], kb[2]);
        a1[8 * j + 6] = fmaf(bf_lo(u.w), ka[3], kb[3]); a1[8 * j + 7] = fmaf(bf_hi(u.w), ka[3], kb[3]);
      }
      reg_fence(a0);
      reg_fence(a1);
      fence_async_smem();
    }
    STAMP_IF(leader, 22);
    {
      int s = 3, ph = 1;
      uint32_t prev = 0;
#pragma unroll 1
      for (int r = 0; r < 16; r++) {
        if (r < 2) nb_sync(NB_OWN0 + r, r ? 256 : 288);
        mbar_wait(B_FULL + 8 * s, ph);
        STAMP_IF(leader && r < 3, 25 + r);
        const uint64_t dw = mkdesc(RING, 8192, 1024, 1) + s * (SLOT >> 4);
        const uint64_t dx = mkdesc(0, 16, 1024, 1) + (r < 2 ? (STG >> 4) + r * 1024 : ((RING + 16384) >> 4) + s * (SLOT >> 4));
        wg_fence();
#pragma unroll
        for (int j = 0; j < 4; j++) {
          wgmma_n128_ss<0, 1>(a0, dx + j * 2, dw + j * 128, 1);
          wgmma_n128_ss<0, 1>(a1, dx + j * 2 + 512, dw + j * 128, 1);
        }
        wg_commit();
        wg_wait<1>();
        if (prev && leader) mbar_arrive(prev);
        prev = B_EMPTY + 8 * s;
        if (++s == NST) { s = 0; ph ^= 1; }
      }
      if (inmask) {
        nb_sync(NB_Y, 256);
        wg_fence();
        wgmma_n128_rs<1>(a0, oh[0], oh[1], 0u, 0u, mkdesc(FR, 1024, 0, 1), 1);
        wgmma_n128_rs<1>(a1, oh[2], oh[3], 0u, 0u, mkdesc(FR, 1024, 0, 1), 1);
        wg_commit();
      }
      nb_sync(NB_ST, 160);
      wg_wait<0>();
      reg_fence(a0);
      reg_fence(a1);
    }
    STAMP_IF(leader, 28);
#pragma unroll
    for (int c = 0; c < 2; c++) {
#pragma unroll
      for (int j = 4 * c; j < 4 * c + 4; j++) {
        stsm4(sw[j & 3] + c * 16384, pack(a0[8 * j], a0[8 * j + 1]), pack(a0[8 * j + 2], a0[8 * j + 3]), pack(a0[8 * j + 4], a0[8 * j + 5]), pack(a0[8 * j + 6], a0[8 * j + 7]));
        stsm4(sw[j & 3] + c * 16384 + 8192, pack(a1[8 * j], a1[8 * j + 1]), pack(a1[8 * j + 2], a1[8 * j + 3]), pack(a1[8 * j + 4], a1[8 * j + 5]), pack(a1[8 * j + 6], a1[8 * j + 7]));
      }
      fence_async_smem();
      e_store2d(&mp.out, tn * 128 + c * 64, tm * 128 + ww * 16, STG + c * 16384 + ww * 2048);
      e_store2d(&mp.out, tn * 128 + c * 64, tm * 128 + 64 + ww * 16, STG + c * 16384 + 8192 + ww * 2048);
    }
    bulk_wait_read();
    if (bid == 0 && leader) st_relaxed(&g_epoch, ep);
    STAMP_IF(leader, 29);
  } else {
    asm volatile("setmaxnreg.inc.sync.aligned.u32 208;");
    const int g = lane >> 2, t4 = lane & 3;
    const bool leader = tid == 0;
    const uint32_t sx = lane & 7, sc = lane >> 4;
    const uint32_t sa = STG + (w * 16 + (lane & 15)) * 128;
    const uint32_t sw[4] = {sa + ((sc ^ sx) << 4), sa + (((2 + sc) ^ sx) << 4), sa + (((4 + sc) ^ sx) << 4), sa + (((6 + sc) ^ sx) << 4)};
    float a0[64], a1[64];
    reg_zero(a0); reg_zero(a1); reg_fence(a0); reg_fence(a1);
    mainloop<true>(a0, a1, 0, 0, NB_KV, leader);
    STAMP_IF(leader, 33);
    {
      nb_sync(NB_FDONE, 416);
      STAMP_IF(leader, 34);
      float c[4], z[4] = {0.f, 0.f, 0.f, 0.f};
#pragma unroll
      for (int i = 0; i < 4; i++) c[i] = -__uint_as_float(lds32(S_CSK + ((i >> 1) * 64 + w * 16 + (i & 1) * 8 + g) * 4));
#pragma unroll
      for (int j = 0; j < 8; j++) {
        const float4 s0 = lds128f(S_KSTAT + (j * 16 + 2 * t4) * 8), s1 = lds128f(S_KSTAT + (j * 16 + 8 + 2 * t4) * 8);
        const float mu[4] = {s0.x, s0.z, s1.x, s1.z}, rl[4] = {s0.y, s0.w, s1.y, s1.w};
#pragma unroll
        for (int m = 0; m < 2; m++) {
          float p[8];
#pragma unroll
          for (int i = 0; i < 8; i++) {
            const int r = m * 2 + ((i >> 1) & 1), cc = (i >> 2) * 2 + (i & 1);
            p[i] = phi2(fmaf(c[r], mu[cc], m ? a1[8 * j + i] : a0[8 * j + i]) * rl[cc]);
            z[r] += p[i];
            p[i] *= rl[cc];
          }
          stsm4(sw[j & 3] + (j >> 2) * 16384 + m * 8192, pack(p[0], p[1]), pack(p[2], p[3]), pack(p[4], p[5]), pack(p[6], p[7]));
        }
      }
      const bool u2 = lane & 2, u1 = lane & 1;
      const float zz = xred(xred(z[0], z[2], u2, 2), xred(z[1], z[3], u2, 2), u1, 1);
      fence_async_smem();
      nb_arrive(NB_PK, 288);
      st_relaxed(g_z + tm * 1024 + tn * 128 + (t4 >> 1) * 64 + w * 16 + (t4 & 1) * 8 + g, tagf(zz * LOG2E, lds32(S_EPOCH) & 1u));
      nb_arrive(NB_Z, 160);
    }
    STAMP_IF(leader, 35);
    float rl[4];
    {
      nb_sync(NB_CSQ, 160);
      float mu[4];
#pragma unroll
      for (int i = 0; i < 4; i++) {
        const float2 st = lds64f(S_KSTAT + ((i >> 1) * 64 + w * 16 + (i & 1) * 8 + g) * 8);
        mu[i] = -st.x; rl[i] = st.y;
      }
#pragma unroll
      for (int j = 0; j < 16; j++) {
        const float2 c = lds64f(S_CSQ + (j * 8 + 2 * t4) * 4);
        a0[4 * j] = mu[0] * c.x; a0[4 * j + 1] = mu[0] * c.y; a0[4 * j + 2] = mu[1] * c.x; a0[4 * j + 3] = mu[1] * c.y;
        a1[4 * j] = mu[2] * c.x; a1[4 * j + 1] = mu[2] * c.y; a1[4 * j + 2] = mu[3] * c.x; a1[4 * j + 3] = mu[3] * c.y;
      }
      reg_fence(a0); reg_fence(a1);
    }
    STAMP_IF(leader, 40);
    nb_sync(NB_VQ, 256);
    mainloop<false>(a0, a1, 2, 0, 0, leader);
    STAMP_IF(leader, 36);
    {
      uint32_t f[2][16];
      float oc[2][2][20];
      auto phi = [&](float (&a)[64], int j, int m, uint32_t (&o)[16]) {
#pragma unroll
        for (int i = 0; i < 32; i++) asm volatile("" : "+f"(a[32 * j + i])::"memory");
#pragma unroll
        for (int i = 0; i < 16; i++) o[i] = pack(phi2(a[32 * j + 2 * i] * rl[2 * m + (i & 1)]), phi2(a[32 * j + 2 * i + 1] * rl[2 * m + (i & 1)]));
      };
      auto mma = [&](int j, const uint32_t (&a)[16], float (&o)[2][20]) {
        const uint64_t db = mkdesc(j ? KVB_Z : KVB_P0, 16, 1024, 1);
        reg_zero(o[0]); reg_zero(o[1]);
        wg_fence();
        wgmma_n40_rs<0>(o[0], a[0], a[1], a[2], a[3], db, 0);
        wgmma_n40_rs<0>(o[1], a[8], a[9], a[10], a[11], db + 4, 0);
        wgmma_n40_rs<0>(o[0], a[4], a[5], a[6], a[7], db + 2, 1);
        wgmma_n40_rs<0>(o[1], a[12], a[13], a[14], a[15], db + 6, 1);
        wg_commit();
      };
      auto fin = [&](int j, int m, float (&o)[2][20]) {
#pragma unroll
        for (int h = 0; h < 2; h++) {
          const float r0 = rcp(o[h][j ? 1 : 16] + 1e-6f * LOG2E), r1 = rcp(o[h][j ? 3 : 18] + 1e-6f * LOG2E);
          const int b = j ? 4 : 0;
#pragma unroll
          for (int q = 0; q < 2; q++)
            stsm4(sw[h * 2 + q] + j * 16384 + m * 8192,
                  pack(o[h][b + 8 * q] * r0, o[h][b + 8 * q + 1] * r0), pack(o[h][b + 8 * q + 2] * r1, o[h][b + 8 * q + 3] * r1),
                  pack(o[h][b + 8 * q + 4] * r0, o[h][b + 8 * q + 5] * r0), pack(o[h][b + 8 * q + 6] * r1, o[h][b + 8 * q + 7] * r1));
        }
      };
#pragma unroll
      for (int j = 0; j < 2; j++) {
        phi(a0, j, 0, f[0]);
        if (j == 0) nb_sync(NB_KVB, 288);
        STAMP_IF(leader && j == 0, 37);
        mma(j, f[0], oc[0]);
        phi(a1, j, 1, f[1]);
        wg_wait<0>();
        reg_fence(oc[0][0]); reg_fence(oc[0][1]);
        mma(j, f[1], oc[1]);
        fin(j, 0, oc[0]);
        if (j == 0) { fence_async_smem(); nb_arrive(NB_Q0, 192); }
        wg_wait<0>();
        reg_fence(oc[1][0]); reg_fence(oc[1][1]);
        fin(j, 1, oc[1]);
        fence_async_smem();
        if (j == 0) nb_arrive(NB_OWN0, 288);
        else { nb_arrive(NB_OWN1, 256); nb_arrive(NB_H1, 160); }
        STAMP_IF(leader, 38 + j);
      }
    }
  }
}

typedef CUresult (*EncodeFn)(CUtensorMap*, CUtensorMapDataType, cuuint32_t, void*, const cuuint64_t*, const cuuint64_t*, const cuuint32_t*,
                             const cuuint32_t*, CUtensorMapInterleave, CUtensorMapSwizzle, CUtensorMapL2promotion, CUtensorMapFloatOOBfill);

void make_map(EncodeFn enc, CUtensorMap* m, const void* p, int rank, uint64_t d0, uint64_t d1, uint64_t d2, uint64_t s1, uint64_t s2,
              uint32_t b0, uint32_t b1, uint32_t b2, CUtensorMapSwizzle sw) {
  cuuint64_t gd[3] = {d0, d1, d2}, gs[2] = {s1, s2};
  cuuint32_t bd[3] = {b0, b1, b2}, es[3] = {1, 1, 1};
  enc(m, CU_TENSOR_MAP_DATA_TYPE_BFLOAT16, rank, const_cast<void*>(p), gd, gs, bd, es, CU_TENSOR_MAP_INTERLEAVE_NONE, sw,
      CU_TENSOR_MAP_L2_PROMOTION_L2_128B, CU_TENSOR_MAP_FLOAT_OOB_FILL_NONE);
}

}

extern "C" void kernel_launch(void* const* d_in, const int* in_sizes, int n_in, void* d_out, int out_size) {
  (void)in_sizes; (void)n_in; (void)out_size;
  void* fn = nullptr;
  cudaDriverEntryPointQueryResult qr;
  cudaGetDriverEntryPoint("cuTensorMapEncodeTiled", &fn, cudaEnableDefault, &qr);
  EncodeFn enc = (EncodeFn)fn;
  void* o;
  cudaGetSymbolAddress(&o, g_o);
  const CUtensorMapSwizzle S128 = CU_TENSOR_MAP_SWIZZLE_128B, S64 = CU_TENSOR_MAP_SWIZZLE_64B, S0 = CU_TENSOR_MAP_SWIZZLE_NONE;
  Maps mp;
  make_map(enc, &mp.wqkv, d_in[1], 3, 64, 1024, 48, 6144, 128, 64, 64, 2, S128);
  make_map(enc, &mp.x, d_in[0], 2, 1024, 2048, 1, 2048, 0, 64, 128, 1, S128);
  make_map(enc, &mp.os, o, 2, 1024, 2048, 1, 2048, 0, 64, 64, 1, S128);
  make_map(enc, &mp.o, o, 2, 1024, 2048, 1, 2048, 0, 64, 128, 1, S128);
  make_map(enc, &mp.wo, d_in[2], 3, 64, 1024, 16, 2048, 128, 64, 64, 2, S128);
  make_map(enc, &mp.xs, d_in[0], 2, 1024, 2048, 1, 2048, 0, 256, 16, 1, S0);
  const char *wg = (const char*)d_in[5], *wu = (const char*)d_in[6];
  make_map(enc, &mp.gu, wu < wg ? wu : wg, 3, 3584, 1024, 2, 7168, (uint64_t)(wu < wg ? wg - wu : wu - wg), 32, 32, 2, S64);
  make_map(enc, &mp.down, d_in[7], 2, 1024, 3584, 1, 2048, 0, 64, 32, 1, S128);
  make_map(enc, &mp.out, d_out, 2, 1024, 2048, 1, 2048, 0, 64, 16, 1, S128);
  cudaFuncSetAttribute(fused_kernel, cudaFuncAttributeMaxDynamicSharedMemorySize, SMEM_BYTES);
  fused_kernel<<<132, 512, SMEM_BYTES>>>(mp, (const __nv_bfloat16*)d_in[4], (const __nv_bfloat16*)d_in[0], (const char*)d_in[5],
                                         (const char*)d_in[6], (const char*)d_in[7]);
}
```

```cpp
#include <cuda_runtime.h>
#include <cuda.h>
#include <cuda_bf16.h>
#include <stdint.h>

namespace {

template <int TA, int TB>
__device__ __forceinline__ void wgmma_n8_ss(float (&d)[4], uint64_t da, uint64_t db, int sc) {
  asm volatile("{\n.reg .pred p;\nsetp.ne.b32 p, %6, 0;\n"
    "wgmma.mma_async.sync.aligned.m64n8k16.f32.bf16.bf16 {%0, %1, %2, %3}, %4, %5, p, 1, 1, %7, %8;\n}\n"
    : "+f"(d[0]), "+f"(d[1]), "+f"(d[2]), "+f"(d[3])
    : "l"(da), "l"(db), "r"(sc), "n"(TA), "n"(TB));
}
template <int TB>
__device__ __forceinline__ void wgmma_n40_rs(float (&d)[20], uint32_t a0, uint32_t a1, uint32_t a2, uint32_t a3, uint64_t db, int sc) {
  asm volatile("{\n.reg .pred p;\nsetp.ne.b32 p, %25, 0;\n"
    "wgmma.mma_async.sync.aligned.m64n40k16.f32.bf16.bf16 {%0, %1, %2, %3, %4, %5, %6, %7, %8, %9, %10, %11, %12, %13, %14, %15, %16, %17, %18, %19}, {%20,%21,%22,%23}, %24, p, 1, 1, %26;\n}\n"
    : "+f"(d[0]), "+f"(d[1]), "+f"(d[2]), "+f"(d[3]), "+f"(d[4]), "+f"(d[5]), "+f"(d[6]), "+f"(d[7]),
      "+f"(d[8]), "+f"(d[9]), "+f"(d[10]), "+f"(d[11]), "+f"(d[12]), "+f"(d[13]), "+f"(d[14]), "+f"(d[15]),
      "+f"(d[16]), "+f"(d[17]), "+f"(d[18]), "+f"(d[19])
    : "r"(a0), "r"(a1), "r"(a2), "r"(a3), "l"(db), "r"(sc), "n"(TB));
}
template <int TB>
__device__ __forceinline__ void wgmma_n64_rs(float (&d)[32], uint32_t a0, uint32_t a1, uint32_t a2, uint32_t a3, uint64_t db, int sc) {
  asm volatile("{\n.reg .pred p;\nsetp.ne.b32 p, %37, 0;\n"
    "wgmma.mma_async.sync.aligned.m64n64k16.f32.bf16.bf16 {%0, %1, %2, %3, %4, %5, %6, %7, %8, %9, %10, %11, %12, %13, %14, %15, %16, %17, %18, %19, %20, %21, %22, %23, %24, %25, %26, %27, %28, %29, %30, %31}, {%32,%33,%34,%35}, %36, p, 1, 1, %38;\n}\n"
    : "+f"(d[0]), "+f"(d[1]), "+f"(d[2]), "+f"(d[3]), "+f"(d[4]), "+f"(d[5]), "+f"(d[6]), "+f"(d[7]),
      "+f"(d[8]), "+f"(d[9]), "+f"(d[10]), "+f"(d[11]), "+f"(d[12]), "+f"(d[13]), "+f"(d[14]), "+f"(d[15]),
      "+f"(d[16]), "+f"(d[17]), "+f"(d[18]), "+f"(d[19]), "+f"(d[20]), "+f"(d[21]), "+f"(d[22]), "+f"(d[23]),
      "+f"(d[24]), "+f"(d[25]), "+f"(d[26]), "+f"(d[27]), "+f"(d[28]), "+f"(d[29]), "+f"(d[30]), "+f"(d[31])
    : "r"(a0), "r"(a1), "r"(a2), "r"(a3), "l"(db), "r"(sc), "n"(TB));
}
template <int TA, int TB>
__device__ __forceinline__ void wgmma_n128_ss(float (&d)[64], uint64_t da, uint64_t db, int sc) {
  asm volatile("{\n.reg .pred p;\nsetp.ne.b32 p, %66, 0;\n"
    "wgmma.mma_async.sync.aligned.m64n128k16.f32.bf16.bf16 {%0, %1, %2, %3, %4, %5, %6, %7, %8, %9, %10, %11, %12, %13, %14, %15, %16, %17, %18, %19, %20, %21, %22, %23, %24, %25, %26, %27, %28, %29, %30, %31, %32, %33, %34, %35, %36, %37, %38, %39, %40, %41, %42, %43, %44, %45, %46, %47, %48, %49, %50, %51, %52, %53, %54, %55, %56, %57, %58, %59, %60, %61, %62, %63}, %64, %65, p, 1, 1, %67, %68;\n}\n"
    : "+f"(d[0]), "+f"(d[1]), "+f"(d[2]), "+f"(d[3]), "+f"(d[4]), "+f"(d[5]), "+f"(d[6]), "+f"(d[7]),
      "+f"(d[8]), "+f"(d[9]), "+f"(d[10]), "+f"(d[11]), "+f"(d[12]), "+f"(d[13]), "+f"(d[14]), "+f"(d[15]),
      "+f"(d[16]), "+f"(d[17]), "+f"(d[18]), "+f"(d[19]), "+f"(d[20]), "+f"(d[21]), "+f"(d[22]), "+f"(d[23]),
      "+f"(d[24]), "+f"(d[25]), "+f"(d[26]), "+f"(d[27]), "+f"(d[28]), "+f"(d[29]), "+f"(d[30]), "+f"(d[31]),
      "+f"(d[32]), "+f"(d[33]), "+f"(d[34]), "+f"(d[35]), "+f"(d[36]), "+f"(d[37]), "+f"(d[38]), "+f"(d[39]),
      "+f"(d[40]), "+f"(d[41]), "+f"(d[42]), "+f"(d[43]), "+f"(d[44]), "+f"(d[45]), "+f"(d[46]), "+f"(d[47]),
      "+f"(d[48]), "+f"(d[49]), "+f"(d[50]), "+f"(d[51]), "+f"(d[52]), "+f"(d[53]), "+f"(d[54]), "+f"(d[55]),
      "+f"(d[56]), "+f"(d[57]), "+f"(d[58]), "+f"(d[59]), "+f"(d[60]), "+f"(d[61]), "+f"(d[62]), "+f"(d[63])
    : "l"(da), "l"(db), "r"(sc), "n"(TA), "n"(TB));
}
template <int TB>
__device__ __forceinline__ void wgmma_n128_rs(float (&d)[64], uint32_t a0, uint32_t a1, uint32_t a2, uint32_t a3, uint64_t db, int sc) {
  asm volatile("{\n.reg .pred p;\nsetp.ne.b32 p, %69, 0;\n"
    "wgmma.mma_async.sync.aligned.m64n128k16.f32.bf16.bf16 {%0, %1, %2, %3, %4, %5, %6, %7, %8, %9, %10, %11, %12, %13, %14, %15, %16, %17, %18, %19, %20, %21, %22, %23, %24, %25, %26, %27, %28, %29, %30, %31, %32, %33, %34, %35, %36, %37, %38, %39, %40, %41, %42, %43, %44, %45, %46, %47, %48, %49, %50, %51, %52, %53, %54, %55, %56, %57, %58, %59, %60, %61, %62, %63}, {%64,%65,%66,%67}, %68, p, 1, 1, %70;\n}\n"
    : "+f"(d[0]), "+f"(d[1]), "+f"(d[2]), "+f"(d[3]), "+f"(d[4]), "+f"(d[5]), "+f"(d[6]), "+f"(d[7]),
      "+f"(d[8]), "+f"(d[9]), "+f"(d[10]), "+f"(d[11]), "+f"(d[12]), "+f"(d[13]), "+f"(d[14]), "+f"(d[15]),
      "+f"(d[16]), "+f"(d[17]), "+f"(d[18]), "+f"(d[19]), "+f"(d[20]), "+f"(d[21]), "+f"(d[22]), "+f"(d[23]),
      "+f"(d[24]), "+f"(d[25]), "+f"(d[26]), "+f"(d[27]), "+f"(d[28]), "+f"(d[29]), "+f"(d[30]), "+f"(d[31]),
      "+f"(d[32]), "+f"(d[33]), "+f"(d[34]), "+f"(d[35]), "+f"(d[36]), "+f"(d[37]), "+f"(d[38]), "+f"(d[39]),
      "+f"(d[40]), "+f"(d[41]), "+f"(d[42]), "+f"(d[43]), "+f"(d[44]), "+f"(d[45]), "+f"(d[46]), "+f"(d[47]),
      "+f"(d[48]), "+f"(d[49]), "+f"(d[50]), "+f"(d[51]), "+f"(d[52]), "+f"(d[53]), "+f"(d[54]), "+f"(d[55]),
      "+f"(d[56]), "+f"(d[57]), "+f"(d[58]), "+f"(d[59]), "+f"(d[60]), "+f"(d[61]), "+f"(d[62]), "+f"(d[63])
    : "r"(a0), "r"(a1), "r"(a2), "r"(a3), "l"(db), "r"(sc), "n"(TB));
}

__device__ __forceinline__ void poll1(uint32_t (&v)[1], const void* p, uint32_t tag, uint32_t mask) {
  asm volatile("{\n.reg .pred p, q;\n.reg .u32 c, b;\n.reg .b64 x, y;\n.reg .b128 z;\nmov.u32 c, 0;\nLW:\n"
               "ld.relaxed.gpu.global.u32 %0, [%1+0];\n"
               "xor.b32 b, %0, %2;\n"
               "and.b32 b, b, %3;\nsetp.eq.u32 p, b, 0;\nvote.sync.all.pred p, p, 0xffffffff;\n@p bra.uni LD;\n"
               "nanosleep.u32 100;\nadd.u32 c, c, 1;\nsetp.lt.u32 q, c, 1000000;\n@q bra.uni LW;\ntrap;\nLD:\n}"
               : "=&r"(v[0])
               : "l"(p), "r"(tag), "r"(mask) : "memory");
}
__device__ __forceinline__ void poll1f(uint32_t (&v)[1], const void* p, uint32_t tag, uint32_t mask) {
  asm volatile("{\n.reg .pred p, q;\n.reg .u32 c, b;\n.reg .b64 x, y;\n.reg .b128 z;\nmov.u32 c, 0;\nLW:\n"
               "ld.relaxed.gpu.global.u32 %0, [%1+0];\n"
               "xor.b32 b, %0, %2;\n"
               "and.b32 b, b, %3;\nsetp.eq.u32 p, b, 0;\nvote.sync.all.pred p, p, 0xffffffff;\n@p bra.uni LD;\n"
               "nanosleep.u32 50;\nadd.u32 c, c, 1;\nsetp.lt.u32 q, c, 1000000;\n@q bra.uni LW;\ntrap;\nLD:\n}"
               : "=&r"(v[0])
               : "l"(p), "r"(tag), "r"(mask) : "memory");
}
__device__ __forceinline__ void poll0(uint32_t (&v)[1], const void* p, uint32_t tag, uint32_t mask) {
  asm volatile("{\n.reg .pred p, q;\n.reg .u32 c, b;\n.reg .b64 x, y;\n.reg .b128 z;\nmov.u32 c, 0;\nLW:\n"
               "ld.relaxed.gpu.global.u32 %0, [%1+0];\n"
               "xor.b32 b, %0, %2;\n"
               "and.b32 b, b, %3;\nsetp.eq.u32 p, b, 0;\nvote.sync.all.pred p, p, 0xffffffff;\n@p bra.uni LD;\n"
               "add.u32 c, c, 1;\nsetp.lt.u32 q, c, 1000000;\n@q bra.uni LW;\ntrap;\nLD:\n}"
               : "=&r"(v[0])
               : "l"(p), "r"(tag), "r"(mask) : "memory");
}
__device__ __forceinline__ void poll_pair(uint32_t (&v)[2], const void* p, uint32_t tag, uint32_t mask) {
  asm volatile("{\n.reg .pred p, q;\n.reg .u32 c, b;\n.reg .b64 x, y;\n.reg .b128 z;\nmov.u32 c, 0;\nLW:\n"
               "ld.relaxed.gpu.global.b64 x, [%2+0];\nmov.b64 {%0,%1}, x;\n"
               "xor.b32 b, %0, %3;\n"
               "and.b32 b, b, %4;\nsetp.eq.u32 p, b, 0;\nvote.sync.all.pred p, p, 0xffffffff;\n@p bra.uni LD;\n"
               "nanosleep.u32 100;\nadd.u32 c, c, 1;\nsetp.lt.u32 q, c, 1000000;\n@q bra.uni LW;\ntrap;\nLD:\n}"
               : "=&r"(v[0]), "=&r"(v[1])
               : "l"(p), "r"(tag), "r"(mask) : "memory");
}
__device__ __forceinline__ void poll_quad(uint32_t (&v)[4], const void* p, uint32_t tag, uint32_t mask) {
  asm volatile("{\n.reg .pred p, q;\n.reg .u32 c, b;\n.reg .b64 x, y;\n.reg .b128 z;\nmov.u32 c, 0;\nLW:\n"
               "ld.relaxed.gpu.global.v4.u32 {%0,%1,%2,%3}, [%4+0];\n"
               "xor.b32 b, %0, %5;\n"
               "lop3.b32 b, b, %1, %5, 0xf6;\nlop3.b32 b, b, %2, %5, 0xf6;\nlop3.b32 b, b, %3, %5, 0xf6;\n"
               "and.b32 b, b, %6;\nsetp.eq.u32 p, b, 0;\nvote.sync.all.pred p, p, 0xffffffff;\n@p bra.uni LD;\n"
               "nanosleep.u32 200;\nadd.u32 c, c, 1;\nsetp.lt.u32 q, c, 1000000;\n@q bra.uni LW;\ntrap;\nLD:\n}"
               : "=&r"(v[0]), "=&r"(v[1]), "=&r"(v[2]), "=&r"(v[3])
               : "l"(p), "r"(tag), "r"(mask) : "memory");
}
__device__ __forceinline__ void poll8(uint32_t (&v)[8], const void* p, uint32_t tag, uint32_t mask) {
  asm volatile("{\n.reg .pred p, q;\n.reg .u32 c, b;\n.reg .b64 x, y;\n.reg .b128 z;\nmov.u32 c, 0;\nLW:\n"
               "ld.relaxed.gpu.global.u32 %0, [%8+0];\n"
               "ld.relaxed.gpu.global.u32 %1, [%8+2048];\n"
               "ld.relaxed.gpu.global.u32 %2, [%8+4096];\n"
               "ld.relaxed.gpu.global.u32 %3, [%8+6144];\n"
               "ld.relaxed.gpu.global.u32 %4, [%8+8192];\n"
               "ld.relaxed.gpu.global.u32 %5, [%8+10240];\n"
               "ld.relaxed.gpu.global.u32 %6, [%8+12288];\n"
               "ld.relaxed.gpu.global.u32 %7, [%8+14336];\n"
               "xor.b32 b, %0, %9;\n"
               "lop3.b32 b, b, %1, %9, 0xf6;\nlop3.b32 b, b, %2, %9, 0xf6;\nlop3.b32 b, b, %3, %9, 0xf6;\nlop3.b32 b, b, %4, %9, 0xf6;\n"
               "lop3.b32 b, b, %5, %9, 0xf6;\nlop3.b32 b, b, %6, %9, 0xf6;\nlop3.b32 b, b, %7, %9, 0xf6;\n"
               "and.b32 b, b, %10;\nsetp.eq.u32 p, b, 0;\nvote.sync.all.pred p, p, 0xffffffff;\n@p bra.uni LD;\n"
               "nanosleep.u32 50;\nadd.u32 c, c, 1;\nsetp.lt.u32 q, c, 1000000;\n@q bra.uni LW;\ntrap;\nLD:\n}"
               : "=&r"(v[0]), "=&r"(v[1]), "=&r"(v[2]), "=&r"(v[3]), "=&r"(v[4]), "=&r"(v[5]), "=&r"(v[6]), "=&r"(v[7])
               : "l"(p), "r"(tag), "r"(mask) : "memory");
}
__device__ __forceinline__ void poll16(uint32_t (&v)[16], const void* p, uint32_t tag, uint32_t mask) {
  asm volatile("{\n.reg .pred p, q;\n.reg .u32 c, b;\n.reg .b64 x, y;\n.reg .b128 z;\nmov.u32 c, 0;\nLW:\n"
               "ld.relaxed.gpu.global.u32 %0, [%16+0];\n"
               "ld.relaxed.gpu.global.u32 %1, [%16+4096];\n"
               "ld.relaxed.gpu.global.u32 %2, [%16+8192];\n"
               "ld.relaxed.gpu.global.u32 %3, [%16+12288];\n"
               "ld.relaxed.gpu.global.u32 %4, [%16+16384];\n"
               "ld.relaxed.gpu.global.u32 %5, [%16+20480];\n"
               "ld.relaxed.gpu.global.u32 %6, [%16+24576];\n"
               "ld.relaxed.gpu.global.u32 %7, [%16+28672];\n"
               "ld.relaxed.gpu.global.u32 %8, [%16+32768];\n"
               "ld.relaxed.gpu.global.u32 %9, [%16+36864];\n"
               "ld.relaxed.gpu.global.u32 %10, [%16+40960];\n"
               "ld.relaxed.gpu.global.u32 %11, [%16+45056];\n"
               "ld.relaxed.gpu.global.u32 %12, [%16+49152];\n"
               "ld.relaxed.gpu.global.u32 %13, [%16+53248];\n"
               "ld.relaxed.gpu.global.u32 %14, [%16+57344];\n"
               "ld.relaxed.gpu.global.u32 %15, [%16+61440];\n"
               "xor.b32 b, %0, %17;\n"
               "lop3.b32 b, b, %1, %17, 0xf6;\nlop3.b32 b, b, %2, %17, 0xf6;\nlop3.b32 b, b, %3, %17, 0xf6;\nlop3.b32 b, b, %4, %17, 0xf6;\n"
               "lop3.b32 b, b, %5, %17, 0xf6;\nlop3.b32 b, b, %6, %17, 0xf6;\nlop3.b32 b, b, %7, %17, 0xf6;\nlop3.b32 b, b, %8, %17, 0xf6;\n"
               "lop3.b32 b, b, %9, %17, 0xf6;\nlop3.b32 b, b, %10, %17, 0xf6;\nlop3.b32 b, b, %11, %17, 0xf6;\nlop3.b32 b, b, %12, %17, 0xf6;\n"
               "lop3.b32 b, b, %13, %17, 0xf6;\nlop3.b32 b, b, %14, %17, 0xf6;\nlop3.b32 b, b, %15, %17, 0xf6;\n"
               "and.b32 b, b, %18;\nsetp.eq.u32 p, b, 0;\nvote.sync.all.pred p, p, 0xffffffff;\n@p bra.uni LD;\n"
               "nanosleep.u32 200;\nadd.u32 c, c, 1;\nsetp.lt.u32 q, c, 1000000;\n@q bra.uni LW;\ntrap;\nLD:\n}"
               : "=&r"(v[0]), "=&r"(v[1]), "=&r"(v[2]), "=&r"(v[3]), "=&r"(v[4]), "=&r"(v[5]), "=&r"(v[6]), "=&r"(v[7]), "=&r"(v[8]), "=&r"(v[9]), "=&r"(v[10]), "=&r"(v[11]), "=&r"(v[12]), "=&r"(v[13]), "=&r"(v[14]), "=&r"(v[15])
               : "l"(p), "r"(tag), "r"(mask) : "memory");
}
__device__ __forceinline__ void poll_keys(uint32_t (&v)[16], const void* p, uint32_t tag, uint32_t mask) {
  asm volatile("{\n.reg .pred p, q;\n.reg .u32 c, b;\n.reg .b64 x, y;\n.reg .b128 z;\nmov.u32 c, 0;\nLW:\n"
               "ld.relaxed.gpu.global.v2.b64 {x, y}, [%16+0];\nmov.b64 {%0,%1}, x;\nmov.b64 {%2,%3}, y;\n"
               "ld.relaxed.gpu.global.v2.b64 {x, y}, [%16+4096];\nmov.b64 {%4,%5}, x;\nmov.b64 {%6,%7}, y;\n"
               "ld.relaxed.gpu.global.v2.b64 {x, y}, [%16+8192];\nmov.b64 {%8,%9}, x;\nmov.b64 {%10,%11}, y;\n"
               "ld.relaxed.gpu.global.v2.b64 {x, y}, [%16+12288];\nmov.b64 {%12,%13}, x;\nmov.b64 {%14,%15}, y;\n"
               "xor.b32 b, %0, %17;\n"
               "lop3.b32 b, b, %2, %17, 0xf6;\nlop3.b32 b, b, %4, %17, 0xf6;\nlop3.b32 b, b, %6, %17, 0xf6;\nlop3.b32 b, b, %8, %17, 0xf6;\n"
               "lop3.b32 b, b, %10, %17, 0xf6;\nlop3.b32 b, b, %12, %17, 0xf6;\nlop3.b32 b, b, %14, %17, 0xf6;\n"
               "and.b32 b, b, %18;\nsetp.eq.u32 p, b, 0;\nvote.sync.all.pred p, p, 0xffffffff;\n@p bra.uni LD;\n"
               "nanosleep.u32 20;\nadd.u32 c, c, 1;\nsetp.lt.u32 q, c, 1000000;\n@q bra.uni LW;\ntrap;\nLD:\n}"
               : "=&r"(v[0]), "=&r"(v[1]), "=&r"(v[2]), "=&r"(v[3]), "=&r"(v[4]), "=&r"(v[5]), "=&r"(v[6]), "=&r"(v[7]), "=&r"(v[8]), "=&r"(v[9]), "=&r"(v[10]), "=&r"(v[11]), "=&r"(v[12]), "=&r"(v[13]), "=&r"(v[14]), "=&r"(v[15])
               : "l"(p), "r"(tag), "r"(mask) : "memory");
}
__device__ __forceinline__ void poll_z(uint32_t (&v)[16], const void* p, uint32_t tag, uint32_t mask) {
  asm volatile("{\n.reg .pred p, q;\n.reg .u32 c, b;\n.reg .b64 x, y;\n.reg .b128 z;\nmov.u32 c, 0;\nLW:\n"
               "ld.relaxed.gpu.global.v4.u32 {%0,%1,%2,%3}, [%16+0];\n"
               "ld.relaxed.gpu.global.v4.u32 {%4,%5,%6,%7}, [%16+4096];\n"
               "ld.relaxed.gpu.global.v4.u32 {%8,%9,%10,%11}, [%16+8192];\n"
               "ld.relaxed.gpu.global.v4.u32 {%12,%13,%14,%15}, [%16+12288];\n"
               "xor.b32 b, %0, %17;\n"
               "lop3.b32 b, b, %1, %17, 0xf6;\nlop3.b32 b, b, %2, %17, 0xf6;\nlop3.b32 b, b, %3, %17, 0xf6;\nlop3.b32 b, b, %4, %17, 0xf6;\n"
               "lop3.b32 b, b, %5, %17, 0xf6;\nlop3.b32 b, b, %6, %17, 0xf6;\nlop3.b32 b, b, %7, %17, 0xf6;\nlop3.b32 b, b, %8, %17, 0xf6;\n"
               "lop3.b32 b, b, %9, %17, 0xf6;\nlop3.b32 b, b, %10, %17, 0xf6;\nlop3.b32 b, b, %11, %17, 0xf6;\nlop3.b32 b, b, %12, %17, 0xf6;\n"
               "lop3.b32 b, b, %13, %17, 0xf6;\nlop3.b32 b, b, %14, %17, 0xf6;\nlop3.b32 b, b, %15, %17, 0xf6;\n"
               "and.b32 b, b, %18;\nsetp.eq.u32 p, b, 0;\nvote.sync.all.pred p, p, 0xffffffff;\n@p bra.uni LD;\n"
               "nanosleep.u32 300;\nadd.u32 c, c, 1;\nsetp.lt.u32 q, c, 1000000;\n@q bra.uni LW;\ntrap;\nLD:\n}"
               : "=&r"(v[0]), "=&r"(v[1]), "=&r"(v[2]), "=&r"(v[3]), "=&r"(v[4]), "=&r"(v[5]), "=&r"(v[6]), "=&r"(v[7]), "=&r"(v[8]), "=&r"(v[9]), "=&r"(v[10]), "=&r"(v[11]), "=&r"(v[12]), "=&r"(v[13]), "=&r"(v[14]), "=&r"(v[15])
               : "l"(p), "r"(tag), "r"(mask) : "memory");
}
__device__ __forceinline__ void poll7x4(uint32_t (&v)[28], const void* p, uint32_t tag, uint32_t mask) {
  asm volatile("{\n.reg .pred p, q;\n.reg .u32 c, b;\n.reg .b64 x, y;\n.reg .b128 z;\nmov.u32 c, 0;\nLW:\n"
               "ld.relaxed.gpu.global.v4.u32 {%0,%1,%2,%3}, [%28+0];\n"
               "ld.relaxed.gpu.global.v4.u32 {%4,%5,%6,%7}, [%28+2048];\n"
               "ld.relaxed.gpu.global.v4.u32 {%8,%9,%10,%11}, [%28+4096];\n"
               "ld.relaxed.gpu.global.v4.u32 {%12,%13,%14,%15}, [%28+6144];\n"
               "ld.relaxed.gpu.global.v4.u32 {%16,%17,%18,%19}, [%28+8192];\n"
               "ld.relaxed.gpu.global.v4.u32 {%20,%21,%22,%23}, [%28+10240];\n"
               "ld.relaxed.gpu.global.v4.u32 {%24,%25,%26,%27}, [%28+12288];\n"
               "xor.b32 b, %0, %29;\n"
               "lop3.b32 b, b, %1, %29, 0xf6;\nlop3.b32 b, b, %2, %29, 0xf6;\nlop3.b32 b, b, %3, %29, 0xf6;\nlop3.b32 b, b, %4, %29, 0xf6;\n"
               "lop3.b32 b, b, %5, %29, 0xf6;\nlop3.b32 b, b, %6, %29, 0xf6;\nlop3.b32 b, b, %7, %29, 0xf6;\nlop3.b32 b, b, %8, %29, 0xf6;\n"
               "lop3.b32 b, b, %9, %29, 0xf6;\nlop3.b32 b, b, %10, %29, 0xf6;\nlop3.b32 b, b, %11, %29, 0xf6;\nlop3.b32 b, b, %12, %29, 0xf6;\n"
               "lop3.b32 b, b, %13, %29, 0xf6;\nlop3.b32 b, b, %14, %29, 0xf6;\nlop3.b32 b, b, %15, %29, 0xf6;\nlop3.b32 b, b, %16, %29, 0xf6;\n"
               "lop3.b32 b, b, %17, %29, 0xf6;\nlop3.b32 b, b, %18, %29, 0xf6;\nlop3.b32 b, b, %19, %29, 0xf6;\nlop3.b32 b, b, %20, %29, 0xf6;\n"
               "lop3.b32 b, b, %21, %29, 0xf6;\nlop3.b32 b, b, %22, %29, 0xf6;\nlop3.b32 b, b, %23, %29, 0xf6;\nlop3.b32 b, b, %24, %29, 0xf6;\n"
               "lop3.b32 b, b, %25, %29, 0xf6;\nlop3.b32 b, b, %26, %29, 0xf6;\nlop3.b32 b, b, %27, %29, 0xf6;\n"
               "and.b32 b, b, %30;\nsetp.eq.u32 p, b, 0;\nvote.sync.all.pred p, p, 0xffffffff;\n@p bra.uni LD;\n"
               "nanosleep.u32 50;\nadd.u32 c, c, 1;\nsetp.lt.u32 q, c, 1000000;\n@q bra.uni LW;\ntrap;\nLD:\n}"
               : "=&r"(v[0]), "=&r"(v[1]), "=&r"(v[2]), "=&r"(v[3]), "=&r"(v[4]), "=&r"(v[5]), "=&r"(v[6]), "=&r"(v[7]), "=&r"(v[8]), "=&r"(v[9]), "=&r"(v[10]), "=&r"(v[11]), "=&r"(v[12]), "=&r"(v[13]), "=&r"(v[14]), "=&r"(v[15]), "=&r"(v[16]), "=&r"(v[17]), "=&r"(v[18]), "=&r"(v[19]), "=&r"(v[20]), "=&r"(v[21]), "=&r"(v[22]), "=&r"(v[23]), "=&r"(v[24]), "=&r"(v[25]), "=&r"(v[26]), "=&r"(v[27])
               : "l"(p), "r"(tag), "r"(mask) : "memory");
}
__device__ __forceinline__ void poll_kvp(uint32_t (&v)[16], const void* p, uint32_t tag, uint32_t mask) {
  asm volatile("{\n.reg .pred p, q;\n.reg .u32 c, b;\n.reg .b64 x, y;\n.reg .b128 z;\nmov.u32 c, 0;\nLW:\n"
               "ld.relaxed.gpu.global.b128 z, [%16+0];\nmov.b128 {x, y}, z;\nmov.b64 {%0,%1}, x;\nmov.b64 {%2,%3}, y;\n"
               "ld.relaxed.gpu.global.b128 z, [%16+8192];\nmov.b128 {x, y}, z;\nmov.b64 {%4,%5}, x;\nmov.b64 {%6,%7}, y;\n"
               "ld.relaxed.gpu.global.b128 z, [%16+16384];\nmov.b128 {x, y}, z;\nmov.b64 {%8,%9}, x;\nmov.b64 {%10,%11}, y;\n"
               "ld.relaxed.gpu.global.b128 z, [%16+24576];\nmov.b128 {x, y}, z;\nmov.b64 {%12,%13}, x;\nmov.b64 {%14,%15}, y;\n"
               "xor.b32 b, %0, %17;\n"
               "lop3.b32 b, b, %4, %17, 0xf6;\nlop3.b32 b, b, %8, %17, 0xf6;\nlop3.b32 b, b, %12, %17, 0xf6;\n"
               "and.b32 b, b, %18;\nsetp.eq.u32 p, b, 0;\nvote.sync.all.pred p, p, 0xffffffff;\n@p bra.uni LD;\n"
               "nanosleep.u32 50;\nadd.u32 c, c, 1;\nsetp.lt.u32 q, c, 1000000;\n@q bra.uni LW;\ntrap;\nLD:\n}"
               : "=&r"(v[0]), "=&r"(v[1]), "=&r"(v[2]), "=&r"(v[3]), "=&r"(v[4]), "=&r"(v[5]), "=&r"(v[6]), "=&r"(v[7]), "=&r"(v[8]), "=&r"(v[9]), "=&r"(v[10]), "=&r"(v[11]), "=&r"(v[12]), "=&r"(v[13]), "=&r"(v[14]), "=&r"(v[15])
               : "l"(p), "r"(tag), "r"(mask) : "memory");
}
__device__ __forceinline__ void poll_kv(uint32_t (&v)[16], const void* p, uint32_t tag, uint32_t mask) {
  asm volatile("{\n.reg .pred p, q;\n.reg .u32 c, b;\n.reg .b64 x, y;\n.reg .b128 z;\nmov.u32 c, 0;\nLW:\n"
               "ld.relaxed.gpu.global.b128 z, [%16+0];\nmov.b128 {x, y}, z;\nmov.b64 {%0,%1}, x;\nmov.b64 {%2,%3}, y;\n"
               "ld.relaxed.gpu.global.b128 z, [%16+2048];\nmov.b128 {x, y}, z;\nmov.b64 {%4,%5}, x;\nmov.b64 {%6,%7}, y;\n"
               "ld.relaxed.gpu.global.b128 z, [%16+4096];\nmov.b128 {x, y}, z;\nmov.b64 {%8,%9}, x;\nmov.b64 {%10,%11}, y;\n"
               "ld.relaxed.gpu.global.b128 z, [%16+6144];\nmov.b128 {x, y}, z;\nmov.b64 {%12,%13}, x;\nmov.b64 {%14,%15}, y;\n"
               "xor.b32 b, %0, %17;\n"
               "lop3.b32 b, b, %4, %17, 0xf6;\nlop3.b32 b, b, %8, %17, 0xf6;\nlop3.b32 b, b, %12, %17, 0xf6;\n"
               "and.b32 b, b, %18;\nsetp.eq.u32 p, b, 0;\nvote.sync.all.pred p, p, 0xffffffff;\n@p bra.uni LD;\n"
               "nanosleep.u32 50;\nadd.u32 c, c, 1;\nsetp.lt.u32 q, c, 1000000;\n@q bra.uni LW;\ntrap;\nLD:\n}"
               : "=&r"(v[0]), "=&r"(v[1]), "=&r"(v[2]), "=&r"(v[3]), "=&r"(v[4]), "=&r"(v[5]), "=&r"(v[6]), "=&r"(v[7]), "=&r"(v[8]), "=&r"(v[9]), "=&r"(v[10]), "=&r"(v[11]), "=&r"(v[12]), "=&r"(v[13]), "=&r"(v[14]), "=&r"(v[15])
               : "l"(p), "r"(tag), "r"(mask) : "memory");
}

__device__ __align__(1024) __nv_bfloat16 g_o[2048 * 1024];
__device__ __align__(128) uint2 g_keys[2048];
__device__ __align__(128) uint32_t g_csum[18 * 1024];
__device__ __align__(128) uint32_t g_z[16 * 1024];
__device__ __align__(128) uint4 g_kvp[128 * 512];
__device__ __align__(128) uint4 g_kv[8 * 512];
__device__ __align__(128) uint32_t g_h[112 * 256];
__device__ __align__(128) uint32_t g_yp[128 * 512];
__device__ __align__(128) uint32_t g_xsel[4096 + 32];
enum { H_CS = 0, H_KVP = 8, H_KV = 16, H_H = 24, H_Y = 32, H_O = 40, H_R = 56 };
__device__ __align__(128) uint32_t g_sig[57 * 32];
__device__ uint32_t g_epoch;

constexpr uint32_t RING = 1024, SLOT = 32768, SMEM_BYTES = 232448;
constexpr int NST = 5, HST = 7;
constexpr uint32_t STG = RING + 163840, AUX = RING + 196608, FR = RING + 212992, MISC = RING + 229376;
constexpr uint32_t B_FULL = MISC, B_EMPTY = MISC + 56, B_XS = MISC + 112, B_SEL = MISC + 144, B_XRES = MISC + 152, B_WK = MISC + 160, B_CSDN = MISC + 168,
                   B_FR = MISC + 176, B_FE = MISC + 216, B_DR = MISC + 256, B_DE = MISC + 288, B_CSV = MISC + 320, NBAR = 41;
constexpr uint32_t S_EPOCH = MISC + 352, S_NCAND = MISC + 356, S_SEL = MISC + 368, S_WMAX = MISC + 400,
                   S_KSTAT = MISC + 512, S_CSK = MISC + 1536, S_CSV = MISC + 2048, S_CSQ = MISC + 2560, S_ONES = MISC + 512;
constexpr uint32_t KVB_P0 = AUX, KVB_Z = AUX + 4096, KVB_P1 = AUX + 5120, HOP = AUX + 9216, GR = FR - 4096;
enum { NB_Z = 0, NB_KV = 1, NB_VQ = 2, NB_WG0 = 3, NB_FDONE = 4, NB_PK = 5, NB_KVB = 6, NB_WG1 = 7, NB_WG2 = 8, NB_CSQ = 9,
       NB_Y = 10, NB_ST = 11, NB_OWN0 = 12, NB_OWN1 = 13, NB_Q0 = 14, NB_H1 = 15 };

#define XS_AT 0
#define XS_FLY 2
#define H_DELAY 500
#define PFD 6
#define FFN_GAP 400
constexpr uint64_t EVICT_FIRST = 0x12f0000000000000ull;
constexpr float LOG2E = 1.4426950408889634f, LN2 = 0.6931471805599453f;

#define ELECT "{\n.reg .pred p;\nelect.sync _|p, 0xffffffff;\n"
#define TMA2D "cp.async.bulk.tensor.2d.shared::cluster.global.mbarrier::complete_tx::bytes"
#define TMA3D "cp.async.bulk.tensor.3d.shared::cluster.global.mbarrier::complete_tx::bytes"
__device__ __forceinline__ void e_expect(uint32_t b, uint32_t n) {
  asm volatile(ELECT "@p mbarrier.arrive.expect_tx.shared::cta.b64 _, [%0], %1;\n}" ::"r"(b), "r"(n) : "memory");
}
__device__ __forceinline__ void e_arrive(uint32_t b) { asm volatile(ELECT "@p mbarrier.arrive.shared::cta.b64 _, [%0];\n}" ::"r"(b) : "memory"); }
__device__ __forceinline__ void e_tma2d(uint32_t dst, const CUtensorMap* m, int c0, int c1, uint32_t bar) {
  asm volatile(ELECT "@p " TMA2D " [%0], [%1, {%3, %4}], [%2];\n}" ::"r"(dst), "l"(m), "r"(bar), "r"(c0), "r"(c1) : "memory");
}
__device__ __forceinline__ void e_tma2d_ef(uint32_t dst, const CUtensorMap* m, int c0, int c1, uint32_t bar, uint64_t pol) {
  asm volatile(ELECT "@p " TMA2D ".L2::cache_hint [%0], [%1, {%3, %4}], [%2], %5;\n}" ::"r"(dst), "l"(m), "r"(bar), "r"(c0), "r"(c1), "l"(pol) : "memory");
}
__device__ __forceinline__ void e_tma3d(uint32_t dst, const CUtensorMap* m, int c1, int c2, uint32_t bar) {
  asm volatile(ELECT "@p " TMA3D " [%0], [%1, {0, %3, %4}], [%2];\n}" ::"r"(dst), "l"(m), "r"(bar), "r"(c1), "r"(c2) : "memory");
}
__device__ __forceinline__ void e_store2d(const CUtensorMap* m, int c0, int c1, uint32_t src) {
  asm volatile(ELECT "@p cp.async.bulk.tensor.2d.global.shared::cta.bulk_group [%0, {%2, %3}], [%1];\n}" ::"l"(m), "r"(src), "r"(c0), "r"(c1) : "memory");
}
__device__ __forceinline__ void e_tma3d_ef(uint32_t dst, const CUtensorMap* m, int c0, int c1, uint32_t bar, uint64_t pol) {
  asm volatile(ELECT "@p " TMA3D ".L2::cache_hint [%0], [%1, {%3, %4, 0}], [%2], %5;\n}" ::"r"(dst), "l"(m), "r"(bar), "r"(c0), "r"(c1), "l"(pol) : "memory");
}
__device__ __forceinline__ void e_load(uint32_t dst, const void* src, uint32_t n, uint32_t bar) {
  asm volatile(ELECT "@p cp.async.bulk.shared::cluster.global.mbarrier::complete_tx::bytes [%0], [%1], %2, [%3];\n}" ::"r"(dst), "l"(src), "r"(n), "r"(bar) : "memory");
}
__device__ __forceinline__ void e_pfmap(const CUtensorMap* m) { asm volatile(ELECT "@p prefetch.tensormap [%0];\n}" ::"l"(m) : "memory"); }
__device__ __forceinline__ void bulk_wait_read() { asm volatile("cp.async.bulk.commit_group;\ncp.async.bulk.wait_group.read 0;" ::: "memory"); }
__device__ __forceinline__ void e_signal(int word, int bit) {
  asm volatile(ELECT "@p red.relaxed.gpu.global.xor.b32 [%0], %1;\n}" ::"l"(g_sig + word * 32), "r"(1u << bit) : "memory");
}
__device__ __forceinline__ void e_release(int word, int bit) {
  asm volatile("cp.async.bulk.commit_group;\ncp.async.bulk.wait_group 0;\nfence.release.gpu;" ::: "memory");
  e_signal(word, bit);
}
__device__ __forceinline__ void await(int word, uint32_t mask, uint32_t ep) {
  uint32_t f[1];
  poll1f(f, g_sig + word * 32, 0u - (ep & 1u), mask);
}

__device__ __forceinline__ void mbar_arrive(uint32_t b) { asm volatile("mbarrier.arrive.shared::cta.b64 _, [%0];" ::"r"(b) : "memory"); }
__device__ __forceinline__ void mbar_wait(uint32_t b, uint32_t ph) {
  asm volatile("{\n.reg .pred p, q;\n.reg .u32 c;\nmov.u32 c, 0;\nLW:\nmbarrier.try_wait.parity.shared::cta.b64 p, [%0], %1;\n@p bra LD;\n"
               "add.u32 c, c, 1;\nsetp.lt.u32 q, c, 100000;\n@q bra LW;\ntrap;\nLD:\n}" ::"r"(b), "r"(ph) : "memory");
}
__device__ __forceinline__ void nb_sync(int id, int n) { asm volatile("bar.sync %0, %1;" ::"r"(id), "r"(n) : "memory"); }
__device__ __forceinline__ void nb_arrive(int id, int n) { asm volatile("bar.arrive %0, %1;" ::"r"(id), "r"(n) : "memory"); }
__device__ __forceinline__ void wg_fence() { asm volatile("wgmma.fence.sync.aligned;" ::: "memory"); }
__device__ __forceinline__ void wg_commit() { asm volatile("wgmma.commit_group.sync.aligned;" ::: "memory"); }
template <int N> __device__ __forceinline__ void wg_wait() { asm volatile("wgmma.wait_group.sync.aligned %0;" ::"n"(N) : "memory"); }
template <int N> __device__ __forceinline__ void reg_fence(float (&a)[N]) {
#pragma unroll
  for (int i = 0; i < N; i++) asm volatile("" : "+f"(a[i])::"memory");
}
template <int N> __device__ __forceinline__ void reg_zero(float (&a)[N]) {
#pragma unroll
  for (int i = 0; i < N; i++) a[i] = 0.f;
}
__device__ __forceinline__ constexpr uint64_t mkdesc(uint32_t addr, uint32_t lbo, uint32_t sbo, uint32_t swz) {
  return (uint64_t)(addr >> 4) | ((uint64_t)(lbo >> 4) << 16) | ((uint64_t)(sbo >> 4) << 32) | ((uint64_t)swz << 62);
}
__device__ __forceinline__ void fence_async_smem() { asm volatile("fence.proxy.async.shared::cta;" ::: "memory"); }
__device__ __forceinline__ void fence_async_glob() { asm volatile("fence.proxy.async.global;" ::: "memory"); }
__device__ __forceinline__ void fence_acq() { asm volatile("fence.acquire.gpu;" ::: "memory"); }
__device__ __forceinline__ void st_relaxed(uint32_t* p, uint32_t v) { asm volatile("st.relaxed.gpu.global.u32 [%0], %1;" ::"l"(p), "r"(v) : "memory"); }
__device__ __forceinline__ uint32_t ld_relaxed(const uint32_t* p) { uint32_t v; asm volatile("ld.relaxed.gpu.global.u32 %0, [%1];" : "=r"(v) : "l"(p) : "memory"); return v; }
__device__ __forceinline__ void st_unit(uint4* p, uint32_t a, uint32_t b, uint32_t c, uint32_t d, uint32_t par) {
  asm volatile("{\n.reg .b64 x, y;\n.reg .b128 z;\nmov.b64 x, {%1,%2};\nmov.b64 y, {%3,%4};\nmov.b128 z, {x, y};\nst.relaxed.gpu.global.b128 [%0], z;\n}"
               ::"l"(p), "r"((a & ~1u) | par), "r"(b), "r"(c), "r"(d) : "memory");
}
__device__ __forceinline__ uint4 lds128(uint32_t a) { uint4 v; asm volatile("ld.shared.v4.u32 {%0,%1,%2,%3}, [%4];" : "=r"(v.x), "=r"(v.y), "=r"(v.z), "=r"(v.w) : "r"(a)); return v; }
__device__ __forceinline__ float4 lds128f(uint32_t a) { float4 v; asm volatile("ld.shared.v4.f32 {%0,%1,%2,%3}, [%4];" : "=f"(v.x), "=f"(v.y), "=f"(v.z), "=f"(v.w) : "r"(a)); return v; }
__device__ __forceinline__ float4 lds128v(uint32_t a) { float4 v; asm volatile("ld.volatile.shared.v4.f32 {%0,%1,%2,%3}, [%4];" : "=f"(v.x), "=f"(v.y), "=f"(v.z), "=f"(v.w) : "r"(a) : "memory"); return v; }
__device__ __forceinline__ float lds32v(uint32_t a) { float v; asm volatile("ld.volatile.shared.f32 %0, [%1];" : "=f"(v) : "r"(a) : "memory"); return v; }
__device__ __forceinline__ float2 lds64f(uint32_t a) { float2 v; asm volatile("ld.shared.v2.f32 {%0,%1}, [%2];" : "=f"(v.x), "=f"(v.y) : "r"(a)); return v; }
__device__ __forceinline__ uint32_t lds32(uint32_t a) { uint32_t v; asm volatile("ld.shared.u32 %0, [%1];" : "=r"(v) : "r"(a)); return v; }
__device__ __forceinline__ void sts128(uint32_t a, uint32_t x, uint32_t y, uint32_t z, uint32_t w) { asm volatile("st.shared.v4.u32 [%0], {%1,%2,%3,%4};" ::"r"(a), "r"(x), "r"(y), "r"(z), "r"(w) : "memory"); }
__device__ __forceinline__ void sts128f(uint32_t a, float x, float y, float z, float w) { asm volatile("st.shared.v4.f32 [%0], {%1,%2,%3,%4};" ::"r"(a), "f"(x), "f"(y), "f"(z), "f"(w) : "memory"); }
__device__ __forceinline__ void sts32(uint32_t a, uint32_t x) { asm volatile("st.shared.u32 [%0], %1;" ::"r"(a), "r"(x) : "memory"); }
__device__ __forceinline__ void stsm4(uint32_t a, uint32_t r0, uint32_t r1, uint32_t r2, uint32_t r3) {
  asm volatile("stmatrix.sync.aligned.m8n8.x4.shared.b16 [%0], {%1,%2,%3,%4};" ::"r"(a), "r"(r0), "r"(r1), "r"(r2), "r"(r3) : "memory");
}
__device__ __forceinline__ uint4 ldsm4(uint32_t a) {
  uint4 v; asm volatile("ldmatrix.sync.aligned.m8n8.x4.shared.b16 {%0,%1,%2,%3}, [%4];" : "=r"(v.x), "=r"(v.y), "=r"(v.z), "=r"(v.w) : "r"(a) : "memory"); return v;
}
__device__ __forceinline__ uint32_t pack(float lo, float hi) { uint32_t r; asm("cvt.rn.bf16x2.f32 %0, %1, %2;" : "=r"(r) : "f"(hi), "f"(lo)); return r; }
__device__ __forceinline__ float bf_lo(uint32_t w) { return __uint_as_float(w << 16); }
__device__ __forceinline__ float bf_hi(uint32_t w) { return __uint_as_float(w & 0xffff0000u); }
__device__ __forceinline__ float bf_round(float x) { return bf_lo(pack(x, x)); }
__device__ __forceinline__ float ex2(float x) { float v; asm("ex2.approx.ftz.f32 %0, %1;" : "=f"(v) : "f"(x)); return v; }
__device__ __forceinline__ float rcp(float x) { float v; asm("rcp.approx.ftz.f32 %0, %1;" : "=f"(v) : "f"(x)); return v; }
__device__ __forceinline__ float addsat(float a, float b) { float v; asm("add.sat.f32 %0, %1, %2;" : "=f"(v) : "f"(a), "f"(b)); return v; }
__device__ __forceinline__ float phi2(float a) { return fmaf(fmaxf(a, 0.f), LN2, addsat(ex2(a), 1e-6f)); }
__device__ __forceinline__ uint32_t ln_bf16x2(uint32_t x, uint32_t m, uint32_t hi, uint32_t lo) {
  uint32_t o;
  asm("{\n.reg .b32 d, e;\nsub.rn.bf16x2 d, %1, %2;\nmul.rn.bf16x2 e, d, %4;\nfma.rn.bf16x2 %0, d, %3, e;\n}" : "=r"(o) : "r"(x), "r"(m), "r"(hi), "r"(lo));
  return o;
}
__device__ __forceinline__ float key_score(uint32_t key) { uint32_t u = key >> 16; u = (u & 0x8000u) ? (u & 0x7fffu) : (~u & 0xffffu); return __uint_as_float(u << 16); }
__device__ __forceinline__ int key_token(uint32_t key) { return 2047 - (int)((key >> 5) & 2047u); }
__device__ __forceinline__ uint32_t tagf(float v, uint32_t par) { return (__float_as_uint(v) & ~1u) | par; }
__device__ __forceinline__ float xred(float a, float b, bool up, int o) { return (up ? b : a) + __shfl_xor_sync(0xffffffffu, up ? a : b, o); }

#define STAMP(id)
#define STAMP_IF(c, id)
#define STAMP2(i)
#define LITE 1

template <bool TRANS>
__device__ __forceinline__ void mainloop(float (&a0)[64], float (&a1)[64], int s, int ph, int handoff, bool leader) {
  uint32_t prev = 0;
#pragma unroll 1
  for (int kt = 0; kt < 16; kt++) {
    mbar_wait(B_FULL + 8 * s, ph);
    const uint64_t dw = mkdesc(RING, 8192, 1024, 1) + s * (SLOT >> 4), dx = mkdesc(RING + 16384, 16, 1024, 1) + s * (SLOT >> 4);
    wg_fence();
#pragma unroll
    for (int j = 0; j < 4; j++) {
      if (TRANS) {
        wgmma_n128_ss<1, 0>(a0, dw + j * 128, dx + j * 2, 1);
        wgmma_n128_ss<1, 0>(a1, dw + j * 128 + 512, dx + j * 2, 1);
      } else {
        wgmma_n128_ss<0, 1>(a0, dx + j * 2, dw + j * 128, 1);
        wgmma_n128_ss<0, 1>(a1, dx + j * 2 + 512, dw + j * 128, 1);
      }
    }
    wg_commit();
    if (handoff && kt == 15) nb_arrive(handoff, 256);
    wg_wait<1>();
    if (prev && leader) mbar_arrive(prev);
    prev = B_EMPTY + 8 * s;
    if (++s == NST) { s = 0; ph ^= 1; }
  }
  wg_wait<0>();
  if (leader) mbar_arrive(prev);
  reg_fence(a0);
  reg_fence(a1);
}

__device__ __forceinline__ int out_kblock(int r, int tn) {
  const int q = r - 2, half = q >= 7, pi = q - 7 * half;
  return r < 2 ? 2 * tn + r : 2 * (pi + (pi >= tn)) + half;
}

struct Params {
  const char *x, *wqkv, *w_r, *wg, *wu, *wd;
  CUtensorMap m_wqkv, m_x, m_xs, m_o, m_os, m_wo, m_gu, m_down, m_out;
};

template <bool BY_SMID>
__global__ void __launch_bounds__(512, 1) fused_kernel(const __grid_constant__ Params mp) {
  extern __shared__ __align__(1024) uint8_t smem_raw[];
#define CK(i)
  CK(0);
  const int tid = threadIdx.x, lane = tid & 31;
  const int w = __shfl_sync(0xffffffffu, tid >> 5, 0);
  int bid = blockIdx.x;
  if (BY_SMID) {
    uint32_t sm;
    asm volatile("mov.u32 %0, %%smid;" : "=r"(sm));
    const uint32_t p = sm >> 1, q = ((p - 32) * 37) >> 8;
    const uint32_t gpc = p < 32 ? p & 7 : p < 60 ? p - 31 - 7 * q : 0, tpc = p < 32 ? p >> 3 : p < 60 ? 4 + q : p - 58;
    bid = (p >> 1) == 30 ? 128 + ((0x9cu >> (2 * (sm & 3))) & 3) : ((0x75143620u >> (4 * gpc)) & 7) * 16 + tpc * 2 + (sm & 1);
  }
  const int tn = (bid & 3) + 4 * (bid >> 6), tm = (bid >> 2) & 15;

  CK(1);
  if (w == 0) {
#pragma unroll 1
    for (int s = 0; s < NST; s++) {
      asm volatile(ELECT "@p mbarrier.init.shared::cta.b64 [%0], 1;\n}" ::"r"(B_FULL + 8 * s) : "memory");
      if (bid < 128) {
        e_expect(B_FULL + 8 * s, 32768);
        e_tma2d(RING + s * SLOT + 16384, &mp.m_x, s * 64, tm * 128, B_FULL + 8 * s);
        e_tma3d(RING + s * SLOT, &mp.m_wqkv, s * 64, 16 + 2 * tn, B_FULL + 8 * s);
      }
      if (s == 0) CK(2);
    }
  }
  if (w == 1) e_pfmap(&mp.m_wqkv);
  if (w >= 4) {
#pragma unroll 1
    for (uint32_t b = MISC + 8 * (w + 1); b < MISC + 8 * NBAR; b += 96)
      asm volatile(ELECT "@p mbarrier.init.shared::cta.b64 [%0], %1;\n}" ::"r"(b), "r"(b == B_CSDN ? 4 : 1) : "memory");
    if (w == 15) sts32(S_NCAND, 0);
  }
  CK(3);
  asm volatile("fence.mbarrier_init.release.cluster;" ::: "memory");
  __syncthreads();

  if (bid >= 128) {
    const int h0 = bid == 128 ? 14 : bid - 129, hs = bid == 128 ? 1 : 3, h1 = bid == 128 ? 16 : 14;
    if (w == 12) {
      int s = 0, ph = 1;
      if (bid == 128) mbar_wait(B_SEL, 0);
      else if (H_DELAY) __nanosleep(H_DELAY);
#pragma unroll 1
      for (int h = h0; h < h1; h += hs) {
        const int c = 2 * h + (h & 8) * 2;
#pragma unroll 1
        for (int kt = 0; kt < 16; kt += 2) {
          mbar_wait(B_EMPTY + 8 * s, ph);
          e_expect(B_FULL + 8 * s, 32768);
          e_tma3d(RING + s * SLOT, &mp.m_wqkv, kt * 64, c, B_FULL + 8 * s);
          e_tma3d(RING + s * SLOT + 16384, &mp.m_wqkv, kt * 64 + 64, c, B_FULL + 8 * s);
          if (++s == HST) { s = 0; ph ^= 1; }
        }
      }
    } else if (w < 4) {
      const uint32_t par = (ld_relaxed(&g_epoch) + 1) & 1u;
      sts32(S_ONES + tid * 4, 0x3f803f80u);
      fence_async_smem();
      nb_sync(NB_WG0, 128);
      int s = 0, ph = 0;
#pragma unroll 1
      for (int h = h0; h < h1; h += hs) {
        float c[4][4];
#pragma unroll
        for (int i = 0; i < 4; i++) reg_zero(c[i]);
        uint32_t prev = 0;
#pragma unroll 1
        for (int kt = 0; kt < 8; kt++) {
          mbar_wait(B_FULL + 8 * s, ph);
          const uint64_t dw = mkdesc(RING, 8192, 1024, 1) + s * (SLOT >> 4);
          wg_fence();
#pragma unroll
          for (int j = 0; j < 16; j++) wgmma_n8_ss<1, 0>(c[j & 3], dw + (j & 3) * 512 + (j >> 2) * 128, mkdesc(S_ONES, 128, 128, 0), 1);
          wg_commit();
          wg_wait<1>();
          if (prev && tid == 0) mbar_arrive(prev);
          prev = B_EMPTY + 8 * s;
          if (++s == HST) { s = 0; ph ^= 1; }
        }
        wg_wait<0>();
        if (tid == 0) mbar_arrive(prev);
#pragma unroll
        for (int i = 0; i < 4; i++) reg_fence(c[i]);
        const bool u2 = lane & 2, u1 = lane & 1;
        const float lo = u2 ? c[1][0] + c[3][0] : c[0][0] + c[2][0], hi = u2 ? c[1][2] + c[3][2] : c[0][2] + c[2][2];
        st_relaxed(g_csum + h * 128 + (lane & 2) * 32 + w * 16 + (lane & 1) * 8 + (lane >> 2), tagf(u1 ? hi : lo, par));
        STAMP_IF(tid == 0, h >= 8 ? 6 : 30);
      }
    } else if (w < 12 && bid == 128) {
      const int t = tid - 128, j = w - 4;
      const uint32_t ep = ld_relaxed(&g_epoch) + 1;
      uint32_t kk[16];
      poll_keys(kk, g_keys + t * 2, ep, 31u);
      const uint32_t k[8] = {kk[0], kk[2], kk[4], kk[6], kk[8], kk[10], kk[12], kk[14]};
      STAMP_IF(t == 0, 42);
      const uint32_t m = __reduce_max_sync(0xffffffffu, max(max(max(k[0], k[1]), max(k[2], k[3])), max(max(k[4], k[5]), max(k[6], k[7]))));
      if (lane == 0) sts32(S_WMAX + j * 4, m);
      nb_sync(NB_WG1, 256);
      const uint32_t T = __reduce_min_sync(0xffffffffu, lds32(S_WMAX + (lane & 7) * 4));
      uint32_t cnt = 0;
#pragma unroll
      for (int i = 0; i < 8; i++) cnt += k[i] >= T;
      if (cnt) {
        uint32_t pos;
        asm volatile("atom.shared.add.u32 %0, [%1], %2;" : "=r"(pos) : "r"(S_NCAND), "r"(cnt * 4) : "memory");
#pragma unroll
        for (int i = 0; i < 8; i++)
          if (k[i] >= T) { sts32(AUX + pos, k[i]); pos += 4; }
      }
      nb_sync(NB_WG1, 256);
      const uint32_t n4 = lds32(S_NCAND);
#pragma unroll 1
      for (uint32_t i = j * 4; i < n4; i += 32) {
        const uint32_t key = lds32(AUX + i);
        uint32_t rank = 0;
#pragma unroll 1
        for (uint32_t q = lane * 4; q < n4 + lane * 4; q += 128) rank += __popc(__ballot_sync(0xffffffffu, q < n4 && lds32(AUX + q) > key));
        if (rank < 8) sts32(S_SEL + rank * 4, key);
      }
      fence_async_smem();
      nb_sync(NB_WG1, 256);
      STAMP_IF(t == 0, 43);
      const uint32_t key = lds32(S_SEL + j * 4);
      const int tok = key_token(key);
      uint4 v[4];
#pragma unroll
      for (int q = 0; q < 4; q++) v[q] = __ldg(reinterpret_cast<const uint4*>(mp.x + tok * 2048) + q * 32 + lane);
      const uint32_t st = ld_relaxed(&g_keys[tok].y);
      const float rinv = rcp(bf_lo(st)), rhi = bf_round(rinv);
      const uint32_t m2 = __byte_perm(st, 0, 0x3232), hi = pack(rhi, rhi), lo = pack(rinv - rhi, rinv - rhi);
#pragma unroll
      for (int q = 0; q < 4; q++)
        *reinterpret_cast<uint4*>(g_xsel + (q * 8 + (lane >> 2)) * 128 + j * 16 + (((lane & 3) ^ (j >> 1)) << 2)) =
            make_uint4(ln_bf16x2(v[q].x, m2, hi, lo), ln_bf16x2(v[q].y, m2, hi, lo), ln_bf16x2(v[q].z, m2, hi, lo), ln_bf16x2(v[q].w, m2, hi, lo));
      if (lane == 0) g_xsel[4096 + j] = key;
      fence_async_glob();
      nb_sync(NB_WG1, 256);
      STAMP_IF(t == 0, 44);
      if (j == 0) { e_release(H_R, 0); e_arrive(B_SEL); }
      STAMP_IF(t == 0, 45);
    }
  } else if (w >= 12) {
    asm volatile("setmaxnreg.dec.sync.aligned.u32 32;");
    if (w == 12) {
      int s = 0, ph = 0;
#pragma unroll 1
      for (int it = NST; it < 48; it++) {
        const int c = (it < 32 ? (it & 16) + 16 : 0) + 2 * tn;
        mbar_wait(B_EMPTY + 8 * s, ph);
        e_expect(B_FULL + 8 * s, 32768);
        e_tma3d(RING + s * SLOT, &mp.m_wqkv, (it & 15) * 64, c, B_FULL + 8 * s);
        e_tma2d(RING + s * SLOT + 16384, &mp.m_x, (it & 15) * 64, tm * 128, B_FULL + 8 * s);
        if (it >= NST) STAMP2(it - NST);
        if (++s == NST) { s = 0; ph ^= 1; }
      }
#pragma unroll 1
      for (int r = 0; r < 16; r++) {
        const int kb = out_kblock(r, tn);
        mbar_wait(B_EMPTY + 8 * s, ph);
        e_expect(B_FULL + 8 * s, r < 2 ? 16384 : 32768);
        e_tma3d(RING + s * SLOT, &mp.m_wo, kb * 64, 2 * tn, B_FULL + 8 * s);
        if (r < 2) {
          if (r == 0) e_expect(B_XRES, 32768);
          e_tma2d(RING + s * SLOT + 16384, &mp.m_x, kb * 64, tm * 128, B_XRES);
        }
        STAMP2(r + 48 - NST);
        if (++s == NST) { s = 0; ph ^= 1; }
      }
    } else if (w == 13) {
      e_pfmap(&mp.m_xs);
      mbar_wait(B_FULL + 8 * XS_AT, 0);
#pragma unroll 1
      for (int c = 0; c < 4; c++) {
        if (c >= XS_FLY) mbar_wait(B_XS + 8 * (c - XS_FLY), 0);
        if (c == max(tm >> 2, 1)) {
          e_expect(B_WK, 16384);
          e_tma3d(FR, &mp.m_wqkv, tm * 64, 16 + 2 * tn, B_WK);
        }
        e_expect(B_XS + 8 * c, 8192);
        e_tma2d(STG + c * 8192, &mp.m_xs, c * 256, tm * 128 + tn * 16, B_XS + 8 * c);
      }
      nb_sync(NB_Z, 160);
      const uint32_t ep = lds32(S_EPOCH);
      {
        float z[4] = {0.f, 0.f, 0.f, 0.f};
#pragma unroll 1
        for (int i = 0; i < 4; i++) {
          uint32_t p[16];
          poll_z(p, g_z + i * 4096 + tn * 128 + lane * 4, ep, 1u);
#pragma unroll
          for (int q = 0; q < 4; q++) z[q] += (__uint_as_float(p[q]) + __uint_as_float(p[4 + q])) + (__uint_as_float(p[8 + q]) + __uint_as_float(p[12 + q]));
        }
        const uint32_t z01 = pack(z[0], z[1]), z23 = pack(z[2], z[3]);
#pragma unroll
        for (int i = 0; i < 4; i++) {
          const int n = 2 * i + (lane >> 4);
          asm volatile("st.shared.v2.u32 [%0], {%1,%2};" ::"r"(KVB_Z + n * 128 + ((((lane >> 1) & 7) ^ n) << 4) + (lane & 1) * 8), "r"(z01), "r"(z23) : "memory");
        }
        fence_async_smem();
        nb_arrive(NB_KVB, 288);
        STAMP_IF(lane == 0, 46);
      }
      nb_sync(NB_Q0, 192);
      e_store2d(&mp.m_os, tn * 128, tm * 128, STG);
      nb_sync(NB_OWN0, 288);
      e_store2d(&mp.m_os, tn * 128, tm * 128 + 64, STG + 8192);
      e_release(H_O + tm, 2 * tn);
      STAMP_IF(lane == 0, 4);
      nb_sync(NB_H1, 160);
      e_store2d(&mp.m_os, tn * 128 + 64, tm * 128, STG + 16384);
      e_store2d(&mp.m_os, tn * 128 + 64, tm * 128 + 64, STG + 24576);
      e_release(H_O + tm, 2 * tn + 1);
      STAMP_IF(lane == 0, 5);
      nb_arrive(NB_ST, 160);
    } else if (w == 14) {
      e_pfmap(&mp.m_gu); e_pfmap(&mp.m_o); e_pfmap(&mp.m_os); e_pfmap(&mp.m_wo); e_pfmap(&mp.m_down); e_pfmap(&mp.m_out);
      const uint32_t ep = ld_relaxed(&g_epoch) + 1;
      nb_sync(NB_FDONE, 416);
      {
        uint32_t c[4];
        poll_quad(c, g_csum + tn * 128 + lane * 4, ep, 1u);
        sts128(S_CSQ + lane * 16, c[0], c[1], c[2], c[3]);
        nb_arrive(NB_CSQ, 160);
        poll_quad(c, g_csum + 1024 + tn * 128 + lane * 4, ep, 1u);
        sts128(S_CSV + lane * 16, c[0], c[1], c[2], c[3]);
        __syncwarp();
        e_arrive(B_CSV);
      }
      nb_sync(NB_Q0, 192);
      uint32_t ready = 0;
      int s = 0, ph = 1;
#pragma unroll 1
      for (int r = 2; r < 16; r++) {
        const int kb = out_kblock(r, tn);
        if (!((ready >> kb) & 1)) {
          uint32_t f[1];
          poll0(f, g_sig + (H_O + tm) * 32, 0u - (ep & 1u), 1u << kb);
          ready = f[0] ^ ((ep & 1u) - 1u);
          fence_acq();
          fence_async_glob();
        }
        mbar_wait(B_EMPTY + 8 * s, ph);
        e_tma2d(RING + s * SLOT + 16384, &mp.m_o, kb * 64, tm * 128, B_FULL + 8 * s);
        STAMP_IF(lane == 0 && r == 2, 2);
        STAMP_IF(lane == 0 && r == 9, 3);
        if (++s == NST) { s = 0; ph ^= 1; }
      }
    } else {
      uint32_t nsm = 132;
      if (BY_SMID) asm volatile("mov.u32 %0, %%nsmid;" : "=r"(nsm));
      asm volatile("{\n.reg .pred q;\nsetp.eq.u32 q, %0, 1156;\n@q bra LOK;\ntrap;\nLOK:\n}" ::"r"((uint32_t)__cvta_generic_to_shared(smem_raw) + nsm));
      const uint32_t ep = ld_relaxed(&g_epoch) + 1;
      const char* pf = ((bid & 1) ? mp.wu : mp.wg) + (bid >> 1) * 128 + (lane + 160) * 7168;
      mbar_wait(B_CSDN, 0);
#pragma unroll 1
      for (int n = 0; n < 5; n++) {
        __nanosleep(FFN_GAP);
        if (bid < 112) {
          e_expect(B_FR + 8 * n, 4608);
          e_tma3d_ef(GR + n * 4096, &mp.m_gu, bid * 32, n * 32, B_FR + 8 * n, EVICT_FIRST);
          if (PFD) asm volatile("prefetch.global.L2 [%0];" ::"l"(pf));
          pf += 32 * 7168;
        } else if (n > 0) {
          e_expect(B_DR + 8 * (n & 3), 4096);
          e_tma2d_ef(FR + (n & 3) * 4096, &mp.m_down, (bid & 15) * 64, (bid >> 4) * 448 + (n - 1) * 32, B_DR + 8 * (n & 3), EVICT_FIRST);
        }
      }
      uint32_t f[1];
      poll1(f, g_sig + H_R * 32, ep, 1u);
      fence_acq();
      fence_async_glob();
      if (bid < 112) {
#pragma unroll
        for (int n = 0; n < 5; n++) e_load(HOP + n * 512, g_xsel + n * 128, 512, B_FR + 8 * n);
      }
      e_expect(B_SEL, 32);
      e_load(S_SEL, g_xsel + 4096, 32, B_SEL);
      const char* pd = mp.wd + (bid & 15) * 128 + ((bid >> 4) * 448 + lane) * 2048;
      if (bid < 112) {
        int s = 0, ph = 0;
#pragma unroll 1
        for (int n = 5; n < 32; n++) {
          mbar_wait(B_FE + 8 * s, ph);
          e_expect(B_FR + 8 * s, 4608);
          e_tma3d_ef(GR + s * 4096, &mp.m_gu, bid * 32, n * 32, B_FR + 8 * s, EVICT_FIRST);
          e_load(HOP + s * 512, g_xsel + n * 128, 512, B_FR + 8 * s);
          STAMP2(64 + n);
          if (PFD) {
            if (n == 27) pf = pd;
            asm volatile("prefetch.global.L2 [%0];" ::"l"(pf));
            pf += n < 27 ? 32 * 7168 : 65536;
          }
          if (++s == 5) { s = 0; ph ^= 1; }
        }
      }
#pragma unroll 1
      for (int i = bid < 112 ? 0 : 4; i < 14; i++) {
        const int s = (i + 1) & 3;
        mbar_wait(i >= 4 ? B_DE + 8 * s : B_FE + 8 * (s + 1), i >= 4 ? ((i >> 2) & 1) ^ 1 : s != 0);
        e_expect(B_DR + 8 * s, 4096);
        e_tma2d_ef(FR + s * 4096, &mp.m_down, (bid & 15) * 64, (bid >> 4) * 448 + i * 32, B_DR + 8 * s, EVICT_FIRST);
        if (PFD && i < 9) asm volatile("prefetch.global.L2 [%0];" ::"l"(pd + (i + 5) * 65536));
      }
    }
  } else if (w >= 8) {
    asm volatile("setmaxnreg.dec.sync.aligned.u32 56;");
    const int t = tid - 256, ww = w - 8;
    const uint32_t ep = ld_relaxed(&g_epoch) + 1, par = ep & 1u;
    {
      const int r0 = (lane >> 3) + (lane & 4);
      const uint32_t a = FR + (ww >> 1) * 8192 + r0 * 128 + ((((ww & 1) * 4 + (lane & 3)) ^ r0) << 4);
      float c[8];
      reg_zero(c);
      mbar_wait(B_WK, 0);
#pragma unroll 2
      for (int i = 0; i < 8; i++) {
        const uint4 v = lds128(a + i * 1024);
        c[0] += bf_lo(v.x); c[1] += bf_hi(v.x); c[2] += bf_lo(v.y); c[3] += bf_hi(v.y);
        c[4] += bf_lo(v.z); c[5] += bf_hi(v.z); c[6] += bf_lo(v.w); c[7] += bf_hi(v.w);
      }
      const bool u16 = lane & 16, u8 = lane & 8, u4 = lane & 4;
      const float d0 = xred(c[0], c[4], u16, 16), d1 = xred(c[1], c[5], u16, 16), d2 = xred(c[2], c[6], u16, 16), d3 = xred(c[3], c[7], u16, 16);
      fence_async_smem();
      e_arrive(B_CSDN);
      const float sum = xred(xred(d0, d2, u8, 8), xred(d1, d3, u8, 8), u4, 4);
      st_relaxed(g_csum + (2 + tm) * 1024 + tn * 128 + ww * 32 + (lane & 3) * 8 + (lane >> 2), tagf(sum, par));
      STAMP_IF(t == 0, 8);
      nb_sync(NB_WG2, 128);
      if (ww == 0) { e_signal(H_CS + tn, tm); await(H_CS + tn, 0xffffu, ep); }
      nb_sync(NB_WG2, 128);
      uint32_t p[16];
      poll16(p, g_csum + 2048 + tn * 128 + t, par, 1u);
      float tot = 0.f;
#pragma unroll
      for (int i = 0; i < 16; i += 4) tot += (__uint_as_float(p[i]) + __uint_as_float(p[i + 1])) + (__uint_as_float(p[i + 2]) + __uint_as_float(p[i + 3]));
      sts32(S_CSK + t * 4, __float_as_uint(tot));
      nb_arrive(NB_FDONE, 416);
      STAMP_IF(t == 0, 9);
    }
    const int ks = bid >> 4, nt = bid & 15;
    float fa[4] = {0.f, 0.f, 0.f, 0.f};
    if (bid < 112) {
      int s = 0, ph = 0;
      uint32_t prev = 0;
#pragma unroll 1
      for (int n = 0; n < 32; n++) {
        mbar_wait(B_FR + 8 * s, ph);
        const uint64_t da = mkdesc(GR, 2048, 512, 2) + s * 256, db = mkdesc(HOP, 16, 512, 2) + s * 32;
        wg_fence();
        wgmma_n8_ss<1, 0>(fa, da, db, 1);
        wgmma_n8_ss<1, 0>(fa, da + 64, db + 2, 1);
        wg_commit();
        wg_wait<1>();
        if (prev && t == 0) mbar_arrive(prev);
        prev = B_FE + 8 * s;
        if (++s == 5) { s = 0; ph ^= 1; }
      }
      wg_wait<0>();
      reg_fence(fa);
      if (t == 0) mbar_arrive(prev);
      STAMP_IF(t == 0, 12);
      const bool isup = (ww >> 1) != (mp.wu < mp.wg);
      if (isup) sts128f(GR + (t & 63) * 16, fa[0], fa[1], fa[2], fa[3]);
      nb_sync(NB_WG2, 128);
      if (!isup) {
        const float4 u = lds128f(GR + (t & 63) * 16);
        const float uu[4] = {u.x, u.y, u.z, u.w};
        uint32_t* hp = g_h + bid * 256 + (lane & 3) * 64 + (ww & 1) * 16 + (lane >> 2);
#pragma unroll
        for (int i = 0; i < 4; i++) {
          const float g = fa[i], hv = g * rcp(1.f + ex2(-g * LOG2E)) * uu[i];
          st_relaxed(hp + (i & 1) * 32 + (i >> 1) * 8, __byte_perm(pack(hv, hv), ep, 0x3254));
        }
      }
      nb_sync(NB_WG2, 128);
      if (ww == 0) e_signal(H_H + bid / 14, bid % 14);
      reg_zero(fa);
    }
    {
      uint32_t v[28];
      if (ww == 0) await(H_H + ks, 0x3fffu, ep);
      nb_sync(NB_WG2, 128);
      poll7x4(v, g_h + ks * 3584 + t * 4, ep, 0xffffu);
#pragma unroll
      for (int q = 0; q < 7; q++)
        asm volatile("st.shared.v2.u32 [%0], {%1,%2};" ::"r"(HOP + q * 1024 + (t >> 3) * 64 + ((((t >> 1) & 3) ^ ((t >> 4) & 3)) << 4) + (t & 1) * 8),
                     "r"(__byte_perm(v[4 * q], v[4 * q + 1], 0x7632)), "r"(__byte_perm(v[4 * q + 2], v[4 * q + 3], 0x7632)) : "memory");
      fence_async_smem();
      nb_sync(NB_WG2, 128);
    }
    STAMP_IF(t == 0, 13);
#pragma unroll 1
    for (int i = 0; i < 14; i++) {
      const int s = (i + 1) & 3;
      mbar_wait(B_DR + 8 * s, (i >> 2) & 1);
      const uint64_t da = mkdesc(FR, 4096, 1024, 1) + s * 256;
      const uint64_t db = mkdesc(HOP, 16, 512, 2) + i * 32;
      wg_fence();
      wgmma_n8_ss<1, 0>(fa, da, db, 1);
      wgmma_n8_ss<1, 0>(fa, da + 128, db + 2, 1);
      wg_commit();
      wg_wait<1>();
      if (i && t == 0) mbar_arrive(B_DE + 8 * (i & 3));
    }
    wg_wait<0>();
    reg_fence(fa);
    STAMP_IF(t == 0, 14);
    {
      uint32_t* yp = g_yp + (nt * 8 + ks) * 512 + (lane & 3) * 128 + ww * 16 + (lane >> 2);
#pragma unroll
      for (int i = 0; i < 4; i++) st_relaxed(yp + (i & 1) * 64 + (i >> 1) * 8, tagf(fa[i], par));
    }
    nb_sync(NB_WG2, 128);
    if (ww == 0) e_signal(H_Y + (nt >> 1), (nt & 1) * 8 + ks);
    mbar_wait(B_SEL, 0);
    const uint32_t mykey = lds32(S_SEL + (lane & 7) * 4);
    const uint32_t inmask = __ballot_sync(0xffffffffu, (key_token(mykey) >> 7) == tm) & 0xffu;
    if (inmask) {
      if (ww == 0) await(H_Y + tn, 0xffffu, ep);
      nb_sync(NB_WG2, 128);
      const float sg = rcp(1.f + ex2(-key_score(mykey) * LOG2E));
#pragma unroll 1
      for (int j = 0; j < 8; j++) {
        float y = 0.f;
        if ((inmask >> j) & 1) {
          uint32_t p[8];
          poll8(p, g_yp + (tn * 2 + (t >> 6)) * 4096 + j * 64 + (t & 63), par, 1u);
          y = ((__uint_as_float(p[0]) + __uint_as_float(p[1])) + (__uint_as_float(p[2]) + __uint_as_float(p[3]))) +
              ((__uint_as_float(p[4]) + __uint_as_float(p[5])) + (__uint_as_float(p[6]) + __uint_as_float(p[7])));
        }
        y *= __shfl_sync(0xffffffffu, sg, j);
        asm volatile("st.shared.u16 [%0], %1;" ::"r"(FR + (t >> 6) * 1024 + j * 128 + ((((t >> 3) & 7) ^ j) << 4) + (t & 7) * 2),
                     "h"((unsigned short)pack(y, y)) : "memory");
      }
      fence_async_smem();
      nb_arrive(NB_Y, 256);
    }
    STAMP_IF(t == 0, 15);
  } else if (w >= 4) {
    asm volatile("setmaxnreg.inc.sync.aligned.u32 208;");
    const int t = tid - 128, ww = w - 4, g = lane >> 2, t4 = lane & 3;
    const bool leader = t == 0;
    const uint32_t ep = ld_relaxed(&g_epoch) + 1, par = ep & 1u;
    {
      const uint4* wp = reinterpret_cast<const uint4*>(mp.w_r) + lane;
      uint4 w0 = __ldg(wp), w1 = __ldg(wp + 32), w2 = __ldg(wp + 64), w3 = __ldg(wp + 96);
      if (leader) sts32(S_EPOCH, ep);
      float s[4] = {0.f, 0.f, 0.f, 0.f}, q[4] = {0.f, 0.f, 0.f, 0.f}, d[4] = {0.f, 0.f, 0.f, 0.f}, wsum = 0.f;
#pragma unroll 1
      for (int c = 0; c < 4; c++) {
        const float wr[8] = {bf_lo(w0.x), bf_hi(w0.x), bf_lo(w0.y), bf_hi(w0.y), bf_lo(w0.z), bf_hi(w0.z), bf_lo(w0.w), bf_hi(w0.w)};
        w0 = w1; w1 = w2; w2 = w3;
        wsum += ((wr[0] + wr[1]) + (wr[2] + wr[3])) + ((wr[4] + wr[5]) + (wr[6] + wr[7]));
        mbar_wait(B_XS + 8 * c, 0);
#pragma unroll
        for (int r = 0; r < 4; r++) {
          const uint4 v = lds128(STG + c * 8192 + (ww * 4 + r) * 512 + lane * 16);
          const uint32_t xw[4] = {v.x, v.y, v.z, v.w};
#pragma unroll
          for (int i = 0; i < 4; i++) {
            const float lo = bf_lo(xw[i]), hi = bf_hi(xw[i]);
            s[r] += lo; q[r] = fmaf(lo, lo, q[r]); d[r] = fmaf(lo, wr[2 * i], d[r]);
            s[r] += hi; q[r] = fmaf(hi, hi, q[r]); d[r] = fmaf(hi, wr[2 * i + 1], d[r]);
          }
        }
      }
      STAMP_IF(leader, 16);
      const bool u16 = lane & 16, u8 = lane & 8, u4 = lane & 4, u2 = lane & 2;
      const float s1 = xred(xred(s[0], s[2], u16, 16), xred(s[1], s[3], u16, 16), u8, 8);
      const float q1 = xred(xred(q[0], q[2], u16, 16), xred(q[1], q[3], u16, 16), u8, 8);
      const float d1 = xred(xred(d[0], d[2], u16, 16), xred(d[1], d[3], u16, 16), u8, 8);
      wsum += __shfl_xor_sync(0xffffffffu, wsum, 16);
      wsum += __shfl_xor_sync(0xffffffffu, wsum, 8);
      float tot = xred(xred(s1, d1, u4, 4), xred(q1, wsum, u4, 4), u2, 2);
      tot += __shfl_xor_sync(0xffffffffu, tot, 1);
      const float qq = __shfl_down_sync(0xffffffffu, tot, 2), dd = __shfl_down_sync(0xffffffffu, tot, 4), ws = __shfl_down_sync(0xffffffffu, tot, 6);
      if ((lane & 7) == 0) {
        const float mean = tot * (1.f / 1024.f);
        const float var = fmaxf(fmaf(-mean, mean, qq * (1.f / 1024.f)), 0.f);
        float sd;
        asm("sqrt.approx.ftz.f32 %0, %1;" : "=f"(sd) : "f"(bf_round(bf_round(var) + 1e-5f)));
        const uint32_t ms = pack(sd, mean);
        const int row = tm * 128 + tn * 16 + ww * 4 + (lane >> 3);
        const uint32_t rbits = pack(0.f, fmaf(-bf_hi(ms), ws, dd) * rcp(bf_lo(ms)));
        const uint32_t key = (rbits ^ (((int)rbits >> 31 & 0x7fff0000u) | 0x80000000u)) | ((2047 - row) << 5) | (ep & 31u);
        asm volatile("{\n.reg .b64 x;\nmov.b64 x, {%1,%2};\nst.relaxed.gpu.global.b64 [%0], x;\n}" ::"l"(g_keys + row), "r"(key), "r"(ms) : "memory");
      }
      STAMP_IF(leader, 17);
      __nanosleep(400);
      uint32_t st[2];
      poll_pair(st, g_keys + tm * 128 + t, ep, 31u);
      asm volatile("st.shared.v2.f32 [%0], {%1,%2};" ::"r"(S_KSTAT + t * 8), "f"(bf_hi(st[1])), "f"(rcp(bf_lo(st[1])) * LOG2E) : "memory");
      nb_arrive(NB_FDONE, 416);
      STAMP_IF(leader, 10);
    }
    float a0[64], a1[64];
    reg_zero(a0); reg_zero(a1); reg_fence(a0); reg_fence(a1);
    STAMP_IF(leader, 18);
    nb_sync(NB_KV, 256);
    mainloop<true>(a0, a1, 1, 1, NB_VQ, leader);
    STAMP_IF(leader, 19);
    {
      uint32_t f0[32], f1[32];
#pragma unroll
      for (int i = 0; i < 32; i++) { f0[i] = pack(a0[2 * i], a0[2 * i + 1]); f1[i] = pack(a1[2 * i], a1[2 * i + 1]); }
      float c0[32], c1[32];
      reg_zero(c0); reg_zero(c1);
      nb_sync(NB_PK, 256);
      constexpr uint64_t db = mkdesc(STG, 16, 1024, 1);
      wg_fence();
#pragma unroll
      for (int k = 0; k < 8; k++) {
        wgmma_n64_rs<0>(c0, f0[4 * k], f0[4 * k + 1], f0[4 * k + 2], f0[4 * k + 3], db + (k >> 2) * 1024 + (k & 3) * 2, k != 0);
        wgmma_n64_rs<0>(c1, f1[4 * k], f1[4 * k + 1], f1[4 * k + 2], f1[4 * k + 3], db + (k >> 2) * 1024 + (k & 3) * 2 + 512, k != 0);
      }
      wg_commit();
      const bool hp = ww >> 1;
      float c[4];
      float2 tt[8];
#pragma unroll
      for (int i = 0; i < 8; i++) tt[i] = lds64f(S_CSK + ((i >> 2) * 64 + hp * 32 + (i & 3) * 8 + 2 * t4) * 4);
      mbar_wait(B_CSV, 0);
#pragma unroll
      for (int i = 0; i < 4; i++) c[i] = -__uint_as_float(lds32(S_CSV + ((i >> 1) * 64 + ww * 16 + (i & 1) * 8 + g) * 4));
      wg_wait<0>();
      reg_fence(c0);
      reg_fence(c1);
      STAMP_IF(leader, 20);
      uint4* pp = g_kvp + (tn * 16 + tm) * 512 + t;
      auto put = [&](int q, const float* d) {
        const float ca = c[q & 2], cb = c[q | 1];
        const float2 ta = tt[2 * q], tb = tt[2 * q + 1];
        st_unit(pp + q * 128, pack(fmaf(ca, ta.x, d[0]), fmaf(ca, ta.y, d[1])), pack(fmaf(cb, ta.x, d[2]), fmaf(cb, ta.y, d[3])),
                pack(fmaf(ca, tb.x, d[4]), fmaf(ca, tb.y, d[5])), pack(fmaf(cb, tb.x, d[6]), fmaf(cb, tb.y, d[7])), par);
      };
      if (!hp) { put(0, c0); put(1, c0 + 8); put(2, c1); put(3, c1 + 8); }
      else { put(0, c0 + 16); put(1, c0 + 24); put(2, c1 + 16); put(3, c1 + 24); }
      STAMP_IF(leader, 47);
      {
        uint32_t p[16];
        nb_sync(NB_WG1, 128);
        if (ww == 0) { e_signal(H_KVP + tn, tm); await(H_KVP + tn, 0xffffu, ep); }
        nb_sync(NB_Z, 160);
        STAMP_IF(leader, 1);
        poll_kvp(p, g_kvp + (tn * 16 + (lane >> 3) * 4) * 512 + tm * 32 + ww * 8 + (lane & 7), par, 1u);
        float r[8];
#pragma unroll
        for (int i = 0; i < 4; i++) {
          r[2 * i] = (bf_lo(p[i]) + bf_lo(p[4 + i])) + (bf_lo(p[8 + i]) + bf_lo(p[12 + i]));
          r[2 * i + 1] = (bf_hi(p[i]) + bf_hi(p[4 + i])) + (bf_hi(p[8 + i]) + bf_hi(p[12 + i]));
        }
#pragma unroll
        for (int i = 0; i < 8; i++) r[i] += __shfl_xor_sync(0xffffffffu, r[i], 8);
#pragma unroll
        for (int i = 0; i < 8; i++) r[i] += __shfl_xor_sync(0xffffffffu, r[i], 16);
        if (lane < 8) st_unit(g_kv + tn * 512 + tm * 32 + ww * 8 + lane, pack(r[0], r[1]), pack(r[2], r[3]), pack(r[4], r[5]), pack(r[6], r[7]), par);
      }
      STAMP_IF(leader, 21);
    }
    const uint32_t sx = lane & 7, sc = lane >> 4;
    const uint32_t sa = STG + (ww * 16 + (lane & 15)) * 128;
    const uint32_t sw[4] = {sa + ((sc ^ sx) << 4), sa + (((2 + sc) ^ sx) << 4), sa + (((4 + sc) ^ sx) << 4), sa + (((6 + sc) ^ sx) << 4)};
    {
      uint32_t v[16];
      nb_sync(NB_WG1, 128);
      if (ww == 0) { e_signal(H_KV + tn, tm); await(H_KV + tn, 0xffffu, ep); }
      nb_sync(NB_WG1, 128);
      STAMP_IF(leader, 7);
      poll_kv(v, g_kv + tn * 512 + t, par, 1u);
      STAMP_IF(leader, 23);
#pragma unroll
      for (int q = 0; q < 4; q++)
        stsm4((q < 2 ? KVB_P0 : KVB_P1) + ((ww & 1) * 16 + (lane & 15)) * 128 + ((((ww >> 1) * 4 + (q & 1) * 2 + sc) ^ sx) << 4),
              v[4 * q], v[4 * q + 1], v[4 * q + 2], v[4 * q + 3]);
      fence_async_smem();
      nb_arrive(NB_KVB, 288);
    }
    STAMP_IF(leader, 24);
    uint32_t oh[4];
    uint32_t inmask;
    {
      mbar_wait(B_SEL, 0);
      const int r0 = key_token(lds32(S_SEL + t4 * 8)) - tm * 128, r1 = key_token(lds32(S_SEL + t4 * 8 + 4)) - tm * 128;
#pragma unroll
      for (int i = 0; i < 4; i++) {
        const int row = (i >> 1) * 64 + ww * 16 + (i & 1) * 8 + g;
        oh[i] = (r0 == row ? 0x3f80u : 0u) | (r1 == row ? 0x3f800000u : 0u);
      }
      inmask = __ballot_sync(0xffffffffu, (unsigned)r0 < 128u || (unsigned)r1 < 128u);
    }
    {
      float ka[4], kb[4];
#pragma unroll
      for (int i = 0; i < 4; i++) {
        const float2 st = lds64f(S_KSTAT + ((i >> 1) * 64 + ww * 16 + (i & 1) * 8 + g) * 8);
        const float r = st.y * LN2;
        ka[i] = 1.f + r; kb[i] = -st.x * r;
      }
      constexpr uint32_t XOFF = RING + 3 * SLOT + 16384 - STG;
      mbar_wait(B_XRES, 0);
#pragma unroll
      for (int j = 0; j < 8; j++) {
        const uint4 v = ldsm4(sw[j & 3] + XOFF + (j >> 2) * SLOT), u = ldsm4(sw[j & 3] + XOFF + (j >> 2) * SLOT + 8192);
        a0[8 * j + 0] = fmaf(bf_lo(v.x), ka[0], kb[0]); a0[8 * j + 1] = fmaf(bf_hi(v.x), ka[0], kb[0]);
        a0[8 * j + 2] = fmaf(bf_lo(v.y), ka[1], kb[1]); a0[8 * j + 3] = fmaf(bf_hi(v.y), ka[1], kb[1]);
        a0[8 * j + 4] = fmaf(bf_lo(v.z), ka[0], kb[0]); a0[8 * j + 5] = fmaf(bf_hi(v.z), ka[0], kb[0]);
        a0[8 * j + 6] = fmaf(bf_lo(v.w), ka[1], kb[1]); a0[8 * j + 7] = fmaf(bf_hi(v.w), ka[1], kb[1]);
        a1[8 * j + 0] = fmaf(bf_lo(u.x), ka[2], kb[2]); a1[8 * j + 1] = fmaf(bf_hi(u.x), ka[2], kb[2]);
        a1[8 * j + 2] = fmaf(bf_lo(u.y), ka[3], kb[3]); a1[8 * j + 3] = fmaf(bf_hi(u.y), ka[3], kb[3]);
        a1[8 * j + 4] = fmaf(bf_lo(u.z), ka[2], kb[2]); a1[8 * j + 5] = fmaf(bf_hi(u.z), ka[2], kb[2]);
        a1[8 * j + 6] = fmaf(bf_lo(u.w), ka[3], kb[3]); a1[8 * j + 7] = fmaf(bf_hi(u.w), ka[3], kb[3]);
      }
      reg_fence(a0);
      reg_fence(a1);
      fence_async_smem();
    }
    STAMP_IF(leader, 22);
    {
      int s = 3, ph = 1;
      uint32_t prev = 0;
#pragma unroll 1
      for (int r = 0; r < 16; r++) {
        if (r < 2) nb_sync(NB_OWN0 + r, r ? 256 : 288);
        mbar_wait(B_FULL + 8 * s, ph);
        if (!LITE) STAMP_IF(leader && r < 3, 25 + r);
        const uint64_t dw = mkdesc(RING, 8192, 1024, 1) + s * (SLOT >> 4);
        const uint64_t dx = mkdesc(0, 16, 1024, 1) + (r < 2 ? (STG >> 4) + r * 1024 : ((RING + 16384) >> 4) + s * (SLOT >> 4));
        wg_fence();
#pragma unroll
        for (int j = 0; j < 4; j++) {
          wgmma_n128_ss<0, 1>(a0, dx + j * 2, dw + j * 128, 1);
          wgmma_n128_ss<0, 1>(a1, dx + j * 2 + 512, dw + j * 128, 1);
        }
        wg_commit();
        wg_wait<1>();
        if (prev && leader) mbar_arrive(prev);
        prev = B_EMPTY + 8 * s;
        if (++s == NST) { s = 0; ph ^= 1; }
      }
      if (inmask) {
        nb_sync(NB_Y, 256);
        wg_fence();
        wgmma_n128_rs<1>(a0, oh[0], oh[1], 0u, 0u, mkdesc(FR, 1024, 0, 1), 1);
        wgmma_n128_rs<1>(a1, oh[2], oh[3], 0u, 0u, mkdesc(FR, 1024, 0, 1), 1);
        wg_commit();
      }
      nb_sync(NB_ST, 160);
      wg_wait<0>();
      reg_fence(a0);
      reg_fence(a1);
    }
    STAMP_IF(leader, 28);
#pragma unroll
    for (int c = 0; c < 2; c++) {
#pragma unroll
      for (int j = 4 * c; j < 4 * c + 4; j++) {
        stsm4(sw[j & 3] + c * 16384, pack(a0[8 * j], a0[8 * j + 1]), pack(a0[8 * j + 2], a0[8 * j + 3]), pack(a0[8 * j + 4], a0[8 * j + 5]), pack(a0[8 * j + 6], a0[8 * j + 7]));
        stsm4(sw[j & 3] + c * 16384 + 8192, pack(a1[8 * j], a1[8 * j + 1]), pack(a1[8 * j + 2], a1[8 * j + 3]), pack(a1[8 * j + 4], a1[8 * j + 5]), pack(a1[8 * j + 6], a1[8 * j + 7]));
      }
      fence_async_smem();
      e_store2d(&mp.m_out, tn * 128 + c * 64, tm * 128 + ww * 16, STG + c * 16384 + ww * 2048);
      e_store2d(&mp.m_out, tn * 128 + c * 64, tm * 128 + 64 + ww * 16, STG + c * 16384 + 8192 + ww * 2048);
    }
    bulk_wait_read();
    if (bid == 0 && leader) st_relaxed(&g_epoch, ep);
    STAMP_IF(leader, 29);
  } else {
    asm volatile("setmaxnreg.inc.sync.aligned.u32 216;");
    const int g = lane >> 2, t4 = lane & 3;
    const bool leader = tid == 0;
    const uint32_t sx = lane & 7, sc = lane >> 4;
    const uint32_t sa = STG + (w * 16 + (lane & 15)) * 128;
    const uint32_t sw[4] = {sa + ((sc ^ sx) << 4), sa + (((2 + sc) ^ sx) << 4), sa + (((4 + sc) ^ sx) << 4), sa + (((6 + sc) ^ sx) << 4)};
    float a0[64], a1[64];
    reg_zero(a0); reg_zero(a1); reg_fence(a0); reg_fence(a1);
    mainloop<true>(a0, a1, 0, 0, NB_KV, leader);
    STAMP_IF(leader, 33);
    {
      nb_sync(NB_FDONE, 416);
      STAMP_IF(leader, 34);
      float c[4], z[4] = {0.f, 0.f, 0.f, 0.f}, tt[4] = {0.f, 0.f, 0.f, 0.f};
#pragma unroll
      for (int i = 0; i < 4; i++) c[i] = -__uint_as_float(lds32(S_CSK + ((i >> 1) * 64 + w * 16 + (i & 1) * 8 + g) * 4));
#pragma unroll
      for (int j = 0; j < 8; j++) {
        const float4 s0 = lds128v(S_KSTAT + (j * 16 + 2 * t4) * 8), s1 = lds128v(S_KSTAT + (j * 16 + 8 + 2 * t4) * 8);
        const float mu[4] = {s0.x, s0.z, s1.x, s1.z}, rl[4] = {s0.y, s0.w, s1.y, s1.w};
#pragma unroll
        for (int m = 0; m < 2; m++) {
          float p[8];
#pragma unroll
          for (int i = 0; i < 8; i++) {
            const int r = m * 2 + ((i >> 1) & 1), cc = (i >> 2) * 2 + (i & 1);
            p[i] = phi2(fmaf(c[r], mu[cc], m ? a1[8 * j + i] : a0[8 * j + i]) * rl[cc]);
            z[r] += p[i];
            p[i] *= rl[cc];
            tt[r] = fmaf(p[i], mu[cc], tt[r]);
          }
          stsm4(sw[j & 3] + (j >> 2) * 16384 + m * 8192, pack(p[0], p[1]), pack(p[2], p[3]), pack(p[4], p[5]), pack(p[6], p[7]));
        }
      }
      const bool u2 = lane & 2, u1 = lane & 1;
      const float zz = xred(xred(z[0], z[2], u2, 2), xred(z[1], z[3], u2, 2), u1, 1);
      sts32(S_CSK + ((t4 >> 1) * 64 + w * 16 + (t4 & 1) * 8 + g) * 4, __float_as_uint(xred(xred(tt[0], tt[2], u2, 2), xred(tt[1], tt[3], u2, 2), u1, 1)));
      fence_async_smem();
      nb_arrive(NB_PK, 256);
      st_relaxed(g_z + tm * 1024 + tn * 128 + (t4 >> 1) * 64 + w * 16 + (t4 & 1) * 8 + g, tagf(zz * LOG2E, lds32(S_EPOCH) & 1u));
    }
    STAMP_IF(leader, 35);
    float rl0[2];
    {
      nb_sync(NB_CSQ, 160);
      float mu[4];
#pragma unroll
      for (int i = 0; i < 4; i++) {
        const float2 st = lds64f(S_KSTAT + ((i >> 1) * 64 + w * 16 + (i & 1) * 8 + g) * 8);
        mu[i] = -st.x;
        if (i < 2) rl0[i] = st.y;
      }
#pragma unroll
      for (int j = 0; j < 16; j++) {
        const float2 c = lds64f(S_CSQ + (j * 8 + 2 * t4) * 4);
        a0[4 * j] = mu[0] * c.x; a0[4 * j + 1] = mu[0] * c.y; a0[4 * j + 2] = mu[1] * c.x; a0[4 * j + 3] = mu[1] * c.y;
        a1[4 * j] = mu[2] * c.x; a1[4 * j + 1] = mu[2] * c.y; a1[4 * j + 2] = mu[3] * c.x; a1[4 * j + 3] = mu[3] * c.y;
      }
      reg_fence(a0); reg_fence(a1);
    }
    STAMP_IF(leader, 40);
    nb_sync(NB_VQ, 256);
    mainloop<false>(a0, a1, 2, 0, 0, leader);
    STAMP_IF(leader, 36);
    {
      uint32_t f[2][16];
      float oc[2][2][20];
      auto phi = [&](const float (&a)[64], int j, int m, uint32_t (&o)[16]) {
        float rl[2] = {rl0[0], rl0[1]};
        if (j | m) { rl[0] = lds32v(S_KSTAT + (m * 64 + w * 16 + g) * 8 + 4); rl[1] = lds32v(S_KSTAT + (m * 64 + w * 16 + 8 + g) * 8 + 4); }
#pragma unroll
        for (int i = 0; i < 16; i++) o[i] = pack(phi2(a[32 * j + 2 * i] * rl[i & 1]), phi2(a[32 * j + 2 * i + 1] * rl[i & 1]));
      };
      auto mma = [&](int j, const uint32_t (&a)[16], float (&o)[2][20]) {
        const uint64_t db = mkdesc(j ? KVB_Z : KVB_P0, 16, 1024, 1);
        reg_zero(o[0]); reg_zero(o[1]);
        wg_fence();
        wgmma_n40_rs<0>(o[0], a[0], a[1], a[2], a[3], db, 0);
        wgmma_n40_rs<0>(o[1], a[8], a[9], a[10], a[11], db + 4, 0);
        wgmma_n40_rs<0>(o[0], a[4], a[5], a[6], a[7], db + 2, 1);
        wgmma_n40_rs<0>(o[1], a[12], a[13], a[14], a[15], db + 6, 1);
        wg_commit();
      };
      auto fin = [&](int j, int m, float (&o)[2][20]) {
#pragma unroll
        for (int h = 0; h < 2; h++) {
          const float r0 = rcp(o[h][j ? 1 : 16] + 1e-6f * LOG2E), r1 = rcp(o[h][j ? 3 : 18] + 1e-6f * LOG2E);
          const int b = j ? 4 : 0;
#pragma unroll
          for (int q = 0; q < 2; q++)
            stsm4(sw[h * 2 + q] + j * 16384 + m * 8192,
                  pack(o[h][b + 8 * q] * r0, o[h][b + 8 * q + 1] * r0), pack(o[h][b + 8 * q + 2] * r1, o[h][b + 8 * q + 3] * r1),
                  pack(o[h][b + 8 * q + 4] * r0, o[h][b + 8 * q + 5] * r0), pack(o[h][b + 8 * q + 6] * r1, o[h][b + 8 * q + 7] * r1));
        }
      };
#pragma unroll
      for (int j = 0; j < 2; j++) {
        phi(a0, j, 0, f[0]);
        if (j == 0) nb_sync(NB_KVB, 288);
        STAMP_IF(leader && j == 0, 37);
        mma(j, f[0], oc[0]);
        phi(a1, j, 1, f[1]);
        wg_wait<0>();
        reg_fence(oc[0][0]); reg_fence(oc[0][1]);
        mma(j, f[1], oc[1]);
        fin(j, 0, oc[0]);
        if (j == 0) { fence_async_smem(); nb_arrive(NB_Q0, 192); }
        wg_wait<0>();
        reg_fence(oc[1][0]); reg_fence(oc[1][1]);
        fin(j, 1, oc[1]);
        fence_async_smem();
        if (j == 0) nb_arrive(NB_OWN0, 288);
        else { nb_arrive(NB_OWN1, 256); nb_arrive(NB_H1, 160); }
        STAMP_IF(leader, 38 + j);
      }
    }
  }
}

#undef CK
typedef CUresult (*EncodeFn)(CUtensorMap*, CUtensorMapDataType, cuuint32_t, void*, const cuuint64_t*, const cuuint64_t*, const cuuint32_t*,
                             const cuuint32_t*, CUtensorMapInterleave, CUtensorMapSwizzle, CUtensorMapL2promotion, CUtensorMapFloatOOBfill);

void make_map(EncodeFn enc, CUtensorMap* m, const void* p, int rank, uint64_t d0, uint64_t d1, uint64_t d2, uint64_t s1, uint64_t s2,
              uint32_t b0, uint32_t b1, uint32_t b2, CUtensorMapSwizzle sw) {
  cuuint64_t gd[3] = {d0, d1, d2}, gs[2] = {s1, s2};
  cuuint32_t bd[3] = {b0, b1, b2}, es[3] = {1, 1, 1};
  enc(m, CU_TENSOR_MAP_DATA_TYPE_BFLOAT16, rank, const_cast<void*>(p), gd, gs, bd, es, CU_TENSOR_MAP_INTERLEAVE_NONE, sw,
      CU_TENSOR_MAP_L2_PROMOTION_L2_128B, CU_TENSOR_MAP_FLOAT_OOB_FILL_NONE);
}

}

extern "C" void kernel_launch(void* const* d_in, const int* in_sizes, int n_in, void* d_out, int out_size) {
  (void)in_sizes; (void)n_in; (void)out_size;
  void* fn = nullptr;
  cudaDriverEntryPointQueryResult qr;
  cudaGetDriverEntryPoint("cuTensorMapEncodeTiled", &fn, cudaEnableDefault, &qr);
  EncodeFn enc = (EncodeFn)fn;
  void* o;
  cudaGetSymbolAddress(&o, g_o);
  const CUtensorMapSwizzle S128 = CU_TENSOR_MAP_SWIZZLE_128B, S64 = CU_TENSOR_MAP_SWIZZLE_64B, S0 = CU_TENSOR_MAP_SWIZZLE_NONE;
  Params mp;
  mp.x = (const char*)d_in[0]; mp.wqkv = (const char*)d_in[1]; mp.w_r = (const char*)d_in[4];
  mp.wg = (const char*)d_in[5]; mp.wu = (const char*)d_in[6]; mp.wd = (const char*)d_in[7];
  make_map(enc, &mp.m_wqkv, d_in[1], 3, 64, 1024, 48, 6144, 128, 64, 64, 2, S128);
  make_map(enc, &mp.m_x, d_in[0], 2, 1024, 2048, 1, 2048, 0, 64, 128, 1, S128);
  make_map(enc, &mp.m_os, o, 2, 1024, 2048, 1, 2048, 0, 64, 64, 1, S128);
  make_map(enc, &mp.m_o, o, 2, 1024, 2048, 1, 2048, 0, 64, 128, 1, S128);
  make_map(enc, &mp.m_wo, d_in[2], 3, 64, 1024, 16, 2048, 128, 64, 64, 2, S128);
  make_map(enc, &mp.m_xs, d_in[0], 2, 1024, 2048, 1, 2048, 0, 256, 16, 1, S0);
  const char *wg = (const char*)d_in[5], *wu = (const char*)d_in[6];
  make_map(enc, &mp.m_gu, wu < wg ? wu : wg, 3, 3584, 1024, 2, 7168, (uint64_t)(wu < wg ? wg - wu : wu - wg), 32, 32, 2, S64);
  make_map(enc, &mp.m_down, d_in[7], 2, 1024, 3584, 1, 2048, 0, 64, 32, 1, S128);
  make_map(enc, &mp.m_out, d_out, 2, 1024, 2048, 1, 2048, 0, 64, 16, 1, S128);
  int dev = 0, sms = 0;
  cudaGetDevice(&dev);
  cudaDeviceGetAttribute(&sms, cudaDevAttrMultiProcessorCount, dev);
  auto kern = sms == 132 ? fused_kernel<true> : fused_kernel<false>;
  cudaFuncSetAttribute(kern, cudaFuncAttributeMaxDynamicSharedMemorySize, SMEM_BYTES);
  kern<<<132, 512, SMEM_BYTES>>>(mp);
}
```

```cpp
#include <cuda_runtime.h>
#include <cuda.h>
#include <cuda_bf16.h>
#include <stdint.h>

namespace {

template <int TA, int TB>
__device__ __forceinline__ void wgmma_n8_ss(float (&d)[4], uint64_t da, uint64_t db, int sc) {
  asm volatile("{\n.reg .pred p;\nsetp.ne.b32 p, %6, 0;\n"
    "wgmma.mma_async.sync.aligned.m64n8k16.f32.bf16.bf16 {%0, %1, %2, %3}, %4, %5, p, 1, 1, %7, %8;\n}\n"
    : "+f"(d[0]), "+f"(d[1]), "+f"(d[2]), "+f"(d[3])
    : "l"(da), "l"(db), "r"(sc), "n"(TA), "n"(TB));
}
template <int TB>
__device__ __forceinline__ void wgmma_n40_rs(float (&d)[20], uint32_t a0, uint32_t a1, uint32_t a2, uint32_t a3, uint64_t db, int sc) {
  asm volatile("{\n.reg .pred p;\nsetp.ne.b32 p, %25, 0;\n"
    "wgmma.mma_async.sync.aligned.m64n40k16.f32.bf16.bf16 {%0, %1, %2, %3, %4, %5, %6, %7, %8, %9, %10, %11, %12, %13, %14, %15, %16, %17, %18, %19}, {%20,%21,%22,%23}, %24, p, 1, 1, %26;\n}\n"
    : "+f"(d[0]), "+f"(d[1]), "+f"(d[2]), "+f"(d[3]), "+f"(d[4]), "+f"(d[5]), "+f"(d[6]), "+f"(d[7]),
      "+f"(d[8]), "+f"(d[9]), "+f"(d[10]), "+f"(d[11]), "+f"(d[12]), "+f"(d[13]), "+f"(d[14]), "+f"(d[15]),
      "+f"(d[16]), "+f"(d[17]), "+f"(d[18]), "+f"(d[19])
    : "r"(a0), "r"(a1), "r"(a2), "r"(a3), "l"(db), "r"(sc), "n"(TB));
}
template <int TB>
__device__ __forceinline__ void wgmma_n64_rs(float (&d)[32], uint32_t a0, uint32_t a1, uint32_t a2, uint32_t a3, uint64_t db, int sc) {
  asm volatile("{\n.reg .pred p;\nsetp.ne.b32 p, %37, 0;\n"
    "wgmma.mma_async.sync.aligned.m64n64k16.f32.bf16.bf16 {%0, %1, %2, %3, %4, %5, %6, %7, %8, %9, %10, %11, %12, %13, %14, %15, %16, %17, %18, %19, %20, %21, %22, %23, %24, %25, %26, %27, %28, %29, %30, %31}, {%32,%33,%34,%35}, %36, p, 1, 1, %38;\n}\n"
    : "+f"(d[0]), "+f"(d[1]), "+f"(d[2]), "+f"(d[3]), "+f"(d[4]), "+f"(d[5]), "+f"(d[6]), "+f"(d[7]),
      "+f"(d[8]), "+f"(d[9]), "+f"(d[10]), "+f"(d[11]), "+f"(d[12]), "+f"(d[13]), "+f"(d[14]), "+f"(d[15]),
      "+f"(d[16]), "+f"(d[17]), "+f"(d[18]), "+f"(d[19]), "+f"(d[20]), "+f"(d[21]), "+f"(d[22]), "+f"(d[23]),
      "+f"(d[24]), "+f"(d[25]), "+f"(d[26]), "+f"(d[27]), "+f"(d[28]), "+f"(d[29]), "+f"(d[30]), "+f"(d[31])
    : "r"(a0), "r"(a1), "r"(a2), "r"(a3), "l"(db), "r"(sc), "n"(TB));
}
template <int TA, int TB>
__device__ __forceinline__ void wgmma_n128_ss(float (&d)[64], uint64_t da, uint64_t db, int sc) {
  asm volatile("{\n.reg .pred p;\nsetp.ne.b32 p, %66, 0;\n"
    "wgmma.mma_async.sync.aligned.m64n128k16.f32.bf16.bf16 {%0, %1, %2, %3, %4, %5, %6, %7, %8, %9, %10, %11, %12, %13, %14, %15, %16, %17, %18, %19, %20, %21, %22, %23, %24, %25, %26, %27, %28, %29, %30, %31, %32, %33, %34, %35, %36, %37, %38, %39, %40, %41, %42, %43, %44, %45, %46, %47, %48, %49, %50, %51, %52, %53, %54, %55, %56, %57, %58, %59, %60, %61, %62, %63}, %64, %65, p, 1, 1, %67, %68;\n}\n"
    : "+f"(d[0]), "+f"(d[1]), "+f"(d[2]), "+f"(d[3]), "+f"(d[4]), "+f"(d[5]), "+f"(d[6]), "+f"(d[7]),
      "+f"(d[8]), "+f"(d[9]), "+f"(d[10]), "+f"(d[11]), "+f"(d[12]), "+f"(d[13]), "+f"(d[14]), "+f"(d[15]),
      "+f"(d[16]), "+f"(d[17]), "+f"(d[18]), "+f"(d[19]), "+f"(d[20]), "+f"(d[21]), "+f"(d[22]), "+f"(d[23]),
      "+f"(d[24]), "+f"(d[25]), "+f"(d[26]), "+f"(d[27]), "+f"(d[28]), "+f"(d[29]), "+f"(d[30]), "+f"(d[31]),
      "+f"(d[32]), "+f"(d[33]), "+f"(d[34]), "+f"(d[35]), "+f"(d[36]), "+f"(d[37]), "+f"(d[38]), "+f"(d[39]),
      "+f"(d[40]), "+f"(d[41]), "+f"(d[42]), "+f"(d[43]), "+f"(d[44]), "+f"(d[45]), "+f"(d[46]), "+f"(d[47]),
      "+f"(d[48]), "+f"(d[49]), "+f"(d[50]), "+f"(d[51]), "+f"(d[52]), "+f"(d[53]), "+f"(d[54]), "+f"(d[55]),
      "+f"(d[56]), "+f"(d[57]), "+f"(d[58]), "+f"(d[59]), "+f"(d[60]), "+f"(d[61]), "+f"(d[62]), "+f"(d[63])
    : "l"(da), "l"(db), "r"(sc), "n"(TA), "n"(TB));
}
template <int TB>
__device__ __forceinline__ void wgmma_n128_rs(float (&d)[64], uint32_t a0, uint32_t a1, uint32_t a2, uint32_t a3, uint64_t db, int sc) {
  asm volatile("{\n.reg .pred p;\nsetp.ne.b32 p, %69, 0;\n"
    "wgmma.mma_async.sync.aligned.m64n128k16.f32.bf16.bf16 {%0, %1, %2, %3, %4, %5, %6, %7, %8, %9, %10, %11, %12, %13, %14, %15, %16, %17, %18, %19, %20, %21, %22, %23, %24, %25, %26, %27, %28, %29, %30, %31, %32, %33, %34, %35, %36, %37, %38, %39, %40, %41, %42, %43, %44, %45, %46, %47, %48, %49, %50, %51, %52, %53, %54, %55, %56, %57, %58, %59, %60, %61, %62, %63}, {%64,%65,%66,%67}, %68, p, 1, 1, %70;\n}\n"
    : "+f"(d[0]), "+f"(d[1]), "+f"(d[2]), "+f"(d[3]), "+f"(d[4]), "+f"(d[5]), "+f"(d[6]), "+f"(d[7]),
      "+f"(d[8]), "+f"(d[9]), "+f"(d[10]), "+f"(d[11]), "+f"(d[12]), "+f"(d[13]), "+f"(d[14]), "+f"(d[15]),
      "+f"(d[16]), "+f"(d[17]), "+f"(d[18]), "+f"(d[19]), "+f"(d[20]), "+f"(d[21]), "+f"(d[22]), "+f"(d[23]),
      "+f"(d[24]), "+f"(d[25]), "+f"(d[26]), "+f"(d[27]), "+f"(d[28]), "+f"(d[29]), "+f"(d[30]), "+f"(d[31]),
      "+f"(d[32]), "+f"(d[33]), "+f"(d[34]), "+f"(d[35]), "+f"(d[36]), "+f"(d[37]), "+f"(d[38]), "+f"(d[39]),
      "+f"(d[40]), "+f"(d[41]), "+f"(d[42]), "+f"(d[43]), "+f"(d[44]), "+f"(d[45]), "+f"(d[46]), "+f"(d[47]),
      "+f"(d[48]), "+f"(d[49]), "+f"(d[50]), "+f"(d[51]), "+f"(d[52]), "+f"(d[53]), "+f"(d[54]), "+f"(d[55]),
      "+f"(d[56]), "+f"(d[57]), "+f"(d[58]), "+f"(d[59]), "+f"(d[60]), "+f"(d[61]), "+f"(d[62]), "+f"(d[63])
    : "r"(a0), "r"(a1), "r"(a2), "r"(a3), "l"(db), "r"(sc), "n"(TB));
}

__device__ __forceinline__ void poll1(uint32_t (&v)[1], const void* p, uint32_t tag, uint32_t mask) {
  asm volatile("{\n.reg .pred p, q;\n.reg .u32 c, b;\n.reg .b64 x, y;\n.reg .b128 z;\nmov.u32 c, 0;\nLW:\n"
               "ld.relaxed.gpu.global.u32 %0, [%1+0];\n"
               "xor.b32 b, %0, %2;\n"
               "and.b32 b, b, %3;\nsetp.eq.u32 p, b, 0;\nvote.sync.all.pred p, p, 0xffffffff;\n@p bra.uni LD;\n"
               "nanosleep.u32 100;\nadd.u32 c, c, 1;\nsetp.lt.u32 q, c, 1000000;\n@q bra.uni LW;\ntrap;\nLD:\n}"
               : "=&r"(v[0])
               : "l"(p), "r"(tag), "r"(mask) : "memory");
}
__device__ __forceinline__ void poll1f(uint32_t (&v)[1], const void* p, uint32_t tag, uint32_t mask) {
  asm volatile("{\n.reg .pred p, q;\n.reg .u32 c, b;\n.reg .b64 x, y;\n.reg .b128 z;\nmov.u32 c, 0;\nLW:\n"
               "ld.relaxed.gpu.global.u32 %0, [%1+0];\n"
               "xor.b32 b, %0, %2;\n"
               "and.b32 b, b, %3;\nsetp.eq.u32 p, b, 0;\nvote.sync.all.pred p, p, 0xffffffff;\n@p bra.uni LD;\n"
               "nanosleep.u32 50;\nadd.u32 c, c, 1;\nsetp.lt.u32 q, c, 1000000;\n@q bra.uni LW;\ntrap;\nLD:\n}"
               : "=&r"(v[0])
               : "l"(p), "r"(tag), "r"(mask) : "memory");
}
__device__ __forceinline__ void poll0(uint32_t (&v)[1], const void* p, uint32_t tag, uint32_t mask) {
  asm volatile("{\n.reg .pred p, q;\n.reg .u32 c, b;\n.reg .b64 x, y;\n.reg .b128 z;\nmov.u32 c, 0;\nLW:\n"
               "ld.relaxed.gpu.global.u32 %0, [%1+0];\n"
               "xor.b32 b, %0, %2;\n"
               "and.b32 b, b, %3;\nsetp.eq.u32 p, b, 0;\nvote.sync.all.pred p, p, 0xffffffff;\n@p bra.uni LD;\n"
               "add.u32 c, c, 1;\nsetp.lt.u32 q, c, 1000000;\n@q bra.uni LW;\ntrap;\nLD:\n}"
               : "=&r"(v[0])
               : "l"(p), "r"(tag), "r"(mask) : "memory");
}
__device__ __forceinline__ void poll_pair(uint32_t (&v)[2], const void* p, uint32_t tag, uint32_t mask) {
  asm volatile("{\n.reg .pred p, q;\n.reg .u32 c, b;\n.reg .b64 x, y;\n.reg .b128 z;\nmov.u32 c, 0;\nLW:\n"
               "ld.relaxed.gpu.global.b64 x, [%2+0];\nmov.b64 {%0,%1}, x;\n"
               "xor.b32 b, %0, %3;\n"
               "and.b32 b, b, %4;\nsetp.eq.u32 p, b, 0;\nvote.sync.all.pred p, p, 0xffffffff;\n@p bra.uni LD;\n"
               "nanosleep.u32 100;\nadd.u32 c, c, 1;\nsetp.lt.u32 q, c, 1000000;\n@q bra.uni LW;\ntrap;\nLD:\n}"
               : "=&r"(v[0]), "=&r"(v[1])
               : "l"(p), "r"(tag), "r"(mask) : "memory");
}
__device__ __forceinline__ void poll_quad(uint32_t (&v)[4], const void* p, uint32_t tag, uint32_t mask) {
  asm volatile("{\n.reg .pred p, q;\n.reg .u32 c, b;\n.reg .b64 x, y;\n.reg .b128 z;\nmov.u32 c, 0;\nLW:\n"
               "ld.relaxed.gpu.global.v4.u32 {%0,%1,%2,%3}, [%4+0];\n"
               "xor.b32 b, %0, %5;\n"
               "lop3.b32 b, b, %1, %5, 0xf6;\nlop3.b32 b, b, %2, %5, 0xf6;\nlop3.b32 b, b, %3, %5, 0xf6;\n"
               "and.b32 b, b, %6;\nsetp.eq.u32 p, b, 0;\nvote.sync.all.pred p, p, 0xffffffff;\n@p bra.uni LD;\n"
               "nanosleep.u32 200;\nadd.u32 c, c, 1;\nsetp.lt.u32 q, c, 1000000;\n@q bra.uni LW;\ntrap;\nLD:\n}"
               : "=&r"(v[0]), "=&r"(v[1]), "=&r"(v[2]), "=&r"(v[3])
               : "l"(p), "r"(tag), "r"(mask) : "memory");
}
__device__ __forceinline__ void poll8x4(uint32_t (&v)[32], const void* p, uint32_t tag, uint32_t mask) {
  asm volatile("{\n.reg .pred p, q;\n.reg .u32 c, b;\n.reg .b64 x, y;\n.reg .b128 z;\nmov.u32 c, 0;\nLW:\n"
               "ld.relaxed.gpu.global.v4.u32 {%0,%1,%2,%3}, [%32+0];\n"
               "ld.relaxed.gpu.global.v4.u32 {%4,%5,%6,%7}, [%32+2048];\n"
               "ld.relaxed.gpu.global.v4.u32 {%8,%9,%10,%11}, [%32+4096];\n"
               "ld.relaxed.gpu.global.v4.u32 {%12,%13,%14,%15}, [%32+6144];\n"
               "ld.relaxed.gpu.global.v4.u32 {%16,%17,%18,%19}, [%32+8192];\n"
               "ld.relaxed.gpu.global.v4.u32 {%20,%21,%22,%23}, [%32+10240];\n"
               "ld.relaxed.gpu.global.v4.u32 {%24,%25,%26,%27}, [%32+12288];\n"
               "ld.relaxed.gpu.global.v4.u32 {%28,%29,%30,%31}, [%32+14336];\n"
               "xor.b32 b, %0, %33;\n"
               "lop3.b32 b, b, %1, %33, 0xf6;\nlop3.b32 b, b, %2, %33, 0xf6;\nlop3.b32 b, b, %3, %33, 0xf6;\nlop3.b32 b, b, %4, %33, 0xf6;\n"
               "lop3.b32 b, b, %5, %33, 0xf6;\nlop3.b32 b, b, %6, %33, 0xf6;\nlop3.b32 b, b, %7, %33, 0xf6;\nlop3.b32 b, b, %8, %33, 0xf6;\n"
               "lop3.b32 b, b, %9, %33, 0xf6;\nlop3.b32 b, b, %10, %33, 0xf6;\nlop3.b32 b, b, %11, %33, 0xf6;\nlop3.b32 b, b, %12, %33, 0xf6;\n"
               "lop3.b32 b, b, %13, %33, 0xf6;\nlop3.b32 b, b, %14, %33, 0xf6;\nlop3.b32 b, b, %15, %33, 0xf6;\nlop3.b32 b, b, %16, %33, 0xf6;\n"
               "lop3.b32 b, b, %17, %33, 0xf6;\nlop3.b32 b, b, %18, %33, 0xf6;\nlop3.b32 b, b, %19, %33, 0xf6;\nlop3.b32 b, b, %20, %33, 0xf6;\n"
               "lop3.b32 b, b, %21, %33, 0xf6;\nlop3.b32 b, b, %22, %33, 0xf6;\nlop3.b32 b, b, %23, %33, 0xf6;\nlop3.b32 b, b, %24, %33, 0xf6;\n"
               "lop3.b32 b, b, %25, %33, 0xf6;\nlop3.b32 b, b, %26, %33, 0xf6;\nlop3.b32 b, b, %27, %33, 0xf6;\nlop3.b32 b, b, %28, %33, 0xf6;\n"
               "lop3.b32 b, b, %29, %33, 0xf6;\nlop3.b32 b, b, %30, %33, 0xf6;\nlop3.b32 b, b, %31, %33, 0xf6;\n"
               "and.b32 b, b, %34;\nsetp.eq.u32 p, b, 0;\nvote.sync.all.pred p, p, 0xffffffff;\n@p bra.uni LD;\n"
               "nanosleep.u32 50;\nadd.u32 c, c, 1;\nsetp.lt.u32 q, c, 1000000;\n@q bra.uni LW;\ntrap;\nLD:\n}"
               : "=&r"(v[0]), "=&r"(v[1]), "=&r"(v[2]), "=&r"(v[3]), "=&r"(v[4]), "=&r"(v[5]), "=&r"(v[6]), "=&r"(v[7]), "=&r"(v[8]), "=&r"(v[9]), "=&r"(v[10]), "=&r"(v[11]), "=&r"(v[12]), "=&r"(v[13]), "=&r"(v[14]), "=&r"(v[15]), "=&r"(v[16]), "=&r"(v[17]), "=&r"(v[18]), "=&r"(v[19]), "=&r"(v[20]), "=&r"(v[21]), "=&r"(v[22]), "=&r"(v[23]), "=&r"(v[24]), "=&r"(v[25]), "=&r"(v[26]), "=&r"(v[27]), "=&r"(v[28]), "=&r"(v[29]), "=&r"(v[30]), "=&r"(v[31])
               : "l"(p), "r"(tag), "r"(mask) : "memory");
}
__device__ __forceinline__ void poll16(uint32_t (&v)[16], const void* p, uint32_t tag, uint32_t mask) {
  asm volatile("{\n.reg .pred p, q;\n.reg .u32 c, b;\n.reg .b64 x, y;\n.reg .b128 z;\nmov.u32 c, 0;\nLW:\n"
               "ld.relaxed.gpu.global.u32 %0, [%16+0];\n"
               "ld.relaxed.gpu.global.u32 %1, [%16+4096];\n"
               "ld.relaxed.gpu.global.u32 %2, [%16+8192];\n"
               "ld.relaxed.gpu.global.u32 %3, [%16+12288];\n"
               "ld.relaxed.gpu.global.u32 %4, [%16+16384];\n"
               "ld.relaxed.gpu.global.u32 %5, [%16+20480];\n"
               "ld.relaxed.gpu.global.u32 %6, [%16+24576];\n"
               "ld.relaxed.gpu.global.u32 %7, [%16+28672];\n"
               "ld.relaxed.gpu.global.u32 %8, [%16+32768];\n"
               "ld.relaxed.gpu.global.u32 %9, [%16+36864];\n"
               "ld.relaxed.gpu.global.u32 %10, [%16+40960];\n"
               "ld.relaxed.gpu.global.u32 %11, [%16+45056];\n"
               "ld.relaxed.gpu.global.u32 %12, [%16+49152];\n"
               "ld.relaxed.gpu.global.u32 %13, [%16+53248];\n"
               "ld.relaxed.gpu.global.u32 %14, [%16+57344];\n"
               "ld.relaxed.gpu.global.u32 %15, [%16+61440];\n"
               "xor.b32 b, %0, %17;\n"
               "lop3.b32 b, b, %1, %17, 0xf6;\nlop3.b32 b, b, %2, %17, 0xf6;\nlop3.b32 b, b, %3, %17, 0xf6;\nlop3.b32 b, b, %4, %17, 0xf6;\n"
               "lop3.b32 b, b, %5, %17, 0xf6;\nlop3.b32 b, b, %6, %17, 0xf6;\nlop3.b32 b, b, %7, %17, 0xf6;\nlop3.b32 b, b, %8, %17, 0xf6;\n"
               "lop3.b32 b, b, %9, %17, 0xf6;\nlop3.b32 b, b, %10, %17, 0xf6;\nlop3.b32 b, b, %11, %17, 0xf6;\nlop3.b32 b, b, %12, %17, 0xf6;\n"
               "lop3.b32 b, b, %13, %17, 0xf6;\nlop3.b32 b, b, %14, %17, 0xf6;\nlop3.b32 b, b, %15, %17, 0xf6;\n"
               "and.b32 b, b, %18;\nsetp.eq.u32 p, b, 0;\nvote.sync.all.pred p, p, 0xffffffff;\n@p bra.uni LD;\n"
               "nanosleep.u32 200;\nadd.u32 c, c, 1;\nsetp.lt.u32 q, c, 1000000;\n@q bra.uni LW;\ntrap;\nLD:\n}"
               : "=&r"(v[0]), "=&r"(v[1]), "=&r"(v[2]), "=&r"(v[3]), "=&r"(v[4]), "=&r"(v[5]), "=&r"(v[6]), "=&r"(v[7]), "=&r"(v[8]), "=&r"(v[9]), "=&r"(v[10]), "=&r"(v[11]), "=&r"(v[12]), "=&r"(v[13]), "=&r"(v[14]), "=&r"(v[15])
               : "l"(p), "r"(tag), "r"(mask) : "memory");
}
__device__ __forceinline__ void poll_keys(uint32_t (&v)[16], const void* p, uint32_t tag, uint32_t mask) {
  asm volatile("{\n.reg .pred p, q;\n.reg .u32 c, b;\n.reg .b64 x, y;\n.reg .b128 z;\nmov.u32 c, 0;\nLW:\n"
               "ld.relaxed.gpu.global.v2.b64 {x, y}, [%16+0];\nmov.b64 {%0,%1}, x;\nmov.b64 {%2,%3}, y;\n"
               "ld.relaxed.gpu.global.v2.b64 {x, y}, [%16+4096];\nmov.b64 {%4,%5}, x;\nmov.b64 {%6,%7}, y;\n"
               "ld.relaxed.gpu.global.v2.b64 {x, y}, [%16+8192];\nmov.b64 {%8,%9}, x;\nmov.b64 {%10,%11}, y;\n"
               "ld.relaxed.gpu.global.v2.b64 {x, y}, [%16+12288];\nmov.b64 {%12,%13}, x;\nmov.b64 {%14,%15}, y;\n"
               "xor.b32 b, %0, %17;\n"
               "lop3.b32 b, b, %2, %17, 0xf6;\nlop3.b32 b, b, %4, %17, 0xf6;\nlop3.b32 b, b, %6, %17, 0xf6;\nlop3.b32 b, b, %8, %17, 0xf6;\n"
               "lop3.b32 b, b, %10, %17, 0xf6;\nlop3.b32 b, b, %12, %17, 0xf6;\nlop3.b32 b, b, %14, %17, 0xf6;\n"
               "and.b32 b, b, %18;\nsetp.eq.u32 p, b, 0;\nvote.sync.all.pred p, p, 0xffffffff;\n@p bra.uni LD;\n"
               "nanosleep.u32 20;\nadd.u32 c, c, 1;\nsetp.lt.u32 q, c, 1000000;\n@q bra.uni LW;\ntrap;\nLD:\n}"
               : "=&r"(v[0]), "=&r"(v[1]), "=&r"(v[2]), "=&r"(v[3]), "=&r"(v[4]), "=&r"(v[5]), "=&r"(v[6]), "=&r"(v[7]), "=&r"(v[8]), "=&r"(v[9]), "=&r"(v[10]), "=&r"(v[11]), "=&r"(v[12]), "=&r"(v[13]), "=&r"(v[14]), "=&r"(v[15])
               : "l"(p), "r"(tag), "r"(mask) : "memory");
}
__device__ __forceinline__ void poll_z(uint32_t (&v)[16], const void* p, uint32_t tag, uint32_t mask) {
  asm volatile("{\n.reg .pred p, q;\n.reg .u32 c, b;\n.reg .b64 x, y;\n.reg .b128 z;\nmov.u32 c, 0;\nLW:\n"
               "ld.relaxed.gpu.global.v4.u32 {%0,%1,%2,%3}, [%16+0];\n"
               "ld.relaxed.gpu.global.v4.u32 {%4,%5,%6,%7}, [%16+4096];\n"
               "ld.relaxed.gpu.global.v4.u32 {%8,%9,%10,%11}, [%16+8192];\n"
               "ld.relaxed.gpu.global.v4.u32 {%12,%13,%14,%15}, [%16+12288];\n"
               "xor.b32 b, %0, %17;\n"
               "lop3.b32 b, b, %1, %17, 0xf6;\nlop3.b32 b, b, %2, %17, 0xf6;\nlop3.b32 b, b, %3, %17, 0xf6;\nlop3.b32 b, b, %4, %17, 0xf6;\n"
               "lop3.b32 b, b, %5, %17, 0xf6;\nlop3.b32 b, b, %6, %17, 0xf6;\nlop3.b32 b, b, %7, %17, 0xf6;\nlop3.b32 b, b, %8, %17, 0xf6;\n"
               "lop3.b32 b, b, %9, %17, 0xf6;\nlop3.b32 b, b, %10, %17, 0xf6;\nlop3.b32 b, b, %11, %17, 0xf6;\nlop3.b32 b, b, %12, %17, 0xf6;\n"
               "lop3.b32 b, b, %13, %17, 0xf6;\nlop3.b32 b, b, %14, %17, 0xf6;\nlop3.b32 b, b, %15, %17, 0xf6;\n"
               "and.b32 b, b, %18;\nsetp.eq.u32 p, b, 0;\nvote.sync.all.pred p, p, 0xffffffff;\n@p bra.uni LD;\n"
               "nanosleep.u32 300;\nadd.u32 c, c, 1;\nsetp.lt.u32 q, c, 1000000;\n@q bra.uni LW;\ntrap;\nLD:\n}"
               : "=&r"(v[0]), "=&r"(v[1]), "=&r"(v[2]), "=&r"(v[3]), "=&r"(v[4]), "=&r"(v[5]), "=&r"(v[6]), "=&r"(v[7]), "=&r"(v[8]), "=&r"(v[9]), "=&r"(v[10]), "=&r"(v[11]), "=&r"(v[12]), "=&r"(v[13]), "=&r"(v[14]), "=&r"(v[15])
               : "l"(p), "r"(tag), "r"(mask) : "memory");
}
__device__ __forceinline__ void poll7x4(uint32_t (&v)[28], const void* p, uint32_t tag, uint32_t mask) {
  asm volatile("{\n.reg .pred p, q;\n.reg .u32 c, b;\n.reg .b64 x, y;\n.reg .b128 z;\nmov.u32 c, 0;\nLW:\n"
               "ld.relaxed.gpu.global.v4.u32 {%0,%1,%2,%3}, [%28+0];\n"
               "ld.relaxed.gpu.global.v4.u32 {%4,%5,%6,%7}, [%28+2048];\n"
               "ld.relaxed.gpu.global.v4.u32 {%8,%9,%10,%11}, [%28+4096];\n"
               "ld.relaxed.gpu.global.v4.u32 {%12,%13,%14,%15}, [%28+6144];\n"
               "ld.relaxed.gpu.global.v4.u32 {%16,%17,%18,%19}, [%28+8192];\n"
               "ld.relaxed.gpu.global.v4.u32 {%20,%21,%22,%23}, [%28+10240];\n"
               "ld.relaxed.gpu.global.v4.u32 {%24,%25,%26,%27}, [%28+12288];\n"
               "xor.b32 b, %0, %29;\n"
               "lop3.b32 b, b, %1, %29, 0xf6;\nlop3.b32 b, b, %2, %29, 0xf6;\nlop3.b32 b, b, %3, %29, 0xf6;\nlop3.b32 b, b, %4, %29, 0xf6;\n"
               "lop3.b32 b, b, %5, %29, 0xf6;\nlop3.b32 b, b, %6, %29, 0xf6;\nlop3.b32 b, b, %7, %29, 0xf6;\nlop3.b32 b, b, %8, %29, 0xf6;\n"
               "lop3.b32 b, b, %9, %29, 0xf6;\nlop3.b32 b, b, %10, %29, 0xf6;\nlop3.b32 b, b, %11, %29, 0xf6;\nlop3.b32 b, b, %12, %29, 0xf6;\n"
               "lop3.b32 b, b, %13, %29, 0xf6;\nlop3.b32 b, b, %14, %29, 0xf6;\nlop3.b32 b, b, %15, %29, 0xf6;\nlop3.b32 b, b, %16, %29, 0xf6;\n"
               "lop3.b32 b, b, %17, %29, 0xf6;\nlop3.b32 b, b, %18, %29, 0xf6;\nlop3.b32 b, b, %19, %29, 0xf6;\nlop3.b32 b, b, %20, %29, 0xf6;\n"
               "lop3.b32 b, b, %21, %29, 0xf6;\nlop3.b32 b, b, %22, %29, 0xf6;\nlop3.b32 b, b, %23, %29, 0xf6;\nlop3.b32 b, b, %24, %29, 0xf6;\n"
               "lop3.b32 b, b, %25, %29, 0xf6;\nlop3.b32 b, b, %26, %29, 0xf6;\nlop3.b32 b, b, %27, %29, 0xf6;\n"
               "and.b32 b, b, %30;\nsetp.eq.u32 p, b, 0;\nvote.sync.all.pred p, p, 0xffffffff;\n@p bra.uni LD;\n"
               "nanosleep.u32 50;\nadd.u32 c, c, 1;\nsetp.lt.u32 q, c, 1000000;\n@q bra.uni LW;\ntrap;\nLD:\n}"
               : "=&r"(v[0]), "=&r"(v[1]), "=&r"(v[2]), "=&r"(v[3]), "=&r"(v[4]), "=&r"(v[5]), "=&r"(v[6]), "=&r"(v[7]), "=&r"(v[8]), "=&r"(v[9]), "=&r"(v[10]), "=&r"(v[11]), "=&r"(v[12]), "=&r"(v[13]), "=&r"(v[14]), "=&r"(v[15]), "=&r"(v[16]), "=&r"(v[17]), "=&r"(v[18]), "=&r"(v[19]), "=&r"(v[20]), "=&r"(v[21]), "=&r"(v[22]), "=&r"(v[23]), "=&r"(v[24]), "=&r"(v[25]), "=&r"(v[26]), "=&r"(v[27])
               : "l"(p), "r"(tag), "r"(mask) : "memory");
}
__device__ __forceinline__ void poll_kvp(uint32_t (&v)[16], const void* p, uint32_t tag, uint32_t mask) {
  asm volatile("{\n.reg .pred p, q;\n.reg .u32 c, b;\n.reg .b64 x, y;\n.reg .b128 z;\nmov.u32 c, 0;\nLW:\n"
               "ld.relaxed.gpu.global.b128 z, [%16+0];\nmov.b128 {x, y}, z;\nmov.b64 {%0,%1}, x;\nmov.b64 {%2,%3}, y;\n"
               "ld.relaxed.gpu.global.b128 z, [%16+8192];\nmov.b128 {x, y}, z;\nmov.b64 {%4,%5}, x;\nmov.b64 {%6,%7}, y;\n"
               "ld.relaxed.gpu.global.b128 z, [%16+16384];\nmov.b128 {x, y}, z;\nmov.b64 {%8,%9}, x;\nmov.b64 {%10,%11}, y;\n"
               "ld.relaxed.gpu.global.b128 z, [%16+24576];\nmov.b128 {x, y}, z;\nmov.b64 {%12,%13}, x;\nmov.b64 {%14,%15}, y;\n"
               "xor.b32 b, %0, %17;\n"
               "lop3.b32 b, b, %4, %17, 0xf6;\nlop3.b32 b, b, %8, %17, 0xf6;\nlop3.b32 b, b, %12, %17, 0xf6;\n"
               "and.b32 b, b, %18;\nsetp.eq.u32 p, b, 0;\nvote.sync.all.pred p, p, 0xffffffff;\n@p bra.uni LD;\n"
               "nanosleep.u32 50;\nadd.u32 c, c, 1;\nsetp.lt.u32 q, c, 1000000;\n@q bra.uni LW;\ntrap;\nLD:\n}"
               : "=&r"(v[0]), "=&r"(v[1]), "=&r"(v[2]), "=&r"(v[3]), "=&r"(v[4]), "=&r"(v[5]), "=&r"(v[6]), "=&r"(v[7]), "=&r"(v[8]), "=&r"(v[9]), "=&r"(v[10]), "=&r"(v[11]), "=&r"(v[12]), "=&r"(v[13]), "=&r"(v[14]), "=&r"(v[15])
               : "l"(p), "r"(tag), "r"(mask) : "memory");
}
__device__ __forceinline__ void poll_kv(uint32_t (&v)[16], const void* p, uint32_t tag, uint32_t mask) {
  asm volatile("{\n.reg .pred p, q;\n.reg .u32 c, b;\n.reg .b64 x, y;\n.reg .b128 z;\nmov.u32 c, 0;\nLW:\n"
               "ld.relaxed.gpu.global.b128 z, [%16+0];\nmov.b128 {x, y}, z;\nmov.b64 {%0,%1}, x;\nmov.b64 {%2,%3}, y;\n"
               "ld.relaxed.gpu.global.b128 z, [%16+2048];\nmov.b128 {x, y}, z;\nmov.b64 {%4,%5}, x;\nmov.b64 {%6,%7}, y;\n"
               "ld.relaxed.gpu.global.b128 z, [%16+4096];\nmov.b128 {x, y}, z;\nmov.b64 {%8,%9}, x;\nmov.b64 {%10,%11}, y;\n"
               "ld.relaxed.gpu.global.b128 z, [%16+6144];\nmov.b128 {x, y}, z;\nmov.b64 {%12,%13}, x;\nmov.b64 {%14,%15}, y;\n"
               "xor.b32 b, %0, %17;\n"
               "lop3.b32 b, b, %4, %17, 0xf6;\nlop3.b32 b, b, %8, %17, 0xf6;\nlop3.b32 b, b, %12, %17, 0xf6;\n"
               "and.b32 b, b, %18;\nsetp.eq.u32 p, b, 0;\nvote.sync.all.pred p, p, 0xffffffff;\n@p bra.uni LD;\n"
               "nanosleep.u32 50;\nadd.u32 c, c, 1;\nsetp.lt.u32 q, c, 1000000;\n@q bra.uni LW;\ntrap;\nLD:\n}"
               : "=&r"(v[0]), "=&r"(v[1]), "=&r"(v[2]), "=&r"(v[3]), "=&r"(v[4]), "=&r"(v[5]), "=&r"(v[6]), "=&r"(v[7]), "=&r"(v[8]), "=&r"(v[9]), "=&r"(v[10]), "=&r"(v[11]), "=&r"(v[12]), "=&r"(v[13]), "=&r"(v[14]), "=&r"(v[15])
               : "l"(p), "r"(tag), "r"(mask) : "memory");
}

__device__ __align__(1024) __nv_bfloat16 g_o[2048 * 1024];
__device__ __align__(128) uint2 g_keys[2048];
__device__ __align__(128) uint32_t g_csum[18 * 1024];
__device__ __align__(128) uint32_t g_z[16 * 1024];
__device__ __align__(128) uint4 g_kvp[128 * 512];
__device__ __align__(128) uint4 g_kv[8 * 512];
__device__ __align__(128) uint32_t g_h[112 * 256];
__device__ __align__(128) uint32_t g_yp[128 * 512];
__device__ __align__(128) uint32_t g_xsel[4096 + 32];
enum { H_CS = 0, H_KVP = 8, H_KV = 16, H_H = 24, H_Y = 32, H_O = 40, H_R = 56, H_Z = 57 };
__device__ __align__(128) uint32_t g_sig[65 * 32];
__device__ uint32_t g_epoch;

constexpr uint32_t RING = 1024, SLOT = 32768, SMEM_BYTES = 232448;
constexpr int NST = 5, HST = 7;
constexpr uint32_t STG = RING + 163840, AUX = RING + 196608, FR = RING + 212992, MISC = RING + 229376;
constexpr uint32_t B_FULL = MISC, B_EMPTY = MISC + 56, B_XS = MISC + 112, B_SEL = MISC + 144, B_XRES = MISC + 152, B_WK = MISC + 160, B_CSDN = MISC + 168,
                   B_FR = MISC + 176, B_FE = MISC + 216, B_DR = MISC + 256, B_CSV = MISC + 288,
                   B_OWN = MISC + 296, NBAR = 39;
constexpr uint32_t S_EPOCH = MISC + 352, S_NCAND = MISC + 356, S_SEL = MISC + 368, S_WMAX = MISC + 400,
                   S_KSTAT = MISC + 512, S_CSK = MISC + 1536, S_CSV = MISC + 2048, S_CSQ = MISC + 2560, S_ONES = MISC + 512;
constexpr uint32_t KVB_P0 = AUX, KVB_Z = AUX + 4096, KVB_P1 = AUX + 5120, HOP = AUX + 9216, GR = FR - 4096;
enum { NB_Z = 0, NB_KV = 1, NB_VQ = 2, NB_WG0 = 3, NB_FDONE = 4, NB_PK = 5, NB_KVB = 6, NB_WG1 = 7, NB_WG2 = 8, NB_CSQ = 9,
       NB_Y = 10, NB_ST = 11, NB_OWN0 = 12, NB_OWN1 = 13, NB_Q0 = 14, NB_H1 = 15 };

#define XS_AT 0
#define XS_FLY 2
#define H_DELAY 500
#define FFN_GAP 400
#define GATE_KT 1
#define GATE_K 6
#define KV_DIRECT 1
#define ALIGN 0
#define DN_GAP 50
#define PF_GAP 200
constexpr uint64_t EVICT_FIRST = 0x12f0000000000000ull;
constexpr float LOG2E = 1.4426950408889634f, LN2 = 0.6931471805599453f;

#define ELECT "{\n.reg .pred p;\nelect.sync _|p, 0xffffffff;\n"
#define TMA2D "cp.async.bulk.tensor.2d.shared::cluster.global.mbarrier::complete_tx::bytes"
#define TMA3D "cp.async.bulk.tensor.3d.shared::cluster.global.mbarrier::complete_tx::bytes"
__device__ __forceinline__ void e_expect(uint32_t b, uint32_t n) {
  asm volatile(ELECT "@p mbarrier.arrive.expect_tx.shared::cta.b64 _, [%0], %1;\n}" ::"r"(b), "r"(n) : "memory");
}
__device__ __forceinline__ void e_arrive(uint32_t b) { asm volatile(ELECT "@p mbarrier.arrive.shared::cta.b64 _, [%0];\n}" ::"r"(b) : "memory"); }
__device__ __forceinline__ void e_tma2d(uint32_t dst, const CUtensorMap* m, int c0, int c1, uint32_t bar) {
  asm volatile(ELECT "@p " TMA2D " [%0], [%1, {%3, %4}], [%2];\n}" ::"r"(dst), "l"(m), "r"(bar), "r"(c0), "r"(c1) : "memory");
}
__device__ __forceinline__ void e_tma2d_ef(uint32_t dst, const CUtensorMap* m, int c0, int c1, uint32_t bar, uint64_t pol) {
  asm volatile(ELECT "@p " TMA2D ".L2::cache_hint [%0], [%1, {%3, %4}], [%2], %5;\n}" ::"r"(dst), "l"(m), "r"(bar), "r"(c0), "r"(c1), "l"(pol) : "memory");
}
__device__ __forceinline__ void e_tma3d(uint32_t dst, const CUtensorMap* m, int c1, int c2, uint32_t bar) {
  asm volatile(ELECT "@p " TMA3D " [%0], [%1, {0, %3, %4}], [%2];\n}" ::"r"(dst), "l"(m), "r"(bar), "r"(c1), "r"(c2) : "memory");
}
__device__ __forceinline__ void e_store2d(const CUtensorMap* m, int c0, int c1, uint32_t src) {
  asm volatile(ELECT "@p cp.async.bulk.tensor.2d.global.shared::cta.bulk_group [%0, {%2, %3}], [%1];\n}" ::"l"(m), "r"(src), "r"(c0), "r"(c1) : "memory");
}
__device__ __forceinline__ void e_tma3d_ef(uint32_t dst, const CUtensorMap* m, int c0, int c1, uint32_t bar, uint64_t pol) {
  asm volatile(ELECT "@p " TMA3D ".L2::cache_hint [%0], [%1, {%3, %4, 0}], [%2], %5;\n}" ::"r"(dst), "l"(m), "r"(bar), "r"(c0), "r"(c1), "l"(pol) : "memory");
}
__device__ __forceinline__ void e_load(uint32_t dst, const void* src, uint32_t n, uint32_t bar) {
  asm volatile(ELECT "@p cp.async.bulk.shared::cluster.global.mbarrier::complete_tx::bytes [%0], [%1], %2, [%3];\n}" ::"r"(dst), "l"(src), "r"(n), "r"(bar) : "memory");
}
__device__ __forceinline__ void e_pfmap(const CUtensorMap* m) { asm volatile(ELECT "@p prefetch.tensormap [%0];\n}" ::"l"(m) : "memory"); }
__device__ __forceinline__ void bulk_wait_read() { asm volatile("cp.async.bulk.commit_group;\ncp.async.bulk.wait_group.read 0;" ::: "memory"); }
__device__ __forceinline__ void e_signal(int word, int bit) {
  asm volatile(ELECT "@p red.relaxed.gpu.global.xor.b32 [%0], %1;\n}" ::"l"(g_sig + word * 32), "r"(1u << bit) : "memory");
}
__device__ __forceinline__ void e_release(int word, int bit) {
  asm volatile("cp.async.bulk.commit_group;\ncp.async.bulk.wait_group 0;\nfence.release.gpu;" ::: "memory");
  e_signal(word, bit);
}
__device__ __forceinline__ void await(int word, uint32_t mask, uint32_t ep) {
  uint32_t f[1];
  poll1f(f, g_sig + word * 32, 0u - (ep & 1u), mask);
}

__device__ __forceinline__ void mbar_arrive(uint32_t b) { asm volatile("mbarrier.arrive.shared::cta.b64 _, [%0];" ::"r"(b) : "memory"); }
__device__ __forceinline__ void mbar_wait(uint32_t b, uint32_t ph) {
  asm volatile("{\n.reg .pred p, q;\n.reg .u32 c;\nmov.u32 c, 0;\nLW:\nmbarrier.try_wait.parity.shared::cta.b64 p, [%0], %1;\n@p bra LD;\n"
               "add.u32 c, c, 1;\nsetp.lt.u32 q, c, 100000;\n@q bra LW;\ntrap;\nLD:\n}" ::"r"(b), "r"(ph) : "memory");
}
__device__ __forceinline__ void nb_sync(int id, int n) { asm volatile("bar.sync %0, %1;" ::"r"(id), "r"(n) : "memory"); }
__device__ __forceinline__ void nb_arrive(int id, int n) { asm volatile("bar.arrive %0, %1;" ::"r"(id), "r"(n) : "memory"); }
__device__ __forceinline__ void wg_fence() { asm volatile("wgmma.fence.sync.aligned;" ::: "memory"); }
__device__ __forceinline__ void wg_commit() { asm volatile("wgmma.commit_group.sync.aligned;" ::: "memory"); }
template <int N> __device__ __forceinline__ void wg_wait() { asm volatile("wgmma.wait_group.sync.aligned %0;" ::"n"(N) : "memory"); }
template <int N> __device__ __forceinline__ void reg_fence(float (&a)[N]) {
#pragma unroll
  for (int i = 0; i < N; i++) asm volatile("" : "+f"(a[i])::"memory");
}
template <int N> __device__ __forceinline__ void reg_zero(float (&a)[N]) {
#pragma unroll
  for (int i = 0; i < N; i++) a[i] = 0.f;
}
__device__ __forceinline__ constexpr uint64_t mkdesc(uint32_t addr, uint32_t lbo, uint32_t sbo, uint32_t swz) {
  return (uint64_t)(addr >> 4) | ((uint64_t)(lbo >> 4) << 16) | ((uint64_t)(sbo >> 4) << 32) | ((uint64_t)swz << 62);
}
__device__ __forceinline__ void fence_async_smem() { asm volatile("fence.proxy.async.shared::cta;" ::: "memory"); }
__device__ __forceinline__ void fence_async_glob() { asm volatile("fence.proxy.async.global;" ::: "memory"); }
__device__ __forceinline__ void fence_acq() { asm volatile("fence.acquire.gpu;" ::: "memory"); }
__device__ __forceinline__ void st_relaxed(uint32_t* p, uint32_t v) { asm volatile("st.relaxed.gpu.global.u32 [%0], %1;" ::"l"(p), "r"(v) : "memory"); }
__device__ __forceinline__ uint32_t ld_relaxed(const uint32_t* p) { uint32_t v; asm volatile("ld.relaxed.gpu.global.u32 %0, [%1];" : "=r"(v) : "l"(p) : "memory"); return v; }
__device__ __forceinline__ void st_unit(uint4* p, uint32_t a, uint32_t b, uint32_t c, uint32_t d, uint32_t par) {
  asm volatile("{\n.reg .b64 x, y;\n.reg .b128 z;\nmov.b64 x, {%1,%2};\nmov.b64 y, {%3,%4};\nmov.b128 z, {x, y};\nst.relaxed.gpu.global.b128 [%0], z;\n}"
               ::"l"(p), "r"((a & ~1u) | par), "r"(b), "r"(c), "r"(d) : "memory");
}
__device__ __forceinline__ uint4 lds128(uint32_t a) { uint4 v; asm volatile("ld.shared.v4.u32 {%0,%1,%2,%3}, [%4];" : "=r"(v.x), "=r"(v.y), "=r"(v.z), "=r"(v.w) : "r"(a)); return v; }
__device__ __forceinline__ float4 lds128f(uint32_t a) { float4 v; asm volatile("ld.shared.v4.f32 {%0,%1,%2,%3}, [%4];" : "=f"(v.x), "=f"(v.y), "=f"(v.z), "=f"(v.w) : "r"(a)); return v; }
__device__ __forceinline__ float4 lds128v(uint32_t a) { float4 v; asm volatile("ld.volatile.shared.v4.f32 {%0,%1,%2,%3}, [%4];" : "=f"(v.x), "=f"(v.y), "=f"(v.z), "=f"(v.w) : "r"(a) : "memory"); return v; }
__device__ __forceinline__ float lds32v(uint32_t a) { float v; asm volatile("ld.volatile.shared.f32 %0, [%1];" : "=f"(v) : "r"(a) : "memory"); return v; }
__device__ __forceinline__ float2 lds64f(uint32_t a) { float2 v; asm volatile("ld.shared.v2.f32 {%0,%1}, [%2];" : "=f"(v.x), "=f"(v.y) : "r"(a)); return v; }
__device__ __forceinline__ uint32_t lds32(uint32_t a) { uint32_t v; asm volatile("ld.shared.u32 %0, [%1];" : "=r"(v) : "r"(a)); return v; }
__device__ __forceinline__ void sts128(uint32_t a, uint32_t x, uint32_t y, uint32_t z, uint32_t w) { asm volatile("st.shared.v4.u32 [%0], {%1,%2,%3,%4};" ::"r"(a), "r"(x), "r"(y), "r"(z), "r"(w) : "memory"); }
__device__ __forceinline__ void sts128f(uint32_t a, float x, float y, float z, float w) { asm volatile("st.shared.v4.f32 [%0], {%1,%2,%3,%4};" ::"r"(a), "f"(x), "f"(y), "f"(z), "f"(w) : "memory"); }
__device__ __forceinline__ void sts32(uint32_t a, uint32_t x) { asm volatile("st.shared.u32 [%0], %1;" ::"r"(a), "r"(x) : "memory"); }
__device__ __forceinline__ void stsm4(uint32_t a, uint32_t r0, uint32_t r1, uint32_t r2, uint32_t r3) {
  asm volatile("stmatrix.sync.aligned.m8n8.x4.shared.b16 [%0], {%1,%2,%3,%4};" ::"r"(a), "r"(r0), "r"(r1), "r"(r2), "r"(r3) : "memory");
}
__device__ __forceinline__ uint4 ldsm4(uint32_t a) {
  uint4 v; asm volatile("ldmatrix.sync.aligned.m8n8.x4.shared.b16 {%0,%1,%2,%3}, [%4];" : "=r"(v.x), "=r"(v.y), "=r"(v.z), "=r"(v.w) : "r"(a) : "memory"); return v;
}
__device__ __forceinline__ uint32_t pack(float lo, float hi) { uint32_t r; asm("cvt.rn.bf16x2.f32 %0, %1, %2;" : "=r"(r) : "f"(hi), "f"(lo)); return r; }
__device__ __forceinline__ float bf_lo(uint32_t w) { return __uint_as_float(w << 16); }
__device__ __forceinline__ float bf_hi(uint32_t w) { return __uint_as_float(w & 0xffff0000u); }
__device__ __forceinline__ float bf_round(float x) { return bf_lo(pack(x, x)); }
__device__ __forceinline__ float ex2(float x) { float v; asm("ex2.approx.ftz.f32 %0, %1;" : "=f"(v) : "f"(x)); return v; }
__device__ __forceinline__ float rcp(float x) { float v; asm("rcp.approx.ftz.f32 %0, %1;" : "=f"(v) : "f"(x)); return v; }
__device__ __forceinline__ float addsat(float a, float b) { float v; asm("add.sat.f32 %0, %1, %2;" : "=f"(v) : "f"(a), "f"(b)); return v; }
__device__ __forceinline__ float phi2(float a) { return fmaf(fmaxf(a, 0.f), LN2, addsat(ex2(a), 1e-6f)); }
__device__ __forceinline__ uint32_t ln_bf16x2(uint32_t x, uint32_t m, uint32_t hi, uint32_t lo) {
  uint32_t o;
  asm("{\n.reg .b32 d, e;\nsub.rn.bf16x2 d, %1, %2;\nmul.rn.bf16x2 e, d, %4;\nfma.rn.bf16x2 %0, d, %3, e;\n}" : "=r"(o) : "r"(x), "r"(m), "r"(hi), "r"(lo));
  return o;
}
__device__ __forceinline__ float key_score(uint32_t key) { uint32_t u = key >> 16; u = (u & 0x8000u) ? (u & 0x7fffu) : (~u & 0xffffu); return __uint_as_float(u << 16); }
__device__ __forceinline__ int key_token(uint32_t key) { return 2047 - (int)((key >> 5) & 2047u); }
__device__ __forceinline__ uint32_t bsel(uint32_t a, uint32_t b, uint32_t m) { uint32_t r; asm("lop3.b32 %0, %1, %2, %3, 0xd8;" : "=r"(r) : "r"(a), "r"(b), "r"(m)); return r; }
__device__ __forceinline__ uint32_t tagf(float v, uint32_t par) { return (__float_as_uint(v) & ~1u) | par; }
__device__ __forceinline__ float xred(float a, float b, bool up, int o) { return (up ? b : a) + __shfl_xor_sync(0xffffffffu, up ? a : b, o); }

#define STAMP(id)
#define STAMP_IF(c, id)
#define STAMP2(i)
#define LITE 1

template <bool TRANS>
__device__ __forceinline__ void mainloop(float (&a0)[64], float (&a1)[64], int s, int ph, int handoff, int gate, bool leader) {
  uint32_t prev = 0;
#pragma unroll 1
  for (int kt = 0; kt < 16; kt++) {
    mbar_wait(B_FULL + 8 * s, ph);
    if (gate && kt == GATE_KT) nb_sync(gate, 256);
    const uint64_t dw = mkdesc(RING, 8192, 1024, 1) + s * (SLOT >> 4), dx = mkdesc(RING + 16384, 16, 1024, 1) + s * (SLOT >> 4);
    wg_fence();
#pragma unroll
    for (int j = 0; j < 4; j++) {
      if (TRANS) {
        wgmma_n128_ss<1, 0>(a0, dw + j * 128, dx + j * 2, 1);
        wgmma_n128_ss<1, 0>(a1, dw + j * 128 + 512, dx + j * 2, 1);
      } else {
        wgmma_n128_ss<0, 1>(a0, dx + j * 2, dw + j * 128, 1);
        wgmma_n128_ss<0, 1>(a1, dx + j * 2 + 512, dw + j * 128, 1);
      }
    }
    wg_commit();
    if (handoff && kt == 15) nb_arrive(handoff, 256);
    wg_wait<1>();
    if (prev && leader) mbar_arrive(prev);
    prev = B_EMPTY + 8 * s;
    if (++s == NST) { s = 0; ph ^= 1; }
  }
  wg_wait<0>();
  if (leader) mbar_arrive(prev);
  reg_fence(a0);
  reg_fence(a1);
}

__device__ __forceinline__ int out_kblock(int r, int tn) {
  const int q = r - 2, half = q >= 7, pi = q - 7 * half;
  return r < 2 ? 2 * tn + r : 2 * (pi + (pi >= tn)) + half;
}

struct Params {
  const char *x, *wqkv, *w_r, *wg, *wu, *wd;
  CUtensorMap m_wqkv, m_x, m_xs, m_o, m_os, m_wo, m_gu, m_down, m_out;
};

template <bool BY_SMID>
__global__ void __launch_bounds__(512, 1) fused_kernel(const __grid_constant__ Params mp) {
  extern __shared__ __align__(1024) uint8_t smem_raw[];
#define CK(i)
  CK(0);
  uint32_t ck0 = 0;
  if (ALIGN) asm volatile("mov.u32 %0, %%clock;" : "=r"(ck0));
  const int tid = threadIdx.x, lane = tid & 31;
  const int w = __shfl_sync(0xffffffffu, tid >> 5, 0);
  int bid = blockIdx.x;
  if (BY_SMID) {
    uint32_t sm;
    asm volatile("mov.u32 %0, %%smid;" : "=r"(sm));
    const uint32_t p = sm >> 1, q = ((p - 32) * 37) >> 8;
    const uint32_t gpc = p < 32 ? p & 7 : p < 60 ? p - 31 - 7 * q : 0, tpc = p < 32 ? p >> 3 : p < 60 ? 4 + q : p - 58;
    bid = (p >> 1) == 30 ? 128 + ((0x9cu >> (2 * (sm & 3))) & 3) : ((0x75143620u >> (4 * gpc)) & 7) * 16 + tpc * 2 + (sm & 1);
  }
  const int tn = (bid & 3) + 4 * (bid >> 6), tm = (bid >> 2) & 15;

  CK(1);
  if (w == 0) {
#pragma unroll 1
    for (int s = 0; s < NST; s++) {
      asm volatile(ELECT "@p mbarrier.init.shared::cta.b64 [%0], 1;\n}" ::"r"(B_FULL + 8 * s) : "memory");
      if (bid < 128) {
        e_expect(B_FULL + 8 * s, 32768);
        e_tma2d(RING + s * SLOT + 16384, &mp.m_x, s * 64, tm * 128, B_FULL + 8 * s);
        e_tma3d(RING + s * SLOT, &mp.m_wqkv, s * 64, 16 + 2 * tn, B_FULL + 8 * s);
      }
      if (s == 0) CK(2);
    }
  }
  if (w == 1) e_pfmap(&mp.m_wqkv);
  if (w >= 4) {
#pragma unroll 1
    for (uint32_t b = MISC + 8 * (w + 1); b < MISC + 8 * NBAR; b += 96)
      asm volatile(ELECT "@p mbarrier.init.shared::cta.b64 [%0], %1;\n}" ::"r"(b), "r"(b == B_CSDN ? 4 : 1) : "memory");
    if (w == 15) sts32(S_NCAND, 0);
  }
  CK(3);
  asm volatile("fence.mbarrier_init.release.cluster;" ::: "memory");
  __syncthreads();

  if (bid >= 128) {
    const int h0 = bid == 128 ? 14 : bid - 129, hs = bid == 128 ? 1 : 3, h1 = bid == 128 ? 16 : 14;
    if (w == 12) {
      int s = 0, ph = 1;
      if (bid == 128) mbar_wait(B_SEL, 0);
      else if (H_DELAY) __nanosleep(H_DELAY);
#pragma unroll 1
      for (int h = h0; h < h1; h += hs) {
        const int c = 2 * h + (h & 8) * 2;
#pragma unroll 1
        for (int kt = 0; kt < 16; kt += 2) {
          mbar_wait(B_EMPTY + 8 * s, ph);
          e_expect(B_FULL + 8 * s, 32768);
          e_tma3d(RING + s * SLOT, &mp.m_wqkv, kt * 64, c, B_FULL + 8 * s);
          e_tma3d(RING + s * SLOT + 16384, &mp.m_wqkv, kt * 64 + 64, c, B_FULL + 8 * s);
          if (++s == HST) { s = 0; ph ^= 1; }
        }
      }
    } else if (w < 4) {
      const uint32_t par = (ld_relaxed(&g_epoch) + 1) & 1u;
      sts32(S_ONES + tid * 4, 0x3f803f80u);
      fence_async_smem();
      nb_sync(NB_WG0, 128);
      int s = 0, ph = 0;
#pragma unroll 1
      for (int h = h0; h < h1; h += hs) {
        float c[4][4];
#pragma unroll
        for (int i = 0; i < 4; i++) reg_zero(c[i]);
        uint32_t prev = 0;
#pragma unroll 1
        for (int kt = 0; kt < 8; kt++) {
          mbar_wait(B_FULL + 8 * s, ph);
          const uint64_t dw = mkdesc(RING, 8192, 1024, 1) + s * (SLOT >> 4);
          wg_fence();
#pragma unroll
          for (int j = 0; j < 16; j++) wgmma_n8_ss<1, 0>(c[j & 3], dw + (j & 3) * 512 + (j >> 2) * 128, mkdesc(S_ONES, 128, 128, 0), 1);
          wg_commit();
          wg_wait<1>();
          if (prev && tid == 0) mbar_arrive(prev);
          prev = B_EMPTY + 8 * s;
          if (++s == HST) { s = 0; ph ^= 1; }
        }
        wg_wait<0>();
        if (tid == 0) mbar_arrive(prev);
#pragma unroll
        for (int i = 0; i < 4; i++) reg_fence(c[i]);
        const bool u2 = lane & 2, u1 = lane & 1;
        const float lo = u2 ? c[1][0] + c[3][0] : c[0][0] + c[2][0], hi = u2 ? c[1][2] + c[3][2] : c[0][2] + c[2][2];
        st_relaxed(g_csum + h * 128 + (lane & 2) * 32 + w * 16 + (lane & 1) * 8 + (lane >> 2), tagf(u1 ? hi : lo, par));
        STAMP_IF(tid == 0, h >= 8 ? 6 : 30);
      }
    } else if (w < 12 && bid == 128) {
      const int t = tid - 128, j = w - 4;
      const uint32_t ep = ld_relaxed(&g_epoch) + 1;
      uint32_t kk[16];
      poll_keys(kk, g_keys + t * 2, ep, 31u);
      const uint32_t k[8] = {kk[0], kk[2], kk[4], kk[6], kk[8], kk[10], kk[12], kk[14]};
      STAMP_IF(t == 0, 42);
      const uint32_t m = __reduce_max_sync(0xffffffffu, max(max(max(k[0], k[1]), max(k[2], k[3])), max(max(k[4], k[5]), max(k[6], k[7]))));
      if (lane == 0) sts32(S_WMAX + j * 4, m);
      nb_sync(NB_WG1, 256);
      const uint32_t T = __reduce_min_sync(0xffffffffu, lds32(S_WMAX + (lane & 7) * 4));
      uint32_t cnt = 0;
#pragma unroll
      for (int i = 0; i < 8; i++) cnt += k[i] >= T;
      if (cnt) {
        uint32_t pos;
        asm volatile("atom.shared.add.u32 %0, [%1], %2;" : "=r"(pos) : "r"(S_NCAND), "r"(cnt * 4) : "memory");
#pragma unroll
        for (int i = 0; i < 8; i++)
          if (k[i] >= T) { sts32(AUX + pos, k[i]); pos += 4; }
      }
      nb_sync(NB_WG1, 256);
      const uint32_t n4 = lds32(S_NCAND);
#pragma unroll 1
      for (uint32_t i = j * 4; i < n4; i += 32) {
        const uint32_t key = lds32(AUX + i);
        uint32_t rank = 0;
#pragma unroll 1
        for (uint32_t q = lane * 4; q < n4 + lane * 4; q += 128) rank += __popc(__ballot_sync(0xffffffffu, q < n4 && lds32(AUX + q) > key));
        if (rank < 8) sts32(S_SEL + rank * 4, key);
      }
      fence_async_smem();
      nb_sync(NB_WG1, 256);
      STAMP_IF(t == 0, 43);
      const uint32_t key = lds32(S_SEL + j * 4);
      const int tok = key_token(key);
      uint4 v[4];
#pragma unroll
      for (int q = 0; q < 4; q++) v[q] = __ldg(reinterpret_cast<const uint4*>(mp.x + tok * 2048) + q * 32 + lane);
      const uint32_t st = ld_relaxed(&g_keys[tok].y);
      const float rinv = rcp(bf_lo(st)), rhi = bf_round(rinv);
      const uint32_t m2 = __byte_perm(st, 0, 0x3232), hi = pack(rhi, rhi), lo = pack(rinv - rhi, rinv - rhi);
#pragma unroll
      for (int q = 0; q < 4; q++)
        *reinterpret_cast<uint4*>(g_xsel + (q * 8 + (lane >> 2)) * 128 + j * 16 + (((lane & 3) ^ (j >> 1)) << 2)) =
            make_uint4(ln_bf16x2(v[q].x, m2, hi, lo), ln_bf16x2(v[q].y, m2, hi, lo), ln_bf16x2(v[q].z, m2, hi, lo), ln_bf16x2(v[q].w, m2, hi, lo));
      if (lane == 0) g_xsel[4096 + j] = key;
      fence_async_glob();
      nb_sync(NB_WG1, 256);
      STAMP_IF(t == 0, 44);
      if (j == 0) { e_release(H_R, 0); e_arrive(B_SEL); }
      STAMP_IF(t == 0, 45);
    }
  } else if (w >= 12) {
    asm volatile("setmaxnreg.dec.sync.aligned.u32 32;");
    if (w == 12) {
      int s = 0, ph = 0;
#pragma unroll 1
      for (int it = NST; it < 48; it++) {
        const int c = (it < 32 ? (it & 16) + 16 : 0) + 2 * tn;
        mbar_wait(B_EMPTY + 8 * s, ph);
        e_expect(B_FULL + 8 * s, 32768);
        e_tma3d(RING + s * SLOT, &mp.m_wqkv, (it & 15) * 64, c, B_FULL + 8 * s);
        e_tma2d(RING + s * SLOT + 16384, &mp.m_x, (it & 15) * 64, tm * 128, B_FULL + 8 * s);
        if (it >= NST) STAMP2(it - NST);
        if (++s == NST) { s = 0; ph ^= 1; }
      }
#pragma unroll 1
      for (int r = 0; r < 16; r++) {
        const int kb = out_kblock(r, tn);
        mbar_wait(B_EMPTY + 8 * s, ph);
        e_expect(B_FULL + 8 * s, r < 2 ? 16384 : 32768);
        e_tma3d(RING + s * SLOT, &mp.m_wo, kb * 64, 2 * tn, B_FULL + 8 * s);
        if (r < 2) {
          if (r == 0) e_expect(B_XRES, 32768);
          e_tma2d(RING + s * SLOT + 16384, &mp.m_x, kb * 64, tm * 128, B_XRES);
        }
        STAMP2(r + 48 - NST);
        if (++s == NST) { s = 0; ph ^= 1; }
      }
    } else if (w == 13) {
      e_pfmap(&mp.m_xs);
      mbar_wait(B_FULL + 8 * XS_AT, 0);
#pragma unroll 1
      for (int c = 0; c < 4; c++) {
        if (c >= XS_FLY) mbar_wait(B_XS + 8 * (c - XS_FLY), 0);
        if (c == max(tm >> 2, 1)) {
          e_expect(B_WK, 16384);
          e_tma3d(FR, &mp.m_wqkv, tm * 64, 16 + 2 * tn, B_WK);
        }
        e_expect(B_XS + 8 * c, 8192);
        e_tma2d(STG + c * 8192, &mp.m_xs, c * 256, tm * 128 + tn * 16, B_XS + 8 * c);
      }
      nb_sync(NB_Z, 160);
      const uint32_t ep = lds32(S_EPOCH);
      {
        float z[4] = {0.f, 0.f, 0.f, 0.f};
        e_signal(H_Z + tn, tm);
        await(H_Z + tn, 0xffffu, ep);
#pragma unroll 1
        for (int i = 0; i < 4; i++) {
          uint32_t p[16];
          poll_z(p, g_z + i * 4096 + tn * 128 + lane * 4, ep, 1u);
#pragma unroll
          for (int q = 0; q < 4; q++) z[q] += (__uint_as_float(p[q]) + __uint_as_float(p[4 + q])) + (__uint_as_float(p[8 + q]) + __uint_as_float(p[12 + q]));
        }
        const uint32_t z01 = pack(z[0], z[1]), z23 = pack(z[2], z[3]);
#pragma unroll
        for (int i = 0; i < 4; i++) {
          const int n = 2 * i + (lane >> 4);
          asm volatile("st.shared.v2.u32 [%0], {%1,%2};" ::"r"(KVB_Z + n * 128 + ((((lane >> 1) & 7) ^ n) << 4) + (lane & 1) * 8), "r"(z01), "r"(z23) : "memory");
        }
        fence_async_smem();
        nb_arrive(NB_KVB, 288);
        STAMP_IF(lane == 0, 46);
      }
      nb_sync(NB_Q0, 192);
      e_store2d(&mp.m_os, tn * 128, tm * 128, STG);
      nb_sync(NB_OWN0, 288);
      e_store2d(&mp.m_os, tn * 128, tm * 128 + 64, STG + 8192);
      bulk_wait_read();
      e_signal(H_O + tm, 2 * tn);
      STAMP_IF(lane == 0, 4);
      nb_sync(NB_H1, 160);
      e_store2d(&mp.m_os, tn * 128 + 64, tm * 128, STG + 16384);
      e_store2d(&mp.m_os, tn * 128 + 64, tm * 128 + 64, STG + 24576);
      bulk_wait_read();
      e_signal(H_O + tm, 2 * tn + 1);
      STAMP_IF(lane == 0, 5);
#pragma unroll 1
      for (int i = 4; i < 14; i++) {
        const int q = (i + 2) >> 2;
        if (i == 4 || (i & 3) == 2) {
          if (i > 4) mbar_wait(B_OWN + 8 * (q - 2), 0);
          e_expect(B_DR + 8 * q, i == 4 ? 8192 : 16384);
        }
        e_tma2d_ef((i < 6 ? AUX - 16384 : STG - 24576) + i * 4096, &mp.m_down, (bid & 15) * 64, (bid >> 4) * 448 + i * 32, B_DR + 8 * q, EVICT_FIRST);
        if (DN_GAP) __nanosleep(DN_GAP);
      }
    } else if (w == 14) {
      e_pfmap(&mp.m_gu); e_pfmap(&mp.m_o); e_pfmap(&mp.m_os); e_pfmap(&mp.m_wo); e_pfmap(&mp.m_down); e_pfmap(&mp.m_out);
      const uint32_t ep = ld_relaxed(&g_epoch) + 1;
      nb_sync(NB_FDONE, 416);
      {
        uint32_t c[4];
        poll_quad(c, g_csum + tn * 128 + lane * 4, ep, 1u);
        sts128(S_CSQ + lane * 16, c[0], c[1], c[2], c[3]);
        nb_arrive(NB_CSQ, 160);
        poll_quad(c, g_csum + 1024 + tn * 128 + lane * 4, ep, 1u);
        sts128(S_CSV + lane * 16, c[0], c[1], c[2], c[3]);
        __syncwarp();
        e_arrive(B_CSV);
      }
      nb_sync(NB_Q0, 192);
      uint32_t ready = 0;
      int s = 0, ph = 1;
#pragma unroll 1
      for (int r = 2; r < 16; r++) {
        const int kb = out_kblock(r, tn);
        if (!((ready >> kb) & 1)) {
          uint32_t f[1];
          poll0(f, g_sig + (H_O + tm) * 32, 0u - (ep & 1u), 1u << kb);
          ready = f[0] ^ ((ep & 1u) - 1u);
        }
        mbar_wait(B_EMPTY + 8 * s, ph);
        e_tma2d(RING + s * SLOT + 16384, &mp.m_o, kb * 64, tm * 128, B_FULL + 8 * s);
        STAMP_IF(lane == 0 && r == 2, 2);
        STAMP_IF(lane == 0 && r == 9, 3);
        if (++s == NST) { s = 0; ph ^= 1; }
      }
    } else {
      uint32_t nsm = 132;
      if (BY_SMID) asm volatile("mov.u32 %0, %%nsmid;" : "=r"(nsm));
      asm volatile("{\n.reg .pred q;\nsetp.eq.u32 q, %0, 1156;\n@q bra LOK;\ntrap;\nLOK:\n}" ::"r"((uint32_t)__cvta_generic_to_shared(smem_raw) + nsm));
      const uint32_t ep = ld_relaxed(&g_epoch) + 1;
      mbar_wait(B_CSDN, 0);
#pragma unroll 1
      for (int n = 0; n < 5; n++) {
        __nanosleep(FFN_GAP);
        if (bid < 112) {
          e_expect(B_FR + 8 * n, 4608);
          e_tma3d_ef(GR + n * 4096, &mp.m_gu, bid * 32, n * 32, B_FR + 8 * n, EVICT_FIRST);
        }
      }
      {
        const char* pd = mp.wd + (bid & 15) * 128 + ((bid >> 4) * 448 + lane) * 2048;
#pragma unroll 1
        for (int i = 0; i < 14; i++, pd += 65536) {
          if (PF_GAP) asm volatile("prefetch.global.L2 [%0];" ::"l"(pd));
          if (PF_GAP) __nanosleep(PF_GAP);
        }
      }
      uint32_t f[1];
      poll1(f, g_sig + H_R * 32, ep, 1u);
      fence_acq();
      fence_async_glob();
      if (bid < 112) {
#pragma unroll
        for (int n = 0; n < 5; n++) e_load(HOP + n * 512, g_xsel + n * 128, 512, B_FR + 8 * n);
      }
      e_expect(B_SEL, 32);
      e_load(S_SEL, g_xsel + 4096, 32, B_SEL);
      if (bid < 112) {
        int s = 0, ph = 0;
#pragma unroll 1
        for (int n = 5; n < 32; n++) {
          mbar_wait(B_FE + 8 * s, ph);
          e_expect(B_FR + 8 * s, 4608);
          e_tma3d_ef(GR + s * 4096, &mp.m_gu, bid * 32 , n * 32 , B_FR + 8 * s, EVICT_FIRST);
          e_load(HOP + s * 512, g_xsel + n * 128, 512, B_FR + 8 * s);
          STAMP2(64 + n);
          if (++s == 5) { s = 0; ph ^= 1; }
        }
      }
      e_expect(B_DR, 16384);
#pragma unroll 1
      for (int i = 1; i < 5; i++) {
        if (bid < 112) mbar_wait(B_FE + 8 * ((i & 3) + 1), i != 4);
        e_tma2d_ef(FR + (i & 3) * 4096, &mp.m_down, (bid & 15) * 64, (bid >> 4) * 448 + (i & 3) * 32, B_DR, EVICT_FIRST);
      }
    }
  } else if (w >= 8) {
    asm volatile("setmaxnreg.dec.sync.aligned.u32 56;");
    const int t = tid - 256, ww = w - 8;
    const uint32_t ep = ld_relaxed(&g_epoch) + 1, par = ep & 1u;
    {
      const int r0 = (lane >> 3) + (lane & 4);
      const uint32_t a = FR + (ww >> 1) * 8192 + r0 * 128 + ((((ww & 1) * 4 + (lane & 3)) ^ r0) << 4);
      float c[8];
      reg_zero(c);
      mbar_wait(B_WK, 0);
#pragma unroll 2
      for (int i = 0; i < 8; i++) {
        const uint4 v = lds128(a + i * 1024);
        c[0] += bf_lo(v.x); c[1] += bf_hi(v.x); c[2] += bf_lo(v.y); c[3] += bf_hi(v.y);
        c[4] += bf_lo(v.z); c[5] += bf_hi(v.z); c[6] += bf_lo(v.w); c[7] += bf_hi(v.w);
      }
      const bool u16 = lane & 16, u8 = lane & 8, u4 = lane & 4;
      const float d0 = xred(c[0], c[4], u16, 16), d1 = xred(c[1], c[5], u16, 16), d2 = xred(c[2], c[6], u16, 16), d3 = xred(c[3], c[7], u16, 16);
      fence_async_smem();
      e_arrive(B_CSDN);
      const float sum = xred(xred(d0, d2, u8, 8), xred(d1, d3, u8, 8), u4, 4);
      st_relaxed(g_csum + (2 + tm) * 1024 + tn * 128 + ww * 32 + (lane & 3) * 8 + (lane >> 2), tagf(sum, par));
      STAMP_IF(t == 0, 8);
      nb_sync(NB_WG2, 128);
      if (ww == 0) { e_signal(H_CS + tn, tm); await(H_CS + tn, 0xffffu, ep); }
      nb_sync(NB_WG2, 128);
      uint32_t p[16];
      poll16(p, g_csum + 2048 + tn * 128 + t, par, 1u);
      float tot = 0.f;
#pragma unroll
      for (int i = 0; i < 16; i += 4) tot += (__uint_as_float(p[i]) + __uint_as_float(p[i + 1])) + (__uint_as_float(p[i + 2]) + __uint_as_float(p[i + 3]));
      sts32(S_CSK + t * 4, __float_as_uint(tot));
      nb_arrive(NB_FDONE, 416);
      STAMP_IF(t == 0, 9);
    }
    const int ks = bid >> 4, nt = bid & 15;
    float fa[4] = {0.f, 0.f, 0.f, 0.f};
    if (bid < 112) {
      int s = 0, ph = 0;
      uint32_t prev = 0;
#pragma unroll 1
      for (int n = 0; n < 32; n++) {
        mbar_wait(B_FR + 8 * s, ph);
        const uint64_t da = mkdesc(GR, 2048, 512, 2) + s * 256, db = mkdesc(HOP, 16, 512, 2) + s * 32;
        wg_fence();
        wgmma_n8_ss<1, 0>(fa, da, db, 1);
        wgmma_n8_ss<1, 0>(fa, da + 64, db + 2, 1);
        wg_commit();
        wg_wait<1>();
        if (prev && t == 0) mbar_arrive(prev);
        prev = B_FE + 8 * s;
        if (++s == 5) { s = 0; ph ^= 1; }
      }
      wg_wait<0>();
      reg_fence(fa);
      if (t == 0) mbar_arrive(prev);
      STAMP_IF(t == 0, 12);
      const bool isup = (ww >> 1) != (mp.wu < mp.wg);
      if (isup) sts128f(GR + (t & 63) * 16, fa[0], fa[1], fa[2], fa[3]);
      nb_sync(NB_WG2, 128);
      if (!isup) {
        const float4 u = lds128f(GR + (t & 63) * 16);
        const float uu[4] = {u.x, u.y, u.z, u.w};
        uint32_t* hp = g_h + bid * 256 + (lane & 3) * 64 + (ww & 1) * 16 + (lane >> 2);
#pragma unroll
        for (int i = 0; i < 4; i++) {
          const float g = fa[i], hv = g * rcp(1.f + ex2(-g * LOG2E)) * uu[i];
          st_relaxed(hp + (i & 1) * 32 + (i >> 1) * 8, __byte_perm(pack(hv, hv), ep, 0x3254));
        }
      }
      nb_sync(NB_WG2, 128);
      if (ww == 0) e_signal(H_H + bid / 14, bid % 14);
      reg_zero(fa);
    }
    {
      uint32_t v[28];
      if (ww == 0) await(H_H + ks, 0x3fffu, ep);
      nb_sync(NB_WG2, 128);
      poll7x4(v, g_h + ks * 3584 + t * 4, ep, 0xffffu);
#pragma unroll
      for (int q = 0; q < 7; q++)
        asm volatile("st.shared.v2.u32 [%0], {%1,%2};" ::"r"(HOP + q * 1024 + (t >> 3) * 64 + ((((t >> 1) & 3) ^ ((t >> 4) & 3)) << 4) + (t & 1) * 8),
                     "r"(__byte_perm(v[4 * q], v[4 * q + 1], 0x7632)), "r"(__byte_perm(v[4 * q + 2], v[4 * q + 3], 0x7632)) : "memory");
      fence_async_smem();
      nb_sync(NB_WG2, 128);
    }
    STAMP_IF(t == 0, 13);
#pragma unroll 1
    for (int i = 0; i < 14; i += 2) {
      mbar_wait(B_DR + 8 * (i < 4 ? 0 : (i + 2) >> 2), 0);
      const uint64_t da = mkdesc(0, 4096, 1024, 1) + ((i < 4 ? FR : i < 6 ? AUX - 16384 : STG - 24576) >> 4) + i * 256;
      const uint64_t db = mkdesc(HOP, 16, 512, 2) + i * 32;
      wg_fence();
#pragma unroll
      for (int q = 0; q < 4; q++) wgmma_n8_ss<1, 0>(fa, da + q * 128, db + (q >> 1) * 32 + (q & 1) * 2, 1);
      wg_commit();
    }
    wg_wait<0>();
    reg_fence(fa);
    nb_arrive(NB_ST, 256);
    STAMP_IF(t == 0, 14);
    {
      uint32_t* yp = g_yp + (nt * 8 + ks) * 512 + (lane & 3) * 128 + ww * 16 + (lane >> 2);
#pragma unroll
      for (int i = 0; i < 4; i++) st_relaxed(yp + (i & 1) * 64 + (i >> 1) * 8, tagf(fa[i], par));
    }
    nb_sync(NB_WG2, 128);
    if (ww == 0) e_signal(H_Y + (nt >> 1), (nt & 1) * 8 + ks);
    mbar_wait(B_SEL, 0);
    const uint32_t mykey = lds32(S_SEL + (lane & 7) * 4);
    const uint32_t inmask = __ballot_sync(0xffffffffu, (key_token(mykey) >> 7) == tm) & 0xffu;
    if (inmask) {
      sts128(FR + t * 16, 0u, 0u, 0u, 0u);
      if (ww == 0) await(H_Y + tn, 0xffffu, ep);
      nb_sync(NB_WG2, 128);
      const float sg = rcp(1.f + ex2(-key_score(mykey) * LOG2E));
#pragma unroll 1
      for (int n = ww + 1; n <= __popc(inmask); n += 4) {
        const int j = __fns(inmask, 0, n);
        uint32_t p[32];
        poll8x4(p, g_yp + (tn * 2 + (lane >> 4)) * 4096 + j * 64 + (lane & 15) * 4, par, 1u);
        float y[4];
        const float sj = __shfl_sync(0xffffffffu, sg, j);
#pragma unroll
        for (int i = 0; i < 4; i++)
          y[i] = sj * (((__uint_as_float(p[i]) + __uint_as_float(p[4 + i])) + (__uint_as_float(p[8 + i]) + __uint_as_float(p[12 + i]))) +
                       ((__uint_as_float(p[16 + i]) + __uint_as_float(p[20 + i])) + (__uint_as_float(p[24 + i]) + __uint_as_float(p[28 + i]))));
        asm volatile("st.shared.v2.u32 [%0], {%1,%2};" ::"r"(FR + (lane >> 4) * 1024 + j * 128 + ((((lane >> 1) & 7) ^ j) << 4) + (lane & 1) * 8),
                     "r"(pack(y[0], y[1])), "r"(pack(y[2], y[3])) : "memory");
      }
      fence_async_smem();
      nb_arrive(NB_Y, 256);
    }
    STAMP_IF(t == 0, 15);
  } else if (w >= 4) {
    asm volatile("setmaxnreg.inc.sync.aligned.u32 208;");
    const int t = tid - 128, ww = w - 4, g = lane >> 2, t4 = lane & 3;
    const bool leader = t == 0;
    const uint32_t ep = ld_relaxed(&g_epoch) + 1, par = ep & 1u;
    {
      const uint4* wp = reinterpret_cast<const uint4*>(mp.w_r) + lane;
      uint4 w0 = __ldg(wp), w1 = __ldg(wp + 32), w2 = __ldg(wp + 64), w3 = __ldg(wp + 96);
      if (leader) sts32(S_EPOCH, ep);
      if (KV_DIRECT && lane < 8) st_unit(g_kv + tn * 512 + tm * 32 + ww * 8 + lane, 0u, 0u, 0u, 0u, par ^ 1u);
      float s[4] = {0.f, 0.f, 0.f, 0.f}, q[4] = {0.f, 0.f, 0.f, 0.f}, d[4] = {0.f, 0.f, 0.f, 0.f}, wsum = 0.f;
#pragma unroll 1
      for (int c = 0; c < 4; c++) {
        const float wr[8] = {bf_lo(w0.x), bf_hi(w0.x), bf_lo(w0.y), bf_hi(w0.y), bf_lo(w0.z), bf_hi(w0.z), bf_lo(w0.w), bf_hi(w0.w)};
        w0 = w1; w1 = w2; w2 = w3;
        wsum += ((wr[0] + wr[1]) + (wr[2] + wr[3])) + ((wr[4] + wr[5]) + (wr[6] + wr[7]));
        mbar_wait(B_XS + 8 * c, 0);
#pragma unroll
        for (int r = 0; r < 4; r++) {
          const uint4 v = lds128(STG + c * 8192 + (ww * 4 + r) * 512 + lane * 16);
          const uint32_t xw[4] = {v.x, v.y, v.z, v.w};
#pragma unroll
          for (int i = 0; i < 4; i++) {
            const float lo = bf_lo(xw[i]), hi = bf_hi(xw[i]);
            s[r] += lo; q[r] = fmaf(lo, lo, q[r]); d[r] = fmaf(lo, wr[2 * i], d[r]);
            s[r] += hi; q[r] = fmaf(hi, hi, q[r]); d[r] = fmaf(hi, wr[2 * i + 1], d[r]);
          }
        }
      }
      STAMP_IF(leader, 16);
      const bool u16 = lane & 16, u8 = lane & 8, u4 = lane & 4, u2 = lane & 2;
      const float s1 = xred(xred(s[0], s[2], u16, 16), xred(s[1], s[3], u16, 16), u8, 8);
      const float q1 = xred(xred(q[0], q[2], u16, 16), xred(q[1], q[3], u16, 16), u8, 8);
      const float d1 = xred(xred(d[0], d[2], u16, 16), xred(d[1], d[3], u16, 16), u8, 8);
      wsum += __shfl_xor_sync(0xffffffffu, wsum, 16);
      wsum += __shfl_xor_sync(0xffffffffu, wsum, 8);
      float tot = xred(xred(s1, d1, u4, 4), xred(q1, wsum, u4, 4), u2, 2);
      tot += __shfl_xor_sync(0xffffffffu, tot, 1);
      const float qq = __shfl_down_sync(0xffffffffu, tot, 2), dd = __shfl_down_sync(0xffffffffu, tot, 4), ws = __shfl_down_sync(0xffffffffu, tot, 6);
      if ((lane & 7) == 0) {
        const float mean = tot * (1.f / 1024.f);
        const float var = fmaxf(fmaf(-mean, mean, qq * (1.f / 1024.f)), 0.f);
        float sd;
        asm("sqrt.approx.ftz.f32 %0, %1;" : "=f"(sd) : "f"(bf_round(bf_round(var) + 1e-5f)));
        const uint32_t ms = pack(sd, mean);
        const int row = tm * 128 + tn * 16 + ww * 4 + (lane >> 3);
        const uint32_t rbits = pack(0.f, fmaf(-bf_hi(ms), ws, dd) * rcp(bf_lo(ms)));
        const uint32_t key = (rbits ^ (((int)rbits >> 31 & 0x7fff0000u) | 0x80000000u)) | ((2047 - row) << 5) | (ep & 31u);
        asm volatile("{\n.reg .b64 x;\nmov.b64 x, {%1,%2};\nst.relaxed.gpu.global.b64 [%0], x;\n}" ::"l"(g_keys + row), "r"(key), "r"(ms) : "memory");
      }
      STAMP_IF(leader, 17);
      __nanosleep(400);
      uint32_t st[2];
      poll_pair(st, g_keys + tm * 128 + t, ep, 31u);
      asm volatile("st.shared.v2.f32 [%0], {%1,%2};" ::"r"(S_KSTAT + t * 8), "f"(bf_hi(st[1])), "f"(rcp(bf_lo(st[1])) * LOG2E) : "memory");
      nb_arrive(NB_FDONE, 416);
      STAMP_IF(leader, 10);
    }
    float a0[64], a1[64];
    reg_zero(a0); reg_zero(a1); reg_fence(a0); reg_fence(a1);
    STAMP_IF(leader, 18);
    nb_sync(NB_KV, 256);
    mainloop<true>(a0, a1, 1, 1, NB_VQ, 0, leader);
    STAMP_IF(leader, 19);
    {
      uint32_t f0[32], f1[32];
#pragma unroll
      for (int i = 0; i < 32; i++) { f0[i] = pack(a0[2 * i], a0[2 * i + 1]); f1[i] = pack(a1[2 * i], a1[2 * i + 1]); }
      float c0[32], c1[32];
      reg_zero(c0); reg_zero(c1);
      nb_sync(NB_PK, 256);
      constexpr uint64_t db = mkdesc(STG, 16, 1024, 1);
      wg_fence();
#pragma unroll
      for (int k = 0; k < 8; k++) {
        wgmma_n64_rs<0>(c0, f0[4 * k], f0[4 * k + 1], f0[4 * k + 2], f0[4 * k + 3], db + (k >> 2) * 1024 + (k & 3) * 2, k != 0);
        wgmma_n64_rs<0>(c1, f1[4 * k], f1[4 * k + 1], f1[4 * k + 2], f1[4 * k + 3], db + (k >> 2) * 1024 + (k & 3) * 2 + 512, k != 0);
        if (GATE_KT && k == GATE_K) nb_arrive(NB_KV, 256);
      }
      wg_commit();
      const bool hp = ww >> 1;
      float c[4];
      float2 tt[8];
#pragma unroll
      for (int i = 0; i < 8; i++) tt[i] = lds64f(S_CSK + ((i >> 2) * 64 + hp * 32 + (i & 3) * 8 + 2 * t4) * 4);
      mbar_wait(B_CSV, 0);
#pragma unroll
      for (int i = 0; i < 4; i++) c[i] = -__uint_as_float(lds32(S_CSV + ((i >> 1) * 64 + ww * 16 + (i & 1) * 8 + g) * 4));
      wg_wait<0>();
      reg_fence(c0);
      reg_fence(c1);
      STAMP_IF(leader, 20);
      uint4* pp = g_kvp + (tn * 16 + tm) * 512 + t;
      auto put = [&](int q, const float* d) {
        const float ca = c[q & 2], cb = c[q | 1];
        const float2 ta = tt[2 * q], tb = tt[2 * q + 1];
        st_unit(pp + q * 128, pack(fmaf(ca, ta.x, d[0]), fmaf(ca, ta.y, d[1])), pack(fmaf(cb, ta.x, d[2]), fmaf(cb, ta.y, d[3])),
                pack(fmaf(ca, tb.x, d[4]), fmaf(ca, tb.y, d[5])), pack(fmaf(cb, tb.x, d[6]), fmaf(cb, tb.y, d[7])), par);
      };
      if (!hp) { put(0, c0); put(1, c0 + 8); put(2, c1); put(3, c1 + 8); }
      else { put(0, c0 + 16); put(1, c0 + 24); put(2, c1 + 16); put(3, c1 + 24); }
      STAMP_IF(leader, 47);
      {
        uint32_t p[16];
        nb_sync(NB_WG1, 128);
        if (ww == 0) { e_signal(H_KVP + tn, tm); await(H_KVP + tn, 0xffffu, ep); }
        nb_sync(NB_WG1, 128);
        STAMP_IF(leader, 1);
        poll_kvp(p, g_kvp + (tn * 16 + (lane >> 3) * 4) * 512 + tm * 32 + ww * 8 + (lane & 7), par, 1u);
        float r[8];
#pragma unroll
        for (int i = 0; i < 4; i++) {
          r[2 * i] = (bf_lo(p[i]) + bf_lo(p[4 + i])) + (bf_lo(p[8 + i]) + bf_lo(p[12 + i]));
          r[2 * i + 1] = (bf_hi(p[i]) + bf_hi(p[4 + i])) + (bf_hi(p[8 + i]) + bf_hi(p[12 + i]));
        }
#pragma unroll
        for (int i = 0; i < 8; i++) r[i] += __shfl_xor_sync(0xffffffffu, r[i], 8);
#pragma unroll
        for (int i = 0; i < 8; i++) r[i] += __shfl_xor_sync(0xffffffffu, r[i], 16);
        if (lane < 8) st_unit(g_kv + tn * 512 + tm * 32 + ww * 8 + lane, pack(r[0], r[1]), pack(r[2], r[3]), pack(r[4], r[5]), pack(r[6], r[7]), par);
      }
      STAMP_IF(leader, 21);
    }
    const uint32_t sx = lane & 7, sc = lane >> 4;
    const uint32_t sa = STG + (ww * 16 + (lane & 15)) * 128;
    const uint32_t sw[4] = {sa + ((sc ^ sx) << 4), sa + (((2 + sc) ^ sx) << 4), sa + (((4 + sc) ^ sx) << 4), sa + (((6 + sc) ^ sx) << 4)};
    {
      uint32_t v[16];
      if (!KV_DIRECT) {
        nb_sync(NB_WG1, 128);
        if (ww == 0) { e_signal(H_KV + tn, tm); await(H_KV + tn, 0xffffu, ep); }
        nb_sync(NB_WG1, 128);
      } else {
        __nanosleep(KV_DIRECT);
      }
      STAMP_IF(leader, 7);
      poll_kv(v, g_kv + tn * 512 + t, par, 1u);
      STAMP_IF(leader, 23);
#pragma unroll
      for (int q = 0; q < 4; q++)
        stsm4((q < 2 ? KVB_P0 : KVB_P1) + ((ww & 1) * 16 + (lane & 15)) * 128 + ((((ww >> 1) * 4 + (q & 1) * 2 + sc) ^ sx) << 4),
              v[4 * q], v[4 * q + 1], v[4 * q + 2], v[4 * q + 3]);
      fence_async_smem();
      nb_arrive(NB_KVB, 288);
    }
    STAMP_IF(leader, 24);
    uint32_t oh[4];
    uint32_t inmask;
    {
      mbar_wait(B_SEL, 0);
      const int r0 = key_token(lds32(S_SEL + t4 * 8)) - tm * 128, r1 = key_token(lds32(S_SEL + t4 * 8 + 4)) - tm * 128;
#pragma unroll
      for (int i = 0; i < 4; i++) {
        const int row = (i >> 1) * 64 + ww * 16 + (i & 1) * 8 + g;
        oh[i] = (r0 == row ? 0x3f80u : 0u) | (r1 == row ? 0x3f800000u : 0u);
      }
      inmask = __ballot_sync(0xffffffffu, (unsigned)r0 < 128u || (unsigned)r1 < 128u);
    }
    uint32_t va[8];
#pragma unroll
    for (int i = 0; i < 8; i++) va[i] = RING + 16384 + sc * 8192 + (ww * 16 + (lane & 15)) * 128 + ((i ^ sx) << 4) + (lane >> 3) * 4;
    float ka[4];
    {
      float kb[4];
#pragma unroll
      for (int i = 0; i < 4; i++) {
        const float2 st = lds64f(S_KSTAT + ((i >> 1) * 64 + ww * 16 + (i & 1) * 8 + g) * 8);
        const float r = st.y * LN2;
        ka[i] = 1.f + r; kb[i] = -st.x * r;
      }
#pragma unroll
      for (int i = 0; i < 64; i++) { a0[i] = kb[(i >> 1) & 1]; a1[i] = kb[2 + ((i >> 1) & 1)]; }
      reg_fence(a0);
      reg_fence(a1);
    }
    {
      auto own = [&](int r) {
        nb_sync(NB_OWN0 + r, r ? 256 : 288);
        mbar_wait(B_FULL + 8 * (3 + r), 1);
        if (!LITE) STAMP_IF(leader, 25 + r);
        const uint64_t dw = mkdesc(RING + (3 + r) * SLOT, 8192, 1024, 1), dx = mkdesc(STG + r * 16384, 16, 1024, 1);
        wg_fence();
#pragma unroll
        for (int j = 0; j < 4; j++) {
          wgmma_n128_ss<0, 1>(a0, dx + j * 2, dw + j * 128, 1);
          wgmma_n128_ss<0, 1>(a1, dx + j * 2 + 512, dw + j * 128, 1);
        }
        wg_commit();
      };
      own(0);
      constexpr uint32_t XOFF = RING + 3 * SLOT + 16384 - STG;
      mbar_wait(B_XRES, 0);
      wg_wait<0>();
      reg_fence(a0);
      reg_fence(a1);
#pragma unroll
      for (int j = 0; j < 8; j++) {
        const uint4 v = ldsm4(sw[j & 3] + XOFF + (j >> 2) * SLOT), u = ldsm4(sw[j & 3] + XOFF + (j >> 2) * SLOT + 8192);
        const uint32_t vv[4] = {v.x, v.y, v.z, v.w}, uu[4] = {u.x, u.y, u.z, u.w};
#pragma unroll
        for (int i = 0; i < 4; i++) {
          a0[8 * j + 2 * i] = fmaf(bf_lo(vv[i]), ka[i & 1], a0[8 * j + 2 * i]);
          a0[8 * j + 2 * i + 1] = fmaf(bf_hi(vv[i]), ka[i & 1], a0[8 * j + 2 * i + 1]);
          a1[8 * j + 2 * i] = fmaf(bf_lo(uu[i]), ka[2 + (i & 1)], a1[8 * j + 2 * i]);
          a1[8 * j + 2 * i + 1] = fmaf(bf_hi(uu[i]), ka[2 + (i & 1)], a1[8 * j + 2 * i + 1]);
        }
        if (j == 7) {
          fence_async_smem();
          nb_sync(NB_WG1, 128);
          if (leader) { mbar_arrive(B_EMPTY + 24); mbar_arrive(B_OWN); }
        }
      }
      reg_fence(a0);
      reg_fence(a1);
      STAMP_IF(leader, 22);
      own(1);
      int s = 0, ph = 0;
      uint32_t prev = B_EMPTY + 32;
#pragma unroll 1
      for (int r = 2; r < 16; r++) {
        mbar_wait(B_FULL + 8 * s, ph);
        {
          uint32_t bad = 0;
#pragma unroll
          for (int i = 0; i < 8; i++) bad |= lds32(va[i] + s * SLOT) ^ par;
          if (__any_sync(0xffffffffu, bad & 1u)) {
            const uint4* src = reinterpret_cast<const uint4*>(g_o + (tm * 128 + sc * 64 + ww * 16 + (lane & 15)) * 1024 + out_kblock(r, tn) * 64);
#pragma unroll 1
            for (int i = 0; i < 8; i++) {
              uint32_t v[4];
              asm volatile("{\n.reg .b64 x, y;\n.reg .b128 z;\n.reg .pred p, q, h;\n.reg .u32 c, b;\nmov.u32 c, 0;\nsetp.ne.u32 h, %6, 0;\nLW:\n"
                           "ld.relaxed.gpu.global.b128 z, [%4];\nmov.b128 {x, y}, z;\nmov.b64 {%0,%1}, x;\nmov.b64 {%2,%3}, y;\n"
                           "selp.b64 x, y, x, h;\nshr.b64 x, x, %7;\ncvt.u32.u64 b, x;\nand.b32 b, b, 1;\nsetp.eq.u32 p, b, %5;\n"
                           "vote.sync.all.pred p, p, 0xffffffff;\n@p bra.uni LD;\nadd.u32 c, c, 1;\nsetp.lt.u32 q, c, 1000000;\n@q bra.uni LW;\ntrap;\nLD:\n}"
                           : "=&r"(v[0]), "=&r"(v[1]), "=&r"(v[2]), "=&r"(v[3]) : "l"(src + i), "r"(par), "r"(sc), "r"((lane & 8) * 4) : "memory");
              sts128(((va[0] & ~15u) ^ (i << 4)) + s * SLOT, v[0], v[1], v[2], v[3]);
            }
            fence_async_smem();
            __syncwarp();
          }
        }
        if (!LITE) STAMP_IF(leader && r == 2, 27);
        const uint64_t dw = mkdesc(RING, 8192, 1024, 1) + s * (SLOT >> 4), dx = mkdesc(RING + 16384, 16, 1024, 1) + s * (SLOT >> 4);
        wg_fence();
#pragma unroll
        for (int j = 0; j < 4; j++) {
          wgmma_n128_ss<0, 1>(a0, dx + j * 2, dw + j * 128, 1);
          wgmma_n128_ss<0, 1>(a1, dx + j * 2 + 512, dw + j * 128, 1);
        }
        wg_commit();
        wg_wait<1>();
        if (leader) { mbar_arrive(prev); if (r == 2) mbar_arrive(B_OWN + 8); }
        prev = B_EMPTY + 8 * s;
        if (++s == NST) { s = 0; ph ^= 1; }
      }
      if (inmask) {
        nb_sync(NB_Y, 256);
        wg_fence();
        wgmma_n128_rs<1>(a0, oh[0], oh[1], 0u, 0u, mkdesc(FR, 1024, 0, 1), 1);
        wgmma_n128_rs<1>(a1, oh[2], oh[3], 0u, 0u, mkdesc(FR, 1024, 0, 1), 1);
        wg_commit();
      }
      nb_sync(NB_ST, 256);
      wg_wait<0>();
      reg_fence(a0);
      reg_fence(a1);
    }
    STAMP_IF(leader, 28);
#pragma unroll
    for (int c = 0; c < 2; c++) {
#pragma unroll
      for (int j = 4 * c; j < 4 * c + 4; j++) {
        stsm4(sw[j & 3] + c * 16384, pack(a0[8 * j], a0[8 * j + 1]), pack(a0[8 * j + 2], a0[8 * j + 3]), pack(a0[8 * j + 4], a0[8 * j + 5]), pack(a0[8 * j + 6], a0[8 * j + 7]));
        stsm4(sw[j & 3] + c * 16384 + 8192, pack(a1[8 * j], a1[8 * j + 1]), pack(a1[8 * j + 2], a1[8 * j + 3]), pack(a1[8 * j + 4], a1[8 * j + 5]), pack(a1[8 * j + 6], a1[8 * j + 7]));
      }
      fence_async_smem();
      e_store2d(&mp.m_out, tn * 128 + c * 64, tm * 128 + ww * 16, STG + c * 16384 + ww * 2048);
      e_store2d(&mp.m_out, tn * 128 + c * 64, tm * 128 + 64 + ww * 16, STG + c * 16384 + 8192 + ww * 2048);
    }
    bulk_wait_read();
    if (bid == 0 && leader) st_relaxed(&g_epoch, ep);
    STAMP_IF(leader, 29);
  } else {
    asm volatile("setmaxnreg.inc.sync.aligned.u32 216;");
    const int g = lane >> 2, t4 = lane & 3;
    const bool leader = tid == 0;
    const uint32_t sx = lane & 7, sc = lane >> 4;
    const uint32_t sa = STG + (w * 16 + (lane & 15)) * 128;
    const uint32_t sw[4] = {sa + ((sc ^ sx) << 4), sa + (((2 + sc) ^ sx) << 4), sa + (((4 + sc) ^ sx) << 4), sa + (((6 + sc) ^ sx) << 4)};
    float a0[64], a1[64];
    reg_zero(a0); reg_zero(a1); reg_fence(a0); reg_fence(a1);
    if (ALIGN) { uint32_t now; do { asm volatile("mov.u32 %0, %%clock;" : "=r"(now)); } while ((int)(now - ck0) < ALIGN); }
    mainloop<true>(a0, a1, 0, 0, NB_KV, 0, leader);
    STAMP_IF(leader, 33);
    {
      nb_sync(NB_FDONE, 416);
      STAMP_IF(leader, 34);
      float c[4], z[4] = {0.f, 0.f, 0.f, 0.f}, tt[4] = {0.f, 0.f, 0.f, 0.f};
#pragma unroll
      for (int i = 0; i < 4; i++) c[i] = -__uint_as_float(lds32(S_CSK + ((i >> 1) * 64 + w * 16 + (i & 1) * 8 + g) * 4));
#pragma unroll
      for (int j = 0; j < 8; j++) {
        const float4 s0 = lds128v(S_KSTAT + (j * 16 + 2 * t4) * 8), s1 = lds128v(S_KSTAT + (j * 16 + 8 + 2 * t4) * 8);
        const float mu[4] = {s0.x, s0.z, s1.x, s1.z}, rl[4] = {s0.y, s0.w, s1.y, s1.w};
#pragma unroll
        for (int m = 0; m < 2; m++) {
          float p[8];
#pragma unroll
          for (int i = 0; i < 8; i++) {
            const int r = m * 2 + ((i >> 1) & 1), cc = (i >> 2) * 2 + (i & 1);
            p[i] = phi2(fmaf(c[r], mu[cc], m ? a1[8 * j + i] : a0[8 * j + i]) * rl[cc]);
            z[r] += p[i];
            p[i] *= rl[cc];
            tt[r] = fmaf(p[i], mu[cc], tt[r]);
          }
          stsm4(sw[j & 3] + (j >> 2) * 16384 + m * 8192, pack(p[0], p[1]), pack(p[2], p[3]), pack(p[4], p[5]), pack(p[6], p[7]));
        }
      }
      const bool u2 = lane & 2, u1 = lane & 1;
      const float zz = xred(xred(z[0], z[2], u2, 2), xred(z[1], z[3], u2, 2), u1, 1);
      sts32(S_CSK + ((t4 >> 1) * 64 + w * 16 + (t4 & 1) * 8 + g) * 4, __float_as_uint(xred(xred(tt[0], tt[2], u2, 2), xred(tt[1], tt[3], u2, 2), u1, 1)));
      fence_async_smem();
      nb_arrive(NB_PK, 256);
      st_relaxed(g_z + tm * 1024 + tn * 128 + (t4 >> 1) * 64 + w * 16 + (t4 & 1) * 8 + g, tagf(zz * LOG2E, lds32(S_EPOCH) & 1u));
      nb_arrive(NB_Z, 160);
    }
    STAMP_IF(leader, 35);
    float rl0[2];
    const uint32_t ep = lds32(S_EPOCH);
    {
      nb_sync(NB_CSQ, 160);
      float mu[4];
#pragma unroll
      for (int i = 0; i < 4; i++) {
        const float2 st = lds64f(S_KSTAT + ((i >> 1) * 64 + w * 16 + (i & 1) * 8 + g) * 8);
        mu[i] = -st.x;
        if (i < 2) rl0[i] = st.y;
      }
#pragma unroll
      for (int j = 0; j < 16; j++) {
        const float2 c = lds64f(S_CSQ + (j * 8 + 2 * t4) * 4);
        a0[4 * j] = mu[0] * c.x; a0[4 * j + 1] = mu[0] * c.y; a0[4 * j + 2] = mu[1] * c.x; a0[4 * j + 3] = mu[1] * c.y;
        a1[4 * j] = mu[2] * c.x; a1[4 * j + 1] = mu[2] * c.y; a1[4 * j + 2] = mu[3] * c.x; a1[4 * j + 3] = mu[3] * c.y;
      }
      reg_fence(a0); reg_fence(a1);
    }
    STAMP_IF(leader, 40);
    nb_sync(NB_VQ, 256);
    mainloop<false>(a0, a1, 2, 0, 0, GATE_KT ? NB_KV : 0, leader);
    STAMP_IF(leader, 36);
    {
      uint32_t f[2][16];
      float oc[2][2][20];
      auto phi = [&](const float (&a)[64], int j, int m, uint32_t (&o)[16]) {
        float rl[2] = {rl0[0], rl0[1]};
        if (j | m) { rl[0] = lds32v(S_KSTAT + (m * 64 + w * 16 + g) * 8 + 4); rl[1] = lds32v(S_KSTAT + (m * 64 + w * 16 + 8 + g) * 8 + 4); }
#pragma unroll
        for (int i = 0; i < 16; i++) o[i] = pack(phi2(a[32 * j + 2 * i] * rl[i & 1]), phi2(a[32 * j + 2 * i + 1] * rl[i & 1]));
      };
      auto mma = [&](int j, const uint32_t (&a)[16], float (&o)[2][20]) {
        const uint64_t db = mkdesc(j ? KVB_Z : KVB_P0, 16, 1024, 1);
        reg_zero(o[0]); reg_zero(o[1]);
        wg_fence();
        wgmma_n40_rs<0>(o[0], a[0], a[1], a[2], a[3], db, 0);
        wgmma_n40_rs<0>(o[1], a[8], a[9], a[10], a[11], db + 4, 0);
        wgmma_n40_rs<0>(o[0], a[4], a[5], a[6], a[7], db + 2, 1);
        wgmma_n40_rs<0>(o[1], a[12], a[13], a[14], a[15], db + 6, 1);
        wg_commit();
      };
      auto fin = [&](int j, int m, float (&o)[2][20]) {
        const uint32_t m0 = t4 == 2 * m, m1 = t4 == 2 * m + 1;
#pragma unroll
        for (int h = 0; h < 2; h++) {
          const float r0 = rcp(o[h][j ? 1 : 16] + 1e-6f * LOG2E), r1 = rcp(o[h][j ? 3 : 18] + 1e-6f * LOG2E);
          const int b = j ? 4 : 0;
#pragma unroll
          for (int q = 0; q < 2; q++)
            stsm4(sw[h * 2 + q] + j * 16384 + m * 8192,
                  bsel(pack(o[h][b + 8 * q] * r0, o[h][b + 8 * q + 1] * r0), ep, m0), bsel(pack(o[h][b + 8 * q + 2] * r1, o[h][b + 8 * q + 3] * r1), ep, m1),
                  bsel(pack(o[h][b + 8 * q + 4] * r0, o[h][b + 8 * q + 5] * r0), ep, m0), bsel(pack(o[h][b + 8 * q + 6] * r1, o[h][b + 8 * q + 7] * r1), ep, m1));
        }
      };
#pragma unroll
      for (int j = 0; j < 2; j++) {
        phi(a0, j, 0, f[0]);
        if (j == 0) nb_sync(NB_KVB, 288);
        STAMP_IF(leader && j == 0, 37);
        mma(j, f[0], oc[0]);
        phi(a1, j, 1, f[1]);
        wg_wait<0>();
        reg_fence(oc[0][0]); reg_fence(oc[0][1]);
        mma(j, f[1], oc[1]);
        fin(j, 0, oc[0]);
        if (j == 0) { fence_async_smem(); nb_arrive(NB_Q0, 192); }
        wg_wait<0>();
        reg_fence(oc[1][0]); reg_fence(oc[1][1]);
        fin(j, 1, oc[1]);
        fence_async_smem();
        if (j == 0) nb_arrive(NB_OWN0, 288);
        else { nb_arrive(NB_OWN1, 256); nb_arrive(NB_H1, 160); }
        STAMP_IF(leader, 38 + j);
      }
    }
  }
}

#undef CK
typedef CUresult (*EncodeFn)(CUtensorMap*, CUtensorMapDataType, cuuint32_t, void*, const cuuint64_t*, const cuuint64_t*, const cuuint32_t*,
                             const cuuint32_t*, CUtensorMapInterleave, CUtensorMapSwizzle, CUtensorMapL2promotion, CUtensorMapFloatOOBfill);

void make_map(EncodeFn enc, CUtensorMap* m, const void* p, int rank, uint64_t d0, uint64_t d1, uint64_t d2, uint64_t s1, uint64_t s2,
              uint32_t b0, uint32_t b1, uint32_t b2, CUtensorMapSwizzle sw) {
  cuuint64_t gd[3] = {d0, d1, d2}, gs[2] = {s1, s2};
  cuuint32_t bd[3] = {b0, b1, b2}, es[3] = {1, 1, 1};
  enc(m, CU_TENSOR_MAP_DATA_TYPE_BFLOAT16, rank, const_cast<void*>(p), gd, gs, bd, es, CU_TENSOR_MAP_INTERLEAVE_NONE, sw,
      CU_TENSOR_MAP_L2_PROMOTION_L2_128B, CU_TENSOR_MAP_FLOAT_OOB_FILL_NONE);
}

}

extern "C" void kernel_launch(void* const* d_in, const int* in_sizes, int n_in, void* d_out, int out_size) {
  (void)in_sizes; (void)n_in; (void)out_size;
  void* fn = nullptr;
  cudaDriverEntryPointQueryResult qr;
  cudaGetDriverEntryPoint("cuTensorMapEncodeTiled", &fn, cudaEnableDefault, &qr);
  EncodeFn enc = (EncodeFn)fn;
  void* o;
  cudaGetSymbolAddress(&o, g_o);
  const CUtensorMapSwizzle S128 = CU_TENSOR_MAP_SWIZZLE_128B, S64 = CU_TENSOR_MAP_SWIZZLE_64B, S0 = CU_TENSOR_MAP_SWIZZLE_NONE;
  Params mp;
  mp.x = (const char*)d_in[0]; mp.wqkv = (const char*)d_in[1]; mp.w_r = (const char*)d_in[4];
  mp.wg = (const char*)d_in[5]; mp.wu = (const char*)d_in[6]; mp.wd = (const char*)d_in[7];
  make_map(enc, &mp.m_wqkv, d_in[1], 3, 64, 1024, 48, 6144, 128, 64, 64, 2, S128);
  make_map(enc, &mp.m_x, d_in[0], 2, 1024, 2048, 1, 2048, 0, 64, 128, 1, S128);
  make_map(enc, &mp.m_os, o, 2, 1024, 2048, 1, 2048, 0, 64, 64, 1, S128);
  make_map(enc, &mp.m_o, o, 2, 1024, 2048, 1, 2048, 0, 64, 128, 1, S128);
  make_map(enc, &mp.m_wo, d_in[2], 3, 64, 1024, 16, 2048, 128, 64, 64, 2, S128);
  make_map(enc, &mp.m_xs, d_in[0], 2, 1024, 2048, 1, 2048, 0, 256, 16, 1, S0);
  const char *wg = (const char*)d_in[5], *wu = (const char*)d_in[6];
  make_map(enc, &mp.m_gu, wu < wg ? wu : wg, 3, 3584, 1024, 2, 7168, (uint64_t)(wu < wg ? wg - wu : wu - wg), 32, 32, 2, S64);
  make_map(enc, &mp.m_down, d_in[7], 2, 1024, 3584, 1, 2048, 0, 64, 32, 1, S128);
  make_map(enc, &mp.m_out, d_out, 2, 1024, 2048, 1, 2048, 0, 64, 16, 1, S128);
  int dev = 0, sms = 0;
  cudaGetDevice(&dev);
  cudaDeviceGetAttribute(&sms, cudaDevAttrMultiProcessorCount, dev);
  auto kern = sms == 132 ? fused_kernel<true> : fused_kernel<false>;
  cudaFuncSetAttribute(kern, cudaFuncAttributeMaxDynamicSharedMemorySize, SMEM_BYTES);
  kern<<<132, 512, SMEM_BYTES>>>(mp);
}
```

```cpp
#include <cuda_runtime.h>
#include <cuda.h>
#include <cuda_bf16.h>
#include <stdint.h>

namespace {

template <int TA, int TB>
__device__ __forceinline__ void wgmma_n8_ss(float (&d)[4], uint64_t da, uint64_t db, int sc) {
  asm volatile("{\n.reg .pred p;\nsetp.ne.b32 p, %6, 0;\n"
    "wgmma.mma_async.sync.aligned.m64n8k16.f32.bf16.bf16 {%0, %1, %2, %3}, %4, %5, p, 1, 1, %7, %8;\n}\n"
    : "+f"(d[0]), "+f"(d[1]), "+f"(d[2]), "+f"(d[3])
    : "l"(da), "l"(db), "r"(sc), "n"(TA), "n"(TB));
}
template <int TB>
__device__ __forceinline__ void wgmma_n40_rs(float (&d)[20], uint32_t a0, uint32_t a1, uint32_t a2, uint32_t a3, uint64_t db, int sc) {
  asm volatile("{\n.reg .pred p;\nsetp.ne.b32 p, %25, 0;\n"
    "wgmma.mma_async.sync.aligned.m64n40k16.f32.bf16.bf16 {%0, %1, %2, %3, %4, %5, %6, %7, %8, %9, %10, %11, %12, %13, %14, %15, %16, %17, %18, %19}, {%20,%21,%22,%23}, %24, p, 1, 1, %26;\n}\n"
    : "+f"(d[0]), "+f"(d[1]), "+f"(d[2]), "+f"(d[3]), "+f"(d[4]), "+f"(d[5]), "+f"(d[6]), "+f"(d[7]),
      "+f"(d[8]), "+f"(d[9]), "+f"(d[10]), "+f"(d[11]), "+f"(d[12]), "+f"(d[13]), "+f"(d[14]), "+f"(d[15]),
      "+f"(d[16]), "+f"(d[17]), "+f"(d[18]), "+f"(d[19])
    : "r"(a0), "r"(a1), "r"(a2), "r"(a3), "l"(db), "r"(sc), "n"(TB));
}
template <int TB>
__device__ __forceinline__ void wgmma_n64_rs(float (&d)[32], uint32_t a0, uint32_t a1, uint32_t a2, uint32_t a3, uint64_t db, int sc) {
  asm volatile("{\n.reg .pred p;\nsetp.ne.b32 p, %37, 0;\n"
    "wgmma.mma_async.sync.aligned.m64n64k16.f32.bf16.bf16 {%0, %1, %2, %3, %4, %5, %6, %7, %8, %9, %10, %11, %12, %13, %14, %15, %16, %17, %18, %19, %20, %21, %22, %23, %24, %25, %26, %27, %28, %29, %30, %31}, {%32,%33,%34,%35}, %36, p, 1, 1, %38;\n}\n"
    : "+f"(d[0]), "+f"(d[1]), "+f"(d[2]), "+f"(d[3]), "+f"(d[4]), "+f"(d[5]), "+f"(d[6]), "+f"(d[7]),
      "+f"(d[8]), "+f"(d[9]), "+f"(d[10]), "+f"(d[11]), "+f"(d[12]), "+f"(d[13]), "+f"(d[14]), "+f"(d[15]),
      "+f"(d[16]), "+f"(d[17]), "+f"(d[18]), "+f"(d[19]), "+f"(d[20]), "+f"(d[21]), "+f"(d[22]), "+f"(d[23]),
      "+f"(d[24]), "+f"(d[25]), "+f"(d[26]), "+f"(d[27]), "+f"(d[28]), "+f"(d[29]), "+f"(d[30]), "+f"(d[31])
    : "r"(a0), "r"(a1), "r"(a2), "r"(a3), "l"(db), "r"(sc), "n"(TB));
}
template <int TA, int TB>
__device__ __forceinline__ void wgmma_n128_ss(float (&d)[64], uint64_t da, uint64_t db, int sc) {
  asm volatile("{\n.reg .pred p;\nsetp.ne.b32 p, %66, 0;\n"
    "wgmma.mma_async.sync.aligned.m64n128k16.f32.bf16.bf16 {%0, %1, %2, %3, %4, %5, %6, %7, %8, %9, %10, %11, %12, %13, %14, %15, %16, %17, %18, %19, %20, %21, %22, %23, %24, %25, %26, %27, %28, %29, %30, %31, %32, %33, %34, %35, %36, %37, %38, %39, %40, %41, %42, %43, %44, %45, %46, %47, %48, %49, %50, %51, %52, %53, %54, %55, %56, %57, %58, %59, %60, %61, %62, %63}, %64, %65, p, 1, 1, %67, %68;\n}\n"
    : "+f"(d[0]), "+f"(d[1]), "+f"(d[2]), "+f"(d[3]), "+f"(d[4]), "+f"(d[5]), "+f"(d[6]), "+f"(d[7]),
      "+f"(d[8]), "+f"(d[9]), "+f"(d[10]), "+f"(d[11]), "+f"(d[12]), "+f"(d[13]), "+f"(d[14]), "+f"(d[15]),
      "+f"(d[16]), "+f"(d[17]), "+f"(d[18]), "+f"(d[19]), "+f"(d[20]), "+f"(d[21]), "+f"(d[22]), "+f"(d[23]),
      "+f"(d[24]), "+f"(d[25]), "+f"(d[26]), "+f"(d[27]), "+f"(d[28]), "+f"(d[29]), "+f"(d[30]), "+f"(d[31]),
      "+f"(d[32]), "+f"(d[33]), "+f"(d[34]), "+f"(d[35]), "+f"(d[36]), "+f"(d[37]), "+f"(d[38]), "+f"(d[39]),
      "+f"(d[40]), "+f"(d[41]), "+f"(d[42]), "+f"(d[43]), "+f"(d[44]), "+f"(d[45]), "+f"(d[46]), "+f"(d[47]),
      "+f"(d[48]), "+f"(d[49]), "+f"(d[50]), "+f"(d[51]), "+f"(d[52]), "+f"(d[53]), "+f"(d[54]), "+f"(d[55]),
      "+f"(d[56]), "+f"(d[57]), "+f"(d[58]), "+f"(d[59]), "+f"(d[60]), "+f"(d[61]), "+f"(d[62]), "+f"(d[63])
    : "l"(da), "l"(db), "r"(sc), "n"(TA), "n"(TB));
}
template <int TB>
__device__ __forceinline__ void wgmma_n128_rs(float (&d)[64], uint32_t a0, uint32_t a1, uint32_t a2, uint32_t a3, uint64_t db, int sc) {
  asm volatile("{\n.reg .pred p;\nsetp.ne.b32 p, %69, 0;\n"
    "wgmma.mma_async.sync.aligned.m64n128k16.f32.bf16.bf16 {%0, %1, %2, %3, %4, %5, %6, %7, %8, %9, %10, %11, %12, %13, %14, %15, %16, %17, %18, %19, %20, %21, %22, %23, %24, %25, %26, %27, %28, %29, %30, %31, %32, %33, %34, %35, %36, %37, %38, %39, %40, %41, %42, %43, %44, %45, %46, %47, %48, %49, %50, %51, %52, %53, %54, %55, %56, %57, %58, %59, %60, %61, %62, %63}, {%64,%65,%66,%67}, %68, p, 1, 1, %70;\n}\n"
    : "+f"(d[0]), "+f"(d[1]), "+f"(d[2]), "+f"(d[3]), "+f"(d[4]), "+f"(d[5]), "+f"(d[6]), "+f"(d[7]),
      "+f"(d[8]), "+f"(d[9]), "+f"(d[10]), "+f"(d[11]), "+f"(d[12]), "+f"(d[13]), "+f"(d[14]), "+f"(d[15]),
      "+f"(d[16]), "+f"(d[17]), "+f"(d[18]), "+f"(d[19]), "+f"(d[20]), "+f"(d[21]), "+f"(d[22]), "+f"(d[23]),
      "+f"(d[24]), "+f"(d[25]), "+f"(d[26]), "+f"(d[27]), "+f"(d[28]), "+f"(d[29]), "+f"(d[30]), "+f"(d[31]),
      "+f"(d[32]), "+f"(d[33]), "+f"(d[34]), "+f"(d[35]), "+f"(d[36]), "+f"(d[37]), "+f"(d[38]), "+f"(d[39]),
      "+f"(d[40]), "+f"(d[41]), "+f"(d[42]), "+f"(d[43]), "+f"(d[44]), "+f"(d[45]), "+f"(d[46]), "+f"(d[47]),
      "+f"(d[48]), "+f"(d[49]), "+f"(d[50]), "+f"(d[51]), "+f"(d[52]), "+f"(d[53]), "+f"(d[54]), "+f"(d[55]),
      "+f"(d[56]), "+f"(d[57]), "+f"(d[58]), "+f"(d[59]), "+f"(d[60]), "+f"(d[61]), "+f"(d[62]), "+f"(d[63])
    : "r"(a0), "r"(a1), "r"(a2), "r"(a3), "l"(db), "r"(sc), "n"(TB));
}

__device__ __forceinline__ void poll1(uint32_t (&v)[1], const void* p, uint32_t tag, uint32_t mask) {
  asm volatile("{\n.reg .pred p, q;\n.reg .u32 c, b;\n.reg .b64 x, y;\n.reg .b128 z;\nmov.u32 c, 0;\nLW:\n"
               "ld.relaxed.gpu.global.u32 %0, [%1+0];\n"
               "xor.b32 b, %0, %2;\n"
               "and.b32 b, b, %3;\nsetp.eq.u32 p, b, 0;\nvote.sync.all.pred p, p, 0xffffffff;\n@p bra.uni LD;\n"
               "nanosleep.u32 100;\nadd.u32 c, c, 1;\nsetp.lt.u32 q, c, 1000000;\n@q bra.uni LW;\ntrap;\nLD:\n}"
               : "=&r"(v[0])
               : "l"(p), "r"(tag), "r"(mask) : "memory");
}
__device__ __forceinline__ void poll1f(uint32_t (&v)[1], const void* p, uint32_t tag, uint32_t mask) {
  asm volatile("{\n.reg .pred p, q;\n.reg .u32 c, b;\n.reg .b64 x, y;\n.reg .b128 z;\nmov.u32 c, 0;\nLW:\n"
               "ld.relaxed.gpu.global.u32 %0, [%1+0];\n"
               "xor.b32 b, %0, %2;\n"
               "and.b32 b, b, %3;\nsetp.eq.u32 p, b, 0;\nvote.sync.all.pred p, p, 0xffffffff;\n@p bra.uni LD;\n"
               "nanosleep.u32 50;\nadd.u32 c, c, 1;\nsetp.lt.u32 q, c, 1000000;\n@q bra.uni LW;\ntrap;\nLD:\n}"
               : "=&r"(v[0])
               : "l"(p), "r"(tag), "r"(mask) : "memory");
}
__device__ __forceinline__ void poll0(uint32_t (&v)[1], const void* p, uint32_t tag, uint32_t mask) {
  asm volatile("{\n.reg .pred p, q;\n.reg .u32 c, b;\n.reg .b64 x, y;\n.reg .b128 z;\nmov.u32 c, 0;\nLW:\n"
               "ld.relaxed.gpu.global.u32 %0, [%1+0];\n"
               "xor.b32 b, %0, %2;\n"
               "and.b32 b, b, %3;\nsetp.eq.u32 p, b, 0;\nvote.sync.all.pred p, p, 0xffffffff;\n@p bra.uni LD;\n"
               "add.u32 c, c, 1;\nsetp.lt.u32 q, c, 1000000;\n@q bra.uni LW;\ntrap;\nLD:\n}"
               : "=&r"(v[0])
               : "l"(p), "r"(tag), "r"(mask) : "memory");
}
__device__ __forceinline__ void poll_pair(uint32_t (&v)[2], const void* p, uint32_t tag, uint32_t mask) {
  asm volatile("{\n.reg .pred p, q;\n.reg .u32 c, b;\n.reg .b64 x, y;\n.reg .b128 z;\nmov.u32 c, 0;\nLW:\n"
               "ld.relaxed.gpu.global.b64 x, [%2+0];\nmov.b64 {%0,%1}, x;\n"
               "xor.b32 b, %0, %3;\n"
               "and.b32 b, b, %4;\nsetp.eq.u32 p, b, 0;\nvote.sync.all.pred p, p, 0xffffffff;\n@p bra.uni LD;\n"
               "nanosleep.u32 100;\nadd.u32 c, c, 1;\nsetp.lt.u32 q, c, 1000000;\n@q bra.uni LW;\ntrap;\nLD:\n}"
               : "=&r"(v[0]), "=&r"(v[1])
               : "l"(p), "r"(tag), "r"(mask) : "memory");
}
__device__ __forceinline__ void poll_quad(uint32_t (&v)[4], const void* p, uint32_t tag, uint32_t mask) {
  asm volatile("{\n.reg .pred p, q;\n.reg .u32 c, b;\n.reg .b64 x, y;\n.reg .b128 z;\nmov.u32 c, 0;\nLW:\n"
               "ld.relaxed.gpu.global.v4.u32 {%0,%1,%2,%3}, [%4+0];\n"
               "xor.b32 b, %0, %5;\n"
               "lop3.b32 b, b, %1, %5, 0xf6;\nlop3.b32 b, b, %2, %5, 0xf6;\nlop3.b32 b, b, %3, %5, 0xf6;\n"
               "and.b32 b, b, %6;\nsetp.eq.u32 p, b, 0;\nvote.sync.all.pred p, p, 0xffffffff;\n@p bra.uni LD;\n"
               "nanosleep.u32 200;\nadd.u32 c, c, 1;\nsetp.lt.u32 q, c, 1000000;\n@q bra.uni LW;\ntrap;\nLD:\n}"
               : "=&r"(v[0]), "=&r"(v[1]), "=&r"(v[2]), "=&r"(v[3])
               : "l"(p), "r"(tag), "r"(mask) : "memory");
}
__device__ __forceinline__ void poll8x4(uint32_t (&v)[32], const void* p, uint32_t tag, uint32_t mask) {
  asm volatile("{\n.reg .pred p, q;\n.reg .u32 c, b;\n.reg .b64 x, y;\n.reg .b128 z;\nmov.u32 c, 0;\nLW:\n"
               "ld.relaxed.gpu.global.v4.u32 {%0,%1,%2,%3}, [%32+0];\n"
               "ld.relaxed.gpu.global.v4.u32 {%4,%5,%6,%7}, [%32+2048];\n"
               "ld.relaxed.gpu.global.v4.u32 {%8,%9,%10,%11}, [%32+4096];\n"
               "ld.relaxed.gpu.global.v4.u32 {%12,%13,%14,%15}, [%32+6144];\n"
               "ld.relaxed.gpu.global.v4.u32 {%16,%17,%18,%19}, [%32+8192];\n"
               "ld.relaxed.gpu.global.v4.u32 {%20,%21,%22,%23}, [%32+10240];\n"
               "ld.relaxed.gpu.global.v4.u32 {%24,%25,%26,%27}, [%32+12288];\n"
               "ld.relaxed.gpu.global.v4.u32 {%28,%29,%30,%31}, [%32+14336];\n"
               "xor.b32 b, %0, %33;\n"
               "lop3.b32 b, b, %1, %33, 0xf6;\nlop3.b32 b, b, %2, %33, 0xf6;\nlop3.b32 b, b, %3, %33, 0xf6;\nlop3.b32 b, b, %4, %33, 0xf6;\n"
               "lop3.b32 b, b, %5, %33, 0xf6;\nlop3.b32 b, b, %6, %33, 0xf6;\nlop3.b32 b, b, %7, %33, 0xf6;\nlop3.b32 b, b, %8, %33, 0xf6;\n"
               "lop3.b32 b, b, %9, %33, 0xf6;\nlop3.b32 b, b, %10, %33, 0xf6;\nlop3.b32 b, b, %11, %33, 0xf6;\nlop3.b32 b, b, %12, %33, 0xf6;\n"
               "lop3.b32 b, b, %13, %33, 0xf6;\nlop3.b32 b, b, %14, %33, 0xf6;\nlop3.b32 b, b, %15, %33, 0xf6;\nlop3.b32 b, b, %16, %33, 0xf6;\n"
               "lop3.b32 b, b, %17, %33, 0xf6;\nlop3.b32 b, b, %18, %33, 0xf6;\nlop3.b32 b, b, %19, %33, 0xf6;\nlop3.b32 b, b, %20, %33, 0xf6;\n"
               "lop3.b32 b, b, %21, %33, 0xf6;\nlop3.b32 b, b, %22, %33, 0xf6;\nlop3.b32 b, b, %23, %33, 0xf6;\nlop3.b32 b, b, %24, %33, 0xf6;\n"
               "lop3.b32 b, b, %25, %33, 0xf6;\nlop3.b32 b, b, %26, %33, 0xf6;\nlop3.b32 b, b, %27, %33, 0xf6;\nlop3.b32 b, b, %28, %33, 0xf6;\n"
               "lop3.b32 b, b, %29, %33, 0xf6;\nlop3.b32 b, b, %30, %33, 0xf6;\nlop3.b32 b, b, %31, %33, 0xf6;\n"
               "and.b32 b, b, %34;\nsetp.eq.u32 p, b, 0;\nvote.sync.all.pred p, p, 0xffffffff;\n@p bra.uni LD;\n"
               "nanosleep.u32 50;\nadd.u32 c, c, 1;\nsetp.lt.u32 q, c, 1000000;\n@q bra.uni LW;\ntrap;\nLD:\n}"
               : "=&r"(v[0]), "=&r"(v[1]), "=&r"(v[2]), "=&r"(v[3]), "=&r"(v[4]), "=&r"(v[5]), "=&r"(v[6]), "=&r"(v[7]), "=&r"(v[8]), "=&r"(v[9]), "=&r"(v[10]), "=&r"(v[11]), "=&r"(v[12]), "=&r"(v[13]), "=&r"(v[14]), "=&r"(v[15]), "=&r"(v[16]), "=&r"(v[17]), "=&r"(v[18]), "=&r"(v[19]), "=&r"(v[20]), "=&r"(v[21]), "=&r"(v[22]), "=&r"(v[23]), "=&r"(v[24]), "=&r"(v[25]), "=&r"(v[26]), "=&r"(v[27]), "=&r"(v[28]), "=&r"(v[29]), "=&r"(v[30]), "=&r"(v[31])
               : "l"(p), "r"(tag), "r"(mask) : "memory");
}
__device__ __forceinline__ void poll16(uint32_t (&v)[16], const void* p, uint32_t tag, uint32_t mask) {
  asm volatile("{\n.reg .pred p, q;\n.reg .u32 c, b;\n.reg .b64 x, y;\n.reg .b128 z;\nmov.u32 c, 0;\nLW:\n"
               "ld.relaxed.gpu.global.u32 %0, [%16+0];\n"
               "ld.relaxed.gpu.global.u32 %1, [%16+4096];\n"
               "ld.relaxed.gpu.global.u32 %2, [%16+8192];\n"
               "ld.relaxed.gpu.global.u32 %3, [%16+12288];\n"
               "ld.relaxed.gpu.global.u32 %4, [%16+16384];\n"
               "ld.relaxed.gpu.global.u32 %5, [%16+20480];\n"
               "ld.relaxed.gpu.global.u32 %6, [%16+24576];\n"
               "ld.relaxed.gpu.global.u32 %7, [%16+28672];\n"
               "ld.relaxed.gpu.global.u32 %8, [%16+32768];\n"
               "ld.relaxed.gpu.global.u32 %9, [%16+36864];\n"
               "ld.relaxed.gpu.global.u32 %10, [%16+40960];\n"
               "ld.relaxed.gpu.global.u32 %11, [%16+45056];\n"
               "ld.relaxed.gpu.global.u32 %12, [%16+49152];\n"
               "ld.relaxed.gpu.global.u32 %13, [%16+53248];\n"
               "ld.relaxed.gpu.global.u32 %14, [%16+57344];\n"
               "ld.relaxed.gpu.global.u32 %15, [%16+61440];\n"
               "xor.b32 b, %0, %17;\n"
               "lop3.b32 b, b, %1, %17, 0xf6;\nlop3.b32 b, b, %2, %17, 0xf6;\nlop3.b32 b, b, %3, %17, 0xf6;\nlop3.b32 b, b, %4, %17, 0xf6;\n"
               "lop3.b32 b, b, %5, %17, 0xf6;\nlop3.b32 b, b, %6, %17, 0xf6;\nlop3.b32 b, b, %7, %17, 0xf6;\nlop3.b32 b, b, %8, %17, 0xf6;\n"
               "lop3.b32 b, b, %9, %17, 0xf6;\nlop3.b32 b, b, %10, %17, 0xf6;\nlop3.b32 b, b, %11, %17, 0xf6;\nlop3.b32 b, b, %12, %17, 0xf6;\n"
               "lop3.b32 b, b, %13, %17, 0xf6;\nlop3.b32 b, b, %14, %17, 0xf6;\nlop3.b32 b, b, %15, %17, 0xf6;\n"
               "and.b32 b, b, %18;\nsetp.eq.u32 p, b, 0;\nvote.sync.all.pred p, p, 0xffffffff;\n@p bra.uni LD;\n"
               "nanosleep.u32 200;\nadd.u32 c, c, 1;\nsetp.lt.u32 q, c, 1000000;\n@q bra.uni LW;\ntrap;\nLD:\n}"
               : "=&r"(v[0]), "=&r"(v[1]), "=&r"(v[2]), "=&r"(v[3]), "=&r"(v[4]), "=&r"(v[5]), "=&r"(v[6]), "=&r"(v[7]), "=&r"(v[8]), "=&r"(v[9]), "=&r"(v[10]), "=&r"(v[11]), "=&r"(v[12]), "=&r"(v[13]), "=&r"(v[14]), "=&r"(v[15])
               : "l"(p), "r"(tag), "r"(mask) : "memory");
}
__device__ __forceinline__ void poll_keys(uint32_t (&v)[16], const void* p, uint32_t tag, uint32_t mask) {
  asm volatile("{\n.reg .pred p, q;\n.reg .u32 c, b;\n.reg .b64 x, y;\n.reg .b128 z;\nmov.u32 c, 0;\nLW:\n"
               "ld.relaxed.gpu.global.v2.b64 {x, y}, [%16+0];\nmov.b64 {%0,%1}, x;\nmov.b64 {%2,%3}, y;\n"
               "ld.relaxed.gpu.global.v2.b64 {x, y}, [%16+4096];\nmov.b64 {%4,%5}, x;\nmov.b64 {%6,%7}, y;\n"
               "ld.relaxed.gpu.global.v2.b64 {x, y}, [%16+8192];\nmov.b64 {%8,%9}, x;\nmov.b64 {%10,%11}, y;\n"
               "ld.relaxed.gpu.global.v2.b64 {x, y}, [%16+12288];\nmov.b64 {%12,%13}, x;\nmov.b64 {%14,%15}, y;\n"
               "xor.b32 b, %0, %17;\n"
               "lop3.b32 b, b, %2, %17, 0xf6;\nlop3.b32 b, b, %4, %17, 0xf6;\nlop3.b32 b, b, %6, %17, 0xf6;\nlop3.b32 b, b, %8, %17, 0xf6;\n"
               "lop3.b32 b, b, %10, %17, 0xf6;\nlop3.b32 b, b, %12, %17, 0xf6;\nlop3.b32 b, b, %14, %17, 0xf6;\n"
               "and.b32 b, b, %18;\nsetp.eq.u32 p, b, 0;\nvote.sync.all.pred p, p, 0xffffffff;\n@p bra.uni LD;\n"
               "nanosleep.u32 20;\nadd.u32 c, c, 1;\nsetp.lt.u32 q, c, 1000000;\n@q bra.uni LW;\ntrap;\nLD:\n}"
               : "=&r"(v[0]), "=&r"(v[1]), "=&r"(v[2]), "=&r"(v[3]), "=&r"(v[4]), "=&r"(v[5]), "=&r"(v[6]), "=&r"(v[7]), "=&r"(v[8]), "=&r"(v[9]), "=&r"(v[10]), "=&r"(v[11]), "=&r"(v[12]), "=&r"(v[13]), "=&r"(v[14]), "=&r"(v[15])
               : "l"(p), "r"(tag), "r"(mask) : "memory");
}
__device__ __forceinline__ void poll_z(uint32_t (&v)[16], const void* p, uint32_t tag, uint32_t mask) {
  asm volatile("{\n.reg .pred p, q;\n.reg .u32 c, b;\n.reg .b64 x, y;\n.reg .b128 z;\nmov.u32 c, 0;\nLW:\n"
               "ld.relaxed.gpu.global.v4.u32 {%0,%1,%2,%3}, [%16+0];\n"
               "ld.relaxed.gpu.global.v4.u32 {%4,%5,%6,%7}, [%16+4096];\n"
               "ld.relaxed.gpu.global.v4.u32 {%8,%9,%10,%11}, [%16+8192];\n"
               "ld.relaxed.gpu.global.v4.u32 {%12,%13,%14,%15}, [%16+12288];\n"
               "xor.b32 b, %0, %17;\n"
               "lop3.b32 b, b, %1, %17, 0xf6;\nlop3.b32 b, b, %2, %17, 0xf6;\nlop3.b32 b, b, %3, %17, 0xf6;\nlop3.b32 b, b, %4, %17, 0xf6;\n"
               "lop3.b32 b, b, %5, %17, 0xf6;\nlop3.b32 b, b, %6, %17, 0xf6;\nlop3.b32 b, b, %7, %17, 0xf6;\nlop3.b32 b, b, %8, %17, 0xf6;\n"
               "lop3.b32 b, b, %9, %17, 0xf6;\nlop3.b32 b, b, %10, %17, 0xf6;\nlop3.b32 b, b, %11, %17, 0xf6;\nlop3.b32 b, b, %12, %17, 0xf6;\n"
               "lop3.b32 b, b, %13, %17, 0xf6;\nlop3.b32 b, b, %14, %17, 0xf6;\nlop3.b32 b, b, %15, %17, 0xf6;\n"
               "and.b32 b, b, %18;\nsetp.eq.u32 p, b, 0;\nvote.sync.all.pred p, p, 0xffffffff;\n@p bra.uni LD;\n"
               "nanosleep.u32 300;\nadd.u32 c, c, 1;\nsetp.lt.u32 q, c, 1000000;\n@q bra.uni LW;\ntrap;\nLD:\n}"
               : "=&r"(v[0]), "=&r"(v[1]), "=&r"(v[2]), "=&r"(v[3]), "=&r"(v[4]), "=&r"(v[5]), "=&r"(v[6]), "=&r"(v[7]), "=&r"(v[8]), "=&r"(v[9]), "=&r"(v[10]), "=&r"(v[11]), "=&r"(v[12]), "=&r"(v[13]), "=&r"(v[14]), "=&r"(v[15])
               : "l"(p), "r"(tag), "r"(mask) : "memory");
}
__device__ __forceinline__ void poll7x4(uint32_t (&v)[28], const void* p, uint32_t tag, uint32_t mask) {
  asm volatile("{\n.reg .pred p, q;\n.reg .u32 c, b;\n.reg .b64 x, y;\n.reg .b128 z;\nmov.u32 c, 0;\nLW:\n"
               "ld.relaxed.gpu.global.v4.u32 {%0,%1,%2,%3}, [%28+0];\n"
               "ld.relaxed.gpu.global.v4.u32 {%4,%5,%6,%7}, [%28+2048];\n"
               "ld.relaxed.gpu.global.v4.u32 {%8,%9,%10,%11}, [%28+4096];\n"
               "ld.relaxed.gpu.global.v4.u32 {%12,%13,%14,%15}, [%28+6144];\n"
               "ld.relaxed.gpu.global.v4.u32 {%16,%17,%18,%19}, [%28+8192];\n"
               "ld.relaxed.gpu.global.v4.u32 {%20,%21,%22,%23}, [%28+10240];\n"
               "ld.relaxed.gpu.global.v4.u32 {%24,%25,%26,%27}, [%28+12288];\n"
               "xor.b32 b, %0, %29;\n"
               "lop3.b32 b, b, %1, %29, 0xf6;\nlop3.b32 b, b, %2, %29, 0xf6;\nlop3.b32 b, b, %3, %29, 0xf6;\nlop3.b32 b, b, %4, %29, 0xf6;\n"
               "lop3.b32 b, b, %5, %29, 0xf6;\nlop3.b32 b, b, %6, %29, 0xf6;\nlop3.b32 b, b, %7, %29, 0xf6;\nlop3.b32 b, b, %8, %29, 0xf6;\n"
               "lop3.b32 b, b, %9, %29, 0xf6;\nlop3.b32 b, b, %10, %29, 0xf6;\nlop3.b32 b, b, %11, %29, 0xf6;\nlop3.b32 b, b, %12, %29, 0xf6;\n"
               "lop3.b32 b, b, %13, %29, 0xf6;\nlop3.b32 b, b, %14, %29, 0xf6;\nlop3.b32 b, b, %15, %29, 0xf6;\nlop3.b32 b, b, %16, %29, 0xf6;\n"
               "lop3.b32 b, b, %17, %29, 0xf6;\nlop3.b32 b, b, %18, %29, 0xf6;\nlop3.b32 b, b, %19, %29, 0xf6;\nlop3.b32 b, b, %20, %29, 0xf6;\n"
               "lop3.b32 b, b, %21, %29, 0xf6;\nlop3.b32 b, b, %22, %29, 0xf6;\nlop3.b32 b, b, %23, %29, 0xf6;\nlop3.b32 b, b, %24, %29, 0xf6;\n"
               "lop3.b32 b, b, %25, %29, 0xf6;\nlop3.b32 b, b, %26, %29, 0xf6;\nlop3.b32 b, b, %27, %29, 0xf6;\n"
               "and.b32 b, b, %30;\nsetp.eq.u32 p, b, 0;\nvote.sync.all.pred p, p, 0xffffffff;\n@p bra.uni LD;\n"
               "nanosleep.u32 50;\nadd.u32 c, c, 1;\nsetp.lt.u32 q, c, 1000000;\n@q bra.uni LW;\ntrap;\nLD:\n}"
               : "=&r"(v[0]), "=&r"(v[1]), "=&r"(v[2]), "=&r"(v[3]), "=&r"(v[4]), "=&r"(v[5]), "=&r"(v[6]), "=&r"(v[7]), "=&r"(v[8]), "=&r"(v[9]), "=&r"(v[10]), "=&r"(v[11]), "=&r"(v[12]), "=&r"(v[13]), "=&r"(v[14]), "=&r"(v[15]), "=&r"(v[16]), "=&r"(v[17]), "=&r"(v[18]), "=&r"(v[19]), "=&r"(v[20]), "=&r"(v[21]), "=&r"(v[22]), "=&r"(v[23]), "=&r"(v[24]), "=&r"(v[25]), "=&r"(v[26]), "=&r"(v[27])
               : "l"(p), "r"(tag), "r"(mask) : "memory");
}
__device__ __forceinline__ void poll_kvp(uint32_t (&v)[16], const void* p, uint32_t tag, uint32_t mask) {
  asm volatile("{\n.reg .pred p, q;\n.reg .u32 c, b;\n.reg .b64 x, y;\n.reg .b128 z;\nmov.u32 c, 0;\nLW:\n"
               "ld.relaxed.gpu.global.b128 z, [%16+0];\nmov.b128 {x, y}, z;\nmov.b64 {%0,%1}, x;\nmov.b64 {%2,%3}, y;\n"
               "ld.relaxed.gpu.global.b128 z, [%16+8192];\nmov.b128 {x, y}, z;\nmov.b64 {%4,%5}, x;\nmov.b64 {%6,%7}, y;\n"
               "ld.relaxed.gpu.global.b128 z, [%16+16384];\nmov.b128 {x, y}, z;\nmov.b64 {%8,%9}, x;\nmov.b64 {%10,%11}, y;\n"
               "ld.relaxed.gpu.global.b128 z, [%16+24576];\nmov.b128 {x, y}, z;\nmov.b64 {%12,%13}, x;\nmov.b64 {%14,%15}, y;\n"
               "xor.b32 b, %0, %17;\n"
               "lop3.b32 b, b, %4, %17, 0xf6;\nlop3.b32 b, b, %8, %17, 0xf6;\nlop3.b32 b, b, %12, %17, 0xf6;\n"
               "and.b32 b, b, %18;\nsetp.eq.u32 p, b, 0;\nvote.sync.all.pred p, p, 0xffffffff;\n@p bra.uni LD;\n"
               "nanosleep.u32 50;\nadd.u32 c, c, 1;\nsetp.lt.u32 q, c, 1000000;\n@q bra.uni LW;\ntrap;\nLD:\n}"
               : "=&r"(v[0]), "=&r"(v[1]), "=&r"(v[2]), "=&r"(v[3]), "=&r"(v[4]), "=&r"(v[5]), "=&r"(v[6]), "=&r"(v[7]), "=&r"(v[8]), "=&r"(v[9]), "=&r"(v[10]), "=&r"(v[11]), "=&r"(v[12]), "=&r"(v[13]), "=&r"(v[14]), "=&r"(v[15])
               : "l"(p), "r"(tag), "r"(mask) : "memory");
}
__device__ __forceinline__ void poll_kv(uint32_t (&v)[16], const void* p, uint32_t tag, uint32_t mask) {
  asm volatile("{\n.reg .pred p, q;\n.reg .u32 c, b;\n.reg .b64 x, y;\n.reg .b128 z;\nmov.u32 c, 0;\nLW:\n"
               "ld.relaxed.gpu.global.b128 z, [%16+0];\nmov.b128 {x, y}, z;\nmov.b64 {%0,%1}, x;\nmov.b64 {%2,%3}, y;\n"
               "ld.relaxed.gpu.global.b128 z, [%16+2048];\nmov.b128 {x, y}, z;\nmov.b64 {%4,%5}, x;\nmov.b64 {%6,%7}, y;\n"
               "ld.relaxed.gpu.global.b128 z, [%16+4096];\nmov.b128 {x, y}, z;\nmov.b64 {%8,%9}, x;\nmov.b64 {%10,%11}, y;\n"
               "ld.relaxed.gpu.global.b128 z, [%16+6144];\nmov.b128 {x, y}, z;\nmov.b64 {%12,%13}, x;\nmov.b64 {%14,%15}, y;\n"
               "xor.b32 b, %0, %17;\n"
               "lop3.b32 b, b, %4, %17, 0xf6;\nlop3.b32 b, b, %8, %17, 0xf6;\nlop3.b32 b, b, %12, %17, 0xf6;\n"
               "and.b32 b, b, %18;\nsetp.eq.u32 p, b, 0;\nvote.sync.all.pred p, p, 0xffffffff;\n@p bra.uni LD;\n"
               "nanosleep.u32 50;\nadd.u32 c, c, 1;\nsetp.lt.u32 q, c, 1000000;\n@q bra.uni LW;\ntrap;\nLD:\n}"
               : "=&r"(v[0]), "=&r"(v[1]), "=&r"(v[2]), "=&r"(v[3]), "=&r"(v[4]), "=&r"(v[5]), "=&r"(v[6]), "=&r"(v[7]), "=&r"(v[8]), "=&r"(v[9]), "=&r"(v[10]), "=&r"(v[11]), "=&r"(v[12]), "=&r"(v[13]), "=&r"(v[14]), "=&r"(v[15])
               : "l"(p), "r"(tag), "r"(mask) : "memory");
}

__device__ __align__(1024) __nv_bfloat16 g_o[2048 * 1024];
__device__ __align__(128) uint2 g_keys[2048];
__device__ __align__(128) uint32_t g_csum[18 * 1024];
__device__ __align__(128) uint32_t g_z[16 * 1024];
__device__ __align__(128) uint4 g_kvp[128 * 512];
__device__ __align__(128) uint4 g_kv[8 * 512];
__device__ __align__(128) uint32_t g_h[112 * 256];
__device__ __align__(128) uint32_t g_yp[128 * 512];
__device__ __align__(128) uint32_t g_xsel[4096 + 32];
enum { H_CS = 0, H_KVP = 8, H_KV = 16, H_H = 24, H_Y = 32, H_O = 40, H_R = 56, H_Z = 57 };
__device__ __align__(128) uint32_t g_sig[65 * 32];
__device__ uint32_t g_epoch;

constexpr uint32_t RING = 1024, SLOT = 32768, SMEM_BYTES = 232448;
constexpr int NST = 5, HST = 7;
constexpr uint32_t STG = RING + 163840, AUX = RING + 196608, FR = RING + 212992, MISC = RING + 229376;
constexpr uint32_t B_FULL = MISC, B_EMPTY = MISC + 56, B_XS = MISC + 112, B_SEL = MISC + 144, B_XRES = MISC + 152, B_WK = MISC + 160, B_CSDN = MISC + 168,
                   B_FR = MISC + 176, B_FE = MISC + 216, B_DR = MISC + 256, B_CSV = MISC + 288,
                   B_OWN = MISC + 296, NBAR = 39;
constexpr uint32_t S_EPOCH = MISC + 352, S_NCAND = MISC + 356, S_SEL = MISC + 368, S_WMAX = MISC + 400,
                   S_KSTAT = MISC + 512, S_CSK = MISC + 1536, S_CSV = MISC + 2048, S_CSQ = MISC + 2560, S_ONES = MISC + 512;
constexpr uint32_t KVB_P0 = AUX, KVB_Z = AUX + 4096, KVB_P1 = AUX + 5120, HOP = AUX + 9216, GR = FR - 4096;
enum { NB_Z = 0, NB_KV = 1, NB_VQ = 2, NB_WG0 = 3, NB_FDONE = 4, NB_PK = 5, NB_KVB = 6, NB_WG1 = 7, NB_WG2 = 8, NB_CSQ = 9,
       NB_Y = 10, NB_ST = 11, NB_OWN0 = 12, NB_OWN1 = 13, NB_Q0 = 14, NB_H1 = 15 };

#define XS_AT -1
#define XS_FLY 4
#define H_DELAY 500
#define FFN_GAP 200
#define GATE_KT 1
#define GATE_K 6
#define KV_DIRECT 1
#define ALIGN 3400
#define DN_GAP 50
#define PF_GAP 200
#define PF_WAIT 1000
#define POLITE 0
constexpr uint64_t EVICT_FIRST = 0x12f0000000000000ull;
constexpr float LOG2E = 1.4426950408889634f, LN2 = 0.6931471805599453f;

#define ELECT "{\n.reg .pred p;\nelect.sync _|p, 0xffffffff;\n"
#define TMA2D "cp.async.bulk.tensor.2d.shared::cluster.global.mbarrier::complete_tx::bytes"
#define TMA3D "cp.async.bulk.tensor.3d.shared::cluster.global.mbarrier::complete_tx::bytes"
__device__ __forceinline__ void e_expect(uint32_t b, uint32_t n) {
  asm volatile(ELECT "@p mbarrier.arrive.expect_tx.shared::cta.b64 _, [%0], %1;\n}" ::"r"(b), "r"(n) : "memory");
}
__device__ __forceinline__ void e_arrive(uint32_t b) { asm volatile(ELECT "@p mbarrier.arrive.shared::cta.b64 _, [%0];\n}" ::"r"(b) : "memory"); }
__device__ __forceinline__ void e_tma2d(uint32_t dst, const CUtensorMap* m, int c0, int c1, uint32_t bar) {
  asm volatile(ELECT "@p " TMA2D " [%0], [%1, {%3, %4}], [%2];\n}" ::"r"(dst), "l"(m), "r"(bar), "r"(c0), "r"(c1) : "memory");
}
__device__ __forceinline__ void e_tma2d_ef(uint32_t dst, const CUtensorMap* m, int c0, int c1, uint32_t bar, uint64_t pol) {
  asm volatile(ELECT "@p " TMA2D ".L2::cache_hint [%0], [%1, {%3, %4}], [%2], %5;\n}" ::"r"(dst), "l"(m), "r"(bar), "r"(c0), "r"(c1), "l"(pol) : "memory");
}
__device__ __forceinline__ void e_tma3d(uint32_t dst, const CUtensorMap* m, int c1, int c2, uint32_t bar) {
  asm volatile(ELECT "@p " TMA3D " [%0], [%1, {0, %3, %4}], [%2];\n}" ::"r"(dst), "l"(m), "r"(bar), "r"(c1), "r"(c2) : "memory");
}
__device__ __forceinline__ void e_store2d(const CUtensorMap* m, int c0, int c1, uint32_t src) {
  asm volatile(ELECT "@p cp.async.bulk.tensor.2d.global.shared::cta.bulk_group [%0, {%2, %3}], [%1];\n}" ::"l"(m), "r"(src), "r"(c0), "r"(c1) : "memory");
}
__device__ __forceinline__ void e_tma3d_ef(uint32_t dst, const CUtensorMap* m, int c0, int c1, uint32_t bar, uint64_t pol) {
  asm volatile(ELECT "@p " TMA3D ".L2::cache_hint [%0], [%1, {%3, %4, 0}], [%2], %5;\n}" ::"r"(dst), "l"(m), "r"(bar), "r"(c0), "r"(c1), "l"(pol) : "memory");
}
__device__ __forceinline__ void e_load(uint32_t dst, const void* src, uint32_t n, uint32_t bar) {
  asm volatile(ELECT "@p cp.async.bulk.shared::cluster.global.mbarrier::complete_tx::bytes [%0], [%1], %2, [%3];\n}" ::"r"(dst), "l"(src), "r"(n), "r"(bar) : "memory");
}
__device__ __forceinline__ void e_pfmap(const CUtensorMap* m) { asm volatile(ELECT "@p prefetch.tensormap [%0];\n}" ::"l"(m) : "memory"); }
__device__ __forceinline__ void bulk_wait_read() { asm volatile("cp.async.bulk.commit_group;\ncp.async.bulk.wait_group.read 0;" ::: "memory"); }
__device__ __forceinline__ void e_signal(int word, int bit) {
  asm volatile(ELECT "@p red.relaxed.gpu.global.xor.b32 [%0], %1;\n}" ::"l"(g_sig + word * 32), "r"(1u << bit) : "memory");
}
__device__ __forceinline__ void e_release(int word, int bit) {
  asm volatile("cp.async.bulk.commit_group;\ncp.async.bulk.wait_group 0;\nfence.release.gpu;" ::: "memory");
  e_signal(word, bit);
}
__device__ __forceinline__ void await(int word, uint32_t mask, uint32_t ep) {
  uint32_t f[1];
  poll1f(f, g_sig + word * 32, 0u - (ep & 1u), mask);
}

__device__ __forceinline__ void mbar_arrive(uint32_t b) { asm volatile("mbarrier.arrive.shared::cta.b64 _, [%0];" ::"r"(b) : "memory"); }
__device__ __forceinline__ void mbar_wait(uint32_t b, uint32_t ph) {
  asm volatile("{\n.reg .pred p, q;\n.reg .u32 c;\nmov.u32 c, 0;\nLW:\nmbarrier.try_wait.parity.shared::cta.b64 p, [%0], %1;\n@p bra LD;\n"
               "add.u32 c, c, 1;\nsetp.lt.u32 q, c, 100000;\n@q bra LW;\ntrap;\nLD:\n}" ::"r"(b), "r"(ph) : "memory");
}
__device__ __forceinline__ void nb_sync(int id, int n) { asm volatile("bar.sync %0, %1;" ::"r"(id), "r"(n) : "memory"); }
__device__ __forceinline__ void nb_arrive(int id, int n) { asm volatile("bar.arrive %0, %1;" ::"r"(id), "r"(n) : "memory"); }
__device__ __forceinline__ void wg_fence() { asm volatile("wgmma.fence.sync.aligned;" ::: "memory"); }
__device__ __forceinline__ void wg_commit() { asm volatile("wgmma.commit_group.sync.aligned;" ::: "memory"); }
template <int N> __device__ __forceinline__ void wg_wait() { asm volatile("wgmma.wait_group.sync.aligned %0;" ::"n"(N) : "memory"); }
template <int N> __device__ __forceinline__ void reg_fence(float (&a)[N]) {
#pragma unroll
  for (int i = 0; i < N; i++) asm volatile("" : "+f"(a[i])::"memory");
}
template <int N> __device__ __forceinline__ void reg_zero(float (&a)[N]) {
#pragma unroll
  for (int i = 0; i < N; i++) a[i] = 0.f;
}
__device__ __forceinline__ constexpr uint64_t mkdesc(uint32_t addr, uint32_t lbo, uint32_t sbo, uint32_t swz) {
  return (uint64_t)(addr >> 4) | ((uint64_t)(lbo >> 4) << 16) | ((uint64_t)(sbo >> 4) << 32) | ((uint64_t)swz << 62);
}
__device__ __forceinline__ void fence_async_smem() { asm volatile("fence.proxy.async.shared::cta;" ::: "memory"); }
__device__ __forceinline__ void fence_async_glob() { asm volatile("fence.proxy.async.global;" ::: "memory"); }
__device__ __forceinline__ void fence_acq() { asm volatile("fence.acquire.gpu;" ::: "memory"); }
__device__ __forceinline__ void st_relaxed(uint32_t* p, uint32_t v) { asm volatile("st.relaxed.gpu.global.u32 [%0], %1;" ::"l"(p), "r"(v) : "memory"); }
__device__ __forceinline__ uint32_t ld_relaxed(const uint32_t* p) { uint32_t v; asm volatile("ld.relaxed.gpu.global.u32 %0, [%1];" : "=r"(v) : "l"(p) : "memory"); return v; }
__device__ __forceinline__ void st_unit(uint4* p, uint32_t a, uint32_t b, uint32_t c, uint32_t d, uint32_t par) {
  asm volatile("{\n.reg .b64 x, y;\n.reg .b128 z;\nmov.b64 x, {%1,%2};\nmov.b64 y, {%3,%4};\nmov.b128 z, {x, y};\nst.relaxed.gpu.global.b128 [%0], z;\n}"
               ::"l"(p), "r"((a & ~1u) | par), "r"(b), "r"(c), "r"(d) : "memory");
}
__device__ __forceinline__ uint4 lds128(uint32_t a) { uint4 v; asm volatile("ld.shared.v4.u32 {%0,%1,%2,%3}, [%4];" : "=r"(v.x), "=r"(v.y), "=r"(v.z), "=r"(v.w) : "r"(a)); return v; }
__device__ __forceinline__ float4 lds128f(uint32_t a) { float4 v; asm volatile("ld.shared.v4.f32 {%0,%1,%2,%3}, [%4];" : "=f"(v.x), "=f"(v.y), "=f"(v.z), "=f"(v.w) : "r"(a)); return v; }
__device__ __forceinline__ float4 lds128v(uint32_t a) { float4 v; asm volatile("ld.volatile.shared.v4.f32 {%0,%1,%2,%3}, [%4];" : "=f"(v.x), "=f"(v.y), "=f"(v.z), "=f"(v.w) : "r"(a) : "memory"); return v; }
__device__ __forceinline__ float lds32v(uint32_t a) { float v; asm volatile("ld.volatile.shared.f32 %0, [%1];" : "=f"(v) : "r"(a) : "memory"); return v; }
__device__ __forceinline__ float2 lds64f(uint32_t a) { float2 v; asm volatile("ld.shared.v2.f32 {%0,%1}, [%2];" : "=f"(v.x), "=f"(v.y) : "r"(a)); return v; }
__device__ __forceinline__ uint32_t lds32(uint32_t a) { uint32_t v; asm volatile("ld.shared.u32 %0, [%1];" : "=r"(v) : "r"(a)); return v; }
__device__ __forceinline__ void sts128(uint32_t a, uint32_t x, uint32_t y, uint32_t z, uint32_t w) { asm volatile("st.shared.v4.u32 [%0], {%1,%2,%3,%4};" ::"r"(a), "r"(x), "r"(y), "r"(z), "r"(w) : "memory"); }
__device__ __forceinline__ void sts128f(uint32_t a, float x, float y, float z, float w) { asm volatile("st.shared.v4.f32 [%0], {%1,%2,%3,%4};" ::"r"(a), "f"(x), "f"(y), "f"(z), "f"(w) : "memory"); }
__device__ __forceinline__ void sts32(uint32_t a, uint32_t x) { asm volatile("st.shared.u32 [%0], %1;" ::"r"(a), "r"(x) : "memory"); }
__device__ __forceinline__ void stsm4(uint32_t a, uint32_t r0, uint32_t r1, uint32_t r2, uint32_t r3) {
  asm volatile("stmatrix.sync.aligned.m8n8.x4.shared.b16 [%0], {%1,%2,%3,%4};" ::"r"(a), "r"(r0), "r"(r1), "r"(r2), "r"(r3) : "memory");
}
__device__ __forceinline__ uint4 ldsm4(uint32_t a) {
  uint4 v; asm volatile("ldmatrix.sync.aligned.m8n8.x4.shared.b16 {%0,%1,%2,%3}, [%4];" : "=r"(v.x), "=r"(v.y), "=r"(v.z), "=r"(v.w) : "r"(a) : "memory"); return v;
}
__device__ __forceinline__ uint32_t pack(float lo, float hi) { uint32_t r; asm("cvt.rn.bf16x2.f32 %0, %1, %2;" : "=r"(r) : "f"(hi), "f"(lo)); return r; }
__device__ __forceinline__ float bf_lo(uint32_t w) { return __uint_as_float(w << 16); }
__device__ __forceinline__ float bf_hi(uint32_t w) { return __uint_as_float(w & 0xffff0000u); }
__device__ __forceinline__ float bf_round(float x) { return bf_lo(pack(x, x)); }
__device__ __forceinline__ float ex2(float x) { float v; asm("ex2.approx.ftz.f32 %0, %1;" : "=f"(v) : "f"(x)); return v; }
__device__ __forceinline__ float rcp(float x) { float v; asm("rcp.approx.ftz.f32 %0, %1;" : "=f"(v) : "f"(x)); return v; }
__device__ __forceinline__ float addsat(float a, float b) { float v; asm("add.sat.f32 %0, %1, %2;" : "=f"(v) : "f"(a), "f"(b)); return v; }
__device__ __forceinline__ float phi2(float a) { return fmaf(fmaxf(a, 0.f), LN2, addsat(ex2(a), 1e-6f)); }
__device__ __forceinline__ uint32_t ln_bf16x2(uint32_t x, uint32_t m, uint32_t hi, uint32_t lo) {
  uint32_t o;
  asm("{\n.reg .b32 d, e;\nsub.rn.bf16x2 d, %1, %2;\nmul.rn.bf16x2 e, d, %4;\nfma.rn.bf16x2 %0, d, %3, e;\n}" : "=r"(o) : "r"(x), "r"(m), "r"(hi), "r"(lo));
  return o;
}
__device__ __forceinline__ float key_score(uint32_t key) { uint32_t u = key >> 16; u = (u & 0x8000u) ? (u & 0x7fffu) : (~u & 0xffffu); return __uint_as_float(u << 16); }
__device__ __forceinline__ int key_token(uint32_t key) { return 2047 - (int)((key >> 5) & 2047u); }
__device__ __forceinline__ uint32_t bsel(uint32_t a, uint32_t b, uint32_t m) { uint32_t r; asm("lop3.b32 %0, %1, %2, %3, 0xd8;" : "=r"(r) : "r"(a), "r"(b), "r"(m)); return r; }
__device__ __forceinline__ uint32_t prmt(uint32_t a, uint32_t b, uint32_t c) { uint32_t r; asm("prmt.b32 %0, %1, %2, %3;" : "=r"(r) : "r"(a), "r"(b), "r"(c)); return r; }
__device__ __forceinline__ uint32_t tagf(float v, uint32_t par) { return (__float_as_uint(v) & ~1u) | par; }
__device__ __forceinline__ float xred(float a, float b, bool up, int o) { return (up ? b : a) + __shfl_xor_sync(0xffffffffu, up ? a : b, o); }

#define STAMP(id)
#define STAMP_IF(c, id)
#define STAMP2(i)
#define LITE 1

template <bool TRANS>
__device__ __forceinline__ void mainloop(float (&a0)[64], float (&a1)[64], int s, int ph, int handoff, int gate, bool leader) {
  uint32_t prev = 0;
#pragma unroll 1
  for (int kt = 0; kt < 16; kt++) {
    mbar_wait(B_FULL + 8 * s, ph);
    if (gate && kt == GATE_KT) nb_sync(gate, 256);
    const uint64_t dw = mkdesc(RING, 8192, 1024, 1) + s * (SLOT >> 4), dx = mkdesc(RING + 16384, 16, 1024, 1) + s * (SLOT >> 4);
    wg_fence();
#pragma unroll
    for (int j = 0; j < 4; j++) {
      if (TRANS) {
        wgmma_n128_ss<1, 0>(a0, dw + j * 128, dx + j * 2, 1);
        wgmma_n128_ss<1, 0>(a1, dw + j * 128 + 512, dx + j * 2, 1);
      } else {
        wgmma_n128_ss<0, 1>(a0, dx + j * 2, dw + j * 128, 1);
        wgmma_n128_ss<0, 1>(a1, dx + j * 2 + 512, dw + j * 128, 1);
      }
    }
    wg_commit();
    if (handoff && kt == 15) nb_arrive(handoff, 256);
    wg_wait<1>();
    if (prev && leader) mbar_arrive(prev);
    prev = B_EMPTY + 8 * s;
    if (++s == NST) { s = 0; ph ^= 1; }
  }
  wg_wait<0>();
  if (leader) mbar_arrive(prev);
  reg_fence(a0);
  reg_fence(a1);
}

__device__ __forceinline__ int out_kblock(int r, int tn) {
  const int q = r - 2, half = q >= 7, pi = q - 7 * half;
  return r < 2 ? 2 * tn + r : 2 * (pi + (pi >= tn)) + half;
}

struct Params {
  const char *x, *wqkv, *w_r, *wg, *wu, *wd;
  CUtensorMap m_wqkv, m_x, m_xs, m_o, m_os, m_wo, m_gu, m_down, m_out;
};

template <bool BY_SMID>
__global__ void __launch_bounds__(512, 1) fused_kernel(const __grid_constant__ Params mp) {
  extern __shared__ __align__(1024) uint8_t smem_raw[];
#define CK(i)
  CK(0);
  uint32_t ck0 = 0;
  if (ALIGN) asm volatile("mov.u32 %0, %%clock;" : "=r"(ck0));
  const int tid = threadIdx.x, lane = tid & 31;
  const int w = __shfl_sync(0xffffffffu, tid >> 5, 0);
  int bid = blockIdx.x;
  if (BY_SMID) {
    uint32_t sm;
    asm volatile("mov.u32 %0, %%smid;" : "=r"(sm));
    const uint32_t p = sm >> 1, q = ((p - 32) * 37) >> 8;
    const uint32_t gpc = p < 32 ? p & 7 : p < 60 ? p - 31 - 7 * q : 0, tpc = p < 32 ? p >> 3 : p < 60 ? 4 + q : p - 58;
    bid = (p >> 1) == 30 ? 128 + ((0x9cu >> (2 * (sm & 3))) & 3) : ((0x75143620u >> (4 * gpc)) & 7) * 16 + tpc * 2 + (sm & 1);
  }
  const int tn = (bid & 3) + 4 * (bid >> 6), tm = (bid >> 2) & 15;

  CK(1);
  if (w == 0) {
#pragma unroll 1
    for (int s = 0; s < NST; s++) {
      asm volatile(ELECT "@p mbarrier.init.shared::cta.b64 [%0], 1;\n}" ::"r"(B_FULL + 8 * s) : "memory");
      if (bid < 128) {
        e_expect(B_FULL + 8 * s, 32768);
        e_tma2d(RING + s * SLOT + 16384, &mp.m_x, s * 64, tm * 128, B_FULL + 8 * s);
        e_tma3d(RING + s * SLOT, &mp.m_wqkv, s * 64, 16 + 2 * tn, B_FULL + 8 * s);
      }
      if (s == 0) CK(2);
    }
  }
  if (w == 1) e_pfmap(&mp.m_wqkv);
  if (w == 2) e_pfmap(&mp.m_xs);
  if (w >= 4) {
#pragma unroll 1
    for (uint32_t b = MISC + 8 * (w + 1); b < MISC + 8 * NBAR; b += 96)
      asm volatile(ELECT "@p mbarrier.init.shared::cta.b64 [%0], %1;\n}" ::"r"(b), "r"(b == B_CSDN ? 4 : 1) : "memory");
    if (w == 15) sts32(S_NCAND, 0);
  }
  CK(3);
  asm volatile("fence.mbarrier_init.release.cluster;" ::: "memory");
  __syncthreads();

  if (w == 13 && bid < 128) {
    if (XS_AT >= 0) mbar_wait(B_FULL + 8 * XS_AT, 0);
#pragma unroll 1
    for (int c = 0; c < 4; c++) {
      if (c >= XS_FLY) mbar_wait(B_XS + 8 * (c - XS_FLY), 0);
      if (c == max(tm >> 2, 1)) {
        e_expect(B_WK, 16384);
        e_tma3d(FR, &mp.m_wqkv, tm * 64, 16 + 2 * tn, B_WK);
      }
      e_expect(B_XS + 8 * c, 8192);
      e_tma2d(STG + c * 8192, &mp.m_xs, c * 256, tm * 128 + tn * 16, B_XS + 8 * c);
    }
  }

  if (bid >= 128) {
    const int h0 = bid == 128 ? 14 : bid - 129, hs = bid == 128 ? 1 : 3, h1 = bid == 128 ? 16 : 14;
    if (w == 12) {
      int s = 0, ph = 1;
      if (bid == 128) mbar_wait(B_SEL, 0);
      else if (H_DELAY) __nanosleep(H_DELAY);
#pragma unroll 1
      for (int h = h0; h < h1; h += hs) {
        const int c = 2 * h + (h & 8) * 2;
#pragma unroll 1
        for (int kt = 0; kt < 16; kt += 2) {
          mbar_wait(B_EMPTY + 8 * s, ph);
          e_expect(B_FULL + 8 * s, 32768);
          e_tma3d(RING + s * SLOT, &mp.m_wqkv, kt * 64, c, B_FULL + 8 * s);
          e_tma3d(RING + s * SLOT + 16384, &mp.m_wqkv, kt * 64 + 64, c, B_FULL + 8 * s);
          if (++s == HST) { s = 0; ph ^= 1; }
        }
      }
    } else if (w < 4) {
      const uint32_t par = (ld_relaxed(&g_epoch) + 1) & 1u;
      sts32(S_ONES + tid * 4, 0x3f803f80u);
      fence_async_smem();
      nb_sync(NB_WG0, 128);
      int s = 0, ph = 0;
#pragma unroll 1
      for (int h = h0; h < h1; h += hs) {
        float c[4][4];
#pragma unroll
        for (int i = 0; i < 4; i++) reg_zero(c[i]);
        uint32_t prev = 0;
#pragma unroll 1
        for (int kt = 0; kt < 8; kt++) {
          mbar_wait(B_FULL + 8 * s, ph);
          const uint64_t dw = mkdesc(RING, 8192, 1024, 1) + s * (SLOT >> 4);
          wg_fence();
#pragma unroll
          for (int j = 0; j < 16; j++) wgmma_n8_ss<1, 0>(c[j & 3], dw + (j & 3) * 512 + (j >> 2) * 128, mkdesc(S_ONES, 128, 128, 0), 1);
          wg_commit();
          wg_wait<1>();
          if (prev && tid == 0) mbar_arrive(prev);
          prev = B_EMPTY + 8 * s;
          if (++s == HST) { s = 0; ph ^= 1; }
        }
        wg_wait<0>();
        if (tid == 0) mbar_arrive(prev);
#pragma unroll
        for (int i = 0; i < 4; i++) reg_fence(c[i]);
        const bool u2 = lane & 2, u1 = lane & 1;
        const float lo = u2 ? c[1][0] + c[3][0] : c[0][0] + c[2][0], hi = u2 ? c[1][2] + c[3][2] : c[0][2] + c[2][2];
        st_relaxed(g_csum + h * 128 + (lane & 2) * 32 + w * 16 + (lane & 1) * 8 + (lane >> 2), tagf(u1 ? hi : lo, par));
        STAMP_IF(tid == 0, h >= 8 ? 6 : 30);
      }
    } else if (w < 12 && bid == 128) {
      const int t = tid - 128, j = w - 4;
      const uint32_t ep = ld_relaxed(&g_epoch) + 1;
      uint32_t kk[16];
      poll_keys(kk, g_keys + t * 2, ep, 31u);
      const uint32_t k[8] = {kk[0], kk[2], kk[4], kk[6], kk[8], kk[10], kk[12], kk[14]};
      STAMP_IF(t == 0, 42);
      const uint32_t m = __reduce_max_sync(0xffffffffu, max(max(max(k[0], k[1]), max(k[2], k[3])), max(max(k[4], k[5]), max(k[6], k[7]))));
      if (lane == 0) sts32(S_WMAX + j * 4, m);
      nb_sync(NB_WG1, 256);
      const uint32_t T = __reduce_min_sync(0xffffffffu, lds32(S_WMAX + (lane & 7) * 4));
      uint32_t cnt = 0;
#pragma unroll
      for (int i = 0; i < 8; i++) cnt += k[i] >= T;
      if (cnt) {
        uint32_t pos;
        asm volatile("atom.shared.add.u32 %0, [%1], %2;" : "=r"(pos) : "r"(S_NCAND), "r"(cnt * 4) : "memory");
#pragma unroll
        for (int i = 0; i < 8; i++)
          if (k[i] >= T) { sts32(AUX + pos, k[i]); pos += 4; }
      }
      nb_sync(NB_WG1, 256);
      const uint32_t n4 = lds32(S_NCAND);
#pragma unroll 1
      for (uint32_t i = j * 4; i < n4; i += 32) {
        const uint32_t key = lds32(AUX + i);
        uint32_t rank = 0;
#pragma unroll 1
        for (uint32_t q = lane * 4; q < n4 + lane * 4; q += 128) rank += __popc(__ballot_sync(0xffffffffu, q < n4 && lds32(AUX + q) > key));
        if (rank < 8) sts32(S_SEL + rank * 4, key);
      }
      fence_async_smem();
      nb_sync(NB_WG1, 256);
      STAMP_IF(t == 0, 43);
      const uint32_t key = lds32(S_SEL + j * 4);
      const int tok = key_token(key);
      uint4 v[4];
#pragma unroll
      for (int q = 0; q < 4; q++) v[q] = __ldg(reinterpret_cast<const uint4*>(mp.x + tok * 2048) + q * 32 + lane);
      const uint32_t st = ld_relaxed(&g_keys[tok].y);
      const float rinv = rcp(bf_lo(st)), rhi = bf_round(rinv);
      const uint32_t m2 = __byte_perm(st, 0, 0x3232), hi = pack(rhi, rhi), lo = pack(rinv - rhi, rinv - rhi);
#pragma unroll
      for (int q = 0; q < 4; q++)
        *reinterpret_cast<uint4*>(g_xsel + (q * 8 + (lane >> 2)) * 128 + j * 16 + (((lane & 3) ^ (j >> 1)) << 2)) =
            make_uint4(ln_bf16x2(v[q].x, m2, hi, lo), ln_bf16x2(v[q].y, m2, hi, lo), ln_bf16x2(v[q].z, m2, hi, lo), ln_bf16x2(v[q].w, m2, hi, lo));
      if (lane == 0) g_xsel[4096 + j] = key;
      fence_async_glob();
      nb_sync(NB_WG1, 256);
      STAMP_IF(t == 0, 44);
      if (j == 0) { e_release(H_R, 0); e_arrive(B_SEL); }
      STAMP_IF(t == 0, 45);
    }
  } else if (w >= 12) {
    asm volatile("setmaxnreg.dec.sync.aligned.u32 32;");
    if (w == 12) {
      int s = 0, ph = 0;
#pragma unroll 1
      for (int it = NST; it < 48; it++) {
        const int c = (it < 32 ? (it & 16) + 16 : 0) + 2 * tn;
        mbar_wait(B_EMPTY + 8 * s, ph);
        e_expect(B_FULL + 8 * s, 32768);
        e_tma3d(RING + s * SLOT, &mp.m_wqkv, (it & 15) * 64, c, B_FULL + 8 * s);
        e_tma2d(RING + s * SLOT + 16384, &mp.m_x, (it & 15) * 64, tm * 128, B_FULL + 8 * s);
        if (it >= NST) STAMP2(it - NST);
        if (++s == NST) { s = 0; ph ^= 1; }
      }
#pragma unroll 1
      for (int r = 0; r < 16; r++) {
        const int kb = out_kblock(r, tn);
        mbar_wait(B_EMPTY + 8 * s, ph);
        e_expect(B_FULL + 8 * s, r < 2 ? 16384 : 32768);
        e_tma3d(RING + s * SLOT, &mp.m_wo, kb * 64, 2 * tn, B_FULL + 8 * s);
        if (r < 2) {
          if (r == 0) e_expect(B_XRES, 32768);
          e_tma2d(RING + s * SLOT + 16384, &mp.m_x, kb * 64, tm * 128, B_XRES);
        }
        STAMP2(r + 48 - NST);
        if (++s == NST) { s = 0; ph ^= 1; }
      }
    } else if (w == 13) {
      {
        const char* pd = mp.wd + (bid & 15) * 128 + ((bid >> 4) * 448 + lane) * 2048;
        mbar_wait(B_XS + 24, 0);
        __nanosleep(PF_WAIT);
#pragma unroll 1
        for (int i = 0; i < 14; i++, pd += 65536) {
          if (PF_GAP) asm volatile("prefetch.global.L2 [%0];" ::"l"(pd));
          if (PF_GAP) __nanosleep(PF_GAP);
        }
      }
      nb_sync(NB_Z, 160);
      const uint32_t ep = lds32(S_EPOCH);
      {
        float z[4] = {0.f, 0.f, 0.f, 0.f};
        e_signal(H_Z + tn, tm);
        await(H_Z + tn, 0xffffu, ep);
#pragma unroll 1
        for (int i = 0; i < 4; i++) {
          uint32_t p[16];
          poll_z(p, g_z + i * 4096 + tn * 128 + lane * 4, ep, 1u);
#pragma unroll
          for (int q = 0; q < 4; q++) z[q] += (__uint_as_float(p[q]) + __uint_as_float(p[4 + q])) + (__uint_as_float(p[8 + q]) + __uint_as_float(p[12 + q]));
        }
        const uint32_t z01 = pack(z[0], z[1]), z23 = pack(z[2], z[3]);
#pragma unroll
        for (int i = 0; i < 4; i++) {
          const int n = 2 * i + (lane >> 4);
          asm volatile("st.shared.v2.u32 [%0], {%1,%2};" ::"r"(KVB_Z + n * 128 + ((((lane >> 1) & 7) ^ n) << 4) + (lane & 1) * 8), "r"(z01), "r"(z23) : "memory");
        }
        fence_async_smem();
        nb_arrive(NB_KVB, 288);
        STAMP_IF(lane == 0, 46);
      }
      nb_sync(NB_Q0, 192);
      e_store2d(&mp.m_os, tn * 128, tm * 128, STG);
      nb_sync(NB_OWN0, 288);
      e_store2d(&mp.m_os, tn * 128, tm * 128 + 64, STG + 8192);
      bulk_wait_read();
      e_signal(H_O + tm, 2 * tn);
      STAMP_IF(lane == 0, 4);
      nb_sync(NB_H1, 160);
      e_store2d(&mp.m_os, tn * 128 + 64, tm * 128, STG + 16384);
      e_store2d(&mp.m_os, tn * 128 + 64, tm * 128 + 64, STG + 24576);
      bulk_wait_read();
      e_signal(H_O + tm, 2 * tn + 1);
      STAMP_IF(lane == 0, 5);
#pragma unroll 1
      for (int i = 4; i < 14; i++) {
        const int q = (i + 2) >> 2;
        if (i == 4 || (i & 3) == 2) {
          if (i > 4) mbar_wait(B_OWN + 8 * (q - 2), 0);
          e_expect(B_DR + 8 * q, i == 4 ? 8192 : 16384);
        }
        e_tma2d_ef((i < 6 ? AUX - 16384 : STG - 24576) + i * 4096, &mp.m_down, (bid & 15) * 64, (bid >> 4) * 448 + i * 32, B_DR + 8 * q, EVICT_FIRST);
        if (DN_GAP) __nanosleep(DN_GAP);
      }
    } else if (w == 14) {
      e_pfmap(&mp.m_gu); e_pfmap(&mp.m_o); e_pfmap(&mp.m_os); e_pfmap(&mp.m_wo); e_pfmap(&mp.m_down); e_pfmap(&mp.m_out);
      const uint32_t ep = ld_relaxed(&g_epoch) + 1;
      nb_sync(NB_FDONE, 416);
      {
        uint32_t c[4];
        poll_quad(c, g_csum + tn * 128 + lane * 4, ep, 1u);
        sts128(S_CSQ + lane * 16, c[0], c[1], c[2], c[3]);
        nb_arrive(NB_CSQ, 160);
        poll_quad(c, g_csum + 1024 + tn * 128 + lane * 4, ep, 1u);
        sts128(S_CSV + lane * 16, c[0], c[1], c[2], c[3]);
        __syncwarp();
        e_arrive(B_CSV);
      }
      nb_sync(NB_Q0, 192);
      uint32_t ready = 0;
      int s = 0, ph = 1;
#pragma unroll 1
      for (int r = 2; r < 16; r++) {
        const int kb = out_kblock(r, tn);
        if (!((ready >> kb) & 1)) {
          uint32_t f[1];
          poll0(f, g_sig + (H_O + tm) * 32, 0u - (ep & 1u), 1u << kb);
          ready = f[0] ^ ((ep & 1u) - 1u);
        }
        mbar_wait(B_EMPTY + 8 * s, ph);
        e_tma2d(RING + s * SLOT + 16384, &mp.m_o, kb * 64, tm * 128, B_FULL + 8 * s);
        STAMP_IF(lane == 0 && r == 2, 2);
        STAMP_IF(lane == 0 && r == 9, 3);
        if (++s == NST) { s = 0; ph ^= 1; }
      }
    } else {
      uint32_t nsm = 132;
      if (BY_SMID) asm volatile("mov.u32 %0, %%nsmid;" : "=r"(nsm));
      asm volatile("{\n.reg .pred q;\nsetp.eq.u32 q, %0, 1156;\n@q bra LOK;\ntrap;\nLOK:\n}" ::"r"((uint32_t)__cvta_generic_to_shared(smem_raw) + nsm));
      const uint32_t ep = ld_relaxed(&g_epoch) + 1;
      mbar_wait(B_CSDN, 0);
#pragma unroll 1
      for (int n = 0; n < 5; n++) {
        __nanosleep(FFN_GAP);
        if (bid < 112) {
          e_expect(B_FR + 8 * n, 4608);
          e_tma3d_ef(GR + n * 4096, &mp.m_gu, bid * 32, n * 32, B_FR + 8 * n, EVICT_FIRST);
        }
      }
      uint32_t f[1];
      poll1(f, g_sig + H_R * 32, ep, 1u);
      fence_acq();
      fence_async_glob();
      if (bid < 112) {
#pragma unroll
        for (int n = 0; n < 5; n++) e_load(HOP + n * 512, g_xsel + n * 128, 512, B_FR + 8 * n);
      }
      e_expect(B_SEL, 32);
      e_load(S_SEL, g_xsel + 4096, 32, B_SEL);
      if (bid < 112) {
        int s = 0, ph = 0;
#pragma unroll 1
        for (int n = 5; n < 32; n++) {
          mbar_wait(B_FE + 8 * s, ph);
          e_expect(B_FR + 8 * s, 4608);
          e_tma3d_ef(GR + s * 4096, &mp.m_gu, bid * 32 , n * 32 , B_FR + 8 * s, EVICT_FIRST);
          e_load(HOP + s * 512, g_xsel + n * 128, 512, B_FR + 8 * s);
          STAMP2(64 + n);
          if (++s == 5) { s = 0; ph ^= 1; }
        }
      }
      e_expect(B_DR, 16384);
#pragma unroll 1
      for (int i = 1; i < 5; i++) {
        if (bid < 112) mbar_wait(B_FE + 8 * ((i & 3) + 1), i != 4);
        e_tma2d_ef(FR + (i & 3) * 4096, &mp.m_down, (bid & 15) * 64, (bid >> 4) * 448 + (i & 3) * 32, B_DR, EVICT_FIRST);
      }
    }
  } else if (w >= 8) {
    asm volatile("setmaxnreg.dec.sync.aligned.u32 56;");
    const int t = tid - 256, ww = w - 8;
    const uint32_t ep = ld_relaxed(&g_epoch) + 1, par = ep & 1u;
    {
      const int r0 = (lane >> 3) + (lane & 4);
      const uint32_t a = FR + (ww >> 1) * 8192 + r0 * 128 + ((((ww & 1) * 4 + (lane & 3)) ^ r0) << 4);
      float c[8];
      reg_zero(c);
      mbar_wait(B_WK, 0);
#pragma unroll 2
      for (int i = 0; i < 8; i++) {
        const uint4 v = lds128(a + i * 1024);
        c[0] += bf_lo(v.x); c[1] += bf_hi(v.x); c[2] += bf_lo(v.y); c[3] += bf_hi(v.y);
        c[4] += bf_lo(v.z); c[5] += bf_hi(v.z); c[6] += bf_lo(v.w); c[7] += bf_hi(v.w);
      }
      const bool u16 = lane & 16, u8 = lane & 8, u4 = lane & 4;
      const float d0 = xred(c[0], c[4], u16, 16), d1 = xred(c[1], c[5], u16, 16), d2 = xred(c[2], c[6], u16, 16), d3 = xred(c[3], c[7], u16, 16);
      fence_async_smem();
      e_arrive(B_CSDN);
      const float sum = xred(xred(d0, d2, u8, 8), xred(d1, d3, u8, 8), u4, 4);
      st_relaxed(g_csum + (2 + tm) * 1024 + tn * 128 + ww * 32 + (lane & 3) * 8 + (lane >> 2), tagf(sum, par));
      STAMP_IF(t == 0, 8);
      nb_sync(NB_WG2, 128);
      if (ww == 0) { e_signal(H_CS + tn, tm); await(H_CS + tn, 0xffffu, ep); }
      nb_sync(NB_WG2, 128);
      uint32_t p[16];
      poll16(p, g_csum + 2048 + tn * 128 + t, par, 1u);
      float tot = 0.f;
#pragma unroll
      for (int i = 0; i < 16; i += 4) tot += (__uint_as_float(p[i]) + __uint_as_float(p[i + 1])) + (__uint_as_float(p[i + 2]) + __uint_as_float(p[i + 3]));
      sts32(S_CSK + t * 4, __float_as_uint(tot));
      nb_arrive(NB_FDONE, 416);
      STAMP_IF(t == 0, 9);
    }
    const int ks = bid >> 4, nt = bid & 15;
    float fa[4] = {0.f, 0.f, 0.f, 0.f};
    if (bid < 112) {
      int s = 0, ph = 0;
      uint32_t prev = 0;
#pragma unroll 1
      for (int n = 0; n < 32; n++) {
        mbar_wait(B_FR + 8 * s, ph);
        const uint64_t da = mkdesc(GR, 2048, 512, 2) + s * 256, db = mkdesc(HOP, 16, 512, 2) + s * 32;
        wg_fence();
        wgmma_n8_ss<1, 0>(fa, da, db, 1);
        wgmma_n8_ss<1, 0>(fa, da + 64, db + 2, 1);
        wg_commit();
        wg_wait<1>();
        if (prev && t == 0) mbar_arrive(prev);
        prev = B_FE + 8 * s;
        if (++s == 5) { s = 0; ph ^= 1; }
      }
      wg_wait<0>();
      reg_fence(fa);
      if (t == 0) mbar_arrive(prev);
      STAMP_IF(t == 0, 12);
      const bool isup = (ww >> 1) != (mp.wu < mp.wg);
      if (isup) sts128f(GR + (t & 63) * 16, fa[0], fa[1], fa[2], fa[3]);
      nb_sync(NB_WG2, 128);
      if (!isup) {
        const float4 u = lds128f(GR + (t & 63) * 16);
        const float uu[4] = {u.x, u.y, u.z, u.w};
        uint32_t* hp = g_h + bid * 256 + (lane & 3) * 64 + (ww & 1) * 16 + (lane >> 2);
#pragma unroll
        for (int i = 0; i < 4; i++) {
          const float g = fa[i], hv = g * rcp(1.f + ex2(-g * LOG2E)) * uu[i];
          st_relaxed(hp + (i & 1) * 32 + (i >> 1) * 8, __byte_perm(pack(hv, hv), ep, 0x3254));
        }
      }
      nb_sync(NB_WG2, 128);
      if (ww == 0) e_signal(H_H + bid / 14, bid % 14);
      reg_zero(fa);
    }
    {
      uint32_t v[28];
      if (ww == 0) await(H_H + ks, 0x3fffu, ep);
      nb_sync(NB_WG2, 128);
      poll7x4(v, g_h + ks * 3584 + t * 4, ep, 0xffffu);
#pragma unroll
      for (int q = 0; q < 7; q++)
        asm volatile("st.shared.v2.u32 [%0], {%1,%2};" ::"r"(HOP + q * 1024 + (t >> 3) * 64 + ((((t >> 1) & 3) ^ ((t >> 4) & 3)) << 4) + (t & 1) * 8),
                     "r"(__byte_perm(v[4 * q], v[4 * q + 1], 0x7632)), "r"(__byte_perm(v[4 * q + 2], v[4 * q + 3], 0x7632)) : "memory");
      fence_async_smem();
      nb_sync(NB_WG2, 128);
    }
    STAMP_IF(t == 0, 13);
#pragma unroll 1
    for (int i = 0; i < 14; i += 2) {
      mbar_wait(B_DR + 8 * (i < 4 ? 0 : (i + 2) >> 2), 0);
      const uint64_t da = mkdesc(0, 4096, 1024, 1) + ((i < 4 ? FR : i < 6 ? AUX - 16384 : STG - 24576) >> 4) + i * 256;
      const uint64_t db = mkdesc(HOP, 16, 512, 2) + i * 32;
      wg_fence();
#pragma unroll
      for (int q = 0; q < 4; q++) wgmma_n8_ss<1, 0>(fa, da + q * 128, db + (q >> 1) * 32 + (q & 1) * 2, 1);
      wg_commit();
    }
    wg_wait<0>();
    reg_fence(fa);
    nb_arrive(NB_ST, 256);
    STAMP_IF(t == 0, 14);
    {
      uint32_t* yp = g_yp + (nt * 8 + ks) * 512 + (lane & 3) * 128 + ww * 16 + (lane >> 2);
#pragma unroll
      for (int i = 0; i < 4; i++) st_relaxed(yp + (i & 1) * 64 + (i >> 1) * 8, tagf(fa[i], par));
    }
    nb_sync(NB_WG2, 128);
    if (ww == 0) e_signal(H_Y + (nt >> 1), (nt & 1) * 8 + ks);
    mbar_wait(B_SEL, 0);
    const uint32_t mykey = lds32(S_SEL + (lane & 7) * 4);
    const uint32_t inmask = __ballot_sync(0xffffffffu, (key_token(mykey) >> 7) == tm) & 0xffu;
    if (inmask) {
      sts128(FR + t * 16, 0u, 0u, 0u, 0u);
      if (ww == 0) await(H_Y + tn, 0xffffu, ep);
      nb_sync(NB_WG2, 128);
      const float sg = rcp(1.f + ex2(-key_score(mykey) * LOG2E));
#pragma unroll 1
      for (int n = ww + 1; n <= __popc(inmask); n += 4) {
        const int j = __fns(inmask, 0, n);
        uint32_t p[32];
        poll8x4(p, g_yp + (tn * 2 + (lane >> 4)) * 4096 + j * 64 + (lane & 15) * 4, par, 1u);
        float y[4];
        const float sj = __shfl_sync(0xffffffffu, sg, j);
#pragma unroll
        for (int i = 0; i < 4; i++)
          y[i] = sj * (((__uint_as_float(p[i]) + __uint_as_float(p[4 + i])) + (__uint_as_float(p[8 + i]) + __uint_as_float(p[12 + i]))) +
                       ((__uint_as_float(p[16 + i]) + __uint_as_float(p[20 + i])) + (__uint_as_float(p[24 + i]) + __uint_as_float(p[28 + i]))));
        asm volatile("st.shared.v2.u32 [%0], {%1,%2};" ::"r"(FR + (lane >> 4) * 1024 + j * 128 + ((((lane >> 1) & 7) ^ j) << 4) + (lane & 1) * 8),
                     "r"(pack(y[0], y[1])), "r"(pack(y[2], y[3])) : "memory");
      }
      fence_async_smem();
      nb_arrive(NB_Y, 256);
    }
    STAMP_IF(t == 0, 15);
  } else if (w >= 4) {
    asm volatile("setmaxnreg.inc.sync.aligned.u32 208;");
    const int t = tid - 128, ww = w - 4, g = lane >> 2, t4 = lane & 3;
    const bool leader = t == 0;
    const uint32_t ep = ld_relaxed(&g_epoch) + 1, par = ep & 1u;
    {
      const uint4* wp = reinterpret_cast<const uint4*>(mp.w_r) + lane;
      uint4 w0 = __ldg(wp), w1 = __ldg(wp + 32), w2 = __ldg(wp + 64), w3 = __ldg(wp + 96);
      if (leader) sts32(S_EPOCH, ep);
      if (KV_DIRECT && lane < 8) st_unit(g_kv + tn * 512 + tm * 32 + ww * 8 + lane, 0u, 0u, 0u, 0u, par ^ 1u);
      float s[4] = {0.f, 0.f, 0.f, 0.f}, q[4] = {0.f, 0.f, 0.f, 0.f}, d[4] = {0.f, 0.f, 0.f, 0.f}, wsum = 0.f;
#pragma unroll 1
      for (int c = 0; c < 4; c++) {
        const float wr[8] = {bf_lo(w0.x), bf_hi(w0.x), bf_lo(w0.y), bf_hi(w0.y), bf_lo(w0.z), bf_hi(w0.z), bf_lo(w0.w), bf_hi(w0.w)};
        w0 = w1; w1 = w2; w2 = w3;
        wsum += ((wr[0] + wr[1]) + (wr[2] + wr[3])) + ((wr[4] + wr[5]) + (wr[6] + wr[7]));
        mbar_wait(B_XS + 8 * c, 0);
#pragma unroll
        for (int r = 0; r < 4; r++) {
          const uint4 v = lds128(STG + c * 8192 + (ww * 4 + r) * 512 + lane * 16);
          const uint32_t xw[4] = {v.x, v.y, v.z, v.w};
#pragma unroll
          for (int i = 0; i < 4; i++) {
            const uint32_t dep = __float_as_uint(q[i ? r : (r + 3) & 3]);
            const float lo = POLITE ? __uint_as_float(prmt(xw[i], dep, 0x10ff)) : bf_lo(xw[i]), hi = POLITE ? __uint_as_float(prmt(xw[i], dep, 0x32ff)) : bf_hi(xw[i]);
            s[r] += lo; q[r] = fmaf(lo, lo, q[r]); d[r] = fmaf(lo, wr[2 * i], d[r]);
            s[r] += hi; q[r] = fmaf(hi, hi, q[r]); d[r] = fmaf(hi, wr[2 * i + 1], d[r]);
          }
        }
      }
      STAMP_IF(leader, 16);
      const bool u16 = lane & 16, u8 = lane & 8, u4 = lane & 4, u2 = lane & 2;
      const float s1 = xred(xred(s[0], s[2], u16, 16), xred(s[1], s[3], u16, 16), u8, 8);
      const float q1 = xred(xred(q[0], q[2], u16, 16), xred(q[1], q[3], u16, 16), u8, 8);
      const float d1 = xred(xred(d[0], d[2], u16, 16), xred(d[1], d[3], u16, 16), u8, 8);
      wsum += __shfl_xor_sync(0xffffffffu, wsum, 16);
      wsum += __shfl_xor_sync(0xffffffffu, wsum, 8);
      float tot = xred(xred(s1, d1, u4, 4), xred(q1, wsum, u4, 4), u2, 2);
      tot += __shfl_xor_sync(0xffffffffu, tot, 1);
      const float qq = __shfl_down_sync(0xffffffffu, tot, 2), dd = __shfl_down_sync(0xffffffffu, tot, 4), ws = __shfl_down_sync(0xffffffffu, tot, 6);
      if ((lane & 7) == 0) {
        const float mean = tot * (1.f / 1024.f);
        const float var = fmaxf(fmaf(-mean, mean, qq * (1.f / 1024.f)), 0.f);
        float sd;
        asm("sqrt.approx.ftz.f32 %0, %1;" : "=f"(sd) : "f"(bf_round(bf_round(var) + 1e-5f)));
        const uint32_t ms = pack(sd, mean);
        const int row = tm * 128 + tn * 16 + ww * 4 + (lane >> 3);
        const uint32_t rbits = pack(0.f, fmaf(-bf_hi(ms), ws, dd) * rcp(bf_lo(ms)));
        const uint32_t key = (rbits ^ (((int)rbits >> 31 & 0x7fff0000u) | 0x80000000u)) | ((2047 - row) << 5) | (ep & 31u);
        asm volatile("{\n.reg .b64 x;\nmov.b64 x, {%1,%2};\nst.relaxed.gpu.global.b64 [%0], x;\n}" ::"l"(g_keys + row), "r"(key), "r"(ms) : "memory");
      }
      STAMP_IF(leader, 17);
      __nanosleep(400);
      uint32_t st[2];
      poll_pair(st, g_keys + tm * 128 + t, ep, 31u);
      asm volatile("st.shared.v2.f32 [%0], {%1,%2};" ::"r"(S_KSTAT + t * 8), "f"(bf_hi(st[1])), "f"(rcp(bf_lo(st[1])) * LOG2E) : "memory");
      nb_arrive(NB_FDONE, 416);
      STAMP_IF(leader, 10);
    }
    float a0[64], a1[64];
    reg_zero(a0); reg_zero(a1); reg_fence(a0); reg_fence(a1);
    STAMP_IF(leader, 18);
    nb_sync(NB_KV, 256);
    mainloop<true>(a0, a1, 1, 1, NB_VQ, 0, leader);
    STAMP_IF(leader, 19);
    {
      uint32_t f0[32], f1[32];
#pragma unroll
      for (int i = 0; i < 32; i++) { f0[i] = pack(a0[2 * i], a0[2 * i + 1]); f1[i] = pack(a1[2 * i], a1[2 * i + 1]); }
      float c0[32], c1[32];
      reg_zero(c0); reg_zero(c1);
      nb_sync(NB_PK, 256);
      constexpr uint64_t db = mkdesc(STG, 16, 1024, 1);
      wg_fence();
#pragma unroll
      for (int k = 0; k < 8; k++) {
        wgmma_n64_rs<0>(c0, f0[4 * k], f0[4 * k + 1], f0[4 * k + 2], f0[4 * k + 3], db + (k >> 2) * 1024 + (k & 3) * 2, k != 0);
        wgmma_n64_rs<0>(c1, f1[4 * k], f1[4 * k + 1], f1[4 * k + 2], f1[4 * k + 3], db + (k >> 2) * 1024 + (k & 3) * 2 + 512, k != 0);
        if (GATE_KT && k == GATE_K) nb_arrive(NB_KV, 256);
      }
      wg_commit();
      const bool hp = ww >> 1;
      float c[4];
      float2 tt[8];
#pragma unroll
      for (int i = 0; i < 8; i++) tt[i] = lds64f(S_CSK + ((i >> 2) * 64 + hp * 32 + (i & 3) * 8 + 2 * t4) * 4);
      mbar_wait(B_CSV, 0);
#pragma unroll
      for (int i = 0; i < 4; i++) c[i] = -__uint_as_float(lds32(S_CSV + ((i >> 1) * 64 + ww * 16 + (i & 1) * 8 + g) * 4));
      wg_wait<0>();
      reg_fence(c0);
      reg_fence(c1);
      STAMP_IF(leader, 20);
      uint4* pp = g_kvp + (tn * 16 + tm) * 512 + t;
      auto put = [&](int q, const float* d) {
        const float ca = c[q & 2], cb = c[q | 1];
        const float2 ta = tt[2 * q], tb = tt[2 * q + 1];
        st_unit(pp + q * 128, pack(fmaf(ca, ta.x, d[0]), fmaf(ca, ta.y, d[1])), pack(fmaf(cb, ta.x, d[2]), fmaf(cb, ta.y, d[3])),
                pack(fmaf(ca, tb.x, d[4]), fmaf(ca, tb.y, d[5])), pack(fmaf(cb, tb.x, d[6]), fmaf(cb, tb.y, d[7])), par);
      };
      if (!hp) { put(0, c0); put(1, c0 + 8); put(2, c1); put(3, c1 + 8); }
      else { put(0, c0 + 16); put(1, c0 + 24); put(2, c1 + 16); put(3, c1 + 24); }
      STAMP_IF(leader, 47);
      {
        uint32_t p[16];
        nb_sync(NB_WG1, 128);
        if (ww == 0) { e_signal(H_KVP + tn, tm); await(H_KVP + tn, 0xffffu, ep); }
        nb_sync(NB_WG1, 128);
        STAMP_IF(leader, 1);
        poll_kvp(p, g_kvp + (tn * 16 + (lane >> 3) * 4) * 512 + tm * 32 + ww * 8 + (lane & 7), par, 1u);
        float r[8];
#pragma unroll
        for (int i = 0; i < 4; i++) {
          r[2 * i] = (bf_lo(p[i]) + bf_lo(p[4 + i])) + (bf_lo(p[8 + i]) + bf_lo(p[12 + i]));
          r[2 * i + 1] = (bf_hi(p[i]) + bf_hi(p[4 + i])) + (bf_hi(p[8 + i]) + bf_hi(p[12 + i]));
        }
#pragma unroll
        for (int i = 0; i < 8; i++) r[i] += __shfl_xor_sync(0xffffffffu, r[i], 8);
#pragma unroll
        for (int i = 0; i < 8; i++) r[i] += __shfl_xor_sync(0xffffffffu, r[i], 16);
        if (lane < 8) st_unit(g_kv + tn * 512 + tm * 32 + ww * 8 + lane, pack(r[0], r[1]), pack(r[2], r[3]), pack(r[4], r[5]), pack(r[6], r[7]), par);
      }
      STAMP_IF(leader, 21);
    }
    const uint32_t sx = lane & 7, sc = lane >> 4;
    const uint32_t sa = STG + (ww * 16 + (lane & 15)) * 128;
    const uint32_t sw[4] = {sa + ((sc ^ sx) << 4), sa + (((2 + sc) ^ sx) << 4), sa + (((4 + sc) ^ sx) << 4), sa + (((6 + sc) ^ sx) << 4)};
    {
      uint32_t v[16];
      if (!KV_DIRECT) {
        nb_sync(NB_WG1, 128);
        if (ww == 0) { e_signal(H_KV + tn, tm); await(H_KV + tn, 0xffffu, ep); }
        nb_sync(NB_WG1, 128);
      } else {
        __nanosleep(KV_DIRECT);
      }
      STAMP_IF(leader, 7);
      poll_kv(v, g_kv + tn * 512 + t, par, 1u);
      STAMP_IF(leader, 23);
#pragma unroll
      for (int q = 0; q < 4; q++)
        stsm4((q < 2 ? KVB_P0 : KVB_P1) + ((ww & 1) * 16 + (lane & 15)) * 128 + ((((ww >> 1) * 4 + (q & 1) * 2 + sc) ^ sx) << 4),
              v[4 * q], v[4 * q + 1], v[4 * q + 2], v[4 * q + 3]);
      fence_async_smem();
      nb_arrive(NB_KVB, 288);
    }
    STAMP_IF(leader, 24);
    uint32_t oh[4];
    uint32_t inmask;
    {
      mbar_wait(B_SEL, 0);
      const int r0 = key_token(lds32(S_SEL + t4 * 8)) - tm * 128, r1 = key_token(lds32(S_SEL + t4 * 8 + 4)) - tm * 128;
#pragma unroll
      for (int i = 0; i < 4; i++) {
        const int row = (i >> 1) * 64 + ww * 16 + (i & 1) * 8 + g;
        oh[i] = (r0 == row ? 0x3f80u : 0u) | (r1 == row ? 0x3f800000u : 0u);
      }
      inmask = __ballot_sync(0xffffffffu, (unsigned)r0 < 128u || (unsigned)r1 < 128u);
    }
    uint32_t va[8];
#pragma unroll
    for (int i = 0; i < 8; i++) va[i] = RING + 16384 + sc * 8192 + (ww * 16 + (lane & 15)) * 128 + ((i ^ sx) << 4) + (lane >> 3) * 4;
    float ka[4];
    {
      float kb[4];
#pragma unroll
      for (int i = 0; i < 4; i++) {
        const float2 st = lds64f(S_KSTAT + ((i >> 1) * 64 + ww * 16 + (i & 1) * 8 + g) * 8);
        const float r = st.y * LN2;
        ka[i] = 1.f + r; kb[i] = -st.x * r;
      }
#pragma unroll
      for (int i = 0; i < 64; i++) { a0[i] = kb[(i >> 1) & 1]; a1[i] = kb[2 + ((i >> 1) & 1)]; }
      reg_fence(a0);
      reg_fence(a1);
    }
    {
      auto own = [&](int r) {
        nb_sync(NB_OWN0 + r, r ? 256 : 288);
        mbar_wait(B_FULL + 8 * (3 + r), 1);
        if (!LITE) STAMP_IF(leader, 25 + r);
        const uint64_t dw = mkdesc(RING + (3 + r) * SLOT, 8192, 1024, 1), dx = mkdesc(STG + r * 16384, 16, 1024, 1);
        wg_fence();
#pragma unroll
        for (int j = 0; j < 4; j++) {
          wgmma_n128_ss<0, 1>(a0, dx + j * 2, dw + j * 128, 1);
          wgmma_n128_ss<0, 1>(a1, dx + j * 2 + 512, dw + j * 128, 1);
        }
        wg_commit();
      };
      own(0);
      constexpr uint32_t XOFF = RING + 3 * SLOT + 16384 - STG;
      mbar_wait(B_XRES, 0);
      wg_wait<0>();
      reg_fence(a0);
      reg_fence(a1);
#pragma unroll
      for (int j = 0; j < 8; j++) {
        const uint4 v = ldsm4(sw[j & 3] + XOFF + (j >> 2) * SLOT), u = ldsm4(sw[j & 3] + XOFF + (j >> 2) * SLOT + 8192);
        const uint32_t vv[4] = {v.x, v.y, v.z, v.w}, uu[4] = {u.x, u.y, u.z, u.w};
#pragma unroll
        for (int i = 0; i < 4; i++) {
          a0[8 * j + 2 * i] = fmaf(bf_lo(vv[i]), ka[i & 1], a0[8 * j + 2 * i]);
          a0[8 * j + 2 * i + 1] = fmaf(bf_hi(vv[i]), ka[i & 1], a0[8 * j + 2 * i + 1]);
          a1[8 * j + 2 * i] = fmaf(bf_lo(uu[i]), ka[2 + (i & 1)], a1[8 * j + 2 * i]);
          a1[8 * j + 2 * i + 1] = fmaf(bf_hi(uu[i]), ka[2 + (i & 1)], a1[8 * j + 2 * i + 1]);
        }
        if (j == 7) {
          fence_async_smem();
          nb_sync(NB_WG1, 128);
          if (leader) { mbar_arrive(B_EMPTY + 24); mbar_arrive(B_OWN); }
        }
      }
      reg_fence(a0);
      reg_fence(a1);
      STAMP_IF(leader, 22);
      own(1);
      int s = 0, ph = 0;
      uint32_t prev = B_EMPTY + 32;
#pragma unroll 1
      for (int r = 2; r < 16; r++) {
        mbar_wait(B_FULL + 8 * s, ph);
        {
          uint32_t bad = 0;
#pragma unroll
          for (int i = 0; i < 8; i++) bad |= lds32(va[i] + s * SLOT) ^ par;
          if (__any_sync(0xffffffffu, bad & 1u)) {
            const uint4* src = reinterpret_cast<const uint4*>(g_o + (tm * 128 + sc * 64 + ww * 16 + (lane & 15)) * 1024 + out_kblock(r, tn) * 64);
#pragma unroll 1
            for (int i = 0; i < 8; i++) {
              uint32_t v[4];
              asm volatile("{\n.reg .b64 x, y;\n.reg .b128 z;\n.reg .pred p, q, h;\n.reg .u32 c, b;\nmov.u32 c, 0;\nsetp.ne.u32 h, %6, 0;\nLW:\n"
                           "ld.relaxed.gpu.global.b128 z, [%4];\nmov.b128 {x, y}, z;\nmov.b64 {%0,%1}, x;\nmov.b64 {%2,%3}, y;\n"
                           "selp.b64 x, y, x, h;\nshr.b64 x, x, %7;\ncvt.u32.u64 b, x;\nand.b32 b, b, 1;\nsetp.eq.u32 p, b, %5;\n"
                           "vote.sync.all.pred p, p, 0xffffffff;\n@p bra.uni LD;\nadd.u32 c, c, 1;\nsetp.lt.u32 q, c, 1000000;\n@q bra.uni LW;\ntrap;\nLD:\n}"
                           : "=&r"(v[0]), "=&r"(v[1]), "=&r"(v[2]), "=&r"(v[3]) : "l"(src + i), "r"(par), "r"(sc), "r"((lane & 8) * 4) : "memory");
              sts128(((va[0] & ~15u) ^ (i << 4)) + s * SLOT, v[0], v[1], v[2], v[3]);
            }
            fence_async_smem();
            __syncwarp();
          }
        }
        if (!LITE) STAMP_IF(leader && r == 2, 27);
        const uint64_t dw = mkdesc(RING, 8192, 1024, 1) + s * (SLOT >> 4), dx = mkdesc(RING + 16384, 16, 1024, 1) + s * (SLOT >> 4);
        wg_fence();
#pragma unroll
        for (int j = 0; j < 4; j++) {
          wgmma_n128_ss<0, 1>(a0, dx + j * 2, dw + j * 128, 1);
          wgmma_n128_ss<0, 1>(a1, dx + j * 2 + 512, dw + j * 128, 1);
        }
        wg_commit();
        wg_wait<1>();
        if (leader) { mbar_arrive(prev); if (r == 2) mbar_arrive(B_OWN + 8); }
        prev = B_EMPTY + 8 * s;
        if (++s == NST) { s = 0; ph ^= 1; }
      }
      if (inmask) {
        nb_sync(NB_Y, 256);
        wg_fence();
        wgmma_n128_rs<1>(a0, oh[0], oh[1], 0u, 0u, mkdesc(FR, 1024, 0, 1), 1);
        wgmma_n128_rs<1>(a1, oh[2], oh[3], 0u, 0u, mkdesc(FR, 1024, 0, 1), 1);
        wg_commit();
      }
      nb_sync(NB_ST, 256);
      wg_wait<0>();
      reg_fence(a0);
      reg_fence(a1);
    }
    STAMP_IF(leader, 28);
#pragma unroll
    for (int c = 0; c < 2; c++) {
#pragma unroll
      for (int j = 4 * c; j < 4 * c + 4; j++) {
        stsm4(sw[j & 3] + c * 16384, pack(a0[8 * j], a0[8 * j + 1]), pack(a0[8 * j + 2], a0[8 * j + 3]), pack(a0[8 * j + 4], a0[8 * j + 5]), pack(a0[8 * j + 6], a0[8 * j + 7]));
        stsm4(sw[j & 3] + c * 16384 + 8192, pack(a1[8 * j], a1[8 * j + 1]), pack(a1[8 * j + 2], a1[8 * j + 3]), pack(a1[8 * j + 4], a1[8 * j + 5]), pack(a1[8 * j + 6], a1[8 * j + 7]));
      }
      fence_async_smem();
      e_store2d(&mp.m_out, tn * 128 + c * 64, tm * 128 + ww * 16, STG + c * 16384 + ww * 2048);
      e_store2d(&mp.m_out, tn * 128 + c * 64, tm * 128 + 64 + ww * 16, STG + c * 16384 + 8192 + ww * 2048);
    }
    bulk_wait_read();
    if (bid == 0 && leader) st_relaxed(&g_epoch, ep);
    STAMP_IF(leader, 29);
  } else {
    asm volatile("setmaxnreg.inc.sync.aligned.u32 216;");
    const int g = lane >> 2, t4 = lane & 3;
    const bool leader = tid == 0;
    const uint32_t sx = lane & 7, sc = lane >> 4;
    const uint32_t sa = STG + (w * 16 + (lane & 15)) * 128;
    const uint32_t sw[4] = {sa + ((sc ^ sx) << 4), sa + (((2 + sc) ^ sx) << 4), sa + (((4 + sc) ^ sx) << 4), sa + (((6 + sc) ^ sx) << 4)};
    float a0[64], a1[64];
    reg_zero(a0); reg_zero(a1); reg_fence(a0); reg_fence(a1);
    if (ALIGN) { uint32_t now; do { asm volatile("mov.u32 %0, %%clock;" : "=r"(now)); } while ((int)(now - ck0) < ALIGN); }
    mainloop<true>(a0, a1, 0, 0, NB_KV, 0, leader);
    STAMP_IF(leader, 33);
    {
      nb_sync(NB_FDONE, 416);
      STAMP_IF(leader, 34);
      float c[4], z[4] = {0.f, 0.f, 0.f, 0.f}, tt[4] = {0.f, 0.f, 0.f, 0.f};
#pragma unroll
      for (int i = 0; i < 4; i++) c[i] = -__uint_as_float(lds32(S_CSK + ((i >> 1) * 64 + w * 16 + (i & 1) * 8 + g) * 4));
#pragma unroll
      for (int j = 0; j < 8; j++) {
        const float4 s0 = lds128v(S_KSTAT + (j * 16 + 2 * t4) * 8), s1 = lds128v(S_KSTAT + (j * 16 + 8 + 2 * t4) * 8);
        const float mu[4] = {s0.x, s0.z, s1.x, s1.z}, rl[4] = {s0.y, s0.w, s1.y, s1.w};
#pragma unroll
        for (int m = 0; m < 2; m++) {
          float p[8];
#pragma unroll
          for (int i = 0; i < 8; i++) {
            const int r = m * 2 + ((i >> 1) & 1), cc = (i >> 2) * 2 + (i & 1);
            p[i] = phi2(fmaf(c[r], mu[cc], m ? a1[8 * j + i] : a0[8 * j + i]) * rl[cc]);
            z[r] += p[i];
            p[i] *= rl[cc];
            tt[r] = fmaf(p[i], mu[cc], tt[r]);
          }
          stsm4(sw[j & 3] + (j >> 2) * 16384 + m * 8192, pack(p[0], p[1]), pack(p[2], p[3]), pack(p[4], p[5]), pack(p[6], p[7]));
        }
      }
      const bool u2 = lane & 2, u1 = lane & 1;
      const float zz = xred(xred(z[0], z[2], u2, 2), xred(z[1], z[3], u2, 2), u1, 1);
      sts32(S_CSK + ((t4 >> 1) * 64 + w * 16 + (t4 & 1) * 8 + g) * 4, __float_as_uint(xred(xred(tt[0], tt[2], u2, 2), xred(tt[1], tt[3], u2, 2), u1, 1)));
      fence_async_smem();
      nb_arrive(NB_PK, 256);
      st_relaxed(g_z + tm * 1024 + tn * 128 + (t4 >> 1) * 64 + w * 16 + (t4 & 1) * 8 + g, tagf(zz * LOG2E, lds32(S_EPOCH) & 1u));
      nb_arrive(NB_Z, 160);
    }
    STAMP_IF(leader, 35);
    float rl0[2];
    const uint32_t ep = lds32(S_EPOCH);
    {
      nb_sync(NB_CSQ, 160);
      float mu[4];
#pragma unroll
      for (int i = 0; i < 4; i++) {
        const float2 st = lds64f(S_KSTAT + ((i >> 1) * 64 + w * 16 + (i & 1) * 8 + g) * 8);
        mu[i] = -st.x;
        if (i < 2) rl0[i] = st.y;
      }
#pragma unroll
      for (int j = 0; j < 16; j++) {
        const float2 c = lds64f(S_CSQ + (j * 8 + 2 * t4) * 4);
        a0[4 * j] = mu[0] * c.x; a0[4 * j + 1] = mu[0] * c.y; a0[4 * j + 2] = mu[1] * c.x; a0[4 * j + 3] = mu[1] * c.y;
        a1[4 * j] = mu[2] * c.x; a1[4 * j + 1] = mu[2] * c.y; a1[4 * j + 2] = mu[3] * c.x; a1[4 * j + 3] = mu[3] * c.y;
      }
      reg_fence(a0); reg_fence(a1);
    }
    STAMP_IF(leader, 40);
    nb_sync(NB_VQ, 256);
    mainloop<false>(a0, a1, 2, 0, 0, GATE_KT ? NB_KV : 0, leader);
    STAMP_IF(leader, 36);
    {
      uint32_t f[2][16];
      float oc[2][2][20];
      auto phi = [&](const float (&a)[64], int j, int m, uint32_t (&o)[16]) {
        float rl[2] = {rl0[0], rl0[1]};
        if (j | m) { rl[0] = lds32v(S_KSTAT + (m * 64 + w * 16 + g) * 8 + 4); rl[1] = lds32v(S_KSTAT + (m * 64 + w * 16 + 8 + g) * 8 + 4); }
#pragma unroll
        for (int i = 0; i < 16; i++) o[i] = pack(phi2(a[32 * j + 2 * i] * rl[i & 1]), phi2(a[32 * j + 2 * i + 1] * rl[i & 1]));
      };
      auto mma = [&](int j, const uint32_t (&a)[16], float (&o)[2][20]) {
        const uint64_t db = mkdesc(j ? KVB_Z : KVB_P0, 16, 1024, 1);
        reg_zero(o[0]); reg_zero(o[1]);
        wg_fence();
        wgmma_n40_rs<0>(o[0], a[0], a[1], a[2], a[3], db, 0);
        wgmma_n40_rs<0>(o[1], a[8], a[9], a[10], a[11], db + 4, 0);
        wgmma_n40_rs<0>(o[0], a[4], a[5], a[6], a[7], db + 2, 1);
        wgmma_n40_rs<0>(o[1], a[12], a[13], a[14], a[15], db + 6, 1);
        wg_commit();
      };
      auto fin = [&](int j, int m, float (&o)[2][20]) {
        const uint32_t m0 = t4 == 2 * m, m1 = t4 == 2 * m + 1;
#pragma unroll
        for (int h = 0; h < 2; h++) {
          const float r0 = rcp(o[h][j ? 1 : 16] + 1e-6f * LOG2E), r1 = rcp(o[h][j ? 3 : 18] + 1e-6f * LOG2E);
          const int b = j ? 4 : 0;
#pragma unroll
          for (int q = 0; q < 2; q++)
            stsm4(sw[h * 2 + q] + j * 16384 + m * 8192,
                  bsel(pack(o[h][b + 8 * q] * r0, o[h][b + 8 * q + 1] * r0), ep, m0), bsel(pack(o[h][b + 8 * q + 2] * r1, o[h][b + 8 * q + 3] * r1), ep, m1),
                  bsel(pack(o[h][b + 8 * q + 4] * r0, o[h][b + 8 * q + 5] * r0), ep, m0), bsel(pack(o[h][b + 8 * q + 6] * r1, o[h][b + 8 * q + 7] * r1), ep, m1));
        }
      };
#pragma unroll
      for (int j = 0; j < 2; j++) {
        phi(a0, j, 0, f[0]);
        if (j == 0) nb_sync(NB_KVB, 288);
        STAMP_IF(leader && j == 0, 37);
        mma(j, f[0], oc[0]);
        phi(a1, j, 1, f[1]);
        wg_wait<0>();
        reg_fence(oc[0][0]); reg_fence(oc[0][1]);
        mma(j, f[1], oc[1]);
        fin(j, 0, oc[0]);
        if (j == 0) { fence_async_smem(); nb_arrive(NB_Q0, 192); }
        wg_wait<0>();
        reg_fence(oc[1][0]); reg_fence(oc[1][1]);
        fin(j, 1, oc[1]);
        fence_async_smem();
        if (j == 0) nb_arrive(NB_OWN0, 288);
        else { nb_arrive(NB_OWN1, 256); nb_arrive(NB_H1, 160); }
        STAMP_IF(leader, 38 + j);
      }
    }
  }
}

#undef CK
typedef CUresult (*EncodeFn)(CUtensorMap*, CUtensorMapDataType, cuuint32_t, void*, const cuuint64_t*, const cuuint64_t*, const cuuint32_t*,
                             const cuuint32_t*, CUtensorMapInterleave, CUtensorMapSwizzle, CUtensorMapL2promotion, CUtensorMapFloatOOBfill);

void make_map(EncodeFn enc, CUtensorMap* m, const void* p, int rank, uint64_t d0, uint64_t d1, uint64_t d2, uint64_t s1, uint64_t s2,
              uint32_t b0, uint32_t b1, uint32_t b2, CUtensorMapSwizzle sw) {
  cuuint64_t gd[3] = {d0, d1, d2}, gs[2] = {s1, s2};
  cuuint32_t bd[3] = {b0, b1, b2}, es[3] = {1, 1, 1};
  enc(m, CU_TENSOR_MAP_DATA_TYPE_BFLOAT16, rank, const_cast<void*>(p), gd, gs, bd, es, CU_TENSOR_MAP_INTERLEAVE_NONE, sw,
      CU_TENSOR_MAP_L2_PROMOTION_L2_128B, CU_TENSOR_MAP_FLOAT_OOB_FILL_NONE);
}

}

extern "C" void kernel_launch(void* const* d_in, const int* in_sizes, int n_in, void* d_out, int out_size) {
  (void)in_sizes; (void)n_in; (void)out_size;
  void* fn = nullptr;
  cudaDriverEntryPointQueryResult qr;
  cudaGetDriverEntryPoint("cuTensorMapEncodeTiled", &fn, cudaEnableDefault, &qr);
  EncodeFn enc = (EncodeFn)fn;
  void* o;
  cudaGetSymbolAddress(&o, g_o);
  const CUtensorMapSwizzle S128 = CU_TENSOR_MAP_SWIZZLE_128B, S64 = CU_TENSOR_MAP_SWIZZLE_64B, S0 = CU_TENSOR_MAP_SWIZZLE_NONE;
  Params mp;
  mp.x = (const char*)d_in[0]; mp.wqkv = (const char*)d_in[1]; mp.w_r = (const char*)d_in[4];
  mp.wg = (const char*)d_in[5]; mp.wu = (const char*)d_in[6]; mp.wd = (const char*)d_in[7];
  make_map(enc, &mp.m_wqkv, d_in[1], 3, 64, 1024, 48, 6144, 128, 64, 64, 2, S128);
  make_map(enc, &mp.m_x, d_in[0], 2, 1024, 2048, 1, 2048, 0, 64, 128, 1, S128);
  make_map(enc, &mp.m_os, o, 2, 1024, 2048, 1, 2048, 0, 64, 64, 1, S128);
  make_map(enc, &mp.m_o, o, 2, 1024, 2048, 1, 2048, 0, 64, 128, 1, S128);
  make_map(enc, &mp.m_wo, d_in[2], 3, 64, 1024, 16, 2048, 128, 64, 64, 2, S128);
  make_map(enc, &mp.m_xs, d_in[0], 2, 1024, 2048, 1, 2048, 0, 256, 16, 1, S0);
  const char *wg = (const char*)d_in[5], *wu = (const char*)d_in[6];
  make_map(enc, &mp.m_gu, wu < wg ? wu : wg, 3, 3584, 1024, 2, 7168, (uint64_t)(wu < wg ? wg - wu : wu - wg), 32, 32, 2, S64);
  make_map(enc, &mp.m_down, d_in[7], 2, 1024, 3584, 1, 2048, 0, 64, 32, 1, S128);
  make_map(enc, &mp.m_out, d_out, 2, 1024, 2048, 1, 2048, 0, 64, 16, 1, S128);
  int dev = 0, sms = 0;
  cudaGetDevice(&dev);
  cudaDeviceGetAttribute(&sms, cudaDevAttrMultiProcessorCount, dev);
  auto kern = sms == 132 ? fused_kernel<true> : fused_kernel<false>;
  cudaFuncSetAttribute(kern, cudaFuncAttributeMaxDynamicSharedMemorySize, SMEM_BYTES);
  kern<<<132, 512, SMEM_BYTES>>>(mp);
}
```

```cpp
#include <cuda_runtime.h>
#include <cuda.h>
#include <cuda_bf16.h>
#include <stdint.h>

namespace {

template <int TA, int TB>
__device__ __forceinline__ void wgmma_n8_ss(float (&d)[4], uint64_t da, uint64_t db, int sc) {
  asm volatile("{\n.reg .pred p;\nsetp.ne.b32 p, %6, 0;\n"
    "wgmma.mma_async.sync.aligned.m64n8k16.f32.bf16.bf16 {%0, %1, %2, %3}, %4, %5, p, 1, 1, %7, %8;\n}\n"
    : "+f"(d[0]), "+f"(d[1]), "+f"(d[2]), "+f"(d[3])
    : "l"(da), "l"(db), "r"(sc), "n"(TA), "n"(TB));
}
template <int TB>
__device__ __forceinline__ void wgmma_n40_rs(float (&d)[20], uint32_t a0, uint32_t a1, uint32_t a2, uint32_t a3, uint64_t db, int sc) {
  asm volatile("{\n.reg .pred p;\nsetp.ne.b32 p, %25, 0;\n"
    "wgmma.mma_async.sync.aligned.m64n40k16.f32.bf16.bf16 {%0, %1, %2, %3, %4, %5, %6, %7, %8, %9, %10, %11, %12, %13, %14, %15, %16, %17, %18, %19}, {%20,%21,%22,%23}, %24, p, 1, 1, %26;\n}\n"
    : "+f"(d[0]), "+f"(d[1]), "+f"(d[2]), "+f"(d[3]), "+f"(d[4]), "+f"(d[5]), "+f"(d[6]), "+f"(d[7]),
      "+f"(d[8]), "+f"(d[9]), "+f"(d[10]), "+f"(d[11]), "+f"(d[12]), "+f"(d[13]), "+f"(d[14]), "+f"(d[15]),
      "+f"(d[16]), "+f"(d[17]), "+f"(d[18]), "+f"(d[19])
    : "r"(a0), "r"(a1), "r"(a2), "r"(a3), "l"(db), "r"(sc), "n"(TB));
}
template <int TB>
__device__ __forceinline__ void wgmma_n64_rs(float (&d)[32], uint32_t a0, uint32_t a1, uint32_t a2, uint32_t a3, uint64_t db, int sc) {
  asm volatile("{\n.reg .pred p;\nsetp.ne.b32 p, %37, 0;\n"
    "wgmma.mma_async.sync.aligned.m64n64k16.f32.bf16.bf16 {%0, %1, %2, %3, %4, %5, %6, %7, %8, %9, %10, %11, %12, %13, %14, %15, %16, %17, %18, %19, %20, %21, %22, %23, %24, %25, %26, %27, %28, %29, %30, %31}, {%32,%33,%34,%35}, %36, p, 1, 1, %38;\n}\n"
    : "+f"(d[0]), "+f"(d[1]), "+f"(d[2]), "+f"(d[3]), "+f"(d[4]), "+f"(d[5]), "+f"(d[6]), "+f"(d[7]),
      "+f"(d[8]), "+f"(d[9]), "+f"(d[10]), "+f"(d[11]), "+f"(d[12]), "+f"(d[13]), "+f"(d[14]), "+f"(d[15]),
      "+f"(d[16]), "+f"(d[17]), "+f"(d[18]), "+f"(d[19]), "+f"(d[20]), "+f"(d[21]), "+f"(d[22]), "+f"(d[23]),
      "+f"(d[24]), "+f"(d[25]), "+f"(d[26]), "+f"(d[27]), "+f"(d[28]), "+f"(d[29]), "+f"(d[30]), "+f"(d[31])
    : "r"(a0), "r"(a1), "r"(a2), "r"(a3), "l"(db), "r"(sc), "n"(TB));
}
template <int TA, int TB>
__device__ __forceinline__ void wgmma_n128_ss(float (&d)[64], uint64_t da, uint64_t db, int sc) {
  asm volatile("{\n.reg .pred p;\nsetp.ne.b32 p, %66, 0;\n"
    "wgmma.mma_async.sync.aligned.m64n128k16.f32.bf16.bf16 {%0, %1, %2, %3, %4, %5, %6, %7, %8, %9, %10, %11, %12, %13, %14, %15, %16, %17, %18, %19, %20, %21, %22, %23, %24, %25, %26, %27, %28, %29, %30, %31, %32, %33, %34, %35, %36, %37, %38, %39, %40, %41, %42, %43, %44, %45, %46, %47, %48, %49, %50, %51, %52, %53, %54, %55, %56, %57, %58, %59, %60, %61, %62, %63}, %64, %65, p, 1, 1, %67, %68;\n}\n"
    : "+f"(d[0]), "+f"(d[1]), "+f"(d[2]), "+f"(d[3]), "+f"(d[4]), "+f"(d[5]), "+f"(d[6]), "+f"(d[7]),
      "+f"(d[8]), "+f"(d[9]), "+f"(d[10]), "+f"(d[11]), "+f"(d[12]), "+f"(d[13]), "+f"(d[14]), "+f"(d[15]),
      "+f"(d[16]), "+f"(d[17]), "+f"(d[18]), "+f"(d[19]), "+f"(d[20]), "+f"(d[21]), "+f"(d[22]), "+f"(d[23]),
      "+f"(d[24]), "+f"(d[25]), "+f"(d[26]), "+f"(d[27]), "+f"(d[28]), "+f"(d[29]), "+f"(d[30]), "+f"(d[31]),
      "+f"(d[32]), "+f"(d[33]), "+f"(d[34]), "+f"(d[35]), "+f"(d[36]), "+f"(d[37]), "+f"(d[38]), "+f"(d[39]),
      "+f"(d[40]), "+f"(d[41]), "+f"(d[42]), "+f"(d[43]), "+f"(d[44]), "+f"(d[45]), "+f"(d[46]), "+f"(d[47]),
      "+f"(d[48]), "+f"(d[49]), "+f"(d[50]), "+f"(d[51]), "+f"(d[52]), "+f"(d[53]), "+f"(d[54]), "+f"(d[55]),
      "+f"(d[56]), "+f"(d[57]), "+f"(d[58]), "+f"(d[59]), "+f"(d[60]), "+f"(d[61]), "+f"(d[62]), "+f"(d[63])
    : "l"(da), "l"(db), "r"(sc), "n"(TA), "n"(TB));
}
template <int TB>
__device__ __forceinline__ void wgmma_n128_rs(float (&d)[64], uint32_t a0, uint32_t a1, uint32_t a2, uint32_t a3, uint64_t db, int sc) {
  asm volatile("{\n.reg .pred p;\nsetp.ne.b32 p, %69, 0;\n"
    "wgmma.mma_async.sync.aligned.m64n128k16.f32.bf16.bf16 {%0, %1, %2, %3, %4, %5, %6, %7, %8, %9, %10, %11, %12, %13, %14, %15, %16, %17, %18, %19, %20, %21, %22, %23, %24, %25, %26, %27, %28, %29, %30, %31, %32, %33, %34, %35, %36, %37, %38, %39, %40, %41, %42, %43, %44, %45, %46, %47, %48, %49, %50, %51, %52, %53, %54, %55, %56, %57, %58, %59, %60, %61, %62, %63}, {%64,%65,%66,%67}, %68, p, 1, 1, %70;\n}\n"
    : "+f"(d[0]), "+f"(d[1]), "+f"(d[2]), "+f"(d[3]), "+f"(d[4]), "+f"(d[5]), "+f"(d[6]), "+f"(d[7]),
      "+f"(d[8]), "+f"(d[9]), "+f"(d[10]), "+f"(d[11]), "+f"(d[12]), "+f"(d[13]), "+f"(d[14]), "+f"(d[15]),
      "+f"(d[16]), "+f"(d[17]), "+f"(d[18]), "+f"(d[19]), "+f"(d[20]), "+f"(d[21]), "+f"(d[22]), "+f"(d[23]),
      "+f"(d[24]), "+f"(d[25]), "+f"(d[26]), "+f"(d[27]), "+f"(d[28]), "+f"(d[29]), "+f"(d[30]), "+f"(d[31]),
      "+f"(d[32]), "+f"(d[33]), "+f"(d[34]), "+f"(d[35]), "+f"(d[36]), "+f"(d[37]), "+f"(d[38]), "+f"(d[39]),
      "+f"(d[40]), "+f"(d[41]), "+f"(d[42]), "+f"(d[43]), "+f"(d[44]), "+f"(d[45]), "+f"(d[46]), "+f"(d[47]),
      "+f"(d[48]), "+f"(d[49]), "+f"(d[50]), "+f"(d[51]), "+f"(d[52]), "+f"(d[53]), "+f"(d[54]), "+f"(d[55]),
      "+f"(d[56]), "+f"(d[57]), "+f"(d[58]), "+f"(d[59]), "+f"(d[60]), "+f"(d[61]), "+f"(d[62]), "+f"(d[63])
    : "r"(a0), "r"(a1), "r"(a2), "r"(a3), "l"(db), "r"(sc), "n"(TB));
}

__device__ __forceinline__ void poll1(uint32_t (&v)[1], const void* p, uint32_t tag, uint32_t mask) {
  asm volatile("{\n.reg .pred p, q;\n.reg .u32 c, b;\n.reg .b64 x, y;\n.reg .b128 z;\nmov.u32 c, 0;\nLW:\n"
               "ld.relaxed.gpu.global.u32 %0, [%1+0];\n"
               "xor.b32 b, %0, %2;\n"
               "and.b32 b, b, %3;\nsetp.eq.u32 p, b, 0;\nvote.sync.all.pred p, p, 0xffffffff;\n@p bra.uni LD;\n"
               "nanosleep.u32 100;\nadd.u32 c, c, 1;\nsetp.lt.u32 q, c, 1000000;\n@q bra.uni LW;\ntrap;\nLD:\n}"
               : "=&r"(v[0])
               : "l"(p), "r"(tag), "r"(mask) : "memory");
}
__device__ __forceinline__ void poll1f(uint32_t (&v)[1], const void* p, uint32_t tag, uint32_t mask) {
  asm volatile("{\n.reg .pred p, q;\n.reg .u32 c, b;\n.reg .b64 x, y;\n.reg .b128 z;\nmov.u32 c, 0;\nLW:\n"
               "ld.relaxed.gpu.global.u32 %0, [%1+0];\n"
               "xor.b32 b, %0, %2;\n"
               "and.b32 b, b, %3;\nsetp.eq.u32 p, b, 0;\nvote.sync.all.pred p, p, 0xffffffff;\n@p bra.uni LD;\n"
               "nanosleep.u32 50;\nadd.u32 c, c, 1;\nsetp.lt.u32 q, c, 1000000;\n@q bra.uni LW;\ntrap;\nLD:\n}"
               : "=&r"(v[0])
               : "l"(p), "r"(tag), "r"(mask) : "memory");
}
__device__ __forceinline__ void poll0(uint32_t (&v)[1], const void* p, uint32_t tag, uint32_t mask) {
  asm volatile("{\n.reg .pred p, q;\n.reg .u32 c, b;\n.reg .b64 x, y;\n.reg .b128 z;\nmov.u32 c, 0;\nLW:\n"
               "ld.relaxed.gpu.global.u32 %0, [%1+0];\n"
               "xor.b32 b, %0, %2;\n"
               "and.b32 b, b, %3;\nsetp.eq.u32 p, b, 0;\nvote.sync.all.pred p, p, 0xffffffff;\n@p bra.uni LD;\n"
               "add.u32 c, c, 1;\nsetp.lt.u32 q, c, 1000000;\n@q bra.uni LW;\ntrap;\nLD:\n}"
               : "=&r"(v[0])
               : "l"(p), "r"(tag), "r"(mask) : "memory");
}
__device__ __forceinline__ void poll_pair(uint32_t (&v)[2], const void* p, uint32_t tag, uint32_t mask) {
  asm volatile("{\n.reg .pred p, q;\n.reg .u32 c, b;\n.reg .b64 x, y;\n.reg .b128 z;\nmov.u32 c, 0;\nLW:\n"
               "ld.relaxed.gpu.global.b64 x, [%2+0];\nmov.b64 {%0,%1}, x;\n"
               "xor.b32 b, %0, %3;\n"
               "and.b32 b, b, %4;\nsetp.eq.u32 p, b, 0;\nvote.sync.all.pred p, p, 0xffffffff;\n@p bra.uni LD;\n"
               "nanosleep.u32 100;\nadd.u32 c, c, 1;\nsetp.lt.u32 q, c, 1000000;\n@q bra.uni LW;\ntrap;\nLD:\n}"
               : "=&r"(v[0]), "=&r"(v[1])
               : "l"(p), "r"(tag), "r"(mask) : "memory");
}
__device__ __forceinline__ void poll_quad(uint32_t (&v)[4], const void* p, uint32_t tag, uint32_t mask) {
  asm volatile("{\n.reg .pred p, q;\n.reg .u32 c, b;\n.reg .b64 x, y;\n.reg .b128 z;\nmov.u32 c, 0;\nLW:\n"
               "ld.relaxed.gpu.global.v4.u32 {%0,%1,%2,%3}, [%4+0];\n"
               "xor.b32 b, %0, %5;\n"
               "lop3.b32 b, b, %1, %5, 0xf6;\nlop3.b32 b, b, %2, %5, 0xf6;\nlop3.b32 b, b, %3, %5, 0xf6;\n"
               "and.b32 b, b, %6;\nsetp.eq.u32 p, b, 0;\nvote.sync.all.pred p, p, 0xffffffff;\n@p bra.uni LD;\n"
               "nanosleep.u32 200;\nadd.u32 c, c, 1;\nsetp.lt.u32 q, c, 1000000;\n@q bra.uni LW;\ntrap;\nLD:\n}"
               : "=&r"(v[0]), "=&r"(v[1]), "=&r"(v[2]), "=&r"(v[3])
               : "l"(p), "r"(tag), "r"(mask) : "memory");
}
__device__ __forceinline__ void poll8x4(uint32_t (&v)[32], const void* p, uint32_t tag, uint32_t mask) {
  asm volatile("{\n.reg .pred p, q;\n.reg .u32 c, b;\n.reg .b64 x, y;\n.reg .b128 z;\nmov.u32 c, 0;\nLW:\n"
               "ld.relaxed.gpu.global.v4.u32 {%0,%1,%2,%3}, [%32+0];\n"
               "ld.relaxed.gpu.global.v4.u32 {%4,%5,%6,%7}, [%32+2048];\n"
               "ld.relaxed.gpu.global.v4.u32 {%8,%9,%10,%11}, [%32+4096];\n"
               "ld.relaxed.gpu.global.v4.u32 {%12,%13,%14,%15}, [%32+6144];\n"
               "ld.relaxed.gpu.global.v4.u32 {%16,%17,%18,%19}, [%32+8192];\n"
               "ld.relaxed.gpu.global.v4.u32 {%20,%21,%22,%23}, [%32+10240];\n"
               "ld.relaxed.gpu.global.v4.u32 {%24,%25,%26,%27}, [%32+12288];\n"
               "ld.relaxed.gpu.global.v4.u32 {%28,%29,%30,%31}, [%32+14336];\n"
               "xor.b32 b, %0, %33;\n"
               "lop3.b32 b, b, %1, %33, 0xf6;\nlop3.b32 b, b, %2, %33, 0xf6;\nlop3.b32 b, b, %3, %33, 0xf6;\nlop3.b32 b, b, %4, %33, 0xf6;\n"
               "lop3.b32 b, b, %5, %33, 0xf6;\nlop3.b32 b, b, %6, %33, 0xf6;\nlop3.b32 b, b, %7, %33, 0xf6;\nlop3.b32 b, b, %8, %33, 0xf6;\n"
               "lop3.b32 b, b, %9, %33, 0xf6;\nlop3.b32 b, b, %10, %33, 0xf6;\nlop3.b32 b, b, %11, %33, 0xf6;\nlop3.b32 b, b, %12, %33, 0xf6;\n"
               "lop3.b32 b, b, %13, %33, 0xf6;\nlop3.b32 b, b, %14, %33, 0xf6;\nlop3.b32 b, b, %15, %33, 0xf6;\nlop3.b32 b, b, %16, %33, 0xf6;\n"
               "lop3.b32 b, b, %17, %33, 0xf6;\nlop3.b32 b, b, %18, %33, 0xf6;\nlop3.b32 b, b, %19, %33, 0xf6;\nlop3.b32 b, b, %20, %33, 0xf6;\n"
               "lop3.b32 b, b, %21, %33, 0xf6;\nlop3.b32 b, b, %22, %33, 0xf6;\nlop3.b32 b, b, %23, %33, 0xf6;\nlop3.b32 b, b, %24, %33, 0xf6;\n"
               "lop3.b32 b, b, %25, %33, 0xf6;\nlop3.b32 b, b, %26, %33, 0xf6;\nlop3.b32 b, b, %27, %33, 0xf6;\nlop3.b32 b, b, %28, %33, 0xf6;\n"
               "lop3.b32 b, b, %29, %33, 0xf6;\nlop3.b32 b, b, %30, %33, 0xf6;\nlop3.b32 b, b, %31, %33, 0xf6;\n"
               "and.b32 b, b, %34;\nsetp.eq.u32 p, b, 0;\nvote.sync.all.pred p, p, 0xffffffff;\n@p bra.uni LD;\n"
               "nanosleep.u32 50;\nadd.u32 c, c, 1;\nsetp.lt.u32 q, c, 1000000;\n@q bra.uni LW;\ntrap;\nLD:\n}"
               : "=&r"(v[0]), "=&r"(v[1]), "=&r"(v[2]), "=&r"(v[3]), "=&r"(v[4]), "=&r"(v[5]), "=&r"(v[6]), "=&r"(v[7]), "=&r"(v[8]), "=&r"(v[9]), "=&r"(v[10]), "=&r"(v[11]), "=&r"(v[12]), "=&r"(v[13]), "=&r"(v[14]), "=&r"(v[15]), "=&r"(v[16]), "=&r"(v[17]), "=&r"(v[18]), "=&r"(v[19]), "=&r"(v[20]), "=&r"(v[21]), "=&r"(v[22]), "=&r"(v[23]), "=&r"(v[24]), "=&r"(v[25]), "=&r"(v[26]), "=&r"(v[27]), "=&r"(v[28]), "=&r"(v[29]), "=&r"(v[30]), "=&r"(v[31])
               : "l"(p), "r"(tag), "r"(mask) : "memory");
}
__device__ __forceinline__ void poll16(uint32_t (&v)[16], const void* p, uint32_t tag, uint32_t mask) {
  asm volatile("{\n.reg .pred p, q;\n.reg .u32 c, b;\n.reg .b64 x, y;\n.reg .b128 z;\nmov.u32 c, 0;\nLW:\n"
               "ld.relaxed.gpu.global.u32 %0, [%16+0];\n"
               "ld.relaxed.gpu.global.u32 %1, [%16+4096];\n"
               "ld.relaxed.gpu.global.u32 %2, [%16+8192];\n"
               "ld.relaxed.gpu.global.u32 %3, [%16+12288];\n"
               "ld.relaxed.gpu.global.u32 %4, [%16+16384];\n"
               "ld.relaxed.gpu.global.u32 %5, [%16+20480];\n"
               "ld.relaxed.gpu.global.u32 %6, [%16+24576];\n"
               "ld.relaxed.gpu.global.u32 %7, [%16+28672];\n"
               "ld.relaxed.gpu.global.u32 %8, [%16+32768];\n"
               "ld.relaxed.gpu.global.u32 %9, [%16+36864];\n"
               "ld.relaxed.gpu.global.u32 %10, [%16+40960];\n"
               "ld.relaxed.gpu.global.u32 %11, [%16+45056];\n"
               "ld.relaxed.gpu.global.u32 %12, [%16+49152];\n"
               "ld.relaxed.gpu.global.u32 %13, [%16+53248];\n"
               "ld.relaxed.gpu.global.u32 %14, [%16+57344];\n"
               "ld.relaxed.gpu.global.u32 %15, [%16+61440];\n"
               "xor.b32 b, %0, %17;\n"
               "lop3.b32 b, b, %1, %17, 0xf6;\nlop3.b32 b, b, %2, %17, 0xf6;\nlop3.b32 b, b, %3, %17, 0xf6;\nlop3.b32 b, b, %4, %17, 0xf6;\n"
               "lop3.b32 b, b, %5, %17, 0xf6;\nlop3.b32 b, b, %6, %17, 0xf6;\nlop3.b32 b, b, %7, %17, 0xf6;\nlop3.b32 b, b, %8, %17, 0xf6;\n"
               "lop3.b32 b, b, %9, %17, 0xf6;\nlop3.b32 b, b, %10, %17, 0xf6;\nlop3.b32 b, b, %11, %17, 0xf6;\nlop3.b32 b, b, %12, %17, 0xf6;\n"
               "lop3.b32 b, b, %13, %17, 0xf6;\nlop3.b32 b, b, %14, %17, 0xf6;\nlop3.b32 b, b, %15, %17, 0xf6;\n"
               "and.b32 b, b, %18;\nsetp.eq.u32 p, b, 0;\nvote.sync.all.pred p, p, 0xffffffff;\n@p bra.uni LD;\n"
               "nanosleep.u32 200;\nadd.u32 c, c, 1;\nsetp.lt.u32 q, c, 1000000;\n@q bra.uni LW;\ntrap;\nLD:\n}"
               : "=&r"(v[0]), "=&r"(v[1]), "=&r"(v[2]), "=&r"(v[3]), "=&r"(v[4]), "=&r"(v[5]), "=&r"(v[6]), "=&r"(v[7]), "=&r"(v[8]), "=&r"(v[9]), "=&r"(v[10]), "=&r"(v[11]), "=&r"(v[12]), "=&r"(v[13]), "=&r"(v[14]), "=&r"(v[15])
               : "l"(p), "r"(tag), "r"(mask) : "memory");
}
__device__ __forceinline__ void poll_keys(uint32_t (&v)[16], const void* p, uint32_t tag, uint32_t mask) {
  asm volatile("{\n.reg .pred p, q;\n.reg .u32 c, b;\n.reg .b64 x, y;\n.reg .b128 z;\nmov.u32 c, 0;\nLW:\n"
               "ld.relaxed.gpu.global.v2.b64 {x, y}, [%16+0];\nmov.b64 {%0,%1}, x;\nmov.b64 {%2,%3}, y;\n"
               "ld.relaxed.gpu.global.v2.b64 {x, y}, [%16+4096];\nmov.b64 {%4,%5}, x;\nmov.b64 {%6,%7}, y;\n"
               "ld.relaxed.gpu.global.v2.b64 {x, y}, [%16+8192];\nmov.b64 {%8,%9}, x;\nmov.b64 {%10,%11}, y;\n"
               "ld.relaxed.gpu.global.v2.b64 {x, y}, [%16+12288];\nmov.b64 {%12,%13}, x;\nmov.b64 {%14,%15}, y;\n"
               "xor.b32 b, %0, %17;\n"
               "lop3.b32 b, b, %2, %17, 0xf6;\nlop3.b32 b, b, %4, %17, 0xf6;\nlop3.b32 b, b, %6, %17, 0xf6;\nlop3.b32 b, b, %8, %17, 0xf6;\n"
               "lop3.b32 b, b, %10, %17, 0xf6;\nlop3.b32 b, b, %12, %17, 0xf6;\nlop3.b32 b, b, %14, %17, 0xf6;\n"
               "and.b32 b, b, %18;\nsetp.eq.u32 p, b, 0;\nvote.sync.all.pred p, p, 0xffffffff;\n@p bra.uni LD;\n"
               "nanosleep.u32 20;\nadd.u32 c, c, 1;\nsetp.lt.u32 q, c, 1000000;\n@q bra.uni LW;\ntrap;\nLD:\n}"
               : "=&r"(v[0]), "=&r"(v[1]), "=&r"(v[2]), "=&r"(v[3]), "=&r"(v[4]), "=&r"(v[5]), "=&r"(v[6]), "=&r"(v[7]), "=&r"(v[8]), "=&r"(v[9]), "=&r"(v[10]), "=&r"(v[11]), "=&r"(v[12]), "=&r"(v[13]), "=&r"(v[14]), "=&r"(v[15])
               : "l"(p), "r"(tag), "r"(mask) : "memory");
}
__device__ __forceinline__ void poll_z(uint32_t (&v)[16], const void* p, uint32_t tag, uint32_t mask) {
  asm volatile("{\n.reg .pred p, q;\n.reg .u32 c, b;\n.reg .b64 x, y;\n.reg .b128 z;\nmov.u32 c, 0;\nLW:\n"
               "ld.relaxed.gpu.global.v4.u32 {%0,%1,%2,%3}, [%16+0];\n"
               "ld.relaxed.gpu.global.v4.u32 {%4,%5,%6,%7}, [%16+4096];\n"
               "ld.relaxed.gpu.global.v4.u32 {%8,%9,%10,%11}, [%16+8192];\n"
               "ld.relaxed.gpu.global.v4.u32 {%12,%13,%14,%15}, [%16+12288];\n"
               "xor.b32 b, %0, %17;\n"
               "lop3.b32 b, b, %1, %17, 0xf6;\nlop3.b32 b, b, %2, %17, 0xf6;\nlop3.b32 b, b, %3, %17, 0xf6;\nlop3.b32 b, b, %4, %17, 0xf6;\n"
               "lop3.b32 b, b, %5, %17, 0xf6;\nlop3.b32 b, b, %6, %17, 0xf6;\nlop3.b32 b, b, %7, %17, 0xf6;\nlop3.b32 b, b, %8, %17, 0xf6;\n"
               "lop3.b32 b, b, %9, %17, 0xf6;\nlop3.b32 b, b, %10, %17, 0xf6;\nlop3.b32 b, b, %11, %17, 0xf6;\nlop3.b32 b, b, %12, %17, 0xf6;\n"
               "lop3.b32 b, b, %13, %17, 0xf6;\nlop3.b32 b, b, %14, %17, 0xf6;\nlop3.b32 b, b, %15, %17, 0xf6;\n"
               "and.b32 b, b, %18;\nsetp.eq.u32 p, b, 0;\nvote.sync.all.pred p, p, 0xffffffff;\n@p bra.uni LD;\n"
               "nanosleep.u32 300;\nadd.u32 c, c, 1;\nsetp.lt.u32 q, c, 1000000;\n@q bra.uni LW;\ntrap;\nLD:\n}"
               : "=&r"(v[0]), "=&r"(v[1]), "=&r"(v[2]), "=&r"(v[3]), "=&r"(v[4]), "=&r"(v[5]), "=&r"(v[6]), "=&r"(v[7]), "=&r"(v[8]), "=&r"(v[9]), "=&r"(v[10]), "=&r"(v[11]), "=&r"(v[12]), "=&r"(v[13]), "=&r"(v[14]), "=&r"(v[15])
               : "l"(p), "r"(tag), "r"(mask) : "memory");
}
__device__ __forceinline__ void poll7x4(uint32_t (&v)[28], const void* p, uint32_t tag, uint32_t mask) {
  asm volatile("{\n.reg .pred p, q;\n.reg .u32 c, b;\n.reg .b64 x, y;\n.reg .b128 z;\nmov.u32 c, 0;\nLW:\n"
               "ld.relaxed.gpu.global.v4.u32 {%0,%1,%2,%3}, [%28+0];\n"
               "ld.relaxed.gpu.global.v4.u32 {%4,%5,%6,%7}, [%28+2048];\n"
               "ld.relaxed.gpu.global.v4.u32 {%8,%9,%10,%11}, [%28+4096];\n"
               "ld.relaxed.gpu.global.v4.u32 {%12,%13,%14,%15}, [%28+6144];\n"
               "ld.relaxed.gpu.global.v4.u32 {%16,%17,%18,%19}, [%28+8192];\n"
               "ld.relaxed.gpu.global.v4.u32 {%20,%21,%22,%23}, [%28+10240];\n"
               "ld.relaxed.gpu.global.v4.u32 {%24,%25,%26,%27}, [%28+12288];\n"
               "xor.b32 b, %0, %29;\n"
               "lop3.b32 b, b, %1, %29, 0xf6;\nlop3.b32 b, b, %2, %29, 0xf6;\nlop3.b32 b, b, %3, %29, 0xf6;\nlop3.b32 b, b, %4, %29, 0xf6;\n"
               "lop3.b32 b, b, %5, %29, 0xf6;\nlop3.b32 b, b, %6, %29, 0xf6;\nlop3.b32 b, b, %7, %29, 0xf6;\nlop3.b32 b, b, %8, %29, 0xf6;\n"
               "lop3.b32 b, b, %9, %29, 0xf6;\nlop3.b32 b, b, %10, %29, 0xf6;\nlop3.b32 b, b, %11, %29, 0xf6;\nlop3.b32 b, b, %12, %29, 0xf6;\n"
               "lop3.b32 b, b, %13, %29, 0xf6;\nlop3.b32 b, b, %14, %29, 0xf6;\nlop3.b32 b, b, %15, %29, 0xf6;\nlop3.b32 b, b, %16, %29, 0xf6;\n"
               "lop3.b32 b, b, %17, %29, 0xf6;\nlop3.b32 b, b, %18, %29, 0xf6;\nlop3.b32 b, b, %19, %29, 0xf6;\nlop3.b32 b, b, %20, %29, 0xf6;\n"
               "lop3.b32 b, b, %21, %29, 0xf6;\nlop3.b32 b, b, %22, %29, 0xf6;\nlop3.b32 b, b, %23, %29, 0xf6;\nlop3.b32 b, b, %24, %29, 0xf6;\n"
               "lop3.b32 b, b, %25, %29, 0xf6;\nlop3.b32 b, b, %26, %29, 0xf6;\nlop3.b32 b, b, %27, %29, 0xf6;\n"
               "and.b32 b, b, %30;\nsetp.eq.u32 p, b, 0;\nvote.sync.all.pred p, p, 0xffffffff;\n@p bra.uni LD;\n"
               "nanosleep.u32 50;\nadd.u32 c, c, 1;\nsetp.lt.u32 q, c, 1000000;\n@q bra.uni LW;\ntrap;\nLD:\n}"
               : "=&r"(v[0]), "=&r"(v[1]), "=&r"(v[2]), "=&r"(v[3]), "=&r"(v[4]), "=&r"(v[5]), "=&r"(v[6]), "=&r"(v[7]), "=&r"(v[8]), "=&r"(v[9]), "=&r"(v[10]), "=&r"(v[11]), "=&r"(v[12]), "=&r"(v[13]), "=&r"(v[14]), "=&r"(v[15]), "=&r"(v[16]), "=&r"(v[17]), "=&r"(v[18]), "=&r"(v[19]), "=&r"(v[20]), "=&r"(v[21]), "=&r"(v[22]), "=&r"(v[23]), "=&r"(v[24]), "=&r"(v[25]), "=&r"(v[26]), "=&r"(v[27])
               : "l"(p), "r"(tag), "r"(mask) : "memory");
}
__device__ __forceinline__ void poll_kvp(uint32_t (&v)[16], const void* p, uint32_t tag, uint32_t mask) {
  asm volatile("{\n.reg .pred p, q;\n.reg .u32 c, b;\n.reg .b64 x, y;\n.reg .b128 z;\nmov.u32 c, 0;\nLW:\n"
               "ld.relaxed.gpu.global.b128 z, [%16+0];\nmov.b128 {x, y}, z;\nmov.b64 {%0,%1}, x;\nmov.b64 {%2,%3}, y;\n"
               "ld.relaxed.gpu.global.b128 z, [%16+8192];\nmov.b128 {x, y}, z;\nmov.b64 {%4,%5}, x;\nmov.b64 {%6,%7}, y;\n"
               "ld.relaxed.gpu.global.b128 z, [%16+16384];\nmov.b128 {x, y}, z;\nmov.b64 {%8,%9}, x;\nmov.b64 {%10,%11}, y;\n"
               "ld.relaxed.gpu.global.b128 z, [%16+24576];\nmov.b128 {x, y}, z;\nmov.b64 {%12,%13}, x;\nmov.b64 {%14,%15}, y;\n"
               "xor.b32 b, %0, %17;\n"
               "lop3.b32 b, b, %4, %17, 0xf6;\nlop3.b32 b, b, %8, %17, 0xf6;\nlop3.b32 b, b, %12, %17, 0xf6;\n"
               "and.b32 b, b, %18;\nsetp.eq.u32 p, b, 0;\nvote.sync.all.pred p, p, 0xffffffff;\n@p bra.uni LD;\n"
               "nanosleep.u32 50;\nadd.u32 c, c, 1;\nsetp.lt.u32 q, c, 1000000;\n@q bra.uni LW;\ntrap;\nLD:\n}"
               : "=&r"(v[0]), "=&r"(v[1]), "=&r"(v[2]), "=&r"(v[3]), "=&r"(v[4]), "=&r"(v[5]), "=&r"(v[6]), "=&r"(v[7]), "=&r"(v[8]), "=&r"(v[9]), "=&r"(v[10]), "=&r"(v[11]), "=&r"(v[12]), "=&r"(v[13]), "=&r"(v[14]), "=&r"(v[15])
               : "l"(p), "r"(tag), "r"(mask) : "memory");
}
__device__ __forceinline__ void poll_kv(uint32_t (&v)[16], const void* p, uint32_t tag, uint32_t mask) {
  asm volatile("{\n.reg .pred p, q;\n.reg .u32 c, b;\n.reg .b64 x, y;\n.reg .b128 z;\nmov.u32 c, 0;\nLW:\n"
               "ld.relaxed.gpu.global.b128 z, [%16+0];\nmov.b128 {x, y}, z;\nmov.b64 {%0,%1}, x;\nmov.b64 {%2,%3}, y;\n"
               "ld.relaxed.gpu.global.b128 z, [%16+2048];\nmov.b128 {x, y}, z;\nmov.b64 {%4,%5}, x;\nmov.b64 {%6,%7}, y;\n"
               "ld.relaxed.gpu.global.b128 z, [%16+4096];\nmov.b128 {x, y}, z;\nmov.b64 {%8,%9}, x;\nmov.b64 {%10,%11}, y;\n"
               "ld.relaxed.gpu.global.b128 z, [%16+6144];\nmov.b128 {x, y}, z;\nmov.b64 {%12,%13}, x;\nmov.b64 {%14,%15}, y;\n"
               "xor.b32 b, %0, %17;\n"
               "lop3.b32 b, b, %4, %17, 0xf6;\nlop3.b32 b, b, %8, %17, 0xf6;\nlop3.b32 b, b, %12, %17, 0xf6;\n"
               "and.b32 b, b, %18;\nsetp.eq.u32 p, b, 0;\nvote.sync.all.pred p, p, 0xffffffff;\n@p bra.uni LD;\n"
               "nanosleep.u32 50;\nadd.u32 c, c, 1;\nsetp.lt.u32 q, c, 1000000;\n@q bra.uni LW;\ntrap;\nLD:\n}"
               : "=&r"(v[0]), "=&r"(v[1]), "=&r"(v[2]), "=&r"(v[3]), "=&r"(v[4]), "=&r"(v[5]), "=&r"(v[6]), "=&r"(v[7]), "=&r"(v[8]), "=&r"(v[9]), "=&r"(v[10]), "=&r"(v[11]), "=&r"(v[12]), "=&r"(v[13]), "=&r"(v[14]), "=&r"(v[15])
               : "l"(p), "r"(tag), "r"(mask) : "memory");
}

__device__ __align__(1024) __nv_bfloat16 g_o[2048 * 1024];
__device__ __align__(128) uint2 g_keys[2048];
__device__ __align__(128) uint32_t g_csum[18 * 1024];
__device__ __align__(128) uint32_t g_z[16 * 1024];
__device__ __align__(128) uint4 g_kvp[128 * 512];
__device__ __align__(128) uint4 g_kv[8 * 512];
__device__ __align__(128) uint32_t g_h[112 * 256];
__device__ __align__(128) uint32_t g_yp[128 * 512];
__device__ __align__(128) uint32_t g_xsel[4096 + 32];
enum { H_CS = 0, H_KVP = 8, H_KV = 16, H_H = 24, H_Y = 32, H_O = 40, H_R = 56, H_Z = 57 };
__device__ __align__(128) uint32_t g_sig[65 * 32];
__device__ uint32_t g_epoch;

constexpr uint32_t RING = 1024, SLOT = 32768, SMEM_BYTES = 232448;
constexpr int NST = 5, HST = 7;
constexpr uint32_t STG = RING + 163840, AUX = RING + 196608, FR = RING + 212992, MISC = RING + 229376;
constexpr uint32_t B_FULL = MISC, B_EMPTY = MISC + 56, B_XS = MISC + 112, B_SEL = MISC + 144, B_XRES = MISC + 152, B_WK = MISC + 160, B_CSDN = MISC + 168,
                   B_FR = MISC + 176, B_FE = MISC + 216, B_DR = MISC + 256, B_CSV = MISC + 288,
                   B_OWN = MISC + 296, NBAR = 39;
constexpr uint32_t S_EPOCH = MISC + 352, S_NCAND = MISC + 356, S_SEL = MISC + 368, S_WMAX = MISC + 400,
                   S_KSTAT = MISC + 512, S_CSK = MISC + 1536, S_CSV = MISC + 2048, S_CSQ = MISC + 2560, S_ONES = MISC + 512;
constexpr uint32_t KVB_P0 = AUX, KVB_Z = AUX + 4096, KVB_P1 = AUX + 5120, HOP = AUX + 9216, GR = FR - 4096;
enum { NB_Z = 0, NB_KV = 1, NB_VQ = 2, NB_WG0 = 3, NB_FDONE = 4, NB_PK = 5, NB_KVB = 6, NB_WG1 = 7, NB_WG2 = 8, NB_CSQ = 9,
       NB_Y = 10, NB_ST = 11, NB_OWN0 = 12, NB_OWN1 = 13, NB_Q0 = 14, NB_H1 = 15 };

#define XS_ORD 0x3210
#define XS_GO 0
#define XS_FLY 2
#define XS_EARLY 0
#define H_DELAY 0
#define FFN_GAP 200
#define GATE_KT 1
#define GATE_K 6
#define KV_DIRECT 1
#define ALIGN 0
#define DN_GAP 50
#define PF_GAP 200
#define PF_WAIT 1000
#define POLITE 1
constexpr uint64_t EVICT_FIRST = 0x12f0000000000000ull;
constexpr float LOG2E = 1.4426950408889634f, LN2 = 0.6931471805599453f;

#define ELECT "{\n.reg .pred p;\nelect.sync _|p, 0xffffffff;\n"
#define TMA2D "cp.async.bulk.tensor.2d.shared::cluster.global.mbarrier::complete_tx::bytes"
#define TMA3D "cp.async.bulk.tensor.3d.shared::cluster.global.mbarrier::complete_tx::bytes"
__device__ __forceinline__ void e_expect(uint32_t b, uint32_t n) {
  asm volatile(ELECT "@p mbarrier.arrive.expect_tx.shared::cta.b64 _, [%0], %1;\n}" ::"r"(b), "r"(n) : "memory");
}
__device__ __forceinline__ void e_arrive(uint32_t b) { asm volatile(ELECT "@p mbarrier.arrive.shared::cta.b64 _, [%0];\n}" ::"r"(b) : "memory"); }
__device__ __forceinline__ void e_tma2d(uint32_t dst, const CUtensorMap* m, int c0, int c1, uint32_t bar) {
  asm volatile(ELECT "@p " TMA2D " [%0], [%1, {%3, %4}], [%2];\n}" ::"r"(dst), "l"(m), "r"(bar), "r"(c0), "r"(c1) : "memory");
}
__device__ __forceinline__ void e_tma2d_ef(uint32_t dst, const CUtensorMap* m, int c0, int c1, uint32_t bar, uint64_t pol) {
  asm volatile(ELECT "@p " TMA2D ".L2::cache_hint [%0], [%1, {%3, %4}], [%2], %5;\n}" ::"r"(dst), "l"(m), "r"(bar), "r"(c0), "r"(c1), "l"(pol) : "memory");
}
__device__ __forceinline__ void e_tma3d(uint32_t dst, const CUtensorMap* m, int c1, int c2, uint32_t bar) {
  asm volatile(ELECT "@p " TMA3D " [%0], [%1, {0, %3, %4}], [%2];\n}" ::"r"(dst), "l"(m), "r"(bar), "r"(c1), "r"(c2) : "memory");
}
__device__ __forceinline__ void e_store2d(const CUtensorMap* m, int c0, int c1, uint32_t src) {
  asm volatile(ELECT "@p cp.async.bulk.tensor.2d.global.shared::cta.bulk_group [%0, {%2, %3}], [%1];\n}" ::"l"(m), "r"(src), "r"(c0), "r"(c1) : "memory");
}
__device__ __forceinline__ void e_tma3d_ef(uint32_t dst, const CUtensorMap* m, int c0, int c1, uint32_t bar, uint64_t pol) {
  asm volatile(ELECT "@p " TMA3D ".L2::cache_hint [%0], [%1, {%3, %4, 0}], [%2], %5;\n}" ::"r"(dst), "l"(m), "r"(bar), "r"(c0), "r"(c1), "l"(pol) : "memory");
}
__device__ __forceinline__ void e_load(uint32_t dst, const void* src, uint32_t n, uint32_t bar) {
  asm volatile(ELECT "@p cp.async.bulk.shared::cluster.global.mbarrier::complete_tx::bytes [%0], [%1], %2, [%3];\n}" ::"r"(dst), "l"(src), "r"(n), "r"(bar) : "memory");
}
__device__ __forceinline__ void e_pfmap(const CUtensorMap* m) { asm volatile(ELECT "@p prefetch.tensormap [%0];\n}" ::"l"(m) : "memory"); }
__device__ __forceinline__ void bulk_wait_read() { asm volatile("cp.async.bulk.commit_group;\ncp.async.bulk.wait_group.read 0;" ::: "memory"); }
__device__ __forceinline__ void e_signal(int word, int bit) {
  asm volatile(ELECT "@p red.relaxed.gpu.global.xor.b32 [%0], %1;\n}" ::"l"(g_sig + word * 32), "r"(1u << bit) : "memory");
}
__device__ __forceinline__ void e_release(int word, int bit) {
  asm volatile("cp.async.bulk.commit_group;\ncp.async.bulk.wait_group 0;\nfence.release.gpu;" ::: "memory");
  e_signal(word, bit);
}
__device__ __forceinline__ void await(int word, uint32_t mask, uint32_t ep) {
  uint32_t f[1];
  poll1f(f, g_sig + word * 32, 0u - (ep & 1u), mask);
}

__device__ __forceinline__ void mbar_arrive(uint32_t b) { asm volatile("mbarrier.arrive.shared::cta.b64 _, [%0];" ::"r"(b) : "memory"); }
__device__ __forceinline__ void mbar_wait(uint32_t b, uint32_t ph) {
  asm volatile("{\n.reg .pred p, q;\n.reg .u32 c;\nmov.u32 c, 0;\nLW:\nmbarrier.try_wait.parity.shared::cta.b64 p, [%0], %1;\n@p bra LD;\n"
               "add.u32 c, c, 1;\nsetp.lt.u32 q, c, 100000;\n@q bra LW;\ntrap;\nLD:\n}" ::"r"(b), "r"(ph) : "memory");
}
__device__ __forceinline__ void nb_sync(int id, int n) { asm volatile("bar.sync %0, %1;" ::"r"(id), "r"(n) : "memory"); }
__device__ __forceinline__ void nb_arrive(int id, int n) { asm volatile("bar.arrive %0, %1;" ::"r"(id), "r"(n) : "memory"); }
__device__ __forceinline__ void wg_fence() { asm volatile("wgmma.fence.sync.aligned;" ::: "memory"); }
__device__ __forceinline__ void wg_commit() { asm volatile("wgmma.commit_group.sync.aligned;" ::: "memory"); }
template <int N> __device__ __forceinline__ void wg_wait() { asm volatile("wgmma.wait_group.sync.aligned %0;" ::"n"(N) : "memory"); }
template <int N> __device__ __forceinline__ void reg_fence(float (&a)[N]) {
#pragma unroll
  for (int i = 0; i < N; i++) asm volatile("" : "+f"(a[i])::"memory");
}
template <int N> __device__ __forceinline__ void reg_zero(float (&a)[N]) {
#pragma unroll
  for (int i = 0; i < N; i++) a[i] = 0.f;
}
__device__ __forceinline__ constexpr uint64_t mkdesc(uint32_t addr, uint32_t lbo, uint32_t sbo, uint32_t swz) {
  return (uint64_t)(addr >> 4) | ((uint64_t)(lbo >> 4) << 16) | ((uint64_t)(sbo >> 4) << 32) | ((uint64_t)swz << 62);
}
__device__ __forceinline__ void fence_async_smem() { asm volatile("fence.proxy.async.shared::cta;" ::: "memory"); }
__device__ __forceinline__ void fence_async_glob() { asm volatile("fence.proxy.async.global;" ::: "memory"); }
__device__ __forceinline__ void fence_acq() { asm volatile("fence.acquire.gpu;" ::: "memory"); }
__device__ __forceinline__ void st_relaxed(uint32_t* p, uint32_t v) { asm volatile("st.relaxed.gpu.global.u32 [%0], %1;" ::"l"(p), "r"(v) : "memory"); }
__device__ __forceinline__ uint32_t ld_relaxed(const uint32_t* p) { uint32_t v; asm volatile("ld.relaxed.gpu.global.u32 %0, [%1];" : "=r"(v) : "l"(p) : "memory"); return v; }
__device__ __forceinline__ void st_unit(uint4* p, uint32_t a, uint32_t b, uint32_t c, uint32_t d, uint32_t par) {
  asm volatile("{\n.reg .b64 x, y;\n.reg .b128 z;\nmov.b64 x, {%1,%2};\nmov.b64 y, {%3,%4};\nmov.b128 z, {x, y};\nst.relaxed.gpu.global.b128 [%0], z;\n}"
               ::"l"(p), "r"((a & ~1u) | par), "r"(b), "r"(c), "r"(d) : "memory");
}
__device__ __forceinline__ uint4 lds128(uint32_t a) { uint4 v; asm volatile("ld.shared.v4.u32 {%0,%1,%2,%3}, [%4];" : "=r"(v.x), "=r"(v.y), "=r"(v.z), "=r"(v.w) : "r"(a)); return v; }
__device__ __forceinline__ float4 lds128f(uint32_t a) { float4 v; asm volatile("ld.shared.v4.f32 {%0,%1,%2,%3}, [%4];" : "=f"(v.x), "=f"(v.y), "=f"(v.z), "=f"(v.w) : "r"(a)); return v; }
__device__ __forceinline__ float4 lds128v(uint32_t a) { float4 v; asm volatile("ld.volatile.shared.v4.f32 {%0,%1,%2,%3}, [%4];" : "=f"(v.x), "=f"(v.y), "=f"(v.z), "=f"(v.w) : "r"(a) : "memory"); return v; }
__device__ __forceinline__ float lds32v(uint32_t a) { float v; asm volatile("ld.volatile.shared.f32 %0, [%1];" : "=f"(v) : "r"(a) : "memory"); return v; }
__device__ __forceinline__ float2 lds64f(uint32_t a) { float2 v; asm volatile("ld.shared.v2.f32 {%0,%1}, [%2];" : "=f"(v.x), "=f"(v.y) : "r"(a)); return v; }
__device__ __forceinline__ uint32_t lds32(uint32_t a) { uint32_t v; asm volatile("ld.shared.u32 %0, [%1];" : "=r"(v) : "r"(a)); return v; }
__device__ __forceinline__ void sts128(uint32_t a, uint32_t x, uint32_t y, uint32_t z, uint32_t w) { asm volatile("st.shared.v4.u32 [%0], {%1,%2,%3,%4};" ::"r"(a), "r"(x), "r"(y), "r"(z), "r"(w) : "memory"); }
__device__ __forceinline__ void sts128f(uint32_t a, float x, float y, float z, float w) { asm volatile("st.shared.v4.f32 [%0], {%1,%2,%3,%4};" ::"r"(a), "f"(x), "f"(y), "f"(z), "f"(w) : "memory"); }
__device__ __forceinline__ void sts32(uint32_t a, uint32_t x) { asm volatile("st.shared.u32 [%0], %1;" ::"r"(a), "r"(x) : "memory"); }
__device__ __forceinline__ void stsm4(uint32_t a, uint32_t r0, uint32_t r1, uint32_t r2, uint32_t r3) {
  asm volatile("stmatrix.sync.aligned.m8n8.x4.shared.b16 [%0], {%1,%2,%3,%4};" ::"r"(a), "r"(r0), "r"(r1), "r"(r2), "r"(r3) : "memory");
}
__device__ __forceinline__ uint4 ldsm4(uint32_t a) {
  uint4 v; asm volatile("ldmatrix.sync.aligned.m8n8.x4.shared.b16 {%0,%1,%2,%3}, [%4];" : "=r"(v.x), "=r"(v.y), "=r"(v.z), "=r"(v.w) : "r"(a) : "memory"); return v;
}
__device__ __forceinline__ uint32_t pack(float lo, float hi) { uint32_t r; asm("cvt.rn.bf16x2.f32 %0, %1, %2;" : "=r"(r) : "f"(hi), "f"(lo)); return r; }
__device__ __forceinline__ float bf_lo(uint32_t w) { return __uint_as_float(w << 16); }
__device__ __forceinline__ float bf_hi(uint32_t w) { return __uint_as_float(w & 0xffff0000u); }
__device__ __forceinline__ float bf_round(float x) { return bf_lo(pack(x, x)); }
__device__ __forceinline__ float ex2(float x) { float v; asm("ex2.approx.ftz.f32 %0, %1;" : "=f"(v) : "f"(x)); return v; }
__device__ __forceinline__ float rcp(float x) { float v; asm("rcp.approx.ftz.f32 %0, %1;" : "=f"(v) : "f"(x)); return v; }
__device__ __forceinline__ float addsat(float a, float b) { float v; asm("add.sat.f32 %0, %1, %2;" : "=f"(v) : "f"(a), "f"(b)); return v; }
__device__ __forceinline__ float phi2(float a) { return fmaf(fmaxf(a, 0.f), LN2, addsat(ex2(a), 1e-6f)); }
__device__ __forceinline__ uint32_t ln_bf16x2(uint32_t x, uint32_t m, uint32_t hi, uint32_t lo) {
  uint32_t o;
  asm("{\n.reg .b32 d, e;\nsub.rn.bf16x2 d, %1, %2;\nmul.rn.bf16x2 e, d, %4;\nfma.rn.bf16x2 %0, d, %3, e;\n}" : "=r"(o) : "r"(x), "r"(m), "r"(hi), "r"(lo));
  return o;
}
__device__ __forceinline__ float key_score(uint32_t key) { uint32_t u = key >> 16; u = (u & 0x8000u) ? (u & 0x7fffu) : (~u & 0xffffu); return __uint_as_float(u << 16); }
__device__ __forceinline__ int key_token(uint32_t key) { return 2047 - (int)((key >> 5) & 2047u); }
__device__ __forceinline__ uint32_t bsel(uint32_t a, uint32_t b, uint32_t m) { uint32_t r; asm("lop3.b32 %0, %1, %2, %3, 0xd8;" : "=r"(r) : "r"(a), "r"(b), "r"(m)); return r; }
__device__ __forceinline__ uint32_t prmt(uint32_t a, uint32_t b, uint32_t c) { uint32_t r; asm("prmt.b32 %0, %1, %2, %3;" : "=r"(r) : "r"(a), "r"(b), "r"(c)); return r; }
__device__ __forceinline__ uint32_t tagf(float v, uint32_t par) { return (__float_as_uint(v) & ~1u) | par; }
__device__ __forceinline__ float xred(float a, float b, bool up, int o) { return (up ? b : a) + __shfl_xor_sync(0xffffffffu, up ? a : b, o); }

#define STAMP(id)
#define STAMP_IF(c, id)
#define STAMP2(i)
#define LITE 1

template <bool TRANS>
__device__ __forceinline__ void mainloop(float (&a0)[64], float (&a1)[64], int s, int ph, int handoff, int gate, bool leader) {
  uint32_t prev = 0;
#pragma unroll 1
  for (int kt = 0; kt < 16; kt++) {
    mbar_wait(B_FULL + 8 * s, ph);
    if (gate && kt == GATE_KT) nb_sync(gate, 256);
    const uint64_t dw = mkdesc(RING, 8192, 1024, 1) + s * (SLOT >> 4), dx = mkdesc(RING + 16384, 16, 1024, 1) + s * (SLOT >> 4);
    wg_fence();
#pragma unroll
    for (int j = 0; j < 4; j++) {
      if (TRANS) {
        wgmma_n128_ss<1, 0>(a0, dw + j * 128, dx + j * 2, 1);
        wgmma_n128_ss<1, 0>(a1, dw + j * 128 + 512, dx + j * 2, 1);
      } else {
        wgmma_n128_ss<0, 1>(a0, dx + j * 2, dw + j * 128, 1);
        wgmma_n128_ss<0, 1>(a1, dx + j * 2 + 512, dw + j * 128, 1);
      }
    }
    wg_commit();
    if (handoff && kt == 15) nb_arrive(handoff, 256);
    wg_wait<1>();
    if (prev && leader) mbar_arrive(prev);
    prev = B_EMPTY + 8 * s;
    if (++s == NST) { s = 0; ph ^= 1; }
  }
  wg_wait<0>();
  if (leader) mbar_arrive(prev);
  reg_fence(a0);
  reg_fence(a1);
}

__device__ __forceinline__ int out_kblock(int r, int tn) {
  const int q = r - 2, half = q >= 7, pi = q - 7 * half;
  return r < 2 ? 2 * tn + r : 2 * (pi + (pi >= tn)) + half;
}

struct Params {
  const char *x, *wqkv, *w_r, *wg, *wu, *wd;
  CUtensorMap m_wqkv, m_x, m_xs, m_o, m_os, m_wo, m_gu, m_down, m_out;
};

template <bool BY_SMID>
__global__ void __launch_bounds__(512, 1) fused_kernel(const __grid_constant__ Params mp) {
  extern __shared__ __align__(1024) uint8_t smem_raw[];
#define CK(i)
  CK(0);
  uint32_t ck0 = 0;
  if (ALIGN) asm volatile("mov.u32 %0, %%clock;" : "=r"(ck0));
  const int tid = threadIdx.x, lane = tid & 31;
  const int w = __shfl_sync(0xffffffffu, tid >> 5, 0);
  int bid = blockIdx.x;
  if (BY_SMID) {
    uint32_t sm;
    asm volatile("mov.u32 %0, %%smid;" : "=r"(sm));
    const uint32_t p = sm >> 1, q = ((p - 32) * 37) >> 8;
    const uint32_t gpc = p < 32 ? p & 7 : p < 60 ? p - 31 - 7 * q : 0, tpc = p < 32 ? p >> 3 : p < 60 ? 4 + q : p - 58;
    bid = (p >> 1) == 30 ? 128 + ((0x9cu >> (2 * (sm & 3))) & 3) : ((0x75143620u >> (4 * gpc)) & 7) * 16 + tpc * 2 + (sm & 1);
  }
  const int tn = (bid & 3) + 4 * (bid >> 6), tm = (bid >> 2) & 15;

  CK(1);
  if (w == 0) {
#pragma unroll 1
    for (int s = 0; s < NST; s++) {
      asm volatile(ELECT "@p mbarrier.init.shared::cta.b64 [%0], 1;\n}" ::"r"(B_FULL + 8 * s) : "memory");
      if (bid < 128) {
        e_expect(B_FULL + 8 * s, 32768);
        e_tma2d(RING + s * SLOT + 16384, &mp.m_x, s * 64, tm * 128, B_FULL + 8 * s);
        e_tma3d(RING + s * SLOT, &mp.m_wqkv, s * 64, 16 + 2 * tn, B_FULL + 8 * s);
      }
      if (s == 0) CK(2);
    }
  }
  if (w == 1) e_pfmap(&mp.m_wqkv);
  if (w == 2) e_pfmap(&mp.m_xs);
  if (w >= 4) {
#pragma unroll 1
    for (uint32_t b = MISC + 8 * (w + 1); b < MISC + 8 * NBAR; b += 96)
      asm volatile(ELECT "@p mbarrier.init.shared::cta.b64 [%0], %1;\n}" ::"r"(b), "r"(b == B_CSDN ? 4 : 1) : "memory");
    if (w == 15) sts32(S_NCAND, 0);
  }
  CK(3);
  asm volatile("fence.mbarrier_init.release.cluster;" ::: "memory");
  __syncthreads();

  auto front = [&](int i0, int i1) {
#pragma unroll 1
    for (int i = i0; i < i1; i++) {
      const int c = (XS_ORD >> (4 * i)) & 3;
      if (i >= XS_FLY) mbar_wait(B_XS + 8 * (i - XS_FLY), 0);
      if (c == (tm >> 2)) {
        e_expect(B_WK, 16384);
        e_tma3d(FR, &mp.m_wqkv, tm * 64, 16 + 2 * tn, B_WK);
      }
      e_expect(B_XS + 8 * i, 8192);
      e_tma2d(STG + i * 8192, &mp.m_xs, c * 256, tm * 128 + tn * 16, B_XS + 8 * i);
    }
  };
  if (XS_EARLY && w == 5 && bid < 128) front(0, XS_EARLY);

  if (bid >= 128) {
    const int h0 = bid == 128 ? 14 : bid - 129, hs = bid == 128 ? 1 : 3, h1 = bid == 128 ? 16 : 14;
    if (w == 12) {
      int s = 0, ph = 1;
      if (bid == 128) mbar_wait(B_SEL, 0);
      else if (H_DELAY) __nanosleep(H_DELAY);
#pragma unroll 1
      for (int h = h0; h < h1; h += hs) {
        const int c = 2 * h + (h & 8) * 2;
#pragma unroll 1
        for (int kt = 0; kt < 16; kt += 2) {
          mbar_wait(B_EMPTY + 8 * s, ph);
          e_expect(B_FULL + 8 * s, 32768);
          e_tma3d(RING + s * SLOT, &mp.m_wqkv, kt * 64, c, B_FULL + 8 * s);
          e_tma3d(RING + s * SLOT + 16384, &mp.m_wqkv, kt * 64 + 64, c, B_FULL + 8 * s);
          if (++s == HST) { s = 0; ph ^= 1; }
        }
      }
    } else if (w < 4) {
      const uint32_t par = (ld_relaxed(&g_epoch) + 1) & 1u;
      sts32(S_ONES + tid * 4, 0x3f803f80u);
      fence_async_smem();
      nb_sync(NB_WG0, 128);
      int s = 0, ph = 0;
#pragma unroll 1
      for (int h = h0; h < h1; h += hs) {
        float c[4][4];
#pragma unroll
        for (int i = 0; i < 4; i++) reg_zero(c[i]);
        uint32_t prev = 0;
#pragma unroll 1
        for (int kt = 0; kt < 8; kt++) {
          mbar_wait(B_FULL + 8 * s, ph);
          const uint64_t dw = mkdesc(RING, 8192, 1024, 1) + s * (SLOT >> 4);
          wg_fence();
#pragma unroll
          for (int j = 0; j < 16; j++) wgmma_n8_ss<1, 0>(c[j & 3], dw + (j & 3) * 512 + (j >> 2) * 128, mkdesc(S_ONES, 128, 128, 0), 1);
          wg_commit();
          wg_wait<1>();
          if (prev && tid == 0) mbar_arrive(prev);
          prev = B_EMPTY + 8 * s;
          if (++s == HST) { s = 0; ph ^= 1; }
        }
        wg_wait<0>();
        if (tid == 0) mbar_arrive(prev);
#pragma unroll
        for (int i = 0; i < 4; i++) reg_fence(c[i]);
        const bool u2 = lane & 2, u1 = lane & 1;
        const float lo = u2 ? c[1][0] + c[3][0] : c[0][0] + c[2][0], hi = u2 ? c[1][2] + c[3][2] : c[0][2] + c[2][2];
        st_relaxed(g_csum + h * 128 + (lane & 2) * 32 + w * 16 + (lane & 1) * 8 + (lane >> 2), tagf(u1 ? hi : lo, par));
        STAMP_IF(tid == 0, h >= 8 ? 6 : 30);
      }
    } else if (w < 12 && bid == 128) {
      const int t = tid - 128, j = w - 4;
      const uint32_t ep = ld_relaxed(&g_epoch) + 1;
      uint32_t kk[16];
      poll_keys(kk, g_keys + t * 2, ep, 31u);
      const uint32_t k[8] = {kk[0], kk[2], kk[4], kk[6], kk[8], kk[10], kk[12], kk[14]};
      STAMP_IF(t == 0, 42);
      const uint32_t m = __reduce_max_sync(0xffffffffu, max(max(max(k[0], k[1]), max(k[2], k[3])), max(max(k[4], k[5]), max(k[6], k[7]))));
      if (lane == 0) sts32(S_WMAX + j * 4, m);
      nb_sync(NB_WG1, 256);
      const uint32_t T = __reduce_min_sync(0xffffffffu, lds32(S_WMAX + (lane & 7) * 4));
      uint32_t cnt = 0;
#pragma unroll
      for (int i = 0; i < 8; i++) cnt += k[i] >= T;
      if (cnt) {
        uint32_t pos;
        asm volatile("atom.shared.add.u32 %0, [%1], %2;" : "=r"(pos) : "r"(S_NCAND), "r"(cnt * 4) : "memory");
#pragma unroll
        for (int i = 0; i < 8; i++)
          if (k[i] >= T) { sts32(AUX + pos, k[i]); pos += 4; }
      }
      nb_sync(NB_WG1, 256);
      const uint32_t n4 = lds32(S_NCAND);
#pragma unroll 1
      for (uint32_t i = j * 4; i < n4; i += 32) {
        const uint32_t key = lds32(AUX + i);
        uint32_t rank = 0;
#pragma unroll 1
        for (uint32_t q = lane * 4; q < n4 + lane * 4; q += 128) rank += __popc(__ballot_sync(0xffffffffu, q < n4 && lds32(AUX + q) > key));
        if (rank < 8) sts32(S_SEL + rank * 4, key);
      }
      fence_async_smem();
      nb_sync(NB_WG1, 256);
      STAMP_IF(t == 0, 43);
      const uint32_t key = lds32(S_SEL + j * 4);
      const int tok = key_token(key);
      uint4 v[4];
#pragma unroll
      for (int q = 0; q < 4; q++) v[q] = __ldg(reinterpret_cast<const uint4*>(mp.x + tok * 2048) + q * 32 + lane);
      const uint32_t st = ld_relaxed(&g_keys[tok].y);
      const float rinv = rcp(bf_lo(st)), rhi = bf_round(rinv);
      const uint32_t m2 = __byte_perm(st, 0, 0x3232), hi = pack(rhi, rhi), lo = pack(rinv - rhi, rinv - rhi);
#pragma unroll
      for (int q = 0; q < 4; q++)
        *reinterpret_cast<uint4*>(g_xsel + (q * 8 + (lane >> 2)) * 128 + j * 16 + (((lane & 3) ^ (j >> 1)) << 2)) =
            make_uint4(ln_bf16x2(v[q].x, m2, hi, lo), ln_bf16x2(v[q].y, m2, hi, lo), ln_bf16x2(v[q].z, m2, hi, lo), ln_bf16x2(v[q].w, m2, hi, lo));
      if (lane == 0) g_xsel[4096 + j] = key;
      fence_async_glob();
      nb_sync(NB_WG1, 256);
      STAMP_IF(t == 0, 44);
      if (j == 0) { e_release(H_R, 0); e_arrive(B_SEL); }
      STAMP_IF(t == 0, 45);
    }
  } else if (w >= 12) {
    asm volatile("setmaxnreg.dec.sync.aligned.u32 32;");
    if (w == 12) {
      int s = 0, ph = 0;
#pragma unroll 1
      for (int it = NST; it < 48; it++) {
        const int c = (it < 32 ? (it & 16) + 16 : 0) + 2 * tn;
        mbar_wait(B_EMPTY + 8 * s, ph);
        e_expect(B_FULL + 8 * s, 32768);
        e_tma3d(RING + s * SLOT, &mp.m_wqkv, (it & 15) * 64, c, B_FULL + 8 * s);
        e_tma2d(RING + s * SLOT + 16384, &mp.m_x, (it & 15) * 64, tm * 128, B_FULL + 8 * s);
        if (it >= NST) STAMP2(it - NST);
        if (++s == NST) { s = 0; ph ^= 1; }
      }
#pragma unroll 1
      for (int r = 0; r < 16; r++) {
        const int kb = out_kblock(r, tn);
        mbar_wait(B_EMPTY + 8 * s, ph);
        e_expect(B_FULL + 8 * s, r < 2 ? 16384 : 32768);
        e_tma3d(RING + s * SLOT, &mp.m_wo, kb * 64, 2 * tn, B_FULL + 8 * s);
        if (r < 2) {
          if (r == 0) e_expect(B_XRES, 32768);
          e_tma2d(RING + s * SLOT + 16384, &mp.m_x, kb * 64, tm * 128, B_XRES);
        }
        STAMP2(r + 48 - NST);
        if (++s == NST) { s = 0; ph ^= 1; }
      }
    } else if (w == 13) {
      if (XS_EARLY < XS_FLY) mbar_wait(B_FULL + 8 * XS_GO, 0);
      front(XS_EARLY, 4);
      {
        const char* pd = mp.wd + (bid & 15) * 128 + ((bid >> 4) * 448 + lane) * 2048;
        mbar_wait(B_XS + 24, 0);
        __nanosleep(PF_WAIT);
#pragma unroll 1
        for (int i = 0; i < 14; i++, pd += 65536) {
          if (PF_GAP) asm volatile("prefetch.global.L2 [%0];" ::"l"(pd));
          if (PF_GAP) __nanosleep(PF_GAP);
        }
      }
      nb_sync(NB_Z, 160);
      const uint32_t ep = lds32(S_EPOCH);
      {
        float z[4] = {0.f, 0.f, 0.f, 0.f};
        e_signal(H_Z + tn, tm);
        await(H_Z + tn, 0xffffu, ep);
#pragma unroll 1
        for (int i = 0; i < 4; i++) {
          uint32_t p[16];
          poll_z(p, g_z + i * 4096 + tn * 128 + lane * 4, ep, 1u);
#pragma unroll
          for (int q = 0; q < 4; q++) z[q] += (__uint_as_float(p[q]) + __uint_as_float(p[4 + q])) + (__uint_as_float(p[8 + q]) + __uint_as_float(p[12 + q]));
        }
        const uint32_t z01 = pack(z[0], z[1]), z23 = pack(z[2], z[3]);
#pragma unroll
        for (int i = 0; i < 4; i++) {
          const int n = 2 * i + (lane >> 4);
          asm volatile("st.shared.v2.u32 [%0], {%1,%2};" ::"r"(KVB_Z + n * 128 + ((((lane >> 1) & 7) ^ n) << 4) + (lane & 1) * 8), "r"(z01), "r"(z23) : "memory");
        }
        fence_async_smem();
        nb_arrive(NB_KVB, 288);
        STAMP_IF(lane == 0, 46);
      }
      nb_sync(NB_Q0, 192);
      e_store2d(&mp.m_os, tn * 128, tm * 128, STG);
      nb_sync(NB_OWN0, 288);
      e_store2d(&mp.m_os, tn * 128, tm * 128 + 64, STG + 8192);
      bulk_wait_read();
      e_signal(H_O + tm, 2 * tn);
      STAMP_IF(lane == 0, 4);
      nb_sync(NB_H1, 160);
      e_store2d(&mp.m_os, tn * 128 + 64, tm * 128, STG + 16384);
      e_store2d(&mp.m_os, tn * 128 + 64, tm * 128 + 64, STG + 24576);
      bulk_wait_read();
      e_signal(H_O + tm, 2 * tn + 1);
      STAMP_IF(lane == 0, 5);
#pragma unroll 1
      for (int i = 4; i < 14; i++) {
        const int q = (i + 2) >> 2;
        if (i == 4 || (i & 3) == 2) {
          if (i > 4) mbar_wait(B_OWN + 8 * (q - 2), 0);
          e_expect(B_DR + 8 * q, i == 4 ? 8192 : 16384);
        }
        e_tma2d_ef((i < 6 ? AUX - 16384 : STG - 24576) + i * 4096, &mp.m_down, (bid & 15) * 64, (bid >> 4) * 448 + i * 32, B_DR + 8 * q, EVICT_FIRST);
        if (DN_GAP) __nanosleep(DN_GAP);
      }
    } else if (w == 14) {
      e_pfmap(&mp.m_gu); e_pfmap(&mp.m_o); e_pfmap(&mp.m_os); e_pfmap(&mp.m_wo); e_pfmap(&mp.m_down); e_pfmap(&mp.m_out);
      const uint32_t ep = ld_relaxed(&g_epoch) + 1;
      nb_sync(NB_FDONE, 416);
      {
        uint32_t c[4];
        poll_quad(c, g_csum + tn * 128 + lane * 4, ep, 1u);
        sts128(S_CSQ + lane * 16, c[0], c[1], c[2], c[3]);
        nb_arrive(NB_CSQ, 160);
        poll_quad(c, g_csum + 1024 + tn * 128 + lane * 4, ep, 1u);
        sts128(S_CSV + lane * 16, c[0], c[1], c[2], c[3]);
        __syncwarp();
        e_arrive(B_CSV);
      }
      nb_sync(NB_Q0, 192);
      uint32_t ready = 0;
      int s = 0, ph = 1;
#pragma unroll 1
      for (int r = 2; r < 16; r++) {
        const int kb = out_kblock(r, tn);
        if (!((ready >> kb) & 1)) {
          uint32_t f[1];
          poll0(f, g_sig + (H_O + tm) * 32, 0u - (ep & 1u), 1u << kb);
          ready = f[0] ^ ((ep & 1u) - 1u);
        }
        mbar_wait(B_EMPTY + 8 * s, ph);
        e_tma2d(RING + s * SLOT + 16384, &mp.m_o, kb * 64, tm * 128, B_FULL + 8 * s);
        STAMP_IF(lane == 0 && r == 2, 2);
        STAMP_IF(lane == 0 && r == 9, 3);
        if (++s == NST) { s = 0; ph ^= 1; }
      }
    } else {
      uint32_t nsm = 132;
      if (BY_SMID) asm volatile("mov.u32 %0, %%nsmid;" : "=r"(nsm));
      asm volatile("{\n.reg .pred q;\nsetp.eq.u32 q, %0, 1156;\n@q bra LOK;\ntrap;\nLOK:\n}" ::"r"((uint32_t)__cvta_generic_to_shared(smem_raw) + nsm));
      const uint32_t ep = ld_relaxed(&g_epoch) + 1;
      mbar_wait(B_CSDN, 0);
#pragma unroll 1
      for (int n = 0; n < 5; n++) {
        __nanosleep(FFN_GAP);
        if (bid < 112) {
          e_expect(B_FR + 8 * n, 4608);
          e_tma3d_ef(GR + n * 4096, &mp.m_gu, bid * 32, n * 32, B_FR + 8 * n, EVICT_FIRST);
        }
      }
      uint32_t f[1];
      poll1(f, g_sig + H_R * 32, ep, 1u);
      fence_acq();
      fence_async_glob();
      if (bid < 112) {
#pragma unroll
        for (int n = 0; n < 5; n++) e_load(HOP + n * 512, g_xsel + n * 128, 512, B_FR + 8 * n);
      }
      e_expect(B_SEL, 32);
      e_load(S_SEL, g_xsel + 4096, 32, B_SEL);
      if (bid < 112) {
        int s = 0, ph = 0;
#pragma unroll 1
        for (int n = 5; n < 32; n++) {
          mbar_wait(B_FE + 8 * s, ph);
          e_expect(B_FR + 8 * s, 4608);
          e_tma3d_ef(GR + s * 4096, &mp.m_gu, bid * 32 , n * 32 , B_FR + 8 * s, EVICT_FIRST);
          e_load(HOP + s * 512, g_xsel + n * 128, 512, B_FR + 8 * s);
          STAMP2(64 + n);
          if (++s == 5) { s = 0; ph ^= 1; }
        }
      }
      e_expect(B_DR, 16384);
#pragma unroll 1
      for (int i = 1; i < 5; i++) {
        if (bid < 112) mbar_wait(B_FE + 8 * ((i & 3) + 1), i != 4);
        e_tma2d_ef(FR + (i & 3) * 4096, &mp.m_down, (bid & 15) * 64, (bid >> 4) * 448 + (i & 3) * 32, B_DR, EVICT_FIRST);
      }
    }
  } else if (w >= 8) {
    asm volatile("setmaxnreg.dec.sync.aligned.u32 56;");
    const int t = tid - 256, ww = w - 8;
    const uint32_t ep = ld_relaxed(&g_epoch) + 1, par = ep & 1u;
    {
      const int r0 = (lane >> 3) + (lane & 4);
      const uint32_t a = FR + (ww >> 1) * 8192 + r0 * 128 + ((((ww & 1) * 4 + (lane & 3)) ^ r0) << 4);
      float c[8];
      reg_zero(c);
      mbar_wait(B_WK, 0);
#pragma unroll 2
      for (int i = 0; i < 8; i++) {
        const uint4 v = lds128(a + i * 1024);
        c[0] += bf_lo(v.x); c[1] += bf_hi(v.x); c[2] += bf_lo(v.y); c[3] += bf_hi(v.y);
        c[4] += bf_lo(v.z); c[5] += bf_hi(v.z); c[6] += bf_lo(v.w); c[7] += bf_hi(v.w);
      }
      const bool u16 = lane & 16, u8 = lane & 8, u4 = lane & 4;
      const float d0 = xred(c[0], c[4], u16, 16), d1 = xred(c[1], c[5], u16, 16), d2 = xred(c[2], c[6], u16, 16), d3 = xred(c[3], c[7], u16, 16);
      fence_async_smem();
      e_arrive(B_CSDN);
      const float sum = xred(xred(d0, d2, u8, 8), xred(d1, d3, u8, 8), u4, 4);
      st_relaxed(g_csum + (2 + tm) * 1024 + tn * 128 + ww * 32 + (lane & 3) * 8 + (lane >> 2), tagf(sum, par));
      STAMP_IF(t == 0, 8);
      nb_sync(NB_WG2, 128);
      if (ww == 0) { e_signal(H_CS + tn, tm); await(H_CS + tn, 0xffffu, ep); }
      nb_sync(NB_WG2, 128);
      uint32_t p[16];
      poll16(p, g_csum + 2048 + tn * 128 + t, par, 1u);
      float tot = 0.f;
#pragma unroll
      for (int i = 0; i < 16; i += 4) tot += (__uint_as_float(p[i]) + __uint_as_float(p[i + 1])) + (__uint_as_float(p[i + 2]) + __uint_as_float(p[i + 3]));
      sts32(S_CSK + t * 4, __float_as_uint(tot));
      nb_arrive(NB_FDONE, 416);
      STAMP_IF(t == 0, 9);
    }
    const int ks = bid >> 4, nt = bid & 15;
    float fa[4] = {0.f, 0.f, 0.f, 0.f};
    if (bid < 112) {
      int s = 0, ph = 0;
      uint32_t prev = 0;
#pragma unroll 1
      for (int n = 0; n < 32; n++) {
        mbar_wait(B_FR + 8 * s, ph);
        const uint64_t da = mkdesc(GR, 2048, 512, 2) + s * 256, db = mkdesc(HOP, 16, 512, 2) + s * 32;
        wg_fence();
        wgmma_n8_ss<1, 0>(fa, da, db, 1);
        wgmma_n8_ss<1, 0>(fa, da + 64, db + 2, 1);
        wg_commit();
        wg_wait<1>();
        if (prev && t == 0) mbar_arrive(prev);
        prev = B_FE + 8 * s;
        if (++s == 5) { s = 0; ph ^= 1; }
      }
      wg_wait<0>();
      reg_fence(fa);
      if (t == 0) mbar_arrive(prev);
      STAMP_IF(t == 0, 12);
      const bool isup = (ww >> 1) != (mp.wu < mp.wg);
      if (isup) sts128f(GR + (t & 63) * 16, fa[0], fa[1], fa[2], fa[3]);
      nb_sync(NB_WG2, 128);
      if (!isup) {
        const float4 u = lds128f(GR + (t & 63) * 16);
        const float uu[4] = {u.x, u.y, u.z, u.w};
        uint32_t* hp = g_h + bid * 256 + (lane & 3) * 64 + (ww & 1) * 16 + (lane >> 2);
#pragma unroll
        for (int i = 0; i < 4; i++) {
          const float g = fa[i], hv = g * rcp(1.f + ex2(-g * LOG2E)) * uu[i];
          st_relaxed(hp + (i & 1) * 32 + (i >> 1) * 8, __byte_perm(pack(hv, hv), ep, 0x3254));
        }
      }
      nb_sync(NB_WG2, 128);
      if (ww == 0) e_signal(H_H + bid / 14, bid % 14);
      reg_zero(fa);
    }
    {
      uint32_t v[28];
      if (ww == 0) await(H_H + ks, 0x3fffu, ep);
      nb_sync(NB_WG2, 128);
      poll7x4(v, g_h + ks * 3584 + t * 4, ep, 0xffffu);
#pragma unroll
      for (int q = 0; q < 7; q++)
        asm volatile("st.shared.v2.u32 [%0], {%1,%2};" ::"r"(HOP + q * 1024 + (t >> 3) * 64 + ((((t >> 1) & 3) ^ ((t >> 4) & 3)) << 4) + (t & 1) * 8),
                     "r"(__byte_perm(v[4 * q], v[4 * q + 1], 0x7632)), "r"(__byte_perm(v[4 * q + 2], v[4 * q + 3], 0x7632)) : "memory");
      fence_async_smem();
      nb_sync(NB_WG2, 128);
    }
    STAMP_IF(t == 0, 13);
#pragma unroll 1
    for (int i = 0; i < 14; i += 2) {
      mbar_wait(B_DR + 8 * (i < 4 ? 0 : (i + 2) >> 2), 0);
      const uint64_t da = mkdesc(0, 4096, 1024, 1) + ((i < 4 ? FR : i < 6 ? AUX - 16384 : STG - 24576) >> 4) + i * 256;
      const uint64_t db = mkdesc(HOP, 16, 512, 2) + i * 32;
      wg_fence();
#pragma unroll
      for (int q = 0; q < 4; q++) wgmma_n8_ss<1, 0>(fa, da + q * 128, db + (q >> 1) * 32 + (q & 1) * 2, 1);
      wg_commit();
    }
    wg_wait<0>();
    reg_fence(fa);
    nb_arrive(NB_ST, 256);
    STAMP_IF(t == 0, 14);
    {
      uint32_t* yp = g_yp + (nt * 8 + ks) * 512 + (lane & 3) * 128 + ww * 16 + (lane >> 2);
#pragma unroll
      for (int i = 0; i < 4; i++) st_relaxed(yp + (i & 1) * 64 + (i >> 1) * 8, tagf(fa[i], par));
    }
    nb_sync(NB_WG2, 128);
    if (ww == 0) e_signal(H_Y + (nt >> 1), (nt & 1) * 8 + ks);
    mbar_wait(B_SEL, 0);
    const uint32_t mykey = lds32(S_SEL + (lane & 7) * 4);
    const uint32_t inmask = __ballot_sync(0xffffffffu, (key_token(mykey) >> 7) == tm) & 0xffu;
    if (inmask) {
      sts128(FR + t * 16, 0u, 0u, 0u, 0u);
      if (ww == 0) await(H_Y + tn, 0xffffu, ep);
      nb_sync(NB_WG2, 128);
      const float sg = rcp(1.f + ex2(-key_score(mykey) * LOG2E));
#pragma unroll 1
      for (int n = ww + 1; n <= __popc(inmask); n += 4) {
        const int j = __fns(inmask, 0, n);
        uint32_t p[32];
        poll8x4(p, g_yp + (tn * 2 + (lane >> 4)) * 4096 + j * 64 + (lane & 15) * 4, par, 1u);
        float y[4];
        const float sj = __shfl_sync(0xffffffffu, sg, j);
#pragma unroll
        for (int i = 0; i < 4; i++)
          y[i] = sj * (((__uint_as_float(p[i]) + __uint_as_float(p[4 + i])) + (__uint_as_float(p[8 + i]) + __uint_as_float(p[12 + i]))) +
                       ((__uint_as_float(p[16 + i]) + __uint_as_float(p[20 + i])) + (__uint_as_float(p[24 + i]) + __uint_as_float(p[28 + i]))));
        asm volatile("st.shared.v2.u32 [%0], {%1,%2};" ::"r"(FR + (lane >> 4) * 1024 + j * 128 + ((((lane >> 1) & 7) ^ j) << 4) + (lane & 1) * 8),
                     "r"(pack(y[0], y[1])), "r"(pack(y[2], y[3])) : "memory");
      }
      fence_async_smem();
      nb_arrive(NB_Y, 256);
    }
    STAMP_IF(t == 0, 15);
  } else if (w >= 4) {
    asm volatile("setmaxnreg.inc.sync.aligned.u32 208;");
    const int t = tid - 128, ww = w - 4, g = lane >> 2, t4 = lane & 3;
    const bool leader = t == 0;
    const uint32_t ep = ld_relaxed(&g_epoch) + 1, par = ep & 1u;
    {
      const uint4* wp = reinterpret_cast<const uint4*>(mp.w_r) + lane;
      uint4 w0 = __ldg(wp + (XS_ORD & 3) * 32), w1 = __ldg(wp + ((XS_ORD >> 4) & 3) * 32), w2 = __ldg(wp + ((XS_ORD >> 8) & 3) * 32), w3 = __ldg(wp + ((XS_ORD >> 12) & 3) * 32);
      if (leader) sts32(S_EPOCH, ep);
      if (KV_DIRECT && lane < 8) st_unit(g_kv + tn * 512 + tm * 32 + ww * 8 + lane, 0u, 0u, 0u, 0u, par ^ 1u);
      float s[4] = {0.f, 0.f, 0.f, 0.f}, q[4] = {0.f, 0.f, 0.f, 0.f}, d[4] = {0.f, 0.f, 0.f, 0.f}, wsum = 0.f;
#pragma unroll 1
      for (int c = 0; c < 4; c++) {
        const float wr[8] = {bf_lo(w0.x), bf_hi(w0.x), bf_lo(w0.y), bf_hi(w0.y), bf_lo(w0.z), bf_hi(w0.z), bf_lo(w0.w), bf_hi(w0.w)};
        w0 = w1; w1 = w2; w2 = w3;
        wsum += ((wr[0] + wr[1]) + (wr[2] + wr[3])) + ((wr[4] + wr[5]) + (wr[6] + wr[7]));
        mbar_wait(B_XS + 8 * c, 0);
#pragma unroll
        for (int r = 0; r < 4; r++) {
          const uint4 v = lds128(STG + c * 8192 + (ww * 4 + r) * 512 + lane * 16);
          const uint32_t xw[4] = {v.x, v.y, v.z, v.w};
#pragma unroll
          for (int i = 0; i < 4; i++) {
            const uint32_t dep = __float_as_uint(q[i ? r : (r + 3) & 3]);
            const float lo = POLITE ? __uint_as_float(prmt(xw[i], dep, 0x10ff)) : bf_lo(xw[i]), hi = POLITE ? __uint_as_float(prmt(xw[i], dep, 0x32ff)) : bf_hi(xw[i]);
            s[r] += lo; q[r] = fmaf(lo, lo, q[r]); d[r] = fmaf(lo, wr[2 * i], d[r]);
            s[r] += hi; q[r] = fmaf(hi, hi, q[r]); d[r] = fmaf(hi, wr[2 * i + 1], d[r]);
          }
        }
      }
      STAMP_IF(leader, 16);
      const bool u16 = lane & 16, u8 = lane & 8, u4 = lane & 4, u2 = lane & 2;
      const float s1 = xred(xred(s[0], s[2], u16, 16), xred(s[1], s[3], u16, 16), u8, 8);
      const float q1 = xred(xred(q[0], q[2], u16, 16), xred(q[1], q[3], u16, 16), u8, 8);
      const float d1 = xred(xred(d[0], d[2], u16, 16), xred(d[1], d[3], u16, 16), u8, 8);
      wsum += __shfl_xor_sync(0xffffffffu, wsum, 16);
      wsum += __shfl_xor_sync(0xffffffffu, wsum, 8);
      float tot = xred(xred(s1, d1, u4, 4), xred(q1, wsum, u4, 4), u2, 2);
      tot += __shfl_xor_sync(0xffffffffu, tot, 1);
      const float qq = __shfl_down_sync(0xffffffffu, tot, 2), dd = __shfl_down_sync(0xffffffffu, tot, 4), ws = __shfl_down_sync(0xffffffffu, tot, 6);
      if ((lane & 7) == 0) {
        const float mean = tot * (1.f / 1024.f);
        const float var = fmaxf(fmaf(-mean, mean, qq * (1.f / 1024.f)), 0.f);
        float sd;
        asm("sqrt.approx.ftz.f32 %0, %1;" : "=f"(sd) : "f"(bf_round(bf_round(var) + 1e-5f)));
        const uint32_t ms = pack(sd, mean);
        const int row = tm * 128 + tn * 16 + ww * 4 + (lane >> 3);
        const uint32_t rbits = pack(0.f, fmaf(-bf_hi(ms), ws, dd) * rcp(bf_lo(ms)));
        const uint32_t key = (rbits ^ (((int)rbits >> 31 & 0x7fff0000u) | 0x80000000u)) | ((2047 - row) << 5) | (ep & 31u);
        asm volatile("{\n.reg .b64 x;\nmov.b64 x, {%1,%2};\nst.relaxed.gpu.global.b64 [%0], x;\n}" ::"l"(g_keys + row), "r"(key), "r"(ms) : "memory");
      }
      STAMP_IF(leader, 17);
      __nanosleep(400);
      uint32_t st[2];
      poll_pair(st, g_keys + tm * 128 + t, ep, 31u);
      asm volatile("st.shared.v2.f32 [%0], {%1,%2};" ::"r"(S_KSTAT + t * 8), "f"(bf_hi(st[1])), "f"(rcp(bf_lo(st[1])) * LOG2E) : "memory");
      nb_arrive(NB_FDONE, 416);
      STAMP_IF(leader, 10);
    }
    float a0[64], a1[64];
    reg_zero(a0); reg_zero(a1); reg_fence(a0); reg_fence(a1);
    STAMP_IF(leader, 18);
    nb_sync(NB_KV, 256);
    mainloop<true>(a0, a1, 1, 1, NB_VQ, 0, leader);
    STAMP_IF(leader, 19);
    {
      uint32_t f0[32], f1[32];
#pragma unroll
      for (int i = 0; i < 32; i++) { f0[i] = pack(a0[2 * i], a0[2 * i + 1]); f1[i] = pack(a1[2 * i], a1[2 * i + 1]); }
      float c0[32], c1[32];
      reg_zero(c0); reg_zero(c1);
      nb_sync(NB_PK, 256);
      constexpr uint64_t db = mkdesc(STG, 16, 1024, 1);
      wg_fence();
#pragma unroll
      for (int k = 0; k < 8; k++) {
        wgmma_n64_rs<0>(c0, f0[4 * k], f0[4 * k + 1], f0[4 * k + 2], f0[4 * k + 3], db + (k >> 2) * 1024 + (k & 3) * 2, k != 0);
        wgmma_n64_rs<0>(c1, f1[4 * k], f1[4 * k + 1], f1[4 * k + 2], f1[4 * k + 3], db + (k >> 2) * 1024 + (k & 3) * 2 + 512, k != 0);
        if (GATE_KT && k == GATE_K) nb_arrive(NB_KV, 256);
      }
      wg_commit();
      const bool hp = ww >> 1;
      float c[4];
      float2 tt[8];
#pragma unroll
      for (int i = 0; i < 8; i++) tt[i] = lds64f(S_CSK + ((i >> 2) * 64 + hp * 32 + (i & 3) * 8 + 2 * t4) * 4);
      mbar_wait(B_CSV, 0);
#pragma unroll
      for (int i = 0; i < 4; i++) c[i] = -__uint_as_float(lds32(S_CSV + ((i >> 1) * 64 + ww * 16 + (i & 1) * 8 + g) * 4));
      wg_wait<0>();
      reg_fence(c0);
      reg_fence(c1);
      STAMP_IF(leader, 20);
      uint4* pp = g_kvp + (tn * 16 + tm) * 512 + t;
      auto put = [&](int q, const float* d) {
        const float ca = c[q & 2], cb = c[q | 1];
        const float2 ta = tt[2 * q], tb = tt[2 * q + 1];
        st_unit(pp + q * 128, pack(fmaf(ca, ta.x, d[0]), fmaf(ca, ta.y, d[1])), pack(fmaf(cb, ta.x, d[2]), fmaf(cb, ta.y, d[3])),
                pack(fmaf(ca, tb.x, d[4]), fmaf(ca, tb.y, d[5])), pack(fmaf(cb, tb.x, d[6]), fmaf(cb, tb.y, d[7])), par);
      };
      if (!hp) { put(0, c0); put(1, c0 + 8); put(2, c1); put(3, c1 + 8); }
      else { put(0, c0 + 16); put(1, c0 + 24); put(2, c1 + 16); put(3, c1 + 24); }
      STAMP_IF(leader, 47);
      {
        uint32_t p[16];
        nb_sync(NB_WG1, 128);
        if (ww == 0) { e_signal(H_KVP + tn, tm); await(H_KVP + tn, 0xffffu, ep); }
        nb_sync(NB_WG1, 128);
        STAMP_IF(leader, 1);
        poll_kvp(p, g_kvp + (tn * 16 + (lane >> 3) * 4) * 512 + tm * 32 + ww * 8 + (lane & 7), par, 1u);
        float r[8];
#pragma unroll
        for (int i = 0; i < 4; i++) {
          r[2 * i] = (bf_lo(p[i]) + bf_lo(p[4 + i])) + (bf_lo(p[8 + i]) + bf_lo(p[12 + i]));
          r[2 * i + 1] = (bf_hi(p[i]) + bf_hi(p[4 + i])) + (bf_hi(p[8 + i]) + bf_hi(p[12 + i]));
        }
#pragma unroll
        for (int i = 0; i < 8; i++) r[i] += __shfl_xor_sync(0xffffffffu, r[i], 8);
#pragma unroll
        for (int i = 0; i < 8; i++) r[i] += __shfl_xor_sync(0xffffffffu, r[i], 16);
        if (lane < 8) st_unit(g_kv + tn * 512 + tm * 32 + ww * 8 + lane, pack(r[0], r[1]), pack(r[2], r[3]), pack(r[4], r[5]), pack(r[6], r[7]), par);
      }
      STAMP_IF(leader, 21);
    }
    const uint32_t sx = lane & 7, sc = lane >> 4;
    const uint32_t sa = STG + (ww * 16 + (lane & 15)) * 128;
    const uint32_t sw[4] = {sa + ((sc ^ sx) << 4), sa + (((2 + sc) ^ sx) << 4), sa + (((4 + sc) ^ sx) << 4), sa + (((6 + sc) ^ sx) << 4)};
    {
      uint32_t v[16];
      if (!KV_DIRECT) {
        nb_sync(NB_WG1, 128);
        if (ww == 0) { e_signal(H_KV + tn, tm); await(H_KV + tn, 0xffffu, ep); }
        nb_sync(NB_WG1, 128);
      } else {
        __nanosleep(KV_DIRECT);
      }
      STAMP_IF(leader, 7);
      poll_kv(v, g_kv + tn * 512 + t, par, 1u);
      STAMP_IF(leader, 23);
#pragma unroll
      for (int q = 0; q < 4; q++)
        stsm4((q < 2 ? KVB_P0 : KVB_P1) + ((ww & 1) * 16 + (lane & 15)) * 128 + ((((ww >> 1) * 4 + (q & 1) * 2 + sc) ^ sx) << 4),
              v[4 * q], v[4 * q + 1], v[4 * q + 2], v[4 * q + 3]);
      fence_async_smem();
      nb_arrive(NB_KVB, 288);
    }
    STAMP_IF(leader, 24);
    uint32_t oh[4];
    uint32_t inmask;
    {
      mbar_wait(B_SEL, 0);
      const int r0 = key_token(lds32(S_SEL + t4 * 8)) - tm * 128, r1 = key_token(lds32(S_SEL + t4 * 8 + 4)) - tm * 128;
#pragma unroll
      for (int i = 0; i < 4; i++) {
        const int row = (i >> 1) * 64 + ww * 16 + (i & 1) * 8 + g;
        oh[i] = (r0 == row ? 0x3f80u : 0u) | (r1 == row ? 0x3f800000u : 0u);
      }
      inmask = __ballot_sync(0xffffffffu, (unsigned)r0 < 128u || (unsigned)r1 < 128u);
    }
    uint32_t va[8];
#pragma unroll
    for (int i = 0; i < 8; i++) va[i] = RING + 16384 + sc * 8192 + (ww * 16 + (lane & 15)) * 128 + ((i ^ sx) << 4) + (lane >> 3) * 4;
    float ka[4];
    {
      float kb[4];
#pragma unroll
      for (int i = 0; i < 4; i++) {
        const float2 st = lds64f(S_KSTAT + ((i >> 1) * 64 + ww * 16 + (i & 1) * 8 + g) * 8);
        const float r = st.y * LN2;
        ka[i] = 1.f + r; kb[i] = -st.x * r;
      }
#pragma unroll
      for (int i = 0; i < 64; i++) { a0[i] = kb[(i >> 1) & 1]; a1[i] = kb[2 + ((i >> 1) & 1)]; }
      reg_fence(a0);
      reg_fence(a1);
    }
    {
      auto own = [&](int r) {
        nb_sync(NB_OWN0 + r, r ? 256 : 288);
        mbar_wait(B_FULL + 8 * (3 + r), 1);
        if (!LITE) STAMP_IF(leader, 25 + r);
        const uint64_t dw = mkdesc(RING + (3 + r) * SLOT, 8192, 1024, 1), dx = mkdesc(STG + r * 16384, 16, 1024, 1);
        wg_fence();
#pragma unroll
        for (int j = 0; j < 4; j++) {
          wgmma_n128_ss<0, 1>(a0, dx + j * 2, dw + j * 128, 1);
          wgmma_n128_ss<0, 1>(a1, dx + j * 2 + 512, dw + j * 128, 1);
        }
        wg_commit();
      };
      own(0);
      constexpr uint32_t XOFF = RING + 3 * SLOT + 16384 - STG;
      mbar_wait(B_XRES, 0);
      wg_wait<0>();
      reg_fence(a0);
      reg_fence(a1);
#pragma unroll
      for (int j = 0; j < 8; j++) {
        const uint4 v = ldsm4(sw[j & 3] + XOFF + (j >> 2) * SLOT), u = ldsm4(sw[j & 3] + XOFF + (j >> 2) * SLOT + 8192);
        const uint32_t vv[4] = {v.x, v.y, v.z, v.w}, uu[4] = {u.x, u.y, u.z, u.w};
#pragma unroll
        for (int i = 0; i < 4; i++) {
          a0[8 * j + 2 * i] = fmaf(bf_lo(vv[i]), ka[i & 1], a0[8 * j + 2 * i]);
          a0[8 * j + 2 * i + 1] = fmaf(bf_hi(vv[i]), ka[i & 1], a0[8 * j + 2 * i + 1]);
          a1[8 * j + 2 * i] = fmaf(bf_lo(uu[i]), ka[2 + (i & 1)], a1[8 * j + 2 * i]);
          a1[8 * j + 2 * i + 1] = fmaf(bf_hi(uu[i]), ka[2 + (i & 1)], a1[8 * j + 2 * i + 1]);
        }
        if (j == 7) {
          fence_async_smem();
          nb_sync(NB_WG1, 128);
          if (leader) { mbar_arrive(B_EMPTY + 24); mbar_arrive(B_OWN); }
        }
      }
      reg_fence(a0);
      reg_fence(a1);
      STAMP_IF(leader, 22);
      own(1);
      int s = 0, ph = 0;
      uint32_t prev = B_EMPTY + 32;
#pragma unroll 1
      for (int r = 2; r < 16; r++) {
        mbar_wait(B_FULL + 8 * s, ph);
        {
          uint32_t bad = 0;
#pragma unroll
          for (int i = 0; i < 8; i++) bad |= lds32(va[i] + s * SLOT) ^ par;
          if (__any_sync(0xffffffffu, bad & 1u)) {
            const uint4* src = reinterpret_cast<const uint4*>(g_o + (tm * 128 + sc * 64 + ww * 16 + (lane & 15)) * 1024 + out_kblock(r, tn) * 64);
#pragma unroll 1
            for (int i = 0; i < 8; i++) {
              uint32_t v[4];
              asm volatile("{\n.reg .b64 x, y;\n.reg .b128 z;\n.reg .pred p, q, h;\n.reg .u32 c, b;\nmov.u32 c, 0;\nsetp.ne.u32 h, %6, 0;\nLW:\n"
                           "ld.relaxed.gpu.global.b128 z, [%4];\nmov.b128 {x, y}, z;\nmov.b64 {%0,%1}, x;\nmov.b64 {%2,%3}, y;\n"
                           "selp.b64 x, y, x, h;\nshr.b64 x, x, %7;\ncvt.u32.u64 b, x;\nand.b32 b, b, 1;\nsetp.eq.u32 p, b, %5;\n"
                           "vote.sync.all.pred p, p, 0xffffffff;\n@p bra.uni LD;\nadd.u32 c, c, 1;\nsetp.lt.u32 q, c, 1000000;\n@q bra.uni LW;\ntrap;\nLD:\n}"
                           : "=&r"(v[0]), "=&r"(v[1]), "=&r"(v[2]), "=&r"(v[3]) : "l"(src + i), "r"(par), "r"(sc), "r"((lane & 8) * 4) : "memory");
              sts128(((va[0] & ~15u) ^ (i << 4)) + s * SLOT, v[0], v[1], v[2], v[3]);
            }
            fence_async_smem();
            __syncwarp();
          }
        }
        if (!LITE) STAMP_IF(leader && r == 2, 27);
        const uint64_t dw = mkdesc(RING, 8192, 1024, 1) + s * (SLOT >> 4), dx = mkdesc(RING + 16384, 16, 1024, 1) + s * (SLOT >> 4);
        wg_fence();
#pragma unroll
        for (int j = 0; j < 4; j++) {
          wgmma_n128_ss<0, 1>(a0, dx + j * 2, dw + j * 128, 1);
          wgmma_n128_ss<0, 1>(a1, dx + j * 2 + 512, dw + j * 128, 1);
        }
        wg_commit();
        wg_wait<1>();
        if (leader) { mbar_arrive(prev); if (r == 2) mbar_arrive(B_OWN + 8); }
        prev = B_EMPTY + 8 * s;
        if (++s == NST) { s = 0; ph ^= 1; }
      }
      if (inmask) {
        nb_sync(NB_Y, 256);
        wg_fence();
        wgmma_n128_rs<1>(a0, oh[0], oh[1], 0u, 0u, mkdesc(FR, 1024, 0, 1), 1);
        wgmma_n128_rs<1>(a1, oh[2], oh[3], 0u, 0u, mkdesc(FR, 1024, 0, 1), 1);
        wg_commit();
      }
      nb_sync(NB_ST, 256);
      wg_wait<0>();
      reg_fence(a0);
      reg_fence(a1);
    }
    STAMP_IF(leader, 28);
#pragma unroll
    for (int c = 0; c < 2; c++) {
#pragma unroll
      for (int j = 4 * c; j < 4 * c + 4; j++) {
        stsm4(sw[j & 3] + c * 16384, pack(a0[8 * j], a0[8 * j + 1]), pack(a0[8 * j + 2], a0[8 * j + 3]), pack(a0[8 * j + 4], a0[8 * j + 5]), pack(a0[8 * j + 6], a0[8 * j + 7]));
        stsm4(sw[j & 3] + c * 16384 + 8192, pack(a1[8 * j], a1[8 * j + 1]), pack(a1[8 * j + 2], a1[8 * j + 3]), pack(a1[8 * j + 4], a1[8 * j + 5]), pack(a1[8 * j + 6], a1[8 * j + 7]));
      }
      fence_async_smem();
      e_store2d(&mp.m_out, tn * 128 + c * 64, tm * 128 + ww * 16, STG + c * 16384 + ww * 2048);
      e_store2d(&mp.m_out, tn * 128 + c * 64, tm * 128 + 64 + ww * 16, STG + c * 16384 + 8192 + ww * 2048);
    }
    bulk_wait_read();
    if (bid == 0 && leader) st_relaxed(&g_epoch, ep);
    STAMP_IF(leader, 29);
  } else {
    asm volatile("setmaxnreg.inc.sync.aligned.u32 216;");
    const int g = lane >> 2, t4 = lane & 3;
    const bool leader = tid == 0;
    const uint32_t sx = lane & 7, sc = lane >> 4;
    const uint32_t sa = STG + (w * 16 + (lane & 15)) * 128;
    const uint32_t sw[4] = {sa + ((sc ^ sx) << 4), sa + (((2 + sc) ^ sx) << 4), sa + (((4 + sc) ^ sx) << 4), sa + (((6 + sc) ^ sx) << 4)};
    float a0[64], a1[64];
    reg_zero(a0); reg_zero(a1); reg_fence(a0); reg_fence(a1);
    if (ALIGN) { uint32_t now; do { asm volatile("mov.u32 %0, %%clock;" : "=r"(now)); } while ((int)(now - ck0) < ALIGN); }
    mainloop<true>(a0, a1, 0, 0, NB_KV, 0, leader);
    STAMP_IF(leader, 33);
    {
      nb_sync(NB_FDONE, 416);
      STAMP_IF(leader, 34);
      float c[4], z[4] = {0.f, 0.f, 0.f, 0.f}, tt[4] = {0.f, 0.f, 0.f, 0.f};
#pragma unroll
      for (int i = 0; i < 4; i++) c[i] = -__uint_as_float(lds32(S_CSK + ((i >> 1) * 64 + w * 16 + (i & 1) * 8 + g) * 4));
#pragma unroll
      for (int j = 0; j < 8; j++) {
        const float4 s0 = lds128v(S_KSTAT + (j * 16 + 2 * t4) * 8), s1 = lds128v(S_KSTAT + (j * 16 + 8 + 2 * t4) * 8);
        const float mu[4] = {s0.x, s0.z, s1.x, s1.z}, rl[4] = {s0.y, s0.w, s1.y, s1.w};
#pragma unroll
        for (int m = 0; m < 2; m++) {
          float p[8];
#pragma unroll
          for (int i = 0; i < 8; i++) {
            const int r = m * 2 + ((i >> 1) & 1), cc = (i >> 2) * 2 + (i & 1);
            p[i] = phi2(fmaf(c[r], mu[cc], m ? a1[8 * j + i] : a0[8 * j + i]) * rl[cc]);
            z[r] += p[i];
            p[i] *= rl[cc];
            tt[r] = fmaf(p[i], mu[cc], tt[r]);
          }
          stsm4(sw[j & 3] + (j >> 2) * 16384 + m * 8192, pack(p[0], p[1]), pack(p[2], p[3]), pack(p[4], p[5]), pack(p[6], p[7]));
        }
      }
      const bool u2 = lane & 2, u1 = lane & 1;
      const float zz = xred(xred(z[0], z[2], u2, 2), xred(z[1], z[3], u2, 2), u1, 1);
      sts32(S_CSK + ((t4 >> 1) * 64 + w * 16 + (t4 & 1) * 8 + g) * 4, __float_as_uint(xred(xred(tt[0], tt[2], u2, 2), xred(tt[1], tt[3], u2, 2), u1, 1)));
      fence_async_smem();
      nb_arrive(NB_PK, 256);
      st_relaxed(g_z + tm * 1024 + tn * 128 + (t4 >> 1) * 64 + w * 16 + (t4 & 1) * 8 + g, tagf(zz * LOG2E, lds32(S_EPOCH) & 1u));
      nb_arrive(NB_Z, 160);
    }
    STAMP_IF(leader, 35);
    float rl0[2];
    const uint32_t ep = lds32(S_EPOCH);
    {
      nb_sync(NB_CSQ, 160);
      float mu[4];
#pragma unroll
      for (int i = 0; i < 4; i++) {
        const float2 st = lds64f(S_KSTAT + ((i >> 1) * 64 + w * 16 + (i & 1) * 8 + g) * 8);
        mu[i] = -st.x;
        if (i < 2) rl0[i] = st.y;
      }
#pragma unroll
      for (int j = 0; j < 16; j++) {
        const float2 c = lds64f(S_CSQ + (j * 8 + 2 * t4) * 4);
        a0[4 * j] = mu[0] * c.x; a0[4 * j + 1] = mu[0] * c.y; a0[4 * j + 2] = mu[1] * c.x; a0[4 * j + 3] = mu[1] * c.y;
        a1[4 * j] = mu[2] * c.x; a1[4 * j + 1] = mu[2] * c.y; a1[4 * j + 2] = mu[3] * c.x; a1[4 * j + 3] = mu[3] * c.y;
      }
      reg_fence(a0); reg_fence(a1);
    }
    STAMP_IF(leader, 40);
    nb_sync(NB_VQ, 256);
    mainloop<false>(a0, a1, 2, 0, 0, GATE_KT ? NB_KV : 0, leader);
    STAMP_IF(leader, 36);
    {
      uint32_t f[2][16];
      float oc[2][2][20];
      auto phi = [&](const float (&a)[64], int j, int m, uint32_t (&o)[16]) {
        float rl[2] = {rl0[0], rl0[1]};
        if (j | m) { rl[0] = lds32v(S_KSTAT + (m * 64 + w * 16 + g) * 8 + 4); rl[1] = lds32v(S_KSTAT + (m * 64 + w * 16 + 8 + g) * 8 + 4); }
#pragma unroll
        for (int i = 0; i < 16; i++) o[i] = pack(phi2(a[32 * j + 2 * i] * rl[i & 1]), phi2(a[32 * j + 2 * i + 1] * rl[i & 1]));
      };
      auto mma = [&](int j, const uint32_t (&a)[16], float (&o)[2][20]) {
        const uint64_t db = mkdesc(j ? KVB_Z : KVB_P0, 16, 1024, 1);
        reg_zero(o[0]); reg_zero(o[1]);
        wg_fence();
        wgmma_n40_rs<0>(o[0], a[0], a[1], a[2], a[3], db, 0);
        wgmma_n40_rs<0>(o[1], a[8], a[9], a[10], a[11], db + 4, 0);
        wgmma_n40_rs<0>(o[0], a[4], a[5], a[6], a[7], db + 2, 1);
        wgmma_n40_rs<0>(o[1], a[12], a[13], a[14], a[15], db + 6, 1);
        wg_commit();
      };
      auto fin = [&](int j, int m, float (&o)[2][20]) {
        const uint32_t m0 = t4 == 2 * m, m1 = t4 == 2 * m + 1;
#pragma unroll
        for (int h = 0; h < 2; h++) {
          const float r0 = rcp(o[h][j ? 1 : 16] + 1e-6f * LOG2E), r1 = rcp(o[h][j ? 3 : 18] + 1e-6f * LOG2E);
          const int b = j ? 4 : 0;
#pragma unroll
          for (int q = 0; q < 2; q++)
            stsm4(sw[h * 2 + q] + j * 16384 + m * 8192,
                  bsel(pack(o[h][b + 8 * q] * r0, o[h][b + 8 * q + 1] * r0), ep, m0), bsel(pack(o[h][b + 8 * q + 2] * r1, o[h][b + 8 * q + 3] * r1), ep, m1),
                  bsel(pack(o[h][b + 8 * q + 4] * r0, o[h][b + 8 * q + 5] * r0), ep, m0), bsel(pack(o[h][b + 8 * q + 6] * r1, o[h][b + 8 * q + 7] * r1), ep, m1));
        }
      };
#pragma unroll
      for (int j = 0; j < 2; j++) {
        phi(a0, j, 0, f[0]);
        if (j == 0) nb_sync(NB_KVB, 288);
        STAMP_IF(leader && j == 0, 37);
        mma(j, f[0], oc[0]);
        phi(a1, j, 1, f[1]);
        wg_wait<0>();
        reg_fence(oc[0][0]); reg_fence(oc[0][1]);
        mma(j, f[1], oc[1]);
        fin(j, 0, oc[0]);
        if (j == 0) { fence_async_smem(); nb_arrive(NB_Q0, 192); }
        wg_wait<0>();
        reg_fence(oc[1][0]); reg_fence(oc[1][1]);
        fin(j, 1, oc[1]);
        fence_async_smem();
        if (j == 0) nb_arrive(NB_OWN0, 288);
        else { nb_arrive(NB_OWN1, 256); nb_arrive(NB_H1, 160); }
        STAMP_IF(leader, 38 + j);
      }
    }
  }
}

#undef CK
typedef CUresult (*EncodeFn)(CUtensorMap*, CUtensorMapDataType, cuuint32_t, void*, const cuuint64_t*, const cuuint64_t*, const cuuint32_t*,
                             const cuuint32_t*, CUtensorMapInterleave, CUtensorMapSwizzle, CUtensorMapL2promotion, CUtensorMapFloatOOBfill);

void make_map(EncodeFn enc, CUtensorMap* m, const void* p, int rank, uint64_t d0, uint64_t d1, uint64_t d2, uint64_t s1, uint64_t s2,
              uint32_t b0, uint32_t b1, uint32_t b2, CUtensorMapSwizzle sw) {
  cuuint64_t gd[3] = {d0, d1, d2}, gs[2] = {s1, s2};
  cuuint32_t bd[3] = {b0, b1, b2}, es[3] = {1, 1, 1};
  enc(m, CU_TENSOR_MAP_DATA_TYPE_BFLOAT16, rank, const_cast<void*>(p), gd, gs, bd, es, CU_TENSOR_MAP_INTERLEAVE_NONE, sw,
      CU_TENSOR_MAP_L2_PROMOTION_L2_128B, CU_TENSOR_MAP_FLOAT_OOB_FILL_NONE);
}

}

extern "C" void kernel_launch(void* const* d_in, const int* in_sizes, int n_in, void* d_out, int out_size) {
  (void)in_sizes; (void)n_in; (void)out_size;
  void* fn = nullptr;
  cudaDriverEntryPointQueryResult qr;
  cudaGetDriverEntryPoint("cuTensorMapEncodeTiled", &fn, cudaEnableDefault, &qr);
  EncodeFn enc = (EncodeFn)fn;
  void* o;
  cudaGetSymbolAddress(&o, g_o);
  const CUtensorMapSwizzle S128 = CU_TENSOR_MAP_SWIZZLE_128B, S64 = CU_TENSOR_MAP_SWIZZLE_64B, S0 = CU_TENSOR_MAP_SWIZZLE_NONE;
  Params mp;
  mp.x = (const char*)d_in[0]; mp.wqkv = (const char*)d_in[1]; mp.w_r = (const char*)d_in[4];
  mp.wg = (const char*)d_in[5]; mp.wu = (const char*)d_in[6]; mp.wd = (const char*)d_in[7];
  make_map(enc, &mp.m_wqkv, d_in[1], 3, 64, 1024, 48, 6144, 128, 64, 64, 2, S128);
  make_map(enc, &mp.m_x, d_in[0], 2, 1024, 2048, 1, 2048, 0, 64, 128, 1, S128);
  make_map(enc, &mp.m_os, o, 2, 1024, 2048, 1, 2048, 0, 64, 64, 1, S128);
  make_map(enc, &mp.m_o, o, 2, 1024, 2048, 1, 2048, 0, 64, 128, 1, S128);
  make_map(enc, &mp.m_wo, d_in[2], 3, 64, 1024, 16, 2048, 128, 64, 64, 2, S128);
  make_map(enc, &mp.m_xs, d_in[0], 2, 1024, 2048, 1, 2048, 0, 256, 16, 1, S0);
  const char *wg = (const char*)d_in[5], *wu = (const char*)d_in[6];
  make_map(enc, &mp.m_gu, wu < wg ? wu : wg, 3, 3584, 1024, 2, 7168, (uint64_t)(wu < wg ? wg - wu : wu - wg), 32, 32, 2, S64);
  make_map(enc, &mp.m_down, d_in[7], 2, 1024, 3584, 1, 2048, 0, 64, 32, 1, S128);
  make_map(enc, &mp.m_out, d_out, 2, 1024, 2048, 1, 2048, 0, 64, 16, 1, S128);
  int dev = 0, sms = 0;
  cudaGetDevice(&dev);
  cudaDeviceGetAttribute(&sms, cudaDevAttrMultiProcessorCount, dev);
  auto kern = sms == 132 ? fused_kernel<true> : fused_kernel<false>;
  cudaFuncSetAttribute(kern, cudaFuncAttributeMaxDynamicSharedMemorySize, SMEM_BYTES);
  kern<<<132, 512, SMEM_BYTES>>>(mp);
}
```

```cpp
#include <cuda_runtime.h>
#include <cuda.h>
#include <cuda_bf16.h>
#include <stdint.h>

namespace {

template <int TA, int TB>
__device__ __forceinline__ void wgmma_n8_ss(float (&d)[4], uint64_t da, uint64_t db, int sc) {
  asm volatile("{\n.reg .pred p;\nsetp.ne.b32 p, %6, 0;\n"
    "wgmma.mma_async.sync.aligned.m64n8k16.f32.bf16.bf16 {%0, %1, %2, %3}, %4, %5, p, 1, 1, %7, %8;\n}\n"
    : "+f"(d[0]), "+f"(d[1]), "+f"(d[2]), "+f"(d[3])
    : "l"(da), "l"(db), "r"(sc), "n"(TA), "n"(TB));
}
template <int TB>
__device__ __forceinline__ void wgmma_n40_rs(float (&d)[20], uint32_t a0, uint32_t a1, uint32_t a2, uint32_t a3, uint64_t db, int sc) {
  asm volatile("{\n.reg .pred p;\nsetp.ne.b32 p, %25, 0;\n"
    "wgmma.mma_async.sync.aligned.m64n40k16.f32.bf16.bf16 {%0, %1, %2, %3, %4, %5, %6, %7, %8, %9, %10, %11, %12, %13, %14, %15, %16, %17, %18, %19}, {%20,%21,%22,%23}, %24, p, 1, 1, %26;\n}\n"
    : "+f"(d[0]), "+f"(d[1]), "+f"(d[2]), "+f"(d[3]), "+f"(d[4]), "+f"(d[5]), "+f"(d[6]), "+f"(d[7]),
      "+f"(d[8]), "+f"(d[9]), "+f"(d[10]), "+f"(d[11]), "+f"(d[12]), "+f"(d[13]), "+f"(d[14]), "+f"(d[15]),
      "+f"(d[16]), "+f"(d[17]), "+f"(d[18]), "+f"(d[19])
    : "r"(a0), "r"(a1), "r"(a2), "r"(a3), "l"(db), "r"(sc), "n"(TB));
}
template <int TB>
__device__ __forceinline__ void wgmma_n64_rs(float (&d)[32], uint32_t a0, uint32_t a1, uint32_t a2, uint32_t a3, uint64_t db, int sc) {
  asm volatile("{\n.reg .pred p;\nsetp.ne.b32 p, %37, 0;\n"
    "wgmma.mma_async.sync.aligned.m64n64k16.f32.bf16.bf16 {%0, %1, %2, %3, %4, %5, %6, %7, %8, %9, %10, %11, %12, %13, %14, %15, %16, %17, %18, %19, %20, %21, %22, %23, %24, %25, %26, %27, %28, %29, %30, %31}, {%32,%33,%34,%35}, %36, p, 1, 1, %38;\n}\n"
    : "+f"(d[0]), "+f"(d[1]), "+f"(d[2]), "+f"(d[3]), "+f"(d[4]), "+f"(d[5]), "+f"(d[6]), "+f"(d[7]),
      "+f"(d[8]), "+f"(d[9]), "+f"(d[10]), "+f"(d[11]), "+f"(d[12]), "+f"(d[13]), "+f"(d[14]), "+f"(d[15]),
      "+f"(d[16]), "+f"(d[17]), "+f"(d[18]), "+f"(d[19]), "+f"(d[20]), "+f"(d[21]), "+f"(d[22]), "+f"(d[23]),
      "+f"(d[24]), "+f"(d[25]), "+f"(d[26]), "+f"(d[27]), "+f"(d[28]), "+f"(d[29]), "+f"(d[30]), "+f"(d[31])
    : "r"(a0), "r"(a1), "r"(a2), "r"(a3), "l"(db), "r"(sc), "n"(TB));
}
template <int TA, int TB>
__device__ __forceinline__ void wgmma_n128_ss(float (&d)[64], uint64_t da, uint64_t db, int sc) {
  asm volatile("{\n.reg .pred p;\nsetp.ne.b32 p, %66, 0;\n"
    "wgmma.mma_async.sync.aligned.m64n128k16.f32.bf16.bf16 {%0, %1, %2, %3, %4, %5, %6, %7, %8, %9, %10, %11, %12, %13, %14, %15, %16, %17, %18, %19, %20, %21, %22, %23, %24, %25, %26, %27, %28, %29, %30, %31, %32, %33, %34, %35, %36, %37, %38, %39, %40, %41, %42, %43, %44, %45, %46, %47, %48, %49, %50, %51, %52, %53, %54, %55, %56, %57, %58, %59, %60, %61, %62, %63}, %64, %65, p, 1, 1, %67, %68;\n}\n"
    : "+f"(d[0]), "+f"(d[1]), "+f"(d[2]), "+f"(d[3]), "+f"(d[4]), "+f"(d[5]), "+f"(d[6]), "+f"(d[7]),
      "+f"(d[8]), "+f"(d[9]), "+f"(d[10]), "+f"(d[11]), "+f"(d[12]), "+f"(d[13]), "+f"(d[14]), "+f"(d[15]),
      "+f"(d[16]), "+f"(d[17]), "+f"(d[18]), "+f"(d[19]), "+f"(d[20]), "+f"(d[21]), "+f"(d[22]), "+f"(d[23]),
      "+f"(d[24]), "+f"(d[25]), "+f"(d[26]), "+f"(d[27]), "+f"(d[28]), "+f"(d[29]), "+f"(d[30]), "+f"(d[31]),
      "+f"(d[32]), "+f"(d[33]), "+f"(d[34]), "+f"(d[35]), "+f"(d[36]), "+f"(d[37]), "+f"(d[38]), "+f"(d[39]),
      "+f"(d[40]), "+f"(d[41]), "+f"(d[42]), "+f"(d[43]), "+f"(d[44]), "+f"(d[45]), "+f"(d[46]), "+f"(d[47]),
      "+f"(d[48]), "+f"(d[49]), "+f"(d[50]), "+f"(d[51]), "+f"(d[52]), "+f"(d[53]), "+f"(d[54]), "+f"(d[55]),
      "+f"(d[56]), "+f"(d[57]), "+f"(d[58]), "+f"(d[59]), "+f"(d[60]), "+f"(d[61]), "+f"(d[62]), "+f"(d[63])
    : "l"(da), "l"(db), "r"(sc), "n"(TA), "n"(TB));
}
template <int TB>
__device__ __forceinline__ void wgmma_n128_rs(float (&d)[64], uint32_t a0, uint32_t a1, uint32_t a2, uint32_t a3, uint64_t db, int sc) {
  asm volatile("{\n.reg .pred p;\nsetp.ne.b32 p, %69, 0;\n"
    "wgmma.mma_async.sync.aligned.m64n128k16.f32.bf16.bf16 {%0, %1, %2, %3, %4, %5, %6, %7, %8, %9, %10, %11, %12, %13, %14, %15, %16, %17, %18, %19, %20, %21, %22, %23, %24, %25, %26, %27, %28, %29, %30, %31, %32, %33, %34, %35, %36, %37, %38, %39, %40, %41, %42, %43, %44, %45, %46, %47, %48, %49, %50, %51, %52, %53, %54, %55, %56, %57, %58, %59, %60, %61, %62, %63}, {%64,%65,%66,%67}, %68, p, 1, 1, %70;\n}\n"
    : "+f"(d[0]), "+f"(d[1]), "+f"(d[2]), "+f"(d[3]), "+f"(d[4]), "+f"(d[5]), "+f"(d[6]), "+f"(d[7]),
      "+f"(d[8]), "+f"(d[9]), "+f"(d[10]), "+f"(d[11]), "+f"(d[12]), "+f"(d[13]), "+f"(d[14]), "+f"(d[15]),
      "+f"(d[16]), "+f"(d[17]), "+f"(d[18]), "+f"(d[19]), "+f"(d[20]), "+f"(d[21]), "+f"(d[22]), "+f"(d[23]),
      "+f"(d[24]), "+f"(d[25]), "+f"(d[26]), "+f"(d[27]), "+f"(d[28]), "+f"(d[29]), "+f"(d[30]), "+f"(d[31]),
      "+f"(d[32]), "+f"(d[33]), "+f"(d[34]), "+f"(d[35]), "+f"(d[36]), "+f"(d[37]), "+f"(d[38]), "+f"(d[39]),
      "+f"(d[40]), "+f"(d[41]), "+f"(d[42]), "+f"(d[43]), "+f"(d[44]), "+f"(d[45]), "+f"(d[46]), "+f"(d[47]),
      "+f"(d[48]), "+f"(d[49]), "+f"(d[50]), "+f"(d[51]), "+f"(d[52]), "+f"(d[53]), "+f"(d[54]), "+f"(d[55]),
      "+f"(d[56]), "+f"(d[57]), "+f"(d[58]), "+f"(d[59]), "+f"(d[60]), "+f"(d[61]), "+f"(d[62]), "+f"(d[63])
    : "r"(a0), "r"(a1), "r"(a2), "r"(a3), "l"(db), "r"(sc), "n"(TB));
}

__device__ __forceinline__ void poll1(uint32_t (&v)[1], const void* p, uint32_t tag, uint32_t mask) {
  asm volatile("{\n.reg .pred p, q;\n.reg .u32 c, b;\n.reg .b64 x, y;\n.reg .b128 z;\nmov.u32 c, 0;\nLW:\n"
               "ld.relaxed.gpu.global.u32 %0, [%1+0];\n"
               "xor.b32 b, %0, %2;\n"
               "and.b32 b, b, %3;\nsetp.eq.u32 p, b, 0;\nvote.sync.all.pred p, p, 0xffffffff;\n@p bra.uni LD;\n"
               "nanosleep.u32 100;\nadd.u32 c, c, 1;\nsetp.lt.u32 q, c, 1000000;\n@q bra.uni LW;\ntrap;\nLD:\n}"
               : "=&r"(v[0])
               : "l"(p), "r"(tag), "r"(mask) : "memory");
}
__device__ __forceinline__ void poll1f(uint32_t (&v)[1], const void* p, uint32_t tag, uint32_t mask) {
  asm volatile("{\n.reg .pred p, q;\n.reg .u32 c, b;\n.reg .b64 x, y;\n.reg .b128 z;\nmov.u32 c, 0;\nLW:\n"
               "ld.relaxed.gpu.global.u32 %0, [%1+0];\n"
               "xor.b32 b, %0, %2;\n"
               "and.b32 b, b, %3;\nsetp.eq.u32 p, b, 0;\nvote.sync.all.pred p, p, 0xffffffff;\n@p bra.uni LD;\n"
               "nanosleep.u32 50;\nadd.u32 c, c, 1;\nsetp.lt.u32 q, c, 1000000;\n@q bra.uni LW;\ntrap;\nLD:\n}"
               : "=&r"(v[0])
               : "l"(p), "r"(tag), "r"(mask) : "memory");
}
__device__ __forceinline__ void poll0(uint32_t (&v)[1], const void* p, uint32_t tag, uint32_t mask) {
  asm volatile("{\n.reg .pred p, q;\n.reg .u32 c, b;\n.reg .b64 x, y;\n.reg .b128 z;\nmov.u32 c, 0;\nLW:\n"
               "ld.relaxed.gpu.global.u32 %0, [%1+0];\n"
               "xor.b32 b, %0, %2;\n"
               "and.b32 b, b, %3;\nsetp.eq.u32 p, b, 0;\nvote.sync.all.pred p, p, 0xffffffff;\n@p bra.uni LD;\n"
               "add.u32 c, c, 1;\nsetp.lt.u32 q, c, 1000000;\n@q bra.uni LW;\ntrap;\nLD:\n}"
               : "=&r"(v[0])
               : "l"(p), "r"(tag), "r"(mask) : "memory");
}
__device__ __forceinline__ void poll_pair(uint32_t (&v)[2], const void* p, uint32_t tag, uint32_t mask) {
  asm volatile("{\n.reg .pred p, q;\n.reg .u32 c, b;\n.reg .b64 x, y;\n.reg .b128 z;\nmov.u32 c, 0;\nLW:\n"
               "ld.relaxed.gpu.global.b64 x, [%2+0];\nmov.b64 {%0,%1}, x;\n"
               "xor.b32 b, %0, %3;\n"
               "and.b32 b, b, %4;\nsetp.eq.u32 p, b, 0;\nvote.sync.all.pred p, p, 0xffffffff;\n@p bra.uni LD;\n"
               "nanosleep.u32 100;\nadd.u32 c, c, 1;\nsetp.lt.u32 q, c, 1000000;\n@q bra.uni LW;\ntrap;\nLD:\n}"
               : "=&r"(v[0]), "=&r"(v[1])
               : "l"(p), "r"(tag), "r"(mask) : "memory");
}
__device__ __forceinline__ void poll_quad(uint32_t (&v)[4], const void* p, uint32_t tag, uint32_t mask) {
  asm volatile("{\n.reg .pred p, q;\n.reg .u32 c, b;\n.reg .b64 x, y;\n.reg .b128 z;\nmov.u32 c, 0;\nLW:\n"
               "ld.relaxed.gpu.global.v4.u32 {%0,%1,%2,%3}, [%4+0];\n"
               "xor.b32 b, %0, %5;\n"
               "lop3.b32 b, b, %1, %5, 0xf6;\nlop3.b32 b, b, %2, %5, 0xf6;\nlop3.b32 b, b, %3, %5, 0xf6;\n"
               "and.b32 b, b, %6;\nsetp.eq.u32 p, b, 0;\nvote.sync.all.pred p, p, 0xffffffff;\n@p bra.uni LD;\n"
               "nanosleep.u32 200;\nadd.u32 c, c, 1;\nsetp.lt.u32 q, c, 1000000;\n@q bra.uni LW;\ntrap;\nLD:\n}"
               : "=&r"(v[0]), "=&r"(v[1]), "=&r"(v[2]), "=&r"(v[3])
               : "l"(p), "r"(tag), "r"(mask) : "memory");
}
__device__ __forceinline__ void poll8x4(uint32_t (&v)[32], const void* p, uint32_t tag, uint32_t mask) {
  asm volatile("{\n.reg .pred p, q;\n.reg .u32 c, b;\n.reg .b64 x, y;\n.reg .b128 z;\nmov.u32 c, 0;\nLW:\n"
               "ld.relaxed.gpu.global.v4.u32 {%0,%1,%2,%3}, [%32+0];\n"
               "ld.relaxed.gpu.global.v4.u32 {%4,%5,%6,%7}, [%32+2048];\n"
               "ld.relaxed.gpu.global.v4.u32 {%8,%9,%10,%11}, [%32+4096];\n"
               "ld.relaxed.gpu.global.v4.u32 {%12,%13,%14,%15}, [%32+6144];\n"
               "ld.relaxed.gpu.global.v4.u32 {%16,%17,%18,%19}, [%32+8192];\n"
               "ld.relaxed.gpu.global.v4.u32 {%20,%21,%22,%23}, [%32+10240];\n"
               "ld.relaxed.gpu.global.v4.u32 {%24,%25,%26,%27}, [%32+12288];\n"
               "ld.relaxed.gpu.global.v4.u32 {%28,%29,%30,%31}, [%32+14336];\n"
               "xor.b32 b, %0, %33;\n"
               "lop3.b32 b, b, %1, %33, 0xf6;\nlop3.b32 b, b, %2, %33, 0xf6;\nlop3.b32 b, b, %3, %33, 0xf6;\nlop3.b32 b, b, %4, %33, 0xf6;\n"
               "lop3.b32 b, b, %5, %33, 0xf6;\nlop3.b32 b, b, %6, %33, 0xf6;\nlop3.b32 b, b, %7, %33, 0xf6;\nlop3.b32 b, b, %8, %33, 0xf6;\n"
               "lop3.b32 b, b, %9, %33, 0xf6;\nlop3.b32 b, b, %10, %33, 0xf6;\nlop3.b32 b, b, %11, %33, 0xf6;\nlop3.b32 b, b, %12, %33, 0xf6;\n"
               "lop3.b32 b, b, %13, %33, 0xf6;\nlop3.b32 b, b, %14, %33, 0xf6;\nlop3.b32 b, b, %15, %33, 0xf6;\nlop3.b32 b, b, %16, %33, 0xf6;\n"
               "lop3.b32 b, b, %17, %33, 0xf6;\nlop3.b32 b, b, %18, %33, 0xf6;\nlop3.b32 b, b, %19, %33, 0xf6;\nlop3.b32 b, b, %20, %33, 0xf6;\n"
               "lop3.b32 b, b, %21, %33, 0xf6;\nlop3.b32 b, b, %22, %33, 0xf6;\nlop3.b32 b, b, %23, %33, 0xf6;\nlop3.b32 b, b, %24, %33, 0xf6;\n"
               "lop3.b32 b, b, %25, %33, 0xf6;\nlop3.b32 b, b, %26, %33, 0xf6;\nlop3.b32 b, b, %27, %33, 0xf6;\nlop3.b32 b, b, %28, %33, 0xf6;\n"
               "lop3.b32 b, b, %29, %33, 0xf6;\nlop3.b32 b, b, %30, %33, 0xf6;\nlop3.b32 b, b, %31, %33, 0xf6;\n"
               "and.b32 b, b, %34;\nsetp.eq.u32 p, b, 0;\nvote.sync.all.pred p, p, 0xffffffff;\n@p bra.uni LD;\n"
               "nanosleep.u32 50;\nadd.u32 c, c, 1;\nsetp.lt.u32 q, c, 1000000;\n@q bra.uni LW;\ntrap;\nLD:\n}"
               : "=&r"(v[0]), "=&r"(v[1]), "=&r"(v[2]), "=&r"(v[3]), "=&r"(v[4]), "=&r"(v[5]), "=&r"(v[6]), "=&r"(v[7]), "=&r"(v[8]), "=&r"(v[9]), "=&r"(v[10]), "=&r"(v[11]), "=&r"(v[12]), "=&r"(v[13]), "=&r"(v[14]), "=&r"(v[15]), "=&r"(v[16]), "=&r"(v[17]), "=&r"(v[18]), "=&r"(v[19]), "=&r"(v[20]), "=&r"(v[21]), "=&r"(v[22]), "=&r"(v[23]), "=&r"(v[24]), "=&r"(v[25]), "=&r"(v[26]), "=&r"(v[27]), "=&r"(v[28]), "=&r"(v[29]), "=&r"(v[30]), "=&r"(v[31])
               : "l"(p), "r"(tag), "r"(mask) : "memory");
}
__device__ __forceinline__ void poll16(uint32_t (&v)[16], const void* p, uint32_t tag, uint32_t mask) {
  asm volatile("{\n.reg .pred p, q;\n.reg .u32 c, b;\n.reg .b64 x, y;\n.reg .b128 z;\nmov.u32 c, 0;\nLW:\n"
               "ld.relaxed.gpu.global.u32 %0, [%16+0];\n"
               "ld.relaxed.gpu.global.u32 %1, [%16+4096];\n"
               "ld.relaxed.gpu.global.u32 %2, [%16+8192];\n"
               "ld.relaxed.gpu.global.u32 %3, [%16+12288];\n"
               "ld.relaxed.gpu.global.u32 %4, [%16+16384];\n"
               "ld.relaxed.gpu.global.u32 %5, [%16+20480];\n"
               "ld.relaxed.gpu.global.u32 %6, [%16+24576];\n"
               "ld.relaxed.gpu.global.u32 %7, [%16+28672];\n"
               "ld.relaxed.gpu.global.u32 %8, [%16+32768];\n"
               "ld.relaxed.gpu.global.u32 %9, [%16+36864];\n"
               "ld.relaxed.gpu.global.u32 %10, [%16+40960];\n"
               "ld.relaxed.gpu.global.u32 %11, [%16+45056];\n"
               "ld.relaxed.gpu.global.u32 %12, [%16+49152];\n"
               "ld.relaxed.gpu.global.u32 %13, [%16+53248];\n"
               "ld.relaxed.gpu.global.u32 %14, [%16+57344];\n"
               "ld.relaxed.gpu.global.u32 %15, [%16+61440];\n"
               "xor.b32 b, %0, %17;\n"
               "lop3.b32 b, b, %1, %17, 0xf6;\nlop3.b32 b, b, %2, %17, 0xf6;\nlop3.b32 b, b, %3, %17, 0xf6;\nlop3.b32 b, b, %4, %17, 0xf6;\n"
               "lop3.b32 b, b, %5, %17, 0xf6;\nlop3.b32 b, b, %6, %17, 0xf6;\nlop3.b32 b, b, %7, %17, 0xf6;\nlop3.b32 b, b, %8, %17, 0xf6;\n"
               "lop3.b32 b, b, %9, %17, 0xf6;\nlop3.b32 b, b, %10, %17, 0xf6;\nlop3.b32 b, b, %11, %17, 0xf6;\nlop3.b32 b, b, %12, %17, 0xf6;\n"
               "lop3.b32 b, b, %13, %17, 0xf6;\nlop3.b32 b, b, %14, %17, 0xf6;\nlop3.b32 b, b, %15, %17, 0xf6;\n"
               "and.b32 b, b, %18;\nsetp.eq.u32 p, b, 0;\nvote.sync.all.pred p, p, 0xffffffff;\n@p bra.uni LD;\n"
               "nanosleep.u32 200;\nadd.u32 c, c, 1;\nsetp.lt.u32 q, c, 1000000;\n@q bra.uni LW;\ntrap;\nLD:\n}"
               : "=&r"(v[0]), "=&r"(v[1]), "=&r"(v[2]), "=&r"(v[3]), "=&r"(v[4]), "=&r"(v[5]), "=&r"(v[6]), "=&r"(v[7]), "=&r"(v[8]), "=&r"(v[9]), "=&r"(v[10]), "=&r"(v[11]), "=&r"(v[12]), "=&r"(v[13]), "=&r"(v[14]), "=&r"(v[15])
               : "l"(p), "r"(tag), "r"(mask) : "memory");
}
__device__ __forceinline__ void poll_keys(uint32_t (&v)[16], const void* p, uint32_t tag, uint32_t mask) {
  asm volatile("{\n.reg .pred p, q;\n.reg .u32 c, b;\n.reg .b64 x, y;\n.reg .b128 z;\nmov.u32 c, 0;\nLW:\n"
               "ld.relaxed.gpu.global.v2.b64 {x, y}, [%16+0];\nmov.b64 {%0,%1}, x;\nmov.b64 {%2,%3}, y;\n"
               "ld.relaxed.gpu.global.v2.b64 {x, y}, [%16+4096];\nmov.b64 {%4,%5}, x;\nmov.b64 {%6,%7}, y;\n"
               "ld.relaxed.gpu.global.v2.b64 {x, y}, [%16+8192];\nmov.b64 {%8,%9}, x;\nmov.b64 {%10,%11}, y;\n"
               "ld.relaxed.gpu.global.v2.b64 {x, y}, [%16+12288];\nmov.b64 {%12,%13}, x;\nmov.b64 {%14,%15}, y;\n"
               "xor.b32 b, %0, %17;\n"
               "lop3.b32 b, b, %2, %17, 0xf6;\nlop3.b32 b, b, %4, %17, 0xf6;\nlop3.b32 b, b, %6, %17, 0xf6;\nlop3.b32 b, b, %8, %17, 0xf6;\n"
               "lop3.b32 b, b, %10, %17, 0xf6;\nlop3.b32 b, b, %12, %17, 0xf6;\nlop3.b32 b, b, %14, %17, 0xf6;\n"
               "and.b32 b, b, %18;\nsetp.eq.u32 p, b, 0;\nvote.sync.all.pred p, p, 0xffffffff;\n@p bra.uni LD;\n"
               "nanosleep.u32 20;\nadd.u32 c, c, 1;\nsetp.lt.u32 q, c, 1000000;\n@q bra.uni LW;\ntrap;\nLD:\n}"
               : "=&r"(v[0]), "=&r"(v[1]), "=&r"(v[2]), "=&r"(v[3]), "=&r"(v[4]), "=&r"(v[5]), "=&r"(v[6]), "=&r"(v[7]), "=&r"(v[8]), "=&r"(v[9]), "=&r"(v[10]), "=&r"(v[11]), "=&r"(v[12]), "=&r"(v[13]), "=&r"(v[14]), "=&r"(v[15])
               : "l"(p), "r"(tag), "r"(mask) : "memory");
}
__device__ __forceinline__ void poll_z(uint32_t (&v)[16], const void* p, uint32_t tag, uint32_t mask) {
  asm volatile("{\n.reg .pred p, q;\n.reg .u32 c, b;\n.reg .b64 x, y;\n.reg .b128 z;\nmov.u32 c, 0;\nLW:\n"
               "ld.relaxed.gpu.global.v4.u32 {%0,%1,%2,%3}, [%16+0];\n"
               "ld.relaxed.gpu.global.v4.u32 {%4,%5,%6,%7}, [%16+4096];\n"
               "ld.relaxed.gpu.global.v4.u32 {%8,%9,%10,%11}, [%16+8192];\n"
               "ld.relaxed.gpu.global.v4.u32 {%12,%13,%14,%15}, [%16+12288];\n"
               "xor.b32 b, %0, %17;\n"
               "lop3.b32 b, b, %1, %17, 0xf6;\nlop3.b32 b, b, %2, %17, 0xf6;\nlop3.b32 b, b, %3, %17, 0xf6;\nlop3.b32 b, b, %4, %17, 0xf6;\n"
               "lop3.b32 b, b, %5, %17, 0xf6;\nlop3.b32 b, b, %6, %17, 0xf6;\nlop3.b32 b, b, %7, %17, 0xf6;\nlop3.b32 b, b, %8, %17, 0xf6;\n"
               "lop3.b32 b, b, %9, %17, 0xf6;\nlop3.b32 b, b, %10, %17, 0xf6;\nlop3.b32 b, b, %11, %17, 0xf6;\nlop3.b32 b, b, %12, %17, 0xf6;\n"
               "lop3.b32 b, b, %13, %17, 0xf6;\nlop3.b32 b, b, %14, %17, 0xf6;\nlop3.b32 b, b, %15, %17, 0xf6;\n"
               "and.b32 b, b, %18;\nsetp.eq.u32 p, b, 0;\nvote.sync.all.pred p, p, 0xffffffff;\n@p bra.uni LD;\n"
               "nanosleep.u32 300;\nadd.u32 c, c, 1;\nsetp.lt.u32 q, c, 1000000;\n@q bra.uni LW;\ntrap;\nLD:\n}"
               : "=&r"(v[0]), "=&r"(v[1]), "=&r"(v[2]), "=&r"(v[3]), "=&r"(v[4]), "=&r"(v[5]), "=&r"(v[6]), "=&r"(v[7]), "=&r"(v[8]), "=&r"(v[9]), "=&r"(v[10]), "=&r"(v[11]), "=&r"(v[12]), "=&r"(v[13]), "=&r"(v[14]), "=&r"(v[15])
               : "l"(p), "r"(tag), "r"(mask) : "memory");
}
__device__ __forceinline__ void poll7x4(uint32_t (&v)[28], const void* p, uint32_t tag, uint32_t mask) {
  asm volatile("{\n.reg .pred p, q;\n.reg .u32 c, b;\n.reg .b64 x, y;\n.reg .b128 z;\nmov.u32 c, 0;\nLW:\n"
               "ld.relaxed.gpu.global.v4.u32 {%0,%1,%2,%3}, [%28+0];\n"
               "ld.relaxed.gpu.global.v4.u32 {%4,%5,%6,%7}, [%28+2048];\n"
               "ld.relaxed.gpu.global.v4.u32 {%8,%9,%10,%11}, [%28+4096];\n"
               "ld.relaxed.gpu.global.v4.u32 {%12,%13,%14,%15}, [%28+6144];\n"
               "ld.relaxed.gpu.global.v4.u32 {%16,%17,%18,%19}, [%28+8192];\n"
               "ld.relaxed.gpu.global.v4.u32 {%20,%21,%22,%23}, [%28+10240];\n"
               "ld.relaxed.gpu.global.v4.u32 {%24,%25,%26,%27}, [%28+12288];\n"
               "xor.b32 b, %0, %29;\n"
               "lop3.b32 b, b, %1, %29, 0xf6;\nlop3.b32 b, b, %2, %29, 0xf6;\nlop3.b32 b, b, %3, %29, 0xf6;\nlop3.b32 b, b, %4, %29, 0xf6;\n"
               "lop3.b32 b, b, %5, %29, 0xf6;\nlop3.b32 b, b, %6, %29, 0xf6;\nlop3.b32 b, b, %7, %29, 0xf6;\nlop3.b32 b, b, %8, %29, 0xf6;\n"
               "lop3.b32 b, b, %9, %29, 0xf6;\nlop3.b32 b, b, %10, %29, 0xf6;\nlop3.b32 b, b, %11, %29, 0xf6;\nlop3.b32 b, b, %12, %29, 0xf6;\n"
               "lop3.b32 b, b, %13, %29, 0xf6;\nlop3.b32 b, b, %14, %29, 0xf6;\nlop3.b32 b, b, %15, %29, 0xf6;\nlop3.b32 b, b, %16, %29, 0xf6;\n"
               "lop3.b32 b, b, %17, %29, 0xf6;\nlop3.b32 b, b, %18, %29, 0xf6;\nlop3.b32 b, b, %19, %29, 0xf6;\nlop3.b32 b, b, %20, %29, 0xf6;\n"
               "lop3.b32 b, b, %21, %29, 0xf6;\nlop3.b32 b, b, %22, %29, 0xf6;\nlop3.b32 b, b, %23, %29, 0xf6;\nlop3.b32 b, b, %24, %29, 0xf6;\n"
               "lop3.b32 b, b, %25, %29, 0xf6;\nlop3.b32 b, b, %26, %29, 0xf6;\nlop3.b32 b, b, %27, %29, 0xf6;\n"
               "and.b32 b, b, %30;\nsetp.eq.u32 p, b, 0;\nvote.sync.all.pred p, p, 0xffffffff;\n@p bra.uni LD;\n"
               "nanosleep.u32 50;\nadd.u32 c, c, 1;\nsetp.lt.u32 q, c, 1000000;\n@q bra.uni LW;\ntrap;\nLD:\n}"
               : "=&r"(v[0]), "=&r"(v[1]), "=&r"(v[2]), "=&r"(v[3]), "=&r"(v[4]), "=&r"(v[5]), "=&r"(v[6]), "=&r"(v[7]), "=&r"(v[8]), "=&r"(v[9]), "=&r"(v[10]), "=&r"(v[11]), "=&r"(v[12]), "=&r"(v[13]), "=&r"(v[14]), "=&r"(v[15]), "=&r"(v[16]), "=&r"(v[17]), "=&r"(v[18]), "=&r"(v[19]), "=&r"(v[20]), "=&r"(v[21]), "=&r"(v[22]), "=&r"(v[23]), "=&r"(v[24]), "=&r"(v[25]), "=&r"(v[26]), "=&r"(v[27])
               : "l"(p), "r"(tag), "r"(mask) : "memory");
}
__device__ __forceinline__ void poll_kvp(uint32_t (&v)[16], const void* p, uint32_t tag, uint32_t mask) {
  asm volatile("{\n.reg .pred p, q;\n.reg .u32 c, b;\n.reg .b64 x, y;\n.reg .b128 z;\nmov.u32 c, 0;\nLW:\n"
               "ld.relaxed.gpu.global.b128 z, [%16+0];\nmov.b128 {x, y}, z;\nmov.b64 {%0,%1}, x;\nmov.b64 {%2,%3}, y;\n"
               "ld.relaxed.gpu.global.b128 z, [%16+8192];\nmov.b128 {x, y}, z;\nmov.b64 {%4,%5}, x;\nmov.b64 {%6,%7}, y;\n"
               "ld.relaxed.gpu.global.b128 z, [%16+16384];\nmov.b128 {x, y}, z;\nmov.b64 {%8,%9}, x;\nmov.b64 {%10,%11}, y;\n"
               "ld.relaxed.gpu.global.b128 z, [%16+24576];\nmov.b128 {x, y}, z;\nmov.b64 {%12,%13}, x;\nmov.b64 {%14,%15}, y;\n"
               "xor.b32 b, %0, %17;\n"
               "lop3.b32 b, b, %4, %17, 0xf6;\nlop3.b32 b, b, %8, %17, 0xf6;\nlop3.b32 b, b, %12, %17, 0xf6;\n"
               "and.b32 b, b, %18;\nsetp.eq.u32 p, b, 0;\nvote.sync.all.pred p, p, 0xffffffff;\n@p bra.uni LD;\n"
               "nanosleep.u32 50;\nadd.u32 c, c, 1;\nsetp.lt.u32 q, c, 1000000;\n@q bra.uni LW;\ntrap;\nLD:\n}"
               : "=&r"(v[0]), "=&r"(v[1]), "=&r"(v[2]), "=&r"(v[3]), "=&r"(v[4]), "=&r"(v[5]), "=&r"(v[6]), "=&r"(v[7]), "=&r"(v[8]), "=&r"(v[9]), "=&r"(v[10]), "=&r"(v[11]), "=&r"(v[12]), "=&r"(v[13]), "=&r"(v[14]), "=&r"(v[15])
               : "l"(p), "r"(tag), "r"(mask) : "memory");
}
__device__ __forceinline__ void poll_kv(uint32_t (&v)[16], const void* p, uint32_t tag, uint32_t mask) {
  asm volatile("{\n.reg .pred p, q;\n.reg .u32 c, b;\n.reg .b64 x, y;\n.reg .b128 z;\nmov.u32 c, 0;\nLW:\n"
               "ld.relaxed.gpu.global.b128 z, [%16+0];\nmov.b128 {x, y}, z;\nmov.b64 {%0,%1}, x;\nmov.b64 {%2,%3}, y;\n"
               "ld.relaxed.gpu.global.b128 z, [%16+2048];\nmov.b128 {x, y}, z;\nmov.b64 {%4,%5}, x;\nmov.b64 {%6,%7}, y;\n"
               "ld.relaxed.gpu.global.b128 z, [%16+4096];\nmov.b128 {x, y}, z;\nmov.b64 {%8,%9}, x;\nmov.b64 {%10,%11}, y;\n"
               "ld.relaxed.gpu.global.b128 z, [%16+6144];\nmov.b128 {x, y}, z;\nmov.b64 {%12,%13}, x;\nmov.b64 {%14,%15}, y;\n"
               "xor.b32 b, %0, %17;\n"
               "lop3.b32 b, b, %4, %17, 0xf6;\nlop3.b32 b, b, %8, %17, 0xf6;\nlop3.b32 b, b, %12, %17, 0xf6;\n"
               "and.b32 b, b, %18;\nsetp.eq.u32 p, b, 0;\nvote.sync.all.pred p, p, 0xffffffff;\n@p bra.uni LD;\n"
               "nanosleep.u32 50;\nadd.u32 c, c, 1;\nsetp.lt.u32 q, c, 1000000;\n@q bra.uni LW;\ntrap;\nLD:\n}"
               : "=&r"(v[0]), "=&r"(v[1]), "=&r"(v[2]), "=&r"(v[3]), "=&r"(v[4]), "=&r"(v[5]), "=&r"(v[6]), "=&r"(v[7]), "=&r"(v[8]), "=&r"(v[9]), "=&r"(v[10]), "=&r"(v[11]), "=&r"(v[12]), "=&r"(v[13]), "=&r"(v[14]), "=&r"(v[15])
               : "l"(p), "r"(tag), "r"(mask) : "memory");
}

__device__ __align__(1024) __nv_bfloat16 g_o[2048 * 1024];
__device__ __align__(128) uint2 g_keys[2048];
__device__ __align__(128) uint32_t g_csum[18 * 1024];
__device__ __align__(128) uint32_t g_z[16 * 1024];
__device__ __align__(128) uint4 g_kvp[128 * 512];
__device__ __align__(128) uint4 g_kv[8 * 512];
__device__ __align__(128) uint32_t g_h[112 * 256];
__device__ __align__(128) uint32_t g_yp[128 * 512];
__device__ __align__(128) uint32_t g_xsel[4096 + 32];
enum { H_CS = 0, H_KVP = 8, H_KV = 16, H_H = 24, H_Y = 32, H_O = 40, H_R = 56, H_Z = 57 };
__device__ __align__(128) uint32_t g_sig[65 * 32];
__device__ uint32_t g_epoch;

constexpr uint32_t RING = 1024, SLOT = 32768, SMEM_BYTES = 232448;
constexpr int NST = 5, HST = 7;
constexpr uint32_t STG = RING + 163840, AUX = RING + 196608, FR = RING + 212992, MISC = RING + 229376;
constexpr uint32_t B_FULL = MISC, B_EMPTY = MISC + 56, B_XS = MISC + 112, B_SEL = MISC + 144, B_WK = MISC + 160, B_CSDN = MISC + 168,
                   B_FR = MISC + 176, B_FE = MISC + 216, B_DR = MISC + 256, B_CSV = MISC + 288,
                   B_OWN = MISC + 296, B_XRES = MISC + 312, NBAR = 41;
constexpr uint32_t S_EPOCH = MISC + 352, S_NCAND = MISC + 356, S_SEL = MISC + 368, S_WMAX = MISC + 400,
                   S_KSTAT = MISC + 512, S_CSK = MISC + 1536, S_CSV = MISC + 2048, S_CSQ = MISC + 2560, S_ONES = MISC + 512;
constexpr uint32_t KVB_P0 = AUX, KVB_Z = AUX + 4096, KVB_P1 = AUX + 5120, HOP = AUX + 9216, GR = FR - 4096;
enum { NB_Z = 0, NB_KV = 1, NB_VQ = 2, NB_WG0 = 3, NB_FDONE = 4, NB_PK = 5, NB_KVB = 6, NB_WG1 = 7, NB_WG2 = 8, NB_CSQ = 9,
       NB_Y = 10, NB_ST = 11, NB_OWN0 = 12, NB_OWN1 = 13, NB_Q0 = 14, NB_H1 = 15 };

#define XS_ORD 0x3210
#define XS_GO 0
#define XS_FLY 2
#define XS_EARLY 0
#define H_DELAY 0
#define FFN_GAP 200
#define GATE_KT 0
#define GATE_K 6
#define KV_DIRECT 1
#define ALIGN 0
#define DN_GAP 50
#define PF_GAP 200
#define PF_WAIT 1000
#define POLITE 1
constexpr uint64_t EVICT_FIRST = 0x12f0000000000000ull;
constexpr float LOG2E = 1.4426950408889634f, LN2 = 0.6931471805599453f;

#define ELECT "{\n.reg .pred p;\nelect.sync _|p, 0xffffffff;\n"
#define TMA2D "cp.async.bulk.tensor.2d.shared::cluster.global.mbarrier::complete_tx::bytes"
#define TMA3D "cp.async.bulk.tensor.3d.shared::cluster.global.mbarrier::complete_tx::bytes"
__device__ __forceinline__ void e_expect(uint32_t b, uint32_t n) {
  asm volatile(ELECT "@p mbarrier.arrive.expect_tx.shared::cta.b64 _, [%0], %1;\n}" ::"r"(b), "r"(n) : "memory");
}
__device__ __forceinline__ void e_arrive(uint32_t b) { asm volatile(ELECT "@p mbarrier.arrive.shared::cta.b64 _, [%0];\n}" ::"r"(b) : "memory"); }
__device__ __forceinline__ void e_tma2d(uint32_t dst, const CUtensorMap* m, int c0, int c1, uint32_t bar) {
  asm volatile(ELECT "@p " TMA2D " [%0], [%1, {%3, %4}], [%2];\n}" ::"r"(dst), "l"(m), "r"(bar), "r"(c0), "r"(c1) : "memory");
}
__device__ __forceinline__ void e_tma2d_ef(uint32_t dst, const CUtensorMap* m, int c0, int c1, uint32_t bar, uint64_t pol) {
  asm volatile(ELECT "@p " TMA2D ".L2::cache_hint [%0], [%1, {%3, %4}], [%2], %5;\n}" ::"r"(dst), "l"(m), "r"(bar), "r"(c0), "r"(c1), "l"(pol) : "memory");
}
__device__ __forceinline__ void e_tma3d(uint32_t dst, const CUtensorMap* m, int c1, int c2, uint32_t bar) {
  asm volatile(ELECT "@p " TMA3D " [%0], [%1, {0, %3, %4}], [%2];\n}" ::"r"(dst), "l"(m), "r"(bar), "r"(c1), "r"(c2) : "memory");
}
__device__ __forceinline__ void e_store2d(const CUtensorMap* m, int c0, int c1, uint32_t src) {
  asm volatile(ELECT "@p cp.async.bulk.tensor.2d.global.shared::cta.bulk_group [%0, {%2, %3}], [%1];\n}" ::"l"(m), "r"(src), "r"(c0), "r"(c1) : "memory");
}
__device__ __forceinline__ void e_tma3d_ef(uint32_t dst, const CUtensorMap* m, int c0, int c1, uint32_t bar, uint64_t pol) {
  asm volatile(ELECT "@p " TMA3D ".L2::cache_hint [%0], [%1, {%3, %4, 0}], [%2], %5;\n}" ::"r"(dst), "l"(m), "r"(bar), "r"(c0), "r"(c1), "l"(pol) : "memory");
}
__device__ __forceinline__ void e_load(uint32_t dst, const void* src, uint32_t n, uint32_t bar) {
  asm volatile(ELECT "@p cp.async.bulk.shared::cluster.global.mbarrier::complete_tx::bytes [%0], [%1], %2, [%3];\n}" ::"r"(dst), "l"(src), "r"(n), "r"(bar) : "memory");
}
__device__ __forceinline__ void e_pfmap(const CUtensorMap* m) { asm volatile(ELECT "@p prefetch.tensormap [%0];\n}" ::"l"(m) : "memory"); }
__device__ __forceinline__ void bulk_wait_read() { asm volatile("cp.async.bulk.commit_group;\ncp.async.bulk.wait_group.read 0;" ::: "memory"); }
__device__ __forceinline__ void e_signal(int word, int bit) {
  asm volatile(ELECT "@p red.relaxed.gpu.global.xor.b32 [%0], %1;\n}" ::"l"(g_sig + word * 32), "r"(1u << bit) : "memory");
}
__device__ __forceinline__ void e_release(int word, int bit) {
  asm volatile("cp.async.bulk.commit_group;\ncp.async.bulk.wait_group 0;\nfence.release.gpu;" ::: "memory");
  e_signal(word, bit);
}
__device__ __forceinline__ void await(int word, uint32_t mask, uint32_t ep) {
  uint32_t f[1];
  poll1f(f, g_sig + word * 32, 0u - (ep & 1u), mask);
}

__device__ __forceinline__ void mbar_arrive(uint32_t b) { asm volatile("mbarrier.arrive.shared::cta.b64 _, [%0];" ::"r"(b) : "memory"); }
__device__ __forceinline__ void mbar_wait(uint32_t b, uint32_t ph) {
  asm volatile("{\n.reg .pred p, q;\n.reg .u32 c;\nmov.u32 c, 0;\nLW:\nmbarrier.try_wait.parity.shared::cta.b64 p, [%0], %1;\n@p bra LD;\n"
               "add.u32 c, c, 1;\nsetp.lt.u32 q, c, 100000;\n@q bra LW;\ntrap;\nLD:\n}" ::"r"(b), "r"(ph) : "memory");
}
__device__ __forceinline__ void nb_sync(int id, int n) { asm volatile("bar.sync %0, %1;" ::"r"(id), "r"(n) : "memory"); }
__device__ __forceinline__ void nb_arrive(int id, int n) { asm volatile("bar.arrive %0, %1;" ::"r"(id), "r"(n) : "memory"); }
__device__ __forceinline__ void wg_fence() { asm volatile("wgmma.fence.sync.aligned;" ::: "memory"); }
__device__ __forceinline__ void wg_commit() { asm volatile("wgmma.commit_group.sync.aligned;" ::: "memory"); }
template <int N> __device__ __forceinline__ void wg_wait() { asm volatile("wgmma.wait_group.sync.aligned %0;" ::"n"(N) : "memory"); }
template <int N> __device__ __forceinline__ void reg_fence(float (&a)[N]) {
#pragma unroll
  for (int i = 0; i < N; i++) asm volatile("" : "+f"(a[i])::"memory");
}
template <int N> __device__ __forceinline__ void reg_zero(float (&a)[N]) {
#pragma unroll
  for (int i = 0; i < N; i++) a[i] = 0.f;
}
__device__ __forceinline__ constexpr uint64_t mkdesc(uint32_t addr, uint32_t lbo, uint32_t sbo, uint32_t swz) {
  return (uint64_t)(addr >> 4) | ((uint64_t)(lbo >> 4) << 16) | ((uint64_t)(sbo >> 4) << 32) | ((uint64_t)swz << 62);
}
__device__ __forceinline__ void fence_async_smem() { asm volatile("fence.proxy.async.shared::cta;" ::: "memory"); }
__device__ __forceinline__ void fence_async_glob() { asm volatile("fence.proxy.async.global;" ::: "memory"); }
__device__ __forceinline__ void fence_acq() { asm volatile("fence.acquire.gpu;" ::: "memory"); }
__device__ __forceinline__ void st_relaxed(uint32_t* p, uint32_t v) { asm volatile("st.relaxed.gpu.global.u32 [%0], %1;" ::"l"(p), "r"(v) : "memory"); }
__device__ __forceinline__ uint32_t ld_relaxed(const uint32_t* p) { uint32_t v; asm volatile("ld.relaxed.gpu.global.u32 %0, [%1];" : "=r"(v) : "l"(p) : "memory"); return v; }
__device__ __forceinline__ void st_unit(uint4* p, uint32_t a, uint32_t b, uint32_t c, uint32_t d, uint32_t par) {
  asm volatile("{\n.reg .b64 x, y;\n.reg .b128 z;\nmov.b64 x, {%1,%2};\nmov.b64 y, {%3,%4};\nmov.b128 z, {x, y};\nst.relaxed.gpu.global.b128 [%0], z;\n}"
               ::"l"(p), "r"((a & ~1u) | par), "r"(b), "r"(c), "r"(d) : "memory");
}
__device__ __forceinline__ uint4 lds128(uint32_t a) { uint4 v; asm volatile("ld.shared.v4.u32 {%0,%1,%2,%3}, [%4];" : "=r"(v.x), "=r"(v.y), "=r"(v.z), "=r"(v.w) : "r"(a)); return v; }
__device__ __forceinline__ float4 lds128f(uint32_t a) { float4 v; asm volatile("ld.shared.v4.f32 {%0,%1,%2,%3}, [%4];" : "=f"(v.x), "=f"(v.y), "=f"(v.z), "=f"(v.w) : "r"(a)); return v; }
__device__ __forceinline__ float4 lds128v(uint32_t a) { float4 v; asm volatile("ld.volatile.shared.v4.f32 {%0,%1,%2,%3}, [%4];" : "=f"(v.x), "=f"(v.y), "=f"(v.z), "=f"(v.w) : "r"(a) : "memory"); return v; }
__device__ __forceinline__ float lds32v(uint32_t a) { float v; asm volatile("ld.volatile.shared.f32 %0, [%1];" : "=f"(v) : "r"(a) : "memory"); return v; }
__device__ __forceinline__ float2 lds64f(uint32_t a) { float2 v; asm volatile("ld.shared.v2.f32 {%0,%1}, [%2];" : "=f"(v.x), "=f"(v.y) : "r"(a)); return v; }
__device__ __forceinline__ uint32_t lds32(uint32_t a) { uint32_t v; asm volatile("ld.shared.u32 %0, [%1];" : "=r"(v) : "r"(a)); return v; }
__device__ __forceinline__ void sts128(uint32_t a, uint32_t x, uint32_t y, uint32_t z, uint32_t w) { asm volatile("st.shared.v4.u32 [%0], {%1,%2,%3,%4};" ::"r"(a), "r"(x), "r"(y), "r"(z), "r"(w) : "memory"); }
__device__ __forceinline__ void sts128f(uint32_t a, float x, float y, float z, float w) { asm volatile("st.shared.v4.f32 [%0], {%1,%2,%3,%4};" ::"r"(a), "f"(x), "f"(y), "f"(z), "f"(w) : "memory"); }
__device__ __forceinline__ void sts32(uint32_t a, uint32_t x) { asm volatile("st.shared.u32 [%0], %1;" ::"r"(a), "r"(x) : "memory"); }
__device__ __forceinline__ void stsm4(uint32_t a, uint32_t r0, uint32_t r1, uint32_t r2, uint32_t r3) {
  asm volatile("stmatrix.sync.aligned.m8n8.x4.shared.b16 [%0], {%1,%2,%3,%4};" ::"r"(a), "r"(r0), "r"(r1), "r"(r2), "r"(r3) : "memory");
}
__device__ __forceinline__ uint4 ldsm4(uint32_t a) {
  uint4 v; asm volatile("ldmatrix.sync.aligned.m8n8.x4.shared.b16 {%0,%1,%2,%3}, [%4];" : "=r"(v.x), "=r"(v.y), "=r"(v.z), "=r"(v.w) : "r"(a) : "memory"); return v;
}
__device__ __forceinline__ uint32_t pack(float lo, float hi) { uint32_t r; asm("cvt.rn.bf16x2.f32 %0, %1, %2;" : "=r"(r) : "f"(hi), "f"(lo)); return r; }
__device__ __forceinline__ float bf_lo(uint32_t w) { return __uint_as_float(w << 16); }
__device__ __forceinline__ float bf_hi(uint32_t w) { return __uint_as_float(w & 0xffff0000u); }
__device__ __forceinline__ float bf_round(float x) { return bf_lo(pack(x, x)); }
__device__ __forceinline__ float ex2(float x) { float v; asm("ex2.approx.ftz.f32 %0, %1;" : "=f"(v) : "f"(x)); return v; }
__device__ __forceinline__ float rcp(float x) { float v; asm("rcp.approx.ftz.f32 %0, %1;" : "=f"(v) : "f"(x)); return v; }
__device__ __forceinline__ float addsat(float a, float b) { float v; asm("add.sat.f32 %0, %1, %2;" : "=f"(v) : "f"(a), "f"(b)); return v; }
__device__ __forceinline__ float phi2(float a) { return fmaf(fmaxf(a, 0.f), LN2, addsat(ex2(a), 1e-6f)); }
__device__ __forceinline__ uint32_t ln_bf16x2(uint32_t x, uint32_t m, uint32_t hi, uint32_t lo) {
  uint32_t o;
  asm("{\n.reg .b32 d, e;\nsub.rn.bf16x2 d, %1, %2;\nmul.rn.bf16x2 e, d, %4;\nfma.rn.bf16x2 %0, d, %3, e;\n}" : "=r"(o) : "r"(x), "r"(m), "r"(hi), "r"(lo));
  return o;
}
__device__ __forceinline__ float key_score(uint32_t key) { uint32_t u = key >> 16; u = (u & 0x8000u) ? (u & 0x7fffu) : (~u & 0xffffu); return __uint_as_float(u << 16); }
__device__ __forceinline__ int key_token(uint32_t key) { return 2047 - (int)((key >> 5) & 2047u); }
__device__ __forceinline__ uint32_t bsel(uint32_t a, uint32_t b, uint32_t m) { uint32_t r; asm("lop3.b32 %0, %1, %2, %3, 0xd8;" : "=r"(r) : "r"(a), "r"(b), "r"(m)); return r; }
__device__ __forceinline__ uint32_t prmt(uint32_t a, uint32_t b, uint32_t c) { uint32_t r; asm("prmt.b32 %0, %1, %2, %3;" : "=r"(r) : "r"(a), "r"(b), "r"(c)); return r; }
__device__ __forceinline__ uint32_t tagf(float v, uint32_t par) { return (__float_as_uint(v) & ~1u) | par; }
__device__ __forceinline__ float xred(float a, float b, bool up, int o) { return (up ? b : a) + __shfl_xor_sync(0xffffffffu, up ? a : b, o); }

#define STAMP(id)
#define STAMP_IF(c, id)
#define STAMP2(i)
#define LITE 1
#define LITE_MASK 0ull

template <bool TRANS>
__device__ __forceinline__ void mainloop(float (&a0)[64], float (&a1)[64], int s, int ph, int handoff, int gate, bool leader) {
  uint32_t prev = 0;
#pragma unroll 1
  for (int kt = 0; kt < 16; kt++) {
    mbar_wait(B_FULL + 8 * s, ph);
    if (gate && kt == GATE_KT) nb_sync(gate, 256);
    const uint64_t dw = mkdesc(RING, 8192, 1024, 1) + s * (SLOT >> 4), dx = mkdesc(RING + 16384, 16, 1024, 1) + s * (SLOT >> 4);
    wg_fence();
#pragma unroll
    for (int j = 0; j < 4; j++) {
      if (TRANS) {
        wgmma_n128_ss<1, 0>(a0, dw + j * 128, dx + j * 2, 1);
        wgmma_n128_ss<1, 0>(a1, dw + j * 128 + 512, dx + j * 2, 1);
      } else {
        wgmma_n128_ss<0, 1>(a0, dx + j * 2, dw + j * 128, 1);
        wgmma_n128_ss<0, 1>(a1, dx + j * 2 + 512, dw + j * 128, 1);
      }
    }
    wg_commit();
    if (handoff && kt == 15) nb_arrive(handoff, 256);
    wg_wait<1>();
    if (prev && leader) mbar_arrive(prev);
    prev = B_EMPTY + 8 * s;
    if (++s == NST) { s = 0; ph ^= 1; }
  }
  wg_wait<0>();
  if (leader) mbar_arrive(prev);
  reg_fence(a0);
  reg_fence(a1);
}

__device__ __forceinline__ int out_kblock(int r, int tn) {
  const int q = r - 2, half = q >= 7, pi = q - 7 * half;
  return r < 2 ? 2 * tn + r : 2 * (pi + (pi >= tn)) + half;
}

struct Params {
  const char *x, *wqkv, *w_r, *wg, *wu, *wd;
  CUtensorMap m_wqkv, m_x, m_xs, m_o, m_os, m_wo, m_gu, m_down, m_out;
};

template <bool BY_SMID>
__global__ void __launch_bounds__(512, 1) fused_kernel(const __grid_constant__ Params mp) {
  extern __shared__ __align__(1024) uint8_t smem_raw[];
#define CK(i)
  CK(0);
  uint32_t ck0 = 0;
  if (ALIGN) asm volatile("mov.u32 %0, %%clock;" : "=r"(ck0));
  const int tid = threadIdx.x, lane = tid & 31;
  const int w = __shfl_sync(0xffffffffu, tid >> 5, 0);
  int bid = blockIdx.x;
  if (BY_SMID) {
    uint32_t sm;
    asm volatile("mov.u32 %0, %%smid;" : "=r"(sm));
    const uint32_t p = sm >> 1, q = ((p - 32) * 37) >> 8;
    const uint32_t gpc = p < 32 ? p & 7 : p < 60 ? p - 31 - 7 * q : 0, tpc = p < 32 ? p >> 3 : p < 60 ? 4 + q : p - 58;
    bid = (p >> 1) == 30 ? 128 + ((0x9cu >> (2 * (sm & 3))) & 3) : ((0x75143620u >> (4 * gpc)) & 7) * 16 + tpc * 2 + (sm & 1);
  }
  const int tn = (bid & 3) + 4 * (bid >> 6), tm = (bid >> 2) & 15;

  CK(1);
  if (w == 0) {
#pragma unroll 1
    for (int s = 0; s < NST; s++) {
      asm volatile(ELECT "@p mbarrier.init.shared::cta.b64 [%0], 1;\n}" ::"r"(B_FULL + 8 * s) : "memory");
      if (bid < 128) {
        e_expect(B_FULL + 8 * s, 32768);
        e_tma2d(RING + s * SLOT + 16384, &mp.m_x, s * 64, tm * 128, B_FULL + 8 * s);
        e_tma3d(RING + s * SLOT, &mp.m_wqkv, s * 64, 16 + 2 * tn, B_FULL + 8 * s);
      }
      if (s == 0) CK(2);
    }
  }
  if (w == 1) e_pfmap(&mp.m_wqkv);
  if (w == 2) e_pfmap(&mp.m_xs);
  if (w >= 4) {
#pragma unroll 1
    for (uint32_t b = MISC + 8 * (w + 1); b < MISC + 8 * NBAR; b += 96)
      asm volatile(ELECT "@p mbarrier.init.shared::cta.b64 [%0], %1;\n}" ::"r"(b), "r"(b == B_CSDN ? 4 : 1) : "memory");
    if (w == 15) sts32(S_NCAND, 0);
  }
  CK(3);
  asm volatile("fence.mbarrier_init.release.cluster;" ::: "memory");
  __syncthreads();

  auto front = [&](int i0, int i1) {
#pragma unroll 1
    for (int i = i0; i < i1; i++) {
      const int c = (XS_ORD >> (4 * i)) & 3;
      if (i >= XS_FLY) mbar_wait(B_XS + 8 * (i - XS_FLY), 0);
      if (c == (tm >> 2)) {
        e_expect(B_WK, 16384);
        e_tma3d(FR, &mp.m_wqkv, tm * 64, 16 + 2 * tn, B_WK);
      }
      e_expect(B_XS + 8 * i, 8192);
      e_tma2d(STG + i * 8192, &mp.m_xs, c * 256, tm * 128 + tn * 16, B_XS + 8 * i);
    }
  };
  if (XS_EARLY && w == 5 && bid < 128) front(0, XS_EARLY);

  if (bid >= 128) {
    const int h0 = bid == 128 ? 14 : bid - 129, hs = bid == 128 ? 1 : 3, h1 = bid == 128 ? 16 : 14;
    if (w == 12) {
      int s = 0, ph = 1;
      if (bid == 128) mbar_wait(B_SEL, 0);
      else if (H_DELAY) __nanosleep(H_DELAY);
#pragma unroll 1
      for (int h = h0; h < h1; h += hs) {
        const int c = 2 * h + (h & 8) * 2;
#pragma unroll 1
        for (int kt = 0; kt < 16; kt += 2) {
          mbar_wait(B_EMPTY + 8 * s, ph);
          e_expect(B_FULL + 8 * s, 32768);
          e_tma3d(RING + s * SLOT, &mp.m_wqkv, kt * 64, c, B_FULL + 8 * s);
          e_tma3d(RING + s * SLOT + 16384, &mp.m_wqkv, kt * 64 + 64, c, B_FULL + 8 * s);
          if (++s == HST) { s = 0; ph ^= 1; }
        }
      }
    } else if (w < 4) {
      const uint32_t par = (ld_relaxed(&g_epoch) + 1) & 1u;
      sts32(S_ONES + tid * 4, 0x3f803f80u);
      fence_async_smem();
      nb_sync(NB_WG0, 128);
      int s = 0, ph = 0;
#pragma unroll 1
      for (int h = h0; h < h1; h += hs) {
        float c[4][4];
#pragma unroll
        for (int i = 0; i < 4; i++) reg_zero(c[i]);
        uint32_t prev = 0;
#pragma unroll 1
        for (int kt = 0; kt < 8; kt++) {
          mbar_wait(B_FULL + 8 * s, ph);
          const uint64_t dw = mkdesc(RING, 8192, 1024, 1) + s * (SLOT >> 4);
          wg_fence();
#pragma unroll
          for (int j = 0; j < 16; j++) wgmma_n8_ss<1, 0>(c[j & 3], dw + (j & 3) * 512 + (j >> 2) * 128, mkdesc(S_ONES, 128, 128, 0), 1);
          wg_commit();
          wg_wait<1>();
          if (prev && tid == 0) mbar_arrive(prev);
          prev = B_EMPTY + 8 * s;
          if (++s == HST) { s = 0; ph ^= 1; }
        }
        wg_wait<0>();
        if (tid == 0) mbar_arrive(prev);
#pragma unroll
        for (int i = 0; i < 4; i++) reg_fence(c[i]);
        const bool u2 = lane & 2, u1 = lane & 1;
        const float lo = u2 ? c[1][0] + c[3][0] : c[0][0] + c[2][0], hi = u2 ? c[1][2] + c[3][2] : c[0][2] + c[2][2];
        st_relaxed(g_csum + h * 128 + (lane & 2) * 32 + w * 16 + (lane & 1) * 8 + (lane >> 2), tagf(u1 ? hi : lo, par));
        STAMP_IF(tid == 0, h >= 8 ? 6 : 30);
      }
    } else if (w < 12 && bid == 128) {
      const int t = tid - 128, j = w - 4;
      const uint32_t ep = ld_relaxed(&g_epoch) + 1;
      uint32_t kk[16];
      poll_keys(kk, g_keys + t * 2, ep, 31u);
      const uint32_t k[8] = {kk[0], kk[2], kk[4], kk[6], kk[8], kk[10], kk[12], kk[14]};
      STAMP_IF(t == 0, 42);
      const uint32_t m = __reduce_max_sync(0xffffffffu, max(max(max(k[0], k[1]), max(k[2], k[3])), max(max(k[4], k[5]), max(k[6], k[7]))));
      if (lane == 0) sts32(S_WMAX + j * 4, m);
      nb_sync(NB_WG1, 256);
      const uint32_t T = __reduce_min_sync(0xffffffffu, lds32(S_WMAX + (lane & 7) * 4));
      uint32_t cnt = 0;
#pragma unroll
      for (int i = 0; i < 8; i++) cnt += k[i] >= T;
      if (cnt) {
        uint32_t pos;
        asm volatile("atom.shared.add.u32 %0, [%1], %2;" : "=r"(pos) : "r"(S_NCAND), "r"(cnt * 4) : "memory");
#pragma unroll
        for (int i = 0; i < 8; i++)
          if (k[i] >= T) { sts32(AUX + pos, k[i]); pos += 4; }
      }
      nb_sync(NB_WG1, 256);
      const uint32_t n4 = lds32(S_NCAND);
#pragma unroll 1
      for (uint32_t i = j * 4; i < n4; i += 32) {
        const uint32_t key = lds32(AUX + i);
        uint32_t rank = 0;
#pragma unroll 1
        for (uint32_t q = lane * 4; q < n4 + lane * 4; q += 128) rank += __popc(__ballot_sync(0xffffffffu, q < n4 && lds32(AUX + q) > key));
        if (rank < 8) sts32(S_SEL + rank * 4, key);
      }
      fence_async_smem();
      nb_sync(NB_WG1, 256);
      STAMP_IF(t == 0, 43);
      const uint32_t key = lds32(S_SEL + j * 4);
      const int tok = key_token(key);
      uint4 v[4];
#pragma unroll
      for (int q = 0; q < 4; q++) v[q] = __ldg(reinterpret_cast<const uint4*>(mp.x + tok * 2048) + q * 32 + lane);
      const uint32_t st = ld_relaxed(&g_keys[tok].y);
      const float rinv = rcp(bf_lo(st)), rhi = bf_round(rinv);
      const uint32_t m2 = __byte_perm(st, 0, 0x3232), hi = pack(rhi, rhi), lo = pack(rinv - rhi, rinv - rhi);
#pragma unroll
      for (int q = 0; q < 4; q++)
        *reinterpret_cast<uint4*>(g_xsel + (q * 8 + (lane >> 2)) * 128 + j * 16 + (((lane & 3) ^ (j >> 1)) << 2)) =
            make_uint4(ln_bf16x2(v[q].x, m2, hi, lo), ln_bf16x2(v[q].y, m2, hi, lo), ln_bf16x2(v[q].z, m2, hi, lo), ln_bf16x2(v[q].w, m2, hi, lo));
      if (lane == 0) g_xsel[4096 + j] = key;
      fence_async_glob();
      nb_sync(NB_WG1, 256);
      STAMP_IF(t == 0, 44);
      if (j == 0) { e_release(H_R, 0); e_arrive(B_SEL); }
      STAMP_IF(t == 0, 45);
    }
  } else if (w >= 12) {
    asm volatile("setmaxnreg.dec.sync.aligned.u32 32;");
    if (w == 12) {
      int s = 0, ph = 0;
#pragma unroll 1
      for (int it = NST; it < 48; it++) {
        const int c = (it < 32 ? (it & 16) + 16 : 0) + 2 * tn;
        mbar_wait(B_EMPTY + 8 * s, ph);
        e_expect(B_FULL + 8 * s, 32768);
        e_tma3d(RING + s * SLOT, &mp.m_wqkv, (it & 15) * 64, c, B_FULL + 8 * s);
        e_tma2d(RING + s * SLOT + 16384, &mp.m_x, (it & 15) * 64, tm * 128, B_FULL + 8 * s);
        if (it >= NST) STAMP2(it - NST);
        if (++s == NST) { s = 0; ph ^= 1; }
      }
#pragma unroll 1
      for (int r = 0; r < 16; r++) {
        const int kb = out_kblock(r, tn);
        mbar_wait(B_EMPTY + 8 * s, ph);
        e_expect(B_FULL + 8 * s, r < 2 ? 16384 : 32768);
        e_tma3d(RING + s * SLOT, &mp.m_wo, kb * 64, 2 * tn, B_FULL + 8 * s);
        if (r < 2) {
          e_expect(B_XRES + 8 * r, 16384);
          e_tma2d(RING + s * SLOT + 16384, &mp.m_x, kb * 64, tm * 128, B_XRES + 8 * r);
        }
        STAMP2(r + 48 - NST);
        if (++s == NST) { s = 0; ph ^= 1; }
      }
    } else if (w == 13) {
      if (XS_EARLY < XS_FLY) mbar_wait(B_FULL + 8 * XS_GO, 0);
      front(XS_EARLY, 4);
      {
        const char* pd = mp.wd + (bid & 15) * 128 + ((bid >> 4) * 448 + lane) * 2048;
        mbar_wait(B_XS + 24, 0);
        __nanosleep(PF_WAIT);
#pragma unroll 1
        for (int i = 0; i < 14; i++, pd += 65536) {
          if (PF_GAP) asm volatile("prefetch.global.L2 [%0];" ::"l"(pd));
          if (PF_GAP) __nanosleep(PF_GAP);
        }
      }
      nb_sync(NB_Z, 160);
      const uint32_t ep = lds32(S_EPOCH);
      {
        float z[4] = {0.f, 0.f, 0.f, 0.f};
        e_signal(H_Z + tn, tm);
        await(H_Z + tn, 0xffffu, ep);
#pragma unroll 1
        for (int i = 0; i < 4; i++) {
          uint32_t p[16];
          poll_z(p, g_z + i * 4096 + tn * 128 + lane * 4, ep, 1u);
#pragma unroll
          for (int q = 0; q < 4; q++) z[q] += (__uint_as_float(p[q]) + __uint_as_float(p[4 + q])) + (__uint_as_float(p[8 + q]) + __uint_as_float(p[12 + q]));
        }
        const uint32_t z01 = pack(z[0], z[1]), z23 = pack(z[2], z[3]);
#pragma unroll
        for (int i = 0; i < 4; i++) {
          const int n = 2 * i + (lane >> 4);
          asm volatile("st.shared.v2.u32 [%0], {%1,%2};" ::"r"(KVB_Z + n * 128 + ((((lane >> 1) & 7) ^ n) << 4) + (lane & 1) * 8), "r"(z01), "r"(z23) : "memory");
        }
        fence_async_smem();
        nb_arrive(NB_KVB, 288);
        STAMP_IF(lane == 0, 46);
      }
      nb_sync(NB_Q0, 192);
      e_store2d(&mp.m_os, tn * 128, tm * 128, STG);
      nb_sync(NB_OWN0, 288);
      e_store2d(&mp.m_os, tn * 128, tm * 128 + 64, STG + 8192);
      bulk_wait_read();
      e_signal(H_O + tm, 2 * tn);
      STAMP_IF(lane == 0, 4);
      nb_sync(NB_H1, 160);
      e_store2d(&mp.m_os, tn * 128 + 64, tm * 128, STG + 16384);
      e_store2d(&mp.m_os, tn * 128 + 64, tm * 128 + 64, STG + 24576);
      bulk_wait_read();
      e_signal(H_O + tm, 2 * tn + 1);
      STAMP_IF(lane == 0, 5);
#pragma unroll 1
      for (int i = 4; i < 14; i++) {
        const int q = (i + 2) >> 2;
        if (i == 4 || (i & 3) == 2) {
          if (i > 4) mbar_wait(B_OWN + 8 * (q - 2), 0);
          e_expect(B_DR + 8 * q, i == 4 ? 8192 : 16384);
        }
        e_tma2d_ef((i < 6 ? AUX - 16384 : STG - 24576) + i * 4096, &mp.m_down, (bid & 15) * 64, (bid >> 4) * 448 + i * 32, B_DR + 8 * q, EVICT_FIRST);
        if (DN_GAP) __nanosleep(DN_GAP);
      }
    } else if (w == 14) {
      e_pfmap(&mp.m_gu); e_pfmap(&mp.m_o); e_pfmap(&mp.m_os); e_pfmap(&mp.m_wo); e_pfmap(&mp.m_down); e_pfmap(&mp.m_out);
      const uint32_t ep = ld_relaxed(&g_epoch) + 1;
      nb_sync(NB_FDONE, 416);
      {
        uint32_t c[4];
        poll_quad(c, g_csum + tn * 128 + lane * 4, ep, 1u);
        sts128(S_CSQ + lane * 16, c[0], c[1], c[2], c[3]);
        nb_arrive(NB_CSQ, 160);
        poll_quad(c, g_csum + 1024 + tn * 128 + lane * 4, ep, 1u);
        sts128(S_CSV + lane * 16, c[0], c[1], c[2], c[3]);
        __syncwarp();
        e_arrive(B_CSV);
      }
      nb_sync(NB_Q0, 192);
      uint32_t ready = 0;
      int s = 0, ph = 1;
#pragma unroll 1
      for (int r = 2; r < 16; r++) {
        const int kb = out_kblock(r, tn);
        if (!((ready >> kb) & 1)) {
          uint32_t f[1];
          poll0(f, g_sig + (H_O + tm) * 32, 0u - (ep & 1u), 1u << kb);
          ready = f[0] ^ ((ep & 1u) - 1u);
        }
        mbar_wait(B_EMPTY + 8 * s, ph);
        e_tma2d(RING + s * SLOT + 16384, &mp.m_o, kb * 64, tm * 128, B_FULL + 8 * s);
        STAMP_IF(lane == 0 && r == 2, 2);
        STAMP_IF(lane == 0 && r == 9, 3);
        if (++s == NST) { s = 0; ph ^= 1; }
      }
    } else {
      uint32_t nsm = 132;
      if (BY_SMID) asm volatile("mov.u32 %0, %%nsmid;" : "=r"(nsm));
      asm volatile("{\n.reg .pred q;\nsetp.eq.u32 q, %0, 1156;\n@q bra LOK;\ntrap;\nLOK:\n}" ::"r"((uint32_t)__cvta_generic_to_shared(smem_raw) + nsm));
      const uint32_t ep = ld_relaxed(&g_epoch) + 1;
      mbar_wait(B_CSDN, 0);
#pragma unroll 1
      for (int n = 0; n < 5; n++) {
        __nanosleep(FFN_GAP);
        if (bid < 112) {
          e_expect(B_FR + 8 * n, 4608);
          e_tma3d_ef(GR + n * 4096, &mp.m_gu, bid * 32, n * 32, B_FR + 8 * n, EVICT_FIRST);
        }
      }
      uint32_t f[1];
      poll1(f, g_sig + H_R * 32, ep, 1u);
      fence_acq();
      fence_async_glob();
      if (bid < 112) {
#pragma unroll
        for (int n = 0; n < 5; n++) e_load(HOP + n * 512, g_xsel + n * 128, 512, B_FR + 8 * n);
      }
      e_expect(B_SEL, 32);
      e_load(S_SEL, g_xsel + 4096, 32, B_SEL);
      if (bid < 112) {
        int s = 0, ph = 0;
#pragma unroll 1
        for (int n = 5; n < 32; n++) {
          mbar_wait(B_FE + 8 * s, ph);
          e_expect(B_FR + 8 * s, 4608);
          e_tma3d_ef(GR + s * 4096, &mp.m_gu, bid * 32 , n * 32 , B_FR + 8 * s, EVICT_FIRST);
          e_load(HOP + s * 512, g_xsel + n * 128, 512, B_FR + 8 * s);
          STAMP2(64 + n);
          if (++s == 5) { s = 0; ph ^= 1; }
        }
      }
      e_expect(B_DR, 16384);
#pragma unroll 1
      for (int i = 1; i < 5; i++) {
        if (bid < 112) mbar_wait(B_FE + 8 * ((i & 3) + 1), i != 4);
        e_tma2d_ef(FR + (i & 3) * 4096, &mp.m_down, (bid & 15) * 64, (bid >> 4) * 448 + (i & 3) * 32, B_DR, EVICT_FIRST);
      }
    }
  } else if (w >= 8) {
    asm volatile("setmaxnreg.dec.sync.aligned.u32 56;");
    const int t = tid - 256, ww = w - 8;
    const uint32_t ep = ld_relaxed(&g_epoch) + 1, par = ep & 1u;
    {
      const int r0 = (lane >> 3) + (lane & 4);
      const uint32_t a = FR + (ww >> 1) * 8192 + r0 * 128 + ((((ww & 1) * 4 + (lane & 3)) ^ r0) << 4);
      float c[8];
      reg_zero(c);
      mbar_wait(B_WK, 0);
#pragma unroll 2
      for (int i = 0; i < 8; i++) {
        const uint4 v = lds128(a + i * 1024);
        c[0] += bf_lo(v.x); c[1] += bf_hi(v.x); c[2] += bf_lo(v.y); c[3] += bf_hi(v.y);
        c[4] += bf_lo(v.z); c[5] += bf_hi(v.z); c[6] += bf_lo(v.w); c[7] += bf_hi(v.w);
      }
      const bool u16 = lane & 16, u8 = lane & 8, u4 = lane & 4;
      const float d0 = xred(c[0], c[4], u16, 16), d1 = xred(c[1], c[5], u16, 16), d2 = xred(c[2], c[6], u16, 16), d3 = xred(c[3], c[7], u16, 16);
      fence_async_smem();
      e_arrive(B_CSDN);
      const float sum = xred(xred(d0, d2, u8, 8), xred(d1, d3, u8, 8), u4, 4);
      st_relaxed(g_csum + (2 + tm) * 1024 + tn * 128 + ww * 32 + (lane & 3) * 8 + (lane >> 2), tagf(sum, par));
      STAMP_IF(t == 0, 8);
      nb_sync(NB_WG2, 128);
      if (ww == 0) { e_signal(H_CS + tn, tm); await(H_CS + tn, 0xffffu, ep); }
      nb_sync(NB_WG2, 128);
      uint32_t p[16];
      poll16(p, g_csum + 2048 + tn * 128 + t, par, 1u);
      float tot = 0.f;
#pragma unroll
      for (int i = 0; i < 16; i += 4) tot += (__uint_as_float(p[i]) + __uint_as_float(p[i + 1])) + (__uint_as_float(p[i + 2]) + __uint_as_float(p[i + 3]));
      sts32(S_CSK + t * 4, __float_as_uint(tot));
      nb_arrive(NB_FDONE, 416);
      STAMP_IF(t == 0, 9);
    }
    const int ks = bid >> 4, nt = bid & 15;
    float fa[4] = {0.f, 0.f, 0.f, 0.f};
    if (bid < 112) {
      int s = 0, ph = 0;
      uint32_t prev = 0;
#pragma unroll 1
      for (int n = 0; n < 32; n++) {
        mbar_wait(B_FR + 8 * s, ph);
        const uint64_t da = mkdesc(GR, 2048, 512, 2) + s * 256, db = mkdesc(HOP, 16, 512, 2) + s * 32;
        wg_fence();
        wgmma_n8_ss<1, 0>(fa, da, db, 1);
        wgmma_n8_ss<1, 0>(fa, da + 64, db + 2, 1);
        wg_commit();
        wg_wait<1>();
        if (prev && t == 0) mbar_arrive(prev);
        prev = B_FE + 8 * s;
        if (++s == 5) { s = 0; ph ^= 1; }
      }
      wg_wait<0>();
      reg_fence(fa);
      if (t == 0) mbar_arrive(prev);
      STAMP_IF(t == 0, 12);
      const bool isup = (ww >> 1) != (mp.wu < mp.wg);
      if (isup) sts128f(GR + (t & 63) * 16, fa[0], fa[1], fa[2], fa[3]);
      nb_sync(NB_WG2, 128);
      if (!isup) {
        const float4 u = lds128f(GR + (t & 63) * 16);
        const float uu[4] = {u.x, u.y, u.z, u.w};
        uint32_t* hp = g_h + bid * 256 + (lane & 3) * 64 + (ww & 1) * 16 + (lane >> 2);
#pragma unroll
        for (int i = 0; i < 4; i++) {
          const float g = fa[i], hv = g * rcp(1.f + ex2(-g * LOG2E)) * uu[i];
          st_relaxed(hp + (i & 1) * 32 + (i >> 1) * 8, __byte_perm(pack(hv, hv), ep, 0x3254));
        }
      }
      nb_sync(NB_WG2, 128);
      if (ww == 0) e_signal(H_H + bid / 14, bid % 14);
      reg_zero(fa);
    }
    {
      uint32_t v[28];
      if (ww == 0) await(H_H + ks, 0x3fffu, ep);
      nb_sync(NB_WG2, 128);
      poll7x4(v, g_h + ks * 3584 + t * 4, ep, 0xffffu);
#pragma unroll
      for (int q = 0; q < 7; q++)
        asm volatile("st.shared.v2.u32 [%0], {%1,%2};" ::"r"(HOP + q * 1024 + (t >> 3) * 64 + ((((t >> 1) & 3) ^ ((t >> 4) & 3)) << 4) + (t & 1) * 8),
                     "r"(__byte_perm(v[4 * q], v[4 * q + 1], 0x7632)), "r"(__byte_perm(v[4 * q + 2], v[4 * q + 3], 0x7632)) : "memory");
      fence_async_smem();
      nb_sync(NB_WG2, 128);
    }
    STAMP_IF(t == 0, 13);
#pragma unroll 1
    for (int i = 0; i < 14; i += 2) {
      mbar_wait(B_DR + 8 * (i < 4 ? 0 : (i + 2) >> 2), 0);
      const uint64_t da = mkdesc(0, 4096, 1024, 1) + ((i < 4 ? FR : i < 6 ? AUX - 16384 : STG - 24576) >> 4) + i * 256;
      const uint64_t db = mkdesc(HOP, 16, 512, 2) + i * 32;
      wg_fence();
#pragma unroll
      for (int q = 0; q < 4; q++) wgmma_n8_ss<1, 0>(fa, da + q * 128, db + (q >> 1) * 32 + (q & 1) * 2, 1);
      wg_commit();
    }
    wg_wait<0>();
    reg_fence(fa);
    nb_arrive(NB_ST, 256);
    STAMP_IF(t == 0, 14);
    {
      uint32_t* yp = g_yp + (nt * 8 + ks) * 512 + (lane & 3) * 128 + ww * 16 + (lane >> 2);
#pragma unroll
      for (int i = 0; i < 4; i++) st_relaxed(yp + (i & 1) * 64 + (i >> 1) * 8, tagf(fa[i], par));
    }
    nb_sync(NB_WG2, 128);
    if (ww == 0) e_signal(H_Y + (nt >> 1), (nt & 1) * 8 + ks);
    mbar_wait(B_SEL, 0);
    const uint32_t mykey = lds32(S_SEL + (lane & 7) * 4);
    const uint32_t inmask = __ballot_sync(0xffffffffu, (key_token(mykey) >> 7) == tm) & 0xffu;
    if (inmask) {
      sts128(FR + t * 16, 0u, 0u, 0u, 0u);
      if (ww == 0) await(H_Y + tn, 0xffffu, ep);
      nb_sync(NB_WG2, 128);
      const float sg = rcp(1.f + ex2(-key_score(mykey) * LOG2E));
#pragma unroll 1
      for (int n = ww + 1; n <= __popc(inmask); n += 4) {
        const int j = __fns(inmask, 0, n);
        uint32_t p[32];
        poll8x4(p, g_yp + (tn * 2 + (lane >> 4)) * 4096 + j * 64 + (lane & 15) * 4, par, 1u);
        float y[4];
        const float sj = __shfl_sync(0xffffffffu, sg, j);
#pragma unroll
        for (int i = 0; i < 4; i++)
          y[i] = sj * (((__uint_as_float(p[i]) + __uint_as_float(p[4 + i])) + (__uint_as_float(p[8 + i]) + __uint_as_float(p[12 + i]))) +
                       ((__uint_as_float(p[16 + i]) + __uint_as_float(p[20 + i])) + (__uint_as_float(p[24 + i]) + __uint_as_float(p[28 + i]))));
        asm volatile("st.shared.v2.u32 [%0], {%1,%2};" ::"r"(FR + (lane >> 4) * 1024 + j * 128 + ((((lane >> 1) & 7) ^ j) << 4) + (lane & 1) * 8),
                     "r"(pack(y[0], y[1])), "r"(pack(y[2], y[3])) : "memory");
      }
      fence_async_smem();
      nb_arrive(NB_Y, 256);
    }
    STAMP_IF(t == 0, 15);
  } else if (w >= 4) {
    asm volatile("setmaxnreg.inc.sync.aligned.u32 208;");
    const int t = tid - 128, ww = w - 4, g = lane >> 2, t4 = lane & 3;
    const bool leader = t == 0;
    const uint32_t ep = ld_relaxed(&g_epoch) + 1, par = ep & 1u;
    {
      const uint4* wp = reinterpret_cast<const uint4*>(mp.w_r) + lane;
      uint4 w0 = __ldg(wp + (XS_ORD & 3) * 32), w1 = __ldg(wp + ((XS_ORD >> 4) & 3) * 32), w2 = __ldg(wp + ((XS_ORD >> 8) & 3) * 32), w3 = __ldg(wp + ((XS_ORD >> 12) & 3) * 32);
      if (leader) sts32(S_EPOCH, ep);
      if (KV_DIRECT && lane < 8) st_unit(g_kv + tn * 512 + tm * 32 + ww * 8 + lane, 0u, 0u, 0u, 0u, par ^ 1u);
      float s[4] = {0.f, 0.f, 0.f, 0.f}, q[4] = {0.f, 0.f, 0.f, 0.f}, d[4] = {0.f, 0.f, 0.f, 0.f}, wsum = 0.f;
#pragma unroll 1
      for (int c = 0; c < 4; c++) {
        const float wr[8] = {bf_lo(w0.x), bf_hi(w0.x), bf_lo(w0.y), bf_hi(w0.y), bf_lo(w0.z), bf_hi(w0.z), bf_lo(w0.w), bf_hi(w0.w)};
        w0 = w1; w1 = w2; w2 = w3;
        wsum += ((wr[0] + wr[1]) + (wr[2] + wr[3])) + ((wr[4] + wr[5]) + (wr[6] + wr[7]));
        mbar_wait(B_XS + 8 * c, 0);
#pragma unroll
        for (int r = 0; r < 4; r++) {
          const uint4 v = lds128(STG + c * 8192 + (ww * 4 + r) * 512 + lane * 16);
          const uint32_t xw[4] = {v.x, v.y, v.z, v.w};
#pragma unroll
          for (int i = 0; i < 4; i++) {
            const uint32_t dep = __float_as_uint(q[i ? r : (r + 3) & 3]);
            const float lo = POLITE ? __uint_as_float(prmt(xw[i], dep, 0x10ff)) : bf_lo(xw[i]), hi = POLITE ? __uint_as_float(prmt(xw[i], dep, 0x32ff)) : bf_hi(xw[i]);
            s[r] += lo; q[r] = fmaf(lo, lo, q[r]); d[r] = fmaf(lo, wr[2 * i], d[r]);
            s[r] += hi; q[r] = fmaf(hi, hi, q[r]); d[r] = fmaf(hi, wr[2 * i + 1], d[r]);
          }
        }
      }
      STAMP_IF(leader, 16);
      const bool u16 = lane & 16, u8 = lane & 8, u4 = lane & 4, u2 = lane & 2;
      const float s1 = xred(xred(s[0], s[2], u16, 16), xred(s[1], s[3], u16, 16), u8, 8);
      const float q1 = xred(xred(q[0], q[2], u16, 16), xred(q[1], q[3], u16, 16), u8, 8);
      const float d1 = xred(xred(d[0], d[2], u16, 16), xred(d[1], d[3], u16, 16), u8, 8);
      wsum += __shfl_xor_sync(0xffffffffu, wsum, 16);
      wsum += __shfl_xor_sync(0xffffffffu, wsum, 8);
      float tot = xred(xred(s1, d1, u4, 4), xred(q1, wsum, u4, 4), u2, 2);
      tot += __shfl_xor_sync(0xffffffffu, tot, 1);
      const float qq = __shfl_down_sync(0xffffffffu, tot, 2), dd = __shfl_down_sync(0xffffffffu, tot, 4), ws = __shfl_down_sync(0xffffffffu, tot, 6);
      if ((lane & 7) == 0) {
        const float mean = tot * (1.f / 1024.f);
        const float var = fmaxf(fmaf(-mean, mean, qq * (1.f / 1024.f)), 0.f);
        float sd;
        asm("sqrt.approx.ftz.f32 %0, %1;" : "=f"(sd) : "f"(bf_round(bf_round(var) + 1e-5f)));
        const uint32_t ms = pack(sd, mean);
        const int row = tm * 128 + tn * 16 + ww * 4 + (lane >> 3);
        const uint32_t rbits = pack(0.f, fmaf(-bf_hi(ms), ws, dd) * rcp(bf_lo(ms)));
        const uint32_t key = (rbits ^ (((int)rbits >> 31 & 0x7fff0000u) | 0x80000000u)) | ((2047 - row) << 5) | (ep & 31u);
        asm volatile("{\n.reg .b64 x;\nmov.b64 x, {%1,%2};\nst.relaxed.gpu.global.b64 [%0], x;\n}" ::"l"(g_keys + row), "r"(key), "r"(ms) : "memory");
      }
      STAMP_IF(leader, 17);
      __nanosleep(400);
      uint32_t st[2];
      poll_pair(st, g_keys + tm * 128 + t, ep, 31u);
      asm volatile("st.shared.v2.f32 [%0], {%1,%2};" ::"r"(S_KSTAT + t * 8), "f"(bf_hi(st[1])), "f"(rcp(bf_lo(st[1])) * LOG2E) : "memory");
      nb_arrive(NB_FDONE, 416);
      STAMP_IF(leader, 10);
    }
    float a0[64], a1[64];
    reg_zero(a0); reg_zero(a1); reg_fence(a0); reg_fence(a1);
    STAMP_IF(leader, 18);
    nb_sync(NB_KV, 256);
    mainloop<true>(a0, a1, 1, 1, NB_VQ, 0, leader);
    STAMP_IF(leader, 19);
    {
      uint32_t f0[32], f1[32];
#pragma unroll
      for (int i = 0; i < 32; i++) { f0[i] = pack(a0[2 * i], a0[2 * i + 1]); f1[i] = pack(a1[2 * i], a1[2 * i + 1]); }
      float c0[32], c1[32];
      reg_zero(c0); reg_zero(c1);
      nb_sync(NB_PK, 256);
      constexpr uint64_t db = mkdesc(STG, 16, 1024, 1);
      wg_fence();
#pragma unroll
      for (int k = 0; k < 8; k++) {
        wgmma_n64_rs<0>(c0, f0[4 * k], f0[4 * k + 1], f0[4 * k + 2], f0[4 * k + 3], db + (k >> 2) * 1024 + (k & 3) * 2, k != 0);
        wgmma_n64_rs<0>(c1, f1[4 * k], f1[4 * k + 1], f1[4 * k + 2], f1[4 * k + 3], db + (k >> 2) * 1024 + (k & 3) * 2 + 512, k != 0);
        if (GATE_KT && k == GATE_K) nb_arrive(NB_KV, 256);
      }
      wg_commit();
      const bool hp = ww >> 1;
      float c[4];
      float2 tt[8];
#pragma unroll
      for (int i = 0; i < 8; i++) tt[i] = lds64f(S_CSK + ((i >> 2) * 64 + hp * 32 + (i & 3) * 8 + 2 * t4) * 4);
      mbar_wait(B_CSV, 0);
#pragma unroll
      for (int i = 0; i < 4; i++) c[i] = -__uint_as_float(lds32(S_CSV + ((i >> 1) * 64 + ww * 16 + (i & 1) * 8 + g) * 4));
      wg_wait<0>();
      reg_fence(c0);
      reg_fence(c1);
      STAMP_IF(leader, 20);
      uint4* pp = g_kvp + (tn * 16 + tm) * 512 + t;
      auto put = [&](int q, const float* d) {
        const float ca = c[q & 2], cb = c[q | 1];
        const float2 ta = tt[2 * q], tb = tt[2 * q + 1];
        st_unit(pp + q * 128, pack(fmaf(ca, ta.x, d[0]), fmaf(ca, ta.y, d[1])), pack(fmaf(cb, ta.x, d[2]), fmaf(cb, ta.y, d[3])),
                pack(fmaf(ca, tb.x, d[4]), fmaf(ca, tb.y, d[5])), pack(fmaf(cb, tb.x, d[6]), fmaf(cb, tb.y, d[7])), par);
      };
      if (!hp) { put(0, c0); put(1, c0 + 8); put(2, c1); put(3, c1 + 8); }
      else { put(0, c0 + 16); put(1, c0 + 24); put(2, c1 + 16); put(3, c1 + 24); }
      STAMP_IF(leader, 47);
      {
        uint32_t p[16];
        nb_sync(NB_WG1, 128);
        if (ww == 0) { e_signal(H_KVP + tn, tm); await(H_KVP + tn, 0xffffu, ep); }
        nb_sync(NB_WG1, 128);
        STAMP_IF(leader, 1);
        poll_kvp(p, g_kvp + (tn * 16 + (lane >> 3) * 4) * 512 + tm * 32 + ww * 8 + (lane & 7), par, 1u);
        float r[8];
#pragma unroll
        for (int i = 0; i < 4; i++) {
          r[2 * i] = (bf_lo(p[i]) + bf_lo(p[4 + i])) + (bf_lo(p[8 + i]) + bf_lo(p[12 + i]));
          r[2 * i + 1] = (bf_hi(p[i]) + bf_hi(p[4 + i])) + (bf_hi(p[8 + i]) + bf_hi(p[12 + i]));
        }
#pragma unroll
        for (int i = 0; i < 8; i++) r[i] += __shfl_xor_sync(0xffffffffu, r[i], 8);
#pragma unroll
        for (int i = 0; i < 8; i++) r[i] += __shfl_xor_sync(0xffffffffu, r[i], 16);
        if (lane < 8) st_unit(g_kv + tn * 512 + tm * 32 + ww * 8 + lane, pack(r[0], r[1]), pack(r[2], r[3]), pack(r[4], r[5]), pack(r[6], r[7]), par);
      }
      STAMP_IF(leader, 21);
    }
    const uint32_t sx = lane & 7, sc = lane >> 4;
    const uint32_t sa = STG + (ww * 16 + (lane & 15)) * 128;
    const uint32_t sw[4] = {sa + ((sc ^ sx) << 4), sa + (((2 + sc) ^ sx) << 4), sa + (((4 + sc) ^ sx) << 4), sa + (((6 + sc) ^ sx) << 4)};
    {
      uint32_t v[16];
      if (!KV_DIRECT) {
        nb_sync(NB_WG1, 128);
        if (ww == 0) { e_signal(H_KV + tn, tm); await(H_KV + tn, 0xffffu, ep); }
        nb_sync(NB_WG1, 128);
      } else {
        __nanosleep(KV_DIRECT);
      }
      STAMP_IF(leader, 7);
      poll_kv(v, g_kv + tn * 512 + t, par, 1u);
      STAMP_IF(leader, 23);
#pragma unroll
      for (int q = 0; q < 4; q++)
        stsm4((q < 2 ? KVB_P0 : KVB_P1) + ((ww & 1) * 16 + (lane & 15)) * 128 + ((((ww >> 1) * 4 + (q & 1) * 2 + sc) ^ sx) << 4),
              v[4 * q], v[4 * q + 1], v[4 * q + 2], v[4 * q + 3]);
      fence_async_smem();
      nb_arrive(NB_KVB, 288);
    }
    STAMP_IF(leader, 24);
    uint32_t oh[4];
    uint32_t inmask;
    {
      mbar_wait(B_SEL, 0);
      const int r0 = key_token(lds32(S_SEL + t4 * 8)) - tm * 128, r1 = key_token(lds32(S_SEL + t4 * 8 + 4)) - tm * 128;
#pragma unroll
      for (int i = 0; i < 4; i++) {
        const int row = (i >> 1) * 64 + ww * 16 + (i & 1) * 8 + g;
        oh[i] = (r0 == row ? 0x3f00u : 0u) | (r1 == row ? 0x3f000000u : 0u);
      }
      inmask = __ballot_sync(0xffffffffu, (unsigned)r0 < 128u || (unsigned)r1 < 128u);
    }
    uint32_t va = RING + 16384 + sc * 8192 + (ww * 16 + (lane & 8)) * 128 + sx * 16 + (lane >> 3) * 4;
    asm volatile("" : "+r"(va));
    {
      float ka[4], kb[4];
#pragma unroll
      for (int i = 0; i < 4; i++) {
        const float2 st = lds64f(S_KSTAT + ((i >> 1) * 64 + ww * 16 + (i & 1) * 8 + g) * 8);
        const float r = st.y * LN2;
        ka[i] = 1.f + r; kb[i] = -st.x * r;
      }
      constexpr uint32_t XOFF = RING + 3 * SLOT + 16384 - STG;
#pragma unroll
      for (int j = 0; j < 8; j++) {
        if ((j & 3) == 0) mbar_wait(B_XRES + 8 * (j >> 2), 0);
        const uint4 v = ldsm4(sw[j & 3] + XOFF + (j >> 2) * SLOT), u = ldsm4(sw[j & 3] + XOFF + (j >> 2) * SLOT + 8192);
        const uint32_t vv[4] = {v.x, v.y, v.z, v.w}, uu[4] = {u.x, u.y, u.z, u.w};
#pragma unroll
        for (int i = 0; i < 4; i++) {
          a0[8 * j + 2 * i] = fmaf(bf_lo(vv[i]), ka[i & 1], kb[i & 1]);
          a0[8 * j + 2 * i + 1] = fmaf(bf_hi(vv[i]), ka[i & 1], kb[i & 1]);
          a1[8 * j + 2 * i] = fmaf(bf_lo(uu[i]), ka[2 + (i & 1)], kb[2 + (i & 1)]);
          a1[8 * j + 2 * i + 1] = fmaf(bf_hi(uu[i]), ka[2 + (i & 1)], kb[2 + (i & 1)]);
        }
      }
      reg_fence(a0);
      reg_fence(a1);
      fence_async_smem();
      STAMP_IF(leader, 22);
    }
    {
      auto own = [&](int r) {
        nb_sync(NB_OWN0 + r, r ? 256 : 288);
        mbar_wait(B_FULL + 8 * (3 + r), 1);
        STAMP_IF(leader, 25 + r);
        const uint64_t dw = mkdesc(RING + (3 + r) * SLOT, 8192, 1024, 1), dx = mkdesc(STG + r * 16384, 16, 1024, 1);
        wg_fence();
#pragma unroll
        for (int j = 0; j < 4; j++) {
          wgmma_n128_ss<0, 1>(a0, dx + j * 2, dw + j * 128, 1);
          wgmma_n128_ss<0, 1>(a1, dx + j * 2 + 512, dw + j * 128, 1);
        }
        wg_commit();
      };
      own(0);
      wg_wait<0>();
      if (leader) { mbar_arrive(B_EMPTY + 24); mbar_arrive(B_OWN); }
      own(1);
      int s = 0, ph = 0;
      uint32_t prev = B_EMPTY + 32;
#pragma unroll 1
      for (int r = 2; r < 16; r++) {
        mbar_wait(B_FULL + 8 * s, ph);
        {
          uint32_t bad;
          asm volatile("{\n.reg .u32 a, b, c, d, e, f, g, h;\n.reg .pred p;\n"
                       "ld.shared.u32 a, [%1];\nld.shared.u32 b, [%1+128];\nld.shared.u32 c, [%1+256];\nld.shared.u32 d, [%1+384];\n"
                       "ld.shared.u32 e, [%1+512];\nld.shared.u32 f, [%1+640];\nld.shared.u32 g, [%1+768];\nld.shared.u32 h, [%1+896];\n"
                       "lop3.b32 a, a, b, %2, 0x7e;\nlop3.b32 c, c, d, %2, 0x7e;\nlop3.b32 e, e, f, %2, 0x7e;\nlop3.b32 g, g, h, %2, 0x7e;\n"
                       "lop3.b32 a, a, c, e, 0xfe;\nlop3.b32 a, a, g, 1, 0xa8;\nsetp.ne.u32 p, a, 0;\nvote.sync.any.pred p, p, 0xffffffff;\nselp.u32 %0, 1, 0, p;\n}"
                       : "=r"(bad) : "r"(va + s * SLOT), "r"(par) : "memory");
          if (bad) {
            const uint4* src = reinterpret_cast<const uint4*>(g_o + (tm * 128 + sc * 64 + ww * 16 + (lane & 15)) * 1024 + out_kblock(r, tn) * 64);
#pragma unroll 1
            for (int i = 0; i < 8; i++) {
              uint32_t v[4];
              asm volatile("{\n.reg .b64 x, y;\n.reg .b128 z;\n.reg .pred p, q, h;\n.reg .u32 c, b;\nmov.u32 c, 0;\nsetp.ne.u32 h, %6, 0;\nLW:\n"
                           "ld.relaxed.gpu.global.b128 z, [%4];\nmov.b128 {x, y}, z;\nmov.b64 {%0,%1}, x;\nmov.b64 {%2,%3}, y;\n"
                           "selp.b64 x, y, x, h;\nshr.b64 x, x, %7;\ncvt.u32.u64 b, x;\nand.b32 b, b, 1;\nsetp.eq.u32 p, b, %5;\n"
                           "vote.sync.all.pred p, p, 0xffffffff;\n@p bra.uni LD;\nadd.u32 c, c, 1;\nsetp.lt.u32 q, c, 1000000;\n@q bra.uni LW;\ntrap;\nLD:\n}"
                           : "=&r"(v[0]), "=&r"(v[1]), "=&r"(v[2]), "=&r"(v[3]) : "l"(src + i), "r"(par), "r"(sc), "r"((lane & 8) * 4) : "memory");
              sts128(RING + 16384 + s * SLOT + sc * 8192 + (ww * 16 + (lane & 15)) * 128 + ((i ^ sx) << 4), v[0], v[1], v[2], v[3]);
            }
            fence_async_smem();
            __syncwarp();
          }
        }
        if (!LITE || ((LITE_MASK >> 27) & 1)) STAMP_IF(leader && r == 2, 27);
        const uint64_t dw = mkdesc(RING, 8192, 1024, 1) + s * (SLOT >> 4), dx = mkdesc(RING + 16384, 16, 1024, 1) + s * (SLOT >> 4);
        wg_fence();
#pragma unroll
        for (int j = 0; j < 4; j++) {
          wgmma_n128_ss<0, 1>(a0, dx + j * 2, dw + j * 128, 1);
          wgmma_n128_ss<0, 1>(a1, dx + j * 2 + 512, dw + j * 128, 1);
        }
        wg_commit();
        wg_wait<1>();
        if (leader) mbar_arrive(prev);
        if (leader && r == 2) mbar_arrive(B_OWN + 8);
        prev = B_EMPTY + 8 * s;
        if (++s == NST) { s = 0; ph ^= 1; }
      }
      if (inmask) {
        nb_sync(NB_Y, 256);
        wg_fence();
        wgmma_n128_rs<1>(a0, oh[0], oh[1], oh[0], oh[1], mkdesc(FR, 1024, 0, 1), 1);
        wgmma_n128_rs<1>(a1, oh[2], oh[3], oh[2], oh[3], mkdesc(FR, 1024, 0, 1), 1);
        wg_commit();
      }
      nb_sync(NB_ST, 256);
      wg_wait<0>();
      reg_fence(a0);
      reg_fence(a1);
    }
    STAMP_IF(leader, 28);
#pragma unroll
    for (int c = 0; c < 2; c++) {
#pragma unroll
      for (int j = 4 * c; j < 4 * c + 4; j++) {
        stsm4(sw[j & 3] + c * 16384, pack(a0[8 * j], a0[8 * j + 1]), pack(a0[8 * j + 2], a0[8 * j + 3]), pack(a0[8 * j + 4], a0[8 * j + 5]), pack(a0[8 * j + 6], a0[8 * j + 7]));
        stsm4(sw[j & 3] + c * 16384 + 8192, pack(a1[8 * j], a1[8 * j + 1]), pack(a1[8 * j + 2], a1[8 * j + 3]), pack(a1[8 * j + 4], a1[8 * j + 5]), pack(a1[8 * j + 6], a1[8 * j + 7]));
      }
      fence_async_smem();
      e_store2d(&mp.m_out, tn * 128 + c * 64, tm * 128 + ww * 16, STG + c * 16384 + ww * 2048);
      e_store2d(&mp.m_out, tn * 128 + c * 64, tm * 128 + 64 + ww * 16, STG + c * 16384 + 8192 + ww * 2048);
    }
    bulk_wait_read();
    if (bid == 0 && leader) st_relaxed(&g_epoch, ep);
    STAMP_IF(leader, 29);
  } else {
    asm volatile("setmaxnreg.inc.sync.aligned.u32 216;");
    const int g = lane >> 2, t4 = lane & 3;
    const bool leader = tid == 0;
    const uint32_t sx = lane & 7, sc = lane >> 4;
    const uint32_t sa = STG + (w * 16 + (lane & 15)) * 128;
    const uint32_t sw[4] = {sa + ((sc ^ sx) << 4), sa + (((2 + sc) ^ sx) << 4), sa + (((4 + sc) ^ sx) << 4), sa + (((6 + sc) ^ sx) << 4)};
    float a0[64], a1[64];
    reg_zero(a0); reg_zero(a1); reg_fence(a0); reg_fence(a1);
    if (ALIGN) { uint32_t now; do { asm volatile("mov.u32 %0, %%clock;" : "=r"(now)); } while ((int)(now - ck0) < ALIGN); }
    mainloop<true>(a0, a1, 0, 0, NB_KV, 0, leader);
    STAMP_IF(leader, 33);
    {
      nb_sync(NB_FDONE, 416);
      STAMP_IF(leader, 34);
      float c[4], z[4] = {0.f, 0.f, 0.f, 0.f}, tt[4] = {0.f, 0.f, 0.f, 0.f};
#pragma unroll
      for (int i = 0; i < 4; i++) c[i] = -__uint_as_float(lds32(S_CSK + ((i >> 1) * 64 + w * 16 + (i & 1) * 8 + g) * 4));
#pragma unroll
      for (int j = 0; j < 8; j++) {
        const float4 s0 = lds128v(S_KSTAT + (j * 16 + 2 * t4) * 8), s1 = lds128v(S_KSTAT + (j * 16 + 8 + 2 * t4) * 8);
        const float mu[4] = {s0.x, s0.z, s1.x, s1.z}, rl[4] = {s0.y, s0.w, s1.y, s1.w};
#pragma unroll
        for (int m = 0; m < 2; m++) {
          float p[8];
#pragma unroll
          for (int i = 0; i < 8; i++) {
            const int r = m * 2 + ((i >> 1) & 1), cc = (i >> 2) * 2 + (i & 1);
            p[i] = phi2(fmaf(c[r], mu[cc], m ? a1[8 * j + i] : a0[8 * j + i]) * rl[cc]);
            z[r] += p[i];
            p[i] *= rl[cc];
            tt[r] = fmaf(p[i], mu[cc], tt[r]);
          }
          stsm4(sw[j & 3] + (j >> 2) * 16384 + m * 8192, pack(p[0], p[1]), pack(p[2], p[3]), pack(p[4], p[5]), pack(p[6], p[7]));
        }
      }
      const bool u2 = lane & 2, u1 = lane & 1;
      const float zz = xred(xred(z[0], z[2], u2, 2), xred(z[1], z[3], u2, 2), u1, 1);
      sts32(S_CSK + ((t4 >> 1) * 64 + w * 16 + (t4 & 1) * 8 + g) * 4, __float_as_uint(xred(xred(tt[0], tt[2], u2, 2), xred(tt[1], tt[3], u2, 2), u1, 1)));
      fence_async_smem();
      nb_arrive(NB_PK, 256);
      st_relaxed(g_z + tm * 1024 + tn * 128 + (t4 >> 1) * 64 + w * 16 + (t4 & 1) * 8 + g, tagf(zz * LOG2E, lds32(S_EPOCH) & 1u));
      nb_arrive(NB_Z, 160);
    }
    STAMP_IF(leader, 35);
    float rl0[2];
    const uint32_t ep = lds32(S_EPOCH);
    {
      nb_sync(NB_CSQ, 160);
      float mu[4];
#pragma unroll
      for (int i = 0; i < 4; i++) {
        const float2 st = lds64f(S_KSTAT + ((i >> 1) * 64 + w * 16 + (i & 1) * 8 + g) * 8);
        mu[i] = -st.x;
        if (i < 2) rl0[i] = st.y;
      }
#pragma unroll
      for (int j = 0; j < 16; j++) {
        const float2 c = lds64f(S_CSQ + (j * 8 + 2 * t4) * 4);
        a0[4 * j] = mu[0] * c.x; a0[4 * j + 1] = mu[0] * c.y; a0[4 * j + 2] = mu[1] * c.x; a0[4 * j + 3] = mu[1] * c.y;
        a1[4 * j] = mu[2] * c.x; a1[4 * j + 1] = mu[2] * c.y; a1[4 * j + 2] = mu[3] * c.x; a1[4 * j + 3] = mu[3] * c.y;
      }
      reg_fence(a0); reg_fence(a1);
    }
    STAMP_IF(leader, 40);
    nb_sync(NB_VQ, 256);
    mainloop<false>(a0, a1, 2, 0, 0, GATE_KT ? NB_KV : 0, leader);
    STAMP_IF(leader, 36);
    {
      uint32_t f[2][16];
      float oc[2][2][20];
      auto phi = [&](const float (&a)[64], int j, int m, uint32_t (&o)[16]) {
        float rl[2] = {rl0[0], rl0[1]};
        if (j | m) { rl[0] = lds32v(S_KSTAT + (m * 64 + w * 16 + g) * 8 + 4); rl[1] = lds32v(S_KSTAT + (m * 64 + w * 16 + 8 + g) * 8 + 4); }
#pragma unroll
        for (int i = 0; i < 16; i++) o[i] = pack(phi2(a[32 * j + 2 * i] * rl[i & 1]), phi2(a[32 * j + 2 * i + 1] * rl[i & 1]));
      };
      auto mma = [&](int j, const uint32_t (&a)[16], float (&o)[2][20]) {
        const uint64_t db = mkdesc(j ? KVB_Z : KVB_P0, 16, 1024, 1);
        reg_zero(o[0]); reg_zero(o[1]);
        wg_fence();
        wgmma_n40_rs<0>(o[0], a[0], a[1], a[2], a[3], db, 0);
        wgmma_n40_rs<0>(o[1], a[8], a[9], a[10], a[11], db + 4, 0);
        wgmma_n40_rs<0>(o[0], a[4], a[5], a[6], a[7], db + 2, 1);
        wgmma_n40_rs<0>(o[1], a[12], a[13], a[14], a[15], db + 6, 1);
        wg_commit();
      };
      auto fin = [&](int j, int m, float (&o)[2][20]) {
        const uint32_t m0 = t4 == 2 * m, m1 = t4 == 2 * m + 1;
#pragma unroll
        for (int h = 0; h < 2; h++) {
          const float r0 = rcp(o[h][j ? 1 : 16] + 1e-6f * LOG2E), r1 = rcp(o[h][j ? 3 : 18] + 1e-6f * LOG2E);
          const int b = j ? 4 : 0;
#pragma unroll
          for (int q = 0; q < 2; q++)
            stsm4(sw[h * 2 + q] + j * 16384 + m * 8192,
                  bsel(pack(o[h][b + 8 * q] * r0, o[h][b + 8 * q + 1] * r0), ep, m0), bsel(pack(o[h][b + 8 * q + 2] * r1, o[h][b + 8 * q + 3] * r1), ep, m1),
                  bsel(pack(o[h][b + 8 * q + 4] * r0, o[h][b + 8 * q + 5] * r0), ep, m0), bsel(pack(o[h][b + 8 * q + 6] * r1, o[h][b + 8 * q + 7] * r1), ep, m1));
        }
      };
#pragma unroll
      for (int j = 0; j < 2; j++) {
        phi(a0, j, 0, f[0]);
        if (j == 0) nb_sync(NB_KVB, 288);
        STAMP_IF(leader && j == 0, 37);
        mma(j, f[0], oc[0]);
        phi(a1, j, 1, f[1]);
        wg_wait<0>();
        reg_fence(oc[0][0]); reg_fence(oc[0][1]);
        mma(j, f[1], oc[1]);
        fin(j, 0, oc[0]);
        if (j == 0) { fence_async_smem(); nb_arrive(NB_Q0, 192); }
        wg_wait<0>();
        reg_fence(oc[1][0]); reg_fence(oc[1][1]);
        fin(j, 1, oc[1]);
        fence_async_smem();
        if (j == 0) nb_arrive(NB_OWN0, 288);
        else { nb_arrive(NB_OWN1, 256); nb_arrive(NB_H1, 160); }
        STAMP_IF(leader, 38 + j);
      }
    }
  }
}

#undef CK
typedef CUresult (*EncodeFn)(CUtensorMap*, CUtensorMapDataType, cuuint32_t, void*, const cuuint64_t*, const cuuint64_t*, const cuuint32_t*,
                             const cuuint32_t*, CUtensorMapInterleave, CUtensorMapSwizzle, CUtensorMapL2promotion, CUtensorMapFloatOOBfill);

void make_map(EncodeFn enc, CUtensorMap* m, const void* p, int rank, uint64_t d0, uint64_t d1, uint64_t d2, uint64_t s1, uint64_t s2,
              uint32_t b0, uint32_t b1, uint32_t b2, CUtensorMapSwizzle sw) {
  cuuint64_t gd[3] = {d0, d1, d2}, gs[2] = {s1, s2};
  cuuint32_t bd[3] = {b0, b1, b2}, es[3] = {1, 1, 1};
  enc(m, CU_TENSOR_MAP_DATA_TYPE_BFLOAT16, rank, const_cast<void*>(p), gd, gs, bd, es, CU_TENSOR_MAP_INTERLEAVE_NONE, sw,
      CU_TENSOR_MAP_L2_PROMOTION_L2_128B, CU_TENSOR_MAP_FLOAT_OOB_FILL_NONE);
}

}

extern "C" void kernel_launch(void* const* d_in, const int* in_sizes, int n_in, void* d_out, int out_size) {
  (void)in_sizes; (void)n_in; (void)out_size;
  void* fn = nullptr;
  cudaDriverEntryPointQueryResult qr;
  cudaGetDriverEntryPoint("cuTensorMapEncodeTiled", &fn, cudaEnableDefault, &qr);
  EncodeFn enc = (EncodeFn)fn;
  void* o;
  cudaGetSymbolAddress(&o, g_o);
  const CUtensorMapSwizzle S128 = CU_TENSOR_MAP_SWIZZLE_128B, S64 = CU_TENSOR_MAP_SWIZZLE_64B, S0 = CU_TENSOR_MAP_SWIZZLE_NONE;
  Params mp;
  mp.x = (const char*)d_in[0]; mp.wqkv = (const char*)d_in[1]; mp.w_r = (const char*)d_in[4];
  mp.wg = (const char*)d_in[5]; mp.wu = (const char*)d_in[6]; mp.wd = (const char*)d_in[7];
  make_map(enc, &mp.m_wqkv, d_in[1], 3, 64, 1024, 48, 6144, 128, 64, 64, 2, S128);
  make_map(enc, &mp.m_x, d_in[0], 2, 1024, 2048, 1, 2048, 0, 64, 128, 1, S128);
  make_map(enc, &mp.m_os, o, 2, 1024, 2048, 1, 2048, 0, 64, 64, 1, S128);
  make_map(enc, &mp.m_o, o, 2, 1024, 2048, 1, 2048, 0, 64, 128, 1, S128);
  make_map(enc, &mp.m_wo, d_in[2], 3, 64, 1024, 16, 2048, 128, 64, 64, 2, S128);
  make_map(enc, &mp.m_xs, d_in[0], 2, 1024, 2048, 1, 2048, 0, 256, 16, 1, S0);
  const char *wg = (const char*)d_in[5], *wu = (const char*)d_in[6];
  make_map(enc, &mp.m_gu, wu < wg ? wu : wg, 3, 3584, 1024, 2, 7168, (uint64_t)(wu < wg ? wg - wu : wu - wg), 32, 32, 2, S64);
  make_map(enc, &mp.m_down, d_in[7], 2, 1024, 3584, 1, 2048, 0, 64, 32, 1, S128);
  make_map(enc, &mp.m_out, d_out, 2, 1024, 2048, 1, 2048, 0, 64, 16, 1, S128);
  int dev = 0, sms = 0;
  cudaGetDevice(&dev);
  cudaDeviceGetAttribute(&sms, cudaDevAttrMultiProcessorCount, dev);
  auto kern = sms == 132 ? fused_kernel<true> : fused_kernel<false>;
  cudaFuncSetAttribute(kern, cudaFuncAttributeMaxDynamicSharedMemorySize, SMEM_BYTES);
  kern<<<132, 512, SMEM_BYTES>>>(mp);
}
```

```cpp
#include <cuda_runtime.h>
#include <cuda.h>
#include <cuda_bf16.h>
#include <stdint.h>

namespace {

template <int TA, int TB>
__device__ __forceinline__ void wgmma_n8_ss(float (&d)[4], uint64_t da, uint64_t db, int sc) {
  asm volatile("{\n.reg .pred p;\nsetp.ne.b32 p, %6, 0;\n"
    "wgmma.mma_async.sync.aligned.m64n8k16.f32.bf16.bf16 {%0, %1, %2, %3}, %4, %5, p, 1, 1, %7, %8;\n}\n"
    : "+f"(d[0]), "+f"(d[1]), "+f"(d[2]), "+f"(d[3])
    : "l"(da), "l"(db), "r"(sc), "n"(TA), "n"(TB));
}
template <int TA, int TB>
__device__ __forceinline__ void wgmma_n16_ss(float (&d)[8], uint64_t da, uint64_t db, int sc) {
  asm volatile("{\n.reg .pred p;\nsetp.ne.b32 p, %10, 0;\n"
    "wgmma.mma_async.sync.aligned.m64n16k16.f32.bf16.bf16 {%0, %1, %2, %3, %4, %5, %6, %7}, %8, %9, p, 1, 1, %11, %12;\n}\n"
    : "+f"(d[0]), "+f"(d[1]), "+f"(d[2]), "+f"(d[3]), "+f"(d[4]), "+f"(d[5]), "+f"(d[6]), "+f"(d[7])
    : "l"(da), "l"(db), "r"(sc), "n"(TA), "n"(TB));
}
template <int TB>
__device__ __forceinline__ void wgmma_n40_rs(float (&d)[20], uint32_t a0, uint32_t a1, uint32_t a2, uint32_t a3, uint64_t db, int sc) {
  asm volatile("{\n.reg .pred p;\nsetp.ne.b32 p, %25, 0;\n"
    "wgmma.mma_async.sync.aligned.m64n40k16.f32.bf16.bf16 {%0, %1, %2, %3, %4, %5, %6, %7, %8, %9, %10, %11, %12, %13, %14, %15, %16, %17, %18, %19}, {%20,%21,%22,%23}, %24, p, 1, 1, %26;\n}\n"
    : "+f"(d[0]), "+f"(d[1]), "+f"(d[2]), "+f"(d[3]), "+f"(d[4]), "+f"(d[5]), "+f"(d[6]), "+f"(d[7]),
      "+f"(d[8]), "+f"(d[9]), "+f"(d[10]), "+f"(d[11]), "+f"(d[12]), "+f"(d[13]), "+f"(d[14]), "+f"(d[15]),
      "+f"(d[16]), "+f"(d[17]), "+f"(d[18]), "+f"(d[19])
    : "r"(a0), "r"(a1), "r"(a2), "r"(a3), "l"(db), "r"(sc), "n"(TB));
}
template <int TB>
__device__ __forceinline__ void wgmma_n64_rs(float (&d)[32], uint32_t a0, uint32_t a1, uint32_t a2, uint32_t a3, uint64_t db, int sc) {
  asm volatile("{\n.reg .pred p;\nsetp.ne.b32 p, %37, 0;\n"
    "wgmma.mma_async.sync.aligned.m64n64k16.f32.bf16.bf16 {%0, %1, %2, %3, %4, %5, %6, %7, %8, %9, %10, %11, %12, %13, %14, %15, %16, %17, %18, %19, %20, %21, %22, %23, %24, %25, %26, %27, %28, %29, %30, %31}, {%32,%33,%34,%35}, %36, p, 1, 1, %38;\n}\n"
    : "+f"(d[0]), "+f"(d[1]), "+f"(d[2]), "+f"(d[3]), "+f"(d[4]), "+f"(d[5]), "+f"(d[6]), "+f"(d[7]),
      "+f"(d[8]), "+f"(d[9]), "+f"(d[10]), "+f"(d[11]), "+f"(d[12]), "+f"(d[13]), "+f"(d[14]), "+f"(d[15]),
      "+f"(d[16]), "+f"(d[17]), "+f"(d[18]), "+f"(d[19]), "+f"(d[20]), "+f"(d[21]), "+f"(d[22]), "+f"(d[23]),
      "+f"(d[24]), "+f"(d[25]), "+f"(d[26]), "+f"(d[27]), "+f"(d[28]), "+f"(d[29]), "+f"(d[30]), "+f"(d[31])
    : "r"(a0), "r"(a1), "r"(a2), "r"(a3), "l"(db), "r"(sc), "n"(TB));
}
template <int TA, int TB>
__device__ __forceinline__ void wgmma_n128_ss(float (&d)[64], uint64_t da, uint64_t db, int sc) {
  asm volatile("{\n.reg .pred p;\nsetp.ne.b32 p, %66, 0;\n"
    "wgmma.mma_async.sync.aligned.m64n128k16.f32.bf16.bf16 {%0, %1, %2, %3, %4, %5, %6, %7, %8, %9, %10, %11, %12, %13, %14, %15, %16, %17, %18, %19, %20, %21, %22, %23, %24, %25, %26, %27, %28, %29, %30, %31, %32, %33, %34, %35, %36, %37, %38, %39, %40, %41, %42, %43, %44, %45, %46, %47, %48, %49, %50, %51, %52, %53, %54, %55, %56, %57, %58, %59, %60, %61, %62, %63}, %64, %65, p, 1, 1, %67, %68;\n}\n"
    : "+f"(d[0]), "+f"(d[1]), "+f"(d[2]), "+f"(d[3]), "+f"(d[4]), "+f"(d[5]), "+f"(d[6]), "+f"(d[7]),
      "+f"(d[8]), "+f"(d[9]), "+f"(d[10]), "+f"(d[11]), "+f"(d[12]), "+f"(d[13]), "+f"(d[14]), "+f"(d[15]),
      "+f"(d[16]), "+f"(d[17]), "+f"(d[18]), "+f"(d[19]), "+f"(d[20]), "+f"(d[21]), "+f"(d[22]), "+f"(d[23]),
      "+f"(d[24]), "+f"(d[25]), "+f"(d[26]), "+f"(d[27]), "+f"(d[28]), "+f"(d[29]), "+f"(d[30]), "+f"(d[31]),
      "+f"(d[32]), "+f"(d[33]), "+f"(d[34]), "+f"(d[35]), "+f"(d[36]), "+f"(d[37]), "+f"(d[38]), "+f"(d[39]),
      "+f"(d[40]), "+f"(d[41]), "+f"(d[42]), "+f"(d[43]), "+f"(d[44]), "+f"(d[45]), "+f"(d[46]), "+f"(d[47]),
      "+f"(d[48]), "+f"(d[49]), "+f"(d[50]), "+f"(d[51]), "+f"(d[52]), "+f"(d[53]), "+f"(d[54]), "+f"(d[55]),
      "+f"(d[56]), "+f"(d[57]), "+f"(d[58]), "+f"(d[59]), "+f"(d[60]), "+f"(d[61]), "+f"(d[62]), "+f"(d[63])
    : "l"(da), "l"(db), "r"(sc), "n"(TA), "n"(TB));
}
template <int TB>
__device__ __forceinline__ void wgmma_n128_rs(float (&d)[64], uint32_t a0, uint32_t a1, uint32_t a2, uint32_t a3, uint64_t db, int sc) {
  asm volatile("{\n.reg .pred p;\nsetp.ne.b32 p, %69, 0;\n"
    "wgmma.mma_async.sync.aligned.m64n128k16.f32.bf16.bf16 {%0, %1, %2, %3, %4, %5, %6, %7, %8, %9, %10, %11, %12, %13, %14, %15, %16, %17, %18, %19, %20, %21, %22, %23, %24, %25, %26, %27, %28, %29, %30, %31, %32, %33, %34, %35, %36, %37, %38, %39, %40, %41, %42, %43, %44, %45, %46, %47, %48, %49, %50, %51, %52, %53, %54, %55, %56, %57, %58, %59, %60, %61, %62, %63}, {%64,%65,%66,%67}, %68, p, 1, 1, %70;\n}\n"
    : "+f"(d[0]), "+f"(d[1]), "+f"(d[2]), "+f"(d[3]), "+f"(d[4]), "+f"(d[5]), "+f"(d[6]), "+f"(d[7]),
      "+f"(d[8]), "+f"(d[9]), "+f"(d[10]), "+f"(d[11]), "+f"(d[12]), "+f"(d[13]), "+f"(d[14]), "+f"(d[15]),
      "+f"(d[16]), "+f"(d[17]), "+f"(d[18]), "+f"(d[19]), "+f"(d[20]), "+f"(d[21]), "+f"(d[22]), "+f"(d[23]),
      "+f"(d[24]), "+f"(d[25]), "+f"(d[26]), "+f"(d[27]), "+f"(d[28]), "+f"(d[29]), "+f"(d[30]), "+f"(d[31]),
      "+f"(d[32]), "+f"(d[33]), "+f"(d[34]), "+f"(d[35]), "+f"(d[36]), "+f"(d[37]), "+f"(d[38]), "+f"(d[39]),
      "+f"(d[40]), "+f"(d[41]), "+f"(d[42]), "+f"(d[43]), "+f"(d[44]), "+f"(d[45]), "+f"(d[46]), "+f"(d[47]),
      "+f"(d[48]), "+f"(d[49]), "+f"(d[50]), "+f"(d[51]), "+f"(d[52]), "+f"(d[53]), "+f"(d[54]), "+f"(d[55]),
      "+f"(d[56]), "+f"(d[57]), "+f"(d[58]), "+f"(d[59]), "+f"(d[60]), "+f"(d[61]), "+f"(d[62]), "+f"(d[63])
    : "r"(a0), "r"(a1), "r"(a2), "r"(a3), "l"(db), "r"(sc), "n"(TB));
}

__device__ __forceinline__ void poll1(uint32_t (&v)[1], const void* p, uint32_t tag, uint32_t mask) {
  asm volatile("{\n.reg .pred p, q;\n.reg .u32 c, b;\n.reg .b64 x, y;\n.reg .b128 z;\nmov.u32 c, 0;\nLW:\n"
               "ld.relaxed.gpu.global.u32 %0, [%1+0];\n"
               "xor.b32 b, %0, %2;\n"
               "and.b32 b, b, %3;\nsetp.eq.u32 p, b, 0;\nvote.sync.all.pred p, p, 0xffffffff;\n@p bra.uni LD;\n"
               "nanosleep.u32 100;\nadd.u32 c, c, 1;\nsetp.lt.u32 q, c, 1000000;\n@q bra.uni LW;\ntrap;\nLD:\n}"
               : "=&r"(v[0])
               : "l"(p), "r"(tag), "r"(mask) : "memory");
}
__device__ __forceinline__ void poll1f(uint32_t (&v)[1], const void* p, uint32_t tag, uint32_t mask) {
  asm volatile("{\n.reg .pred p, q;\n.reg .u32 c, b;\n.reg .b64 x, y;\n.reg .b128 z;\nmov.u32 c, 0;\nLW:\n"
               "ld.relaxed.gpu.global.u32 %0, [%1+0];\n"
               "xor.b32 b, %0, %2;\n"
               "and.b32 b, b, %3;\nsetp.eq.u32 p, b, 0;\nvote.sync.all.pred p, p, 0xffffffff;\n@p bra.uni LD;\n"
               "nanosleep.u32 50;\nadd.u32 c, c, 1;\nsetp.lt.u32 q, c, 1000000;\n@q bra.uni LW;\ntrap;\nLD:\n}"
               : "=&r"(v[0])
               : "l"(p), "r"(tag), "r"(mask) : "memory");
}
__device__ __forceinline__ void poll0(uint32_t (&v)[1], const void* p, uint32_t tag, uint32_t mask) {
  asm volatile("{\n.reg .pred p, q;\n.reg .u32 c, b;\n.reg .b64 x, y;\n.reg .b128 z;\nmov.u32 c, 0;\nLW:\n"
               "ld.relaxed.gpu.global.u32 %0, [%1+0];\n"
               "xor.b32 b, %0, %2;\n"
               "and.b32 b, b, %3;\nsetp.eq.u32 p, b, 0;\nvote.sync.all.pred p, p, 0xffffffff;\n@p bra.uni LD;\n"
               "add.u32 c, c, 1;\nsetp.lt.u32 q, c, 1000000;\n@q bra.uni LW;\ntrap;\nLD:\n}"
               : "=&r"(v[0])
               : "l"(p), "r"(tag), "r"(mask) : "memory");
}
__device__ __forceinline__ void poll_pair(uint32_t (&v)[2], const void* p, uint32_t tag, uint32_t mask) {
  asm volatile("{\n.reg .pred p, q;\n.reg .u32 c, b;\n.reg .b64 x, y;\n.reg .b128 z;\nmov.u32 c, 0;\nLW:\n"
               "ld.relaxed.gpu.global.b64 x, [%2+0];\nmov.b64 {%0,%1}, x;\n"
               "xor.b32 b, %0, %3;\n"
               "and.b32 b, b, %4;\nsetp.eq.u32 p, b, 0;\nvote.sync.all.pred p, p, 0xffffffff;\n@p bra.uni LD;\n"
               "nanosleep.u32 100;\nadd.u32 c, c, 1;\nsetp.lt.u32 q, c, 1000000;\n@q bra.uni LW;\ntrap;\nLD:\n}"
               : "=&r"(v[0]), "=&r"(v[1])
               : "l"(p), "r"(tag), "r"(mask) : "memory");
}
__device__ __forceinline__ void poll_quad(uint32_t (&v)[4], const void* p, uint32_t tag, uint32_t mask) {
  asm volatile("{\n.reg .pred p, q;\n.reg .u32 c, b;\n.reg .b64 x, y;\n.reg .b128 z;\nmov.u32 c, 0;\nLW:\n"
               "ld.relaxed.gpu.global.v4.u32 {%0,%1,%2,%3}, [%4+0];\n"
               "xor.b32 b, %0, %5;\n"
               "lop3.b32 b, b, %1, %5, 0xf6;\nlop3.b32 b, b, %2, %5, 0xf6;\nlop3.b32 b, b, %3, %5, 0xf6;\n"
               "and.b32 b, b, %6;\nsetp.eq.u32 p, b, 0;\nvote.sync.all.pred p, p, 0xffffffff;\n@p bra.uni LD;\n"
               "nanosleep.u32 200;\nadd.u32 c, c, 1;\nsetp.lt.u32 q, c, 1000000;\n@q bra.uni LW;\ntrap;\nLD:\n}"
               : "=&r"(v[0]), "=&r"(v[1]), "=&r"(v[2]), "=&r"(v[3])
               : "l"(p), "r"(tag), "r"(mask) : "memory");
}
__device__ __forceinline__ void poll8x4(uint32_t (&v)[32], const void* p, uint32_t tag, uint32_t mask) {
  asm volatile("{\n.reg .pred p, q;\n.reg .u32 c, b;\n.reg .b64 x, y;\n.reg .b128 z;\nmov.u32 c, 0;\nLW:\n"
               "ld.relaxed.gpu.global.v4.u32 {%0,%1,%2,%3}, [%32+0];\n"
               "ld.relaxed.gpu.global.v4.u32 {%4,%5,%6,%7}, [%32+2048];\n"
               "ld.relaxed.gpu.global.v4.u32 {%8,%9,%10,%11}, [%32+4096];\n"
               "ld.relaxed.gpu.global.v4.u32 {%12,%13,%14,%15}, [%32+6144];\n"
               "ld.relaxed.gpu.global.v4.u32 {%16,%17,%18,%19}, [%32+8192];\n"
               "ld.relaxed.gpu.global.v4.u32 {%20,%21,%22,%23}, [%32+10240];\n"
               "ld.relaxed.gpu.global.v4.u32 {%24,%25,%26,%27}, [%32+12288];\n"
               "ld.relaxed.gpu.global.v4.u32 {%28,%29,%30,%31}, [%32+14336];\n"
               "xor.b32 b, %0, %33;\n"
               "lop3.b32 b, b, %1, %33, 0xf6;\nlop3.b32 b, b, %2, %33, 0xf6;\nlop3.b32 b, b, %3, %33, 0xf6;\nlop3.b32 b, b, %4, %33, 0xf6;\n"
               "lop3.b32 b, b, %5, %33, 0xf6;\nlop3.b32 b, b, %6, %33, 0xf6;\nlop3.b32 b, b, %7, %33, 0xf6;\nlop3.b32 b, b, %8, %33, 0xf6;\n"
               "lop3.b32 b, b, %9, %33, 0xf6;\nlop3.b32 b, b, %10, %33, 0xf6;\nlop3.b32 b, b, %11, %33, 0xf6;\nlop3.b32 b, b, %12, %33, 0xf6;\n"
               "lop3.b32 b, b, %13, %33, 0xf6;\nlop3.b32 b, b, %14, %33, 0xf6;\nlop3.b32 b, b, %15, %33, 0xf6;\nlop3.b32 b, b, %16, %33, 0xf6;\n"
               "lop3.b32 b, b, %17, %33, 0xf6;\nlop3.b32 b, b, %18, %33, 0xf6;\nlop3.b32 b, b, %19, %33, 0xf6;\nlop3.b32 b, b, %20, %33, 0xf6;\n"
               "lop3.b32 b, b, %21, %33, 0xf6;\nlop3.b32 b, b, %22, %33, 0xf6;\nlop3.b32 b, b, %23, %33, 0xf6;\nlop3.b32 b, b, %24, %33, 0xf6;\n"
               "lop3.b32 b, b, %25, %33, 0xf6;\nlop3.b32 b, b, %26, %33, 0xf6;\nlop3.b32 b, b, %27, %33, 0xf6;\nlop3.b32 b, b, %28, %33, 0xf6;\n"
               "lop3.b32 b, b, %29, %33, 0xf6;\nlop3.b32 b, b, %30, %33, 0xf6;\nlop3.b32 b, b, %31, %33, 0xf6;\n"
               "and.b32 b, b, %34;\nsetp.eq.u32 p, b, 0;\nvote.sync.all.pred p, p, 0xffffffff;\n@p bra.uni LD;\n"
               "nanosleep.u32 50;\nadd.u32 c, c, 1;\nsetp.lt.u32 q, c, 1000000;\n@q bra.uni LW;\ntrap;\nLD:\n}"
               : "=&r"(v[0]), "=&r"(v[1]), "=&r"(v[2]), "=&r"(v[3]), "=&r"(v[4]), "=&r"(v[5]), "=&r"(v[6]), "=&r"(v[7]), "=&r"(v[8]), "=&r"(v[9]), "=&r"(v[10]), "=&r"(v[11]), "=&r"(v[12]), "=&r"(v[13]), "=&r"(v[14]), "=&r"(v[15]), "=&r"(v[16]), "=&r"(v[17]), "=&r"(v[18]), "=&r"(v[19]), "=&r"(v[20]), "=&r"(v[21]), "=&r"(v[22]), "=&r"(v[23]), "=&r"(v[24]), "=&r"(v[25]), "=&r"(v[26]), "=&r"(v[27]), "=&r"(v[28]), "=&r"(v[29]), "=&r"(v[30]), "=&r"(v[31])
               : "l"(p), "r"(tag), "r"(mask) : "memory");
}
__device__ __forceinline__ void poll16(uint32_t (&v)[16], const void* p, uint32_t tag, uint32_t mask) {
  asm volatile("{\n.reg .pred p, q;\n.reg .u32 c, b;\n.reg .b64 x, y;\n.reg .b128 z;\nmov.u32 c, 0;\nLW:\n"
               "ld.relaxed.gpu.global.u32 %0, [%16+0];\n"
               "ld.relaxed.gpu.global.u32 %1, [%16+4096];\n"
               "ld.relaxed.gpu.global.u32 %2, [%16+8192];\n"
               "ld.relaxed.gpu.global.u32 %3, [%16+12288];\n"
               "ld.relaxed.gpu.global.u32 %4, [%16+16384];\n"
               "ld.relaxed.gpu.global.u32 %5, [%16+20480];\n"
               "ld.relaxed.gpu.global.u32 %6, [%16+24576];\n"
               "ld.relaxed.gpu.global.u32 %7, [%16+28672];\n"
               "ld.relaxed.gpu.global.u32 %8, [%16+32768];\n"
               "ld.relaxed.gpu.global.u32 %9, [%16+36864];\n"
               "ld.relaxed.gpu.global.u32 %10, [%16+40960];\n"
               "ld.relaxed.gpu.global.u32 %11, [%16+45056];\n"
               "ld.relaxed.gpu.global.u32 %12, [%16+49152];\n"
               "ld.relaxed.gpu.global.u32 %13, [%16+53248];\n"
               "ld.relaxed.gpu.global.u32 %14, [%16+57344];\n"
               "ld.relaxed.gpu.global.u32 %15, [%16+61440];\n"
               "xor.b32 b, %0, %17;\n"
               "lop3.b32 b, b, %1, %17, 0xf6;\nlop3.b32 b, b, %2, %17, 0xf6;\nlop3.b32 b, b, %3, %17, 0xf6;\nlop3.b32 b, b, %4, %17, 0xf6;\n"
               "lop3.b32 b, b, %5, %17, 0xf6;\nlop3.b32 b, b, %6, %17, 0xf6;\nlop3.b32 b, b, %7, %17, 0xf6;\nlop3.b32 b, b, %8, %17, 0xf6;\n"
               "lop3.b32 b, b, %9, %17, 0xf6;\nlop3.b32 b, b, %10, %17, 0xf6;\nlop3.b32 b, b, %11, %17, 0xf6;\nlop3.b32 b, b, %12, %17, 0xf6;\n"
               "lop3.b32 b, b, %13, %17, 0xf6;\nlop3.b32 b, b, %14, %17, 0xf6;\nlop3.b32 b, b, %15, %17, 0xf6;\n"
               "and.b32 b, b, %18;\nsetp.eq.u32 p, b, 0;\nvote.sync.all.pred p, p, 0xffffffff;\n@p bra.uni LD;\n"
               "nanosleep.u32 200;\nadd.u32 c, c, 1;\nsetp.lt.u32 q, c, 1000000;\n@q bra.uni LW;\ntrap;\nLD:\n}"
               : "=&r"(v[0]), "=&r"(v[1]), "=&r"(v[2]), "=&r"(v[3]), "=&r"(v[4]), "=&r"(v[5]), "=&r"(v[6]), "=&r"(v[7]), "=&r"(v[8]), "=&r"(v[9]), "=&r"(v[10]), "=&r"(v[11]), "=&r"(v[12]), "=&r"(v[13]), "=&r"(v[14]), "=&r"(v[15])
               : "l"(p), "r"(tag), "r"(mask) : "memory");
}
__device__ __forceinline__ void poll_keys(uint32_t (&v)[16], const void* p, uint32_t tag, uint32_t mask) {
  asm volatile("{\n.reg .pred p, q;\n.reg .u32 c, b;\n.reg .b64 x, y;\n.reg .b128 z;\nmov.u32 c, 0;\nLW:\n"
               "ld.relaxed.gpu.global.v2.b64 {x, y}, [%16+0];\nmov.b64 {%0,%1}, x;\nmov.b64 {%2,%3}, y;\n"
               "ld.relaxed.gpu.global.v2.b64 {x, y}, [%16+4096];\nmov.b64 {%4,%5}, x;\nmov.b64 {%6,%7}, y;\n"
               "ld.relaxed.gpu.global.v2.b64 {x, y}, [%16+8192];\nmov.b64 {%8,%9}, x;\nmov.b64 {%10,%11}, y;\n"
               "ld.relaxed.gpu.global.v2.b64 {x, y}, [%16+12288];\nmov.b64 {%12,%13}, x;\nmov.b64 {%14,%15}, y;\n"
               "xor.b32 b, %0, %17;\n"
               "lop3.b32 b, b, %2, %17, 0xf6;\nlop3.b32 b, b, %4, %17, 0xf6;\nlop3.b32 b, b, %6, %17, 0xf6;\nlop3.b32 b, b, %8, %17, 0xf6;\n"
               "lop3.b32 b, b, %10, %17, 0xf6;\nlop3.b32 b, b, %12, %17, 0xf6;\nlop3.b32 b, b, %14, %17, 0xf6;\n"
               "and.b32 b, b, %18;\nsetp.eq.u32 p, b, 0;\nvote.sync.all.pred p, p, 0xffffffff;\n@p bra.uni LD;\n"
               "nanosleep.u32 20;\nadd.u32 c, c, 1;\nsetp.lt.u32 q, c, 1000000;\n@q bra.uni LW;\ntrap;\nLD:\n}"
               : "=&r"(v[0]), "=&r"(v[1]), "=&r"(v[2]), "=&r"(v[3]), "=&r"(v[4]), "=&r"(v[5]), "=&r"(v[6]), "=&r"(v[7]), "=&r"(v[8]), "=&r"(v[9]), "=&r"(v[10]), "=&r"(v[11]), "=&r"(v[12]), "=&r"(v[13]), "=&r"(v[14]), "=&r"(v[15])
               : "l"(p), "r"(tag), "r"(mask) : "memory");
}
__device__ __forceinline__ void poll_z(uint32_t (&v)[16], const void* p, uint32_t tag, uint32_t mask) {
  asm volatile("{\n.reg .pred p, q;\n.reg .u32 c, b;\n.reg .b64 x, y;\n.reg .b128 z;\nmov.u32 c, 0;\nLW:\n"
               "ld.relaxed.gpu.global.v4.u32 {%0,%1,%2,%3}, [%16+0];\n"
               "ld.relaxed.gpu.global.v4.u32 {%4,%5,%6,%7}, [%16+4096];\n"
               "ld.relaxed.gpu.global.v4.u32 {%8,%9,%10,%11}, [%16+8192];\n"
               "ld.relaxed.gpu.global.v4.u32 {%12,%13,%14,%15}, [%16+12288];\n"
               "xor.b32 b, %0, %17;\n"
               "lop3.b32 b, b, %1, %17, 0xf6;\nlop3.b32 b, b, %2, %17, 0xf6;\nlop3.b32 b, b, %3, %17, 0xf6;\nlop3.b32 b, b, %4, %17, 0xf6;\n"
               "lop3.b32 b, b, %5, %17, 0xf6;\nlop3.b32 b, b, %6, %17, 0xf6;\nlop3.b32 b, b, %7, %17, 0xf6;\nlop3.b32 b, b, %8, %17, 0xf6;\n"
               "lop3.b32 b, b, %9, %17, 0xf6;\nlop3.b32 b, b, %10, %17, 0xf6;\nlop3.b32 b, b, %11, %17, 0xf6;\nlop3.b32 b, b, %12, %17, 0xf6;\n"
               "lop3.b32 b, b, %13, %17, 0xf6;\nlop3.b32 b, b, %14, %17, 0xf6;\nlop3.b32 b, b, %15, %17, 0xf6;\n"
               "and.b32 b, b, %18;\nsetp.eq.u32 p, b, 0;\nvote.sync.all.pred p, p, 0xffffffff;\n@p bra.uni LD;\n"
               "nanosleep.u32 300;\nadd.u32 c, c, 1;\nsetp.lt.u32 q, c, 1000000;\n@q bra.uni LW;\ntrap;\nLD:\n}"
               : "=&r"(v[0]), "=&r"(v[1]), "=&r"(v[2]), "=&r"(v[3]), "=&r"(v[4]), "=&r"(v[5]), "=&r"(v[6]), "=&r"(v[7]), "=&r"(v[8]), "=&r"(v[9]), "=&r"(v[10]), "=&r"(v[11]), "=&r"(v[12]), "=&r"(v[13]), "=&r"(v[14]), "=&r"(v[15])
               : "l"(p), "r"(tag), "r"(mask) : "memory");
}
__device__ __forceinline__ void poll7x4(uint32_t (&v)[28], const void* p, uint32_t tag, uint32_t mask) {
  asm volatile("{\n.reg .pred p, q;\n.reg .u32 c, b;\n.reg .b64 x, y;\n.reg .b128 z;\nmov.u32 c, 0;\nLW:\n"
               "ld.relaxed.gpu.global.v4.u32 {%0,%1,%2,%3}, [%28+0];\n"
               "ld.relaxed.gpu.global.v4.u32 {%4,%5,%6,%7}, [%28+2048];\n"
               "ld.relaxed.gpu.global.v4.u32 {%8,%9,%10,%11}, [%28+4096];\n"
               "ld.relaxed.gpu.global.v4.u32 {%12,%13,%14,%15}, [%28+6144];\n"
               "ld.relaxed.gpu.global.v4.u32 {%16,%17,%18,%19}, [%28+8192];\n"
               "ld.relaxed.gpu.global.v4.u32 {%20,%21,%22,%23}, [%28+10240];\n"
               "ld.relaxed.gpu.global.v4.u32 {%24,%25,%26,%27}, [%28+12288];\n"
               "xor.b32 b, %0, %29;\n"
               "lop3.b32 b, b, %1, %29, 0xf6;\nlop3.b32 b, b, %2, %29, 0xf6;\nlop3.b32 b, b, %3, %29, 0xf6;\nlop3.b32 b, b, %4, %29, 0xf6;\n"
               "lop3.b32 b, b, %5, %29, 0xf6;\nlop3.b32 b, b, %6, %29, 0xf6;\nlop3.b32 b, b, %7, %29, 0xf6;\nlop3.b32 b, b, %8, %29, 0xf6;\n"
               "lop3.b32 b, b, %9, %29, 0xf6;\nlop3.b32 b, b, %10, %29, 0xf6;\nlop3.b32 b, b, %11, %29, 0xf6;\nlop3.b32 b, b, %12, %29, 0xf6;\n"
               "lop3.b32 b, b, %13, %29, 0xf6;\nlop3.b32 b, b, %14, %29, 0xf6;\nlop3.b32 b, b, %15, %29, 0xf6;\nlop3.b32 b, b, %16, %29, 0xf6;\n"
               "lop3.b32 b, b, %17, %29, 0xf6;\nlop3.b32 b, b, %18, %29, 0xf6;\nlop3.b32 b, b, %19, %29, 0xf6;\nlop3.b32 b, b, %20, %29, 0xf6;\n"
               "lop3.b32 b, b, %21, %29, 0xf6;\nlop3.b32 b, b, %22, %29, 0xf6;\nlop3.b32 b, b, %23, %29, 0xf6;\nlop3.b32 b, b, %24, %29, 0xf6;\n"
               "lop3.b32 b, b, %25, %29, 0xf6;\nlop3.b32 b, b, %26, %29, 0xf6;\nlop3.b32 b, b, %27, %29, 0xf6;\n"
               "and.b32 b, b, %30;\nsetp.eq.u32 p, b, 0;\nvote.sync.all.pred p, p, 0xffffffff;\n@p bra.uni LD;\n"
               "nanosleep.u32 50;\nadd.u32 c, c, 1;\nsetp.lt.u32 q, c, 1000000;\n@q bra.uni LW;\ntrap;\nLD:\n}"
               : "=&r"(v[0]), "=&r"(v[1]), "=&r"(v[2]), "=&r"(v[3]), "=&r"(v[4]), "=&r"(v[5]), "=&r"(v[6]), "=&r"(v[7]), "=&r"(v[8]), "=&r"(v[9]), "=&r"(v[10]), "=&r"(v[11]), "=&r"(v[12]), "=&r"(v[13]), "=&r"(v[14]), "=&r"(v[15]), "=&r"(v[16]), "=&r"(v[17]), "=&r"(v[18]), "=&r"(v[19]), "=&r"(v[20]), "=&r"(v[21]), "=&r"(v[22]), "=&r"(v[23]), "=&r"(v[24]), "=&r"(v[25]), "=&r"(v[26]), "=&r"(v[27])
               : "l"(p), "r"(tag), "r"(mask) : "memory");
}
__device__ __forceinline__ void poll_kvp(uint32_t (&v)[16], const void* p, uint32_t tag, uint32_t mask) {
  asm volatile("{\n.reg .pred p, q;\n.reg .u32 c, b;\n.reg .b64 x, y;\n.reg .b128 z;\nmov.u32 c, 0;\nLW:\n"
               "ld.relaxed.gpu.global.b128 z, [%16+0];\nmov.b128 {x, y}, z;\nmov.b64 {%0,%1}, x;\nmov.b64 {%2,%3}, y;\n"
               "ld.relaxed.gpu.global.b128 z, [%16+8192];\nmov.b128 {x, y}, z;\nmov.b64 {%4,%5}, x;\nmov.b64 {%6,%7}, y;\n"
               "ld.relaxed.gpu.global.b128 z, [%16+16384];\nmov.b128 {x, y}, z;\nmov.b64 {%8,%9}, x;\nmov.b64 {%10,%11}, y;\n"
               "ld.relaxed.gpu.global.b128 z, [%16+24576];\nmov.b128 {x, y}, z;\nmov.b64 {%12,%13}, x;\nmov.b64 {%14,%15}, y;\n"
               "xor.b32 b, %0, %17;\n"
               "lop3.b32 b, b, %4, %17, 0xf6;\nlop3.b32 b, b, %8, %17, 0xf6;\nlop3.b32 b, b, %12, %17, 0xf6;\n"
               "and.b32 b, b, %18;\nsetp.eq.u32 p, b, 0;\nvote.sync.all.pred p, p, 0xffffffff;\n@p bra.uni LD;\n"
               "nanosleep.u32 50;\nadd.u32 c, c, 1;\nsetp.lt.u32 q, c, 1000000;\n@q bra.uni LW;\ntrap;\nLD:\n}"
               : "=&r"(v[0]), "=&r"(v[1]), "=&r"(v[2]), "=&r"(v[3]), "=&r"(v[4]), "=&r"(v[5]), "=&r"(v[6]), "=&r"(v[7]), "=&r"(v[8]), "=&r"(v[9]), "=&r"(v[10]), "=&r"(v[11]), "=&r"(v[12]), "=&r"(v[13]), "=&r"(v[14]), "=&r"(v[15])
               : "l"(p), "r"(tag), "r"(mask) : "memory");
}
__device__ __forceinline__ void poll_kv(uint32_t (&v)[16], const void* p, uint32_t tag, uint32_t mask) {
  asm volatile("{\n.reg .pred p, q;\n.reg .u32 c, b;\n.reg .b64 x, y;\n.reg .b128 z;\nmov.u32 c, 0;\nLW:\n"
               "ld.relaxed.gpu.global.b128 z, [%16+0];\nmov.b128 {x, y}, z;\nmov.b64 {%0,%1}, x;\nmov.b64 {%2,%3}, y;\n"
               "ld.relaxed.gpu.global.b128 z, [%16+2048];\nmov.b128 {x, y}, z;\nmov.b64 {%4,%5}, x;\nmov.b64 {%6,%7}, y;\n"
               "ld.relaxed.gpu.global.b128 z, [%16+4096];\nmov.b128 {x, y}, z;\nmov.b64 {%8,%9}, x;\nmov.b64 {%10,%11}, y;\n"
               "ld.relaxed.gpu.global.b128 z, [%16+6144];\nmov.b128 {x, y}, z;\nmov.b64 {%12,%13}, x;\nmov.b64 {%14,%15}, y;\n"
               "xor.b32 b, %0, %17;\n"
               "lop3.b32 b, b, %4, %17, 0xf6;\nlop3.b32 b, b, %8, %17, 0xf6;\nlop3.b32 b, b, %12, %17, 0xf6;\n"
               "and.b32 b, b, %18;\nsetp.eq.u32 p, b, 0;\nvote.sync.all.pred p, p, 0xffffffff;\n@p bra.uni LD;\n"
               "nanosleep.u32 50;\nadd.u32 c, c, 1;\nsetp.lt.u32 q, c, 1000000;\n@q bra.uni LW;\ntrap;\nLD:\n}"
               : "=&r"(v[0]), "=&r"(v[1]), "=&r"(v[2]), "=&r"(v[3]), "=&r"(v[4]), "=&r"(v[5]), "=&r"(v[6]), "=&r"(v[7]), "=&r"(v[8]), "=&r"(v[9]), "=&r"(v[10]), "=&r"(v[11]), "=&r"(v[12]), "=&r"(v[13]), "=&r"(v[14]), "=&r"(v[15])
               : "l"(p), "r"(tag), "r"(mask) : "memory");
}

__device__ __align__(1024) __nv_bfloat16 g_o[2048 * 1024];
__device__ __align__(128) uint2 g_keys[2048];
__device__ __align__(128) uint32_t g_csum[18 * 1024];
__device__ __align__(128) uint32_t g_z[16 * 1024];
__device__ __align__(128) uint4 g_kvp[128 * 512];
__device__ __align__(128) uint4 g_kv[8 * 512];
__device__ __align__(128) uint32_t g_h[112 * 256];
__device__ __align__(128) uint32_t g_yp[128 * 512];
__device__ __align__(128) uint2 g_sel[8 * 16];
enum { H_CS = 0, H_KVP = 8, H_KV = 16, H_H = 24, H_Y = 32, H_O = 40, H_Z = 56 };
__device__ __align__(128) uint32_t g_sig[64 * 32];
__device__ uint32_t g_epoch;

constexpr uint32_t RING = 1024, SLOT = 32768, SMEM_BYTES = 232448;
constexpr int NST = 5, HST = 7;
constexpr uint32_t STG = RING + 163840, AUX = RING + 196608, FR = RING + 212992, MISC = RING + 229376;
constexpr uint32_t B_FULL = MISC, B_EMPTY = MISC + 56, B_XS = MISC + 112, B_SEL = MISC + 144, B_WK = MISC + 160, B_CSDN = MISC + 168,
                   B_FR = MISC + 176, B_FE = MISC + 216, B_DR = MISC + 256, B_CSV = MISC + 288,
                   B_DND = MISC + 296, B_XRES = MISC + 304, B_PFREE = MISC + 320, B_DND2 = MISC + 328, B_RESD = MISC + 336, NBAR = 43;
constexpr uint32_t S_EPOCH = MISC + 352, S_NCAND = MISC + 356, S_SEL = MISC + 368, S_WMAX = MISC + 432,
                   S_KSTAT = MISC + 512, S_CSK = MISC + 1536, S_CSV = MISC + 2048, S_CSQ = MISC + 2560, S_ONES = MISC + 512;
constexpr uint32_t KVB_P0 = AUX, KVB_Z = AUX + 4096, KVB_P1 = AUX + 5120, HOP = AUX + 9216, FONES = HOP + 2560, GR = FR - 4096;
enum { NB_Z = 0, NB_KV = 1, NB_VQ = 2, NB_WG0 = 3, NB_FDONE = 4, NB_PK = 5, NB_KVB = 6, NB_WG1 = 7, NB_WG2 = 8, NB_CSQ = 9,
       NB_Y = 10, NB_ST = 11, NB_OWN0 = 12, NB_OWN1 = 13, NB_Q0 = 14, NB_H1 = 15 };

#define XS_ORD 0x3210
#define XS_GO 0
#define XS_FLY 2
#define XS_EARLY 0
#define H_DELAY 0
#define FFN_GAP 200
#define GATE_KT 0
#define GATE_K 6
#define KV_DIRECT 1
#define ALIGN 0
#define PF_GAP 200
#define PF_WAIT 1000
#define POLITE 1
constexpr uint64_t EVICT_FIRST = 0x12f0000000000000ull;
constexpr float LOG2E = 1.4426950408889634f, LN2 = 0.6931471805599453f;

#define ELECT "{\n.reg .pred p;\nelect.sync _|p, 0xffffffff;\n"
#define TMA2D "cp.async.bulk.tensor.2d.shared::cluster.global.mbarrier::complete_tx::bytes"
#define TMA3D "cp.async.bulk.tensor.3d.shared::cluster.global.mbarrier::complete_tx::bytes"
__device__ __forceinline__ void e_expect(uint32_t b, uint32_t n) {
  asm volatile(ELECT "@p mbarrier.arrive.expect_tx.shared::cta.b64 _, [%0], %1;\n}" ::"r"(b), "r"(n) : "memory");
}
__device__ __forceinline__ void e_arrive(uint32_t b) { asm volatile(ELECT "@p mbarrier.arrive.shared::cta.b64 _, [%0];\n}" ::"r"(b) : "memory"); }
__device__ __forceinline__ void e_tma2d(uint32_t dst, const CUtensorMap* m, int c0, int c1, uint32_t bar) {
  asm volatile(ELECT "@p " TMA2D " [%0], [%1, {%3, %4}], [%2];\n}" ::"r"(dst), "l"(m), "r"(bar), "r"(c0), "r"(c1) : "memory");
}
__device__ __forceinline__ void e_tma2d_ef(uint32_t dst, const CUtensorMap* m, int c0, int c1, uint32_t bar, uint64_t pol) {
  asm volatile(ELECT "@p " TMA2D ".L2::cache_hint [%0], [%1, {%3, %4}], [%2], %5;\n}" ::"r"(dst), "l"(m), "r"(bar), "r"(c0), "r"(c1), "l"(pol) : "memory");
}
__device__ __forceinline__ void e_tma3d(uint32_t dst, const CUtensorMap* m, int c1, int c2, uint32_t bar) {
  asm volatile(ELECT "@p " TMA3D " [%0], [%1, {0, %3, %4}], [%2];\n}" ::"r"(dst), "l"(m), "r"(bar), "r"(c1), "r"(c2) : "memory");
}
__device__ __forceinline__ void e_store2d(const CUtensorMap* m, int c0, int c1, uint32_t src) {
  asm volatile(ELECT "@p cp.async.bulk.tensor.2d.global.shared::cta.bulk_group [%0, {%2, %3}], [%1];\n}" ::"l"(m), "r"(src), "r"(c0), "r"(c1) : "memory");
}
__device__ __forceinline__ void e_tma3d_ef(uint32_t dst, const CUtensorMap* m, int c0, int c1, uint32_t bar, uint64_t pol) {
  asm volatile(ELECT "@p " TMA3D ".L2::cache_hint [%0], [%1, {%3, %4, 0}], [%2], %5;\n}" ::"r"(dst), "l"(m), "r"(bar), "r"(c0), "r"(c1), "l"(pol) : "memory");
}
__device__ __forceinline__ void e_pfmap(const CUtensorMap* m) { asm volatile(ELECT "@p prefetch.tensormap [%0];\n}" ::"l"(m) : "memory"); }
__device__ __forceinline__ void bulk_wait_read() { asm volatile("cp.async.bulk.commit_group;\ncp.async.bulk.wait_group.read 0;" ::: "memory"); }
__device__ __forceinline__ void e_signal(int word, int bit) {
  asm volatile(ELECT "@p red.relaxed.gpu.global.xor.b32 [%0], %1;\n}" ::"l"(g_sig + word * 32), "r"(1u << bit) : "memory");
}
__device__ __forceinline__ void await(int word, uint32_t mask, uint32_t ep) {
  uint32_t f[1];
  poll1f(f, g_sig + word * 32, 0u - (ep & 1u), mask);
}

__device__ __forceinline__ void mbar_arrive(uint32_t b) { asm volatile("mbarrier.arrive.shared::cta.b64 _, [%0];" ::"r"(b) : "memory"); }
__device__ __forceinline__ void mbar_wait(uint32_t b, uint32_t ph) {
  asm volatile("{\n.reg .pred p, q;\n.reg .u32 c;\nmov.u32 c, 0;\nLW:\nmbarrier.try_wait.parity.shared::cta.b64 p, [%0], %1;\n@p bra LD;\n"
               "add.u32 c, c, 1;\nsetp.lt.u32 q, c, 100000;\n@q bra LW;\ntrap;\nLD:\n}" ::"r"(b), "r"(ph) : "memory");
}
__device__ __forceinline__ void nb_sync(int id, int n) { asm volatile("bar.sync %0, %1;" ::"r"(id), "r"(n) : "memory"); }
__device__ __forceinline__ void nb_arrive(int id, int n) { asm volatile("bar.arrive %0, %1;" ::"r"(id), "r"(n) : "memory"); }
__device__ __forceinline__ void wg_fence() { asm volatile("wgmma.fence.sync.aligned;" ::: "memory"); }
__device__ __forceinline__ void wg_commit() { asm volatile("wgmma.commit_group.sync.aligned;" ::: "memory"); }
template <int N> __device__ __forceinline__ void wg_wait() { asm volatile("wgmma.wait_group.sync.aligned %0;" ::"n"(N) : "memory"); }
template <int N> __device__ __forceinline__ void reg_fence(float (&a)[N]) {
#pragma unroll
  for (int i = 0; i < N; i++) asm volatile("" : "+f"(a[i])::"memory");
}
template <int N> __device__ __forceinline__ void reg_zero(float (&a)[N]) {
#pragma unroll
  for (int i = 0; i < N; i++) a[i] = 0.f;
}
__device__ __forceinline__ constexpr uint64_t mkdesc(uint32_t addr, uint32_t lbo, uint32_t sbo, uint32_t swz) {
  return (uint64_t)(addr >> 4) | ((uint64_t)(lbo >> 4) << 16) | ((uint64_t)(sbo >> 4) << 32) | ((uint64_t)swz << 62);
}
__device__ __forceinline__ void fence_async_smem() { asm volatile("fence.proxy.async.shared::cta;" ::: "memory"); }
__device__ __forceinline__ void st_relaxed(uint32_t* p, uint32_t v) { asm volatile("st.relaxed.gpu.global.u32 [%0], %1;" ::"l"(p), "r"(v) : "memory"); }
__device__ __forceinline__ uint32_t ld_relaxed(const uint32_t* p) { uint32_t v; asm volatile("ld.relaxed.gpu.global.u32 %0, [%1];" : "=r"(v) : "l"(p) : "memory"); return v; }
__device__ __forceinline__ void st_unit(uint4* p, uint32_t a, uint32_t b, uint32_t c, uint32_t d, uint32_t par) {
  asm volatile("{\n.reg .b64 x, y;\n.reg .b128 z;\nmov.b64 x, {%1,%2};\nmov.b64 y, {%3,%4};\nmov.b128 z, {x, y};\nst.relaxed.gpu.global.b128 [%0], z;\n}"
               ::"l"(p), "r"((a & ~1u) | par), "r"(b), "r"(c), "r"(d) : "memory");
}
__device__ __forceinline__ uint4 lds128(uint32_t a) { uint4 v; asm volatile("ld.shared.v4.u32 {%0,%1,%2,%3}, [%4];" : "=r"(v.x), "=r"(v.y), "=r"(v.z), "=r"(v.w) : "r"(a)); return v; }
__device__ __forceinline__ float4 lds128f(uint32_t a) { float4 v; asm volatile("ld.shared.v4.f32 {%0,%1,%2,%3}, [%4];" : "=f"(v.x), "=f"(v.y), "=f"(v.z), "=f"(v.w) : "r"(a)); return v; }
__device__ __forceinline__ float4 lds128v(uint32_t a) { float4 v; asm volatile("ld.volatile.shared.v4.f32 {%0,%1,%2,%3}, [%4];" : "=f"(v.x), "=f"(v.y), "=f"(v.z), "=f"(v.w) : "r"(a) : "memory"); return v; }
__device__ __forceinline__ float lds32v(uint32_t a) { float v; asm volatile("ld.volatile.shared.f32 %0, [%1];" : "=f"(v) : "r"(a) : "memory"); return v; }
__device__ __forceinline__ float2 lds64f(uint32_t a) { float2 v; asm volatile("ld.shared.v2.f32 {%0,%1}, [%2];" : "=f"(v.x), "=f"(v.y) : "r"(a)); return v; }
__device__ __forceinline__ uint32_t lds32(uint32_t a) { uint32_t v; asm volatile("ld.shared.u32 %0, [%1];" : "=r"(v) : "r"(a)); return v; }
__device__ __forceinline__ void sts128(uint32_t a, uint32_t x, uint32_t y, uint32_t z, uint32_t w) { asm volatile("st.shared.v4.u32 [%0], {%1,%2,%3,%4};" ::"r"(a), "r"(x), "r"(y), "r"(z), "r"(w) : "memory"); }
__device__ __forceinline__ void sts128f(uint32_t a, float x, float y, float z, float w) { asm volatile("st.shared.v4.f32 [%0], {%1,%2,%3,%4};" ::"r"(a), "f"(x), "f"(y), "f"(z), "f"(w) : "memory"); }
__device__ __forceinline__ void sts64(uint32_t a, uint32_t x, uint32_t y) { asm volatile("st.shared.v2.u32 [%0], {%1,%2};" ::"r"(a), "r"(x), "r"(y) : "memory"); }
__device__ __forceinline__ void sts32(uint32_t a, uint32_t x) { asm volatile("st.shared.u32 [%0], %1;" ::"r"(a), "r"(x) : "memory"); }
__device__ __forceinline__ void stsm4(uint32_t a, uint32_t r0, uint32_t r1, uint32_t r2, uint32_t r3) {
  asm volatile("stmatrix.sync.aligned.m8n8.x4.shared.b16 [%0], {%1,%2,%3,%4};" ::"r"(a), "r"(r0), "r"(r1), "r"(r2), "r"(r3) : "memory");
}
__device__ __forceinline__ uint4 ldsm4(uint32_t a) {
  uint4 v; asm volatile("ldmatrix.sync.aligned.m8n8.x4.shared.b16 {%0,%1,%2,%3}, [%4];" : "=r"(v.x), "=r"(v.y), "=r"(v.z), "=r"(v.w) : "r"(a) : "memory"); return v;
}
__device__ __forceinline__ uint32_t pack(float lo, float hi) { uint32_t r; asm("cvt.rn.bf16x2.f32 %0, %1, %2;" : "=r"(r) : "f"(hi), "f"(lo)); return r; }
__device__ __forceinline__ float bf_lo(uint32_t w) { return __uint_as_float(w << 16); }
__device__ __forceinline__ float bf_hi(uint32_t w) { return __uint_as_float(w & 0xffff0000u); }
__device__ __forceinline__ float bf_round(float x) { return bf_lo(pack(x, x)); }
__device__ __forceinline__ float ex2(float x) { float v; asm("ex2.approx.ftz.f32 %0, %1;" : "=f"(v) : "f"(x)); return v; }
__device__ __forceinline__ float rcp(float x) { float v; asm("rcp.approx.ftz.f32 %0, %1;" : "=f"(v) : "f"(x)); return v; }
__device__ __forceinline__ float addsat(float a, float b) { float v; asm("add.sat.f32 %0, %1, %2;" : "=f"(v) : "f"(a), "f"(b)); return v; }
__device__ __forceinline__ float phi2(float a) { return fmaf(fmaxf(a, 0.f), LN2, addsat(ex2(a), 1e-6f)); }
__device__ __forceinline__ float key_score(uint32_t key) { uint32_t u = key >> 16; u = (u & 0x8000u) ? (u & 0x7fffu) : (~u & 0xffffu); return __uint_as_float(u << 16); }
__device__ __forceinline__ int key_token(uint32_t key) { return 2047 - (int)((key >> 5) & 2047u); }
__device__ __forceinline__ uint32_t bsel(uint32_t a, uint32_t b, uint32_t m) { uint32_t r; asm("lop3.b32 %0, %1, %2, %3, 0xd8;" : "=r"(r) : "r"(a), "r"(b), "r"(m)); return r; }
__device__ __forceinline__ uint32_t prmt(uint32_t a, uint32_t b, uint32_t c) { uint32_t r; asm("prmt.b32 %0, %1, %2, %3;" : "=r"(r) : "r"(a), "r"(b), "r"(c)); return r; }
__device__ __forceinline__ uint32_t tagf(float v, uint32_t par) { return (__float_as_uint(v) & ~1u) | par; }
__device__ __forceinline__ float xred(float a, float b, bool up, int o) { return (up ? b : a) + __shfl_xor_sync(0xffffffffu, up ? a : b, o); }

#define STAMP(id)
#define STAMP_IF(c, id)
#define STAMP2(i)
#define LITE 1
#define LITE_MASK 0ull

template <bool TRANS>
__device__ __forceinline__ void mainloop(float (&a0)[64], float (&a1)[64], int s, int ph, int handoff, int gate, bool leader) {
  uint32_t prev = 0;
#pragma unroll 1
  for (int kt = 0; kt < 16; kt++) {
    mbar_wait(B_FULL + 8 * s, ph);
    if (gate && kt == GATE_KT) nb_sync(gate, 256);
    const uint64_t dw = mkdesc(RING, 8192, 1024, 1) + s * (SLOT >> 4), dx = mkdesc(RING + 16384, 16, 1024, 1) + s * (SLOT >> 4);
    wg_fence();
#pragma unroll
    for (int j = 0; j < 4; j++) {
      if (TRANS) {
        wgmma_n128_ss<1, 0>(a0, dw + j * 128, dx + j * 2, 1);
        wgmma_n128_ss<1, 0>(a1, dw + j * 128 + 512, dx + j * 2, 1);
      } else {
        wgmma_n128_ss<0, 1>(a0, dx + j * 2, dw + j * 128, 1);
        wgmma_n128_ss<0, 1>(a1, dx + j * 2 + 512, dw + j * 128, 1);
      }
    }
    wg_commit();
    if (handoff && kt == 15) nb_arrive(handoff, 256);
    wg_wait<1>();
    if (prev && leader) mbar_arrive(prev);
    prev = B_EMPTY + 8 * s;
    if (++s == NST) { s = 0; ph ^= 1; }
  }
  wg_wait<0>();
  if (leader) mbar_arrive(prev);
  reg_fence(a0);
  reg_fence(a1);
}

__device__ __forceinline__ int out_kblock(int r, int tn) {
  const int q = r - 2, half = q >= 7, pi = q - 7 * half;
  return r < 2 ? 2 * tn + r : 2 * (pi + (pi >= tn)) + half;
}

struct Params {
  const char *x, *wqkv, *w_r, *wg, *wu, *wd;
  CUtensorMap m_wqkv, m_x, m_xs, m_o, m_os, m_wo, m_gu, m_down, m_out;
};

template <bool BY_SMID>
__global__ void __launch_bounds__(512, 1) fused_kernel(const __grid_constant__ Params mp) {
  extern __shared__ __align__(1024) uint8_t smem_raw[];
#define CK(i)
  CK(0);
  uint32_t ck0 = 0;
  if (ALIGN) asm volatile("mov.u32 %0, %%clock;" : "=r"(ck0));
  const int tid = threadIdx.x, lane = tid & 31;
  const int w = __shfl_sync(0xffffffffu, tid >> 5, 0);
  int bid = blockIdx.x;
  if (BY_SMID) {
    uint32_t sm;
    asm volatile("mov.u32 %0, %%smid;" : "=r"(sm));
    const uint32_t p = sm >> 1, q = ((p - 32) * 37) >> 8;
    const uint32_t gpc = p < 32 ? p & 7 : p < 60 ? p - 31 - 7 * q : 0, tpc = p < 32 ? p >> 3 : p < 60 ? 4 + q : p - 58;
    bid = (p >> 1) == 30 ? 128 + ((0x9cu >> (2 * (sm & 3))) & 3) : ((0x75143620u >> (4 * gpc)) & 7) * 16 + tpc * 2 + (sm & 1);
  }
  const int tn = (bid & 3) + 4 * (bid >> 6), tm = (bid >> 2) & 15;

  CK(1);
  if (w == 0) {
#pragma unroll 1
    for (int s = 0; s < NST; s++) {
      asm volatile(ELECT "@p mbarrier.init.shared::cta.b64 [%0], 1;\n}" ::"r"(B_FULL + 8 * s) : "memory");
      if (bid < 128) {
        e_expect(B_FULL + 8 * s, 32768);
        e_tma2d(RING + s * SLOT + 16384, &mp.m_x, s * 64, tm * 128, B_FULL + 8 * s);
        e_tma3d(RING + s * SLOT, &mp.m_wqkv, s * 64, 16 + 2 * tn, B_FULL + 8 * s);
      }
      if (s == 0) CK(2);
    }
  }
  if (w == 1) e_pfmap(&mp.m_wqkv);
  if (w == 2) e_pfmap(&mp.m_xs);
  if (w >= 4) {
#pragma unroll 1
    for (uint32_t b = MISC + 8 * (w + 1); b < MISC + 8 * NBAR; b += 96)
      asm volatile(ELECT "@p mbarrier.init.shared::cta.b64 [%0], %1;\n}" ::"r"(b), "r"(b == B_CSDN || b == B_RESD ? 4 : 1) : "memory");
    if (w == 15) sts32(S_NCAND, 0);
  }
  CK(3);
  asm volatile("fence.mbarrier_init.release.cluster;" ::: "memory");
  __syncthreads();

  auto front = [&](int i0, int i1) {
#pragma unroll 1
    for (int i = i0; i < i1; i++) {
      const int c = (XS_ORD >> (4 * i)) & 3;
      if (i >= XS_FLY) mbar_wait(B_XS + 8 * (i - XS_FLY), 0);
      if (c == (tm >> 2)) {
        e_expect(B_WK, 16384);
        e_tma3d(FR, &mp.m_wqkv, tm * 64, 16 + 2 * tn, B_WK);
      }
      e_expect(B_XS + 8 * i, 8192);
      e_tma2d(STG + i * 8192, &mp.m_xs, c * 256, tm * 128 + tn * 16, B_XS + 8 * i);
    }
  };
  if (XS_EARLY && w == 5 && bid < 128) front(0, XS_EARLY);

  if (bid >= 128) {
    const int h0 = bid == 128 ? 14 : bid - 129, hs = bid == 128 ? 1 : 3, h1 = bid == 128 ? 16 : 14;
    if (w == 12) {
      int s = 0, ph = 1;
      if (bid == 128) mbar_wait(B_SEL, 0);
      else if (H_DELAY) __nanosleep(H_DELAY);
#pragma unroll 1
      for (int h = h0; h < h1; h += hs) {
        const int c = 2 * h + (h & 8) * 2;
#pragma unroll 1
        for (int kt = 0; kt < 16; kt += 2) {
          mbar_wait(B_EMPTY + 8 * s, ph);
          e_expect(B_FULL + 8 * s, 32768);
          e_tma3d(RING + s * SLOT, &mp.m_wqkv, kt * 64, c, B_FULL + 8 * s);
          e_tma3d(RING + s * SLOT + 16384, &mp.m_wqkv, kt * 64 + 64, c, B_FULL + 8 * s);
          if (++s == HST) { s = 0; ph ^= 1; }
        }
      }
    } else if (w < 4) {
      const uint32_t par = (ld_relaxed(&g_epoch) + 1) & 1u;
      sts32(S_ONES + tid * 4, 0x3f803f80u);
      fence_async_smem();
      nb_sync(NB_WG0, 128);
      int s = 0, ph = 0;
#pragma unroll 1
      for (int h = h0; h < h1; h += hs) {
        float c[4][4];
#pragma unroll
        for (int i = 0; i < 4; i++) reg_zero(c[i]);
        uint32_t prev = 0;
#pragma unroll 1
        for (int kt = 0; kt < 8; kt++) {
          mbar_wait(B_FULL + 8 * s, ph);
          const uint64_t dw = mkdesc(RING, 8192, 1024, 1) + s * (SLOT >> 4);
          wg_fence();
#pragma unroll
          for (int j = 0; j < 16; j++) wgmma_n8_ss<1, 0>(c[j & 3], dw + (j & 3) * 512 + (j >> 2) * 128, mkdesc(S_ONES, 128, 128, 0), 1);
          wg_commit();
          wg_wait<1>();
          if (prev && tid == 0) mbar_arrive(prev);
          prev = B_EMPTY + 8 * s;
          if (++s == HST) { s = 0; ph ^= 1; }
        }
        wg_wait<0>();
        if (tid == 0) mbar_arrive(prev);
#pragma unroll
        for (int i = 0; i < 4; i++) reg_fence(c[i]);
        const bool u2 = lane & 2, u1 = lane & 1;
        const float lo = u2 ? c[1][0] + c[3][0] : c[0][0] + c[2][0], hi = u2 ? c[1][2] + c[3][2] : c[0][2] + c[2][2];
        st_relaxed(g_csum + h * 128 + (lane & 2) * 32 + w * 16 + (lane & 1) * 8 + (lane >> 2), tagf(u1 ? hi : lo, par));
        STAMP_IF(tid == 0, h >= 8 ? 6 : 30);
      }
    } else if (w < 12 && bid == 128) {
      const int t = tid - 128, j = w - 4;
      const uint32_t ep = ld_relaxed(&g_epoch) + 1;
      uint32_t kk[16];
      poll_keys(kk, g_keys + t * 2, ep, 31u);
      STAMP_IF(t == 0, 42);
      const uint32_t m = __reduce_max_sync(0xffffffffu, max(max(max(kk[0], kk[2]), max(kk[4], kk[6])), max(max(kk[8], kk[10]), max(kk[12], kk[14]))));
      if (lane == 0) sts32(S_WMAX + j * 4, m);
      nb_sync(NB_WG1, 256);
      const uint32_t T = __reduce_min_sync(0xffffffffu, lds32(S_WMAX + (lane & 7) * 4));
      uint32_t cnt = 0;
#pragma unroll
      for (int i = 0; i < 8; i++) cnt += kk[2 * i] >= T;
      if (cnt) {
        uint32_t pos;
        asm volatile("atom.shared.add.u32 %0, [%1], %2;" : "=r"(pos) : "r"(S_NCAND), "r"(cnt * 8) : "memory");
#pragma unroll
        for (int i = 0; i < 8; i++)
          if (kk[2 * i] >= T) { sts64(AUX + pos, kk[2 * i], kk[2 * i + 1]); pos += 8; }
      }
      nb_sync(NB_WG1, 256);
      const uint32_t n8 = lds32(S_NCAND);
#pragma unroll 1
      for (uint32_t i = j * 8; i < n8; i += 64) {
        const float2 c = lds64f(AUX + i);
        uint32_t rank = 0;
#pragma unroll 1
        for (uint32_t q = lane * 8; q < n8 + lane * 8; q += 256) rank += __popc(__ballot_sync(0xffffffffu, q < n8 && lds32(AUX + q) > __float_as_uint(c.x)));
        if (rank < 8) sts64(S_SEL + rank * 8, __float_as_uint(c.x), __float_as_uint(c.y));
      }
      fence_async_smem();
      nb_sync(NB_WG1, 256);
      if (j == 0) {
        const uint4 v = lds128(S_SEL + (lane & 3) * 16);
        asm volatile("{\n.reg .b64 x, y;\nmov.b64 x, {%1,%2};\nmov.b64 y, {%3,%4};\nst.relaxed.gpu.global.v2.b64 [%0], {x, y};\n}"
                     ::"l"(g_sel + (lane >> 2) * 16 + (lane & 3) * 2), "r"(v.x), "r"(v.y), "r"(v.z), "r"(v.w) : "memory");
        e_arrive(B_SEL);
      }
      STAMP_IF(t == 0, 45);
    }
  } else if (w >= 12) {
    asm volatile("setmaxnreg.dec.sync.aligned.u32 32;");
    if (w == 12) {
      int s = 0, ph = 0;
#pragma unroll 1
      for (int it = NST; it < 48; it++) {
        const int c = (it < 32 ? (it & 16) + 16 : 0) + 2 * tn;
        mbar_wait(B_EMPTY + 8 * s, ph);
        e_expect(B_FULL + 8 * s, 32768);
        e_tma3d(RING + s * SLOT, &mp.m_wqkv, (it & 15) * 64, c, B_FULL + 8 * s);
        e_tma2d(RING + s * SLOT + 16384, &mp.m_x, (it & 15) * 64, tm * 128, B_FULL + 8 * s);
        if (it >= NST) STAMP2(it - NST);
        if (++s == NST) { s = 0; ph ^= 1; }
      }
#pragma unroll 1
      for (int r = 0; r < 16; r++) {
        const int kb = out_kblock(r, tn);
        mbar_wait(B_EMPTY + 8 * s, ph);
        e_expect(B_FULL + 8 * s, r < 2 ? 16384 : 32768);
        e_tma3d(RING + s * SLOT, &mp.m_wo, kb * 64, 2 * tn, B_FULL + 8 * s);
        if (r < 2) {
          e_expect(B_XRES + 8 * r, 16384);
          e_tma2d(RING + s * SLOT + 16384, &mp.m_x, kb * 64, tm * 128, B_XRES + 8 * r);
        } else if (r == 4) {
          e_expect(B_DR + 8, 16384);
          e_tma2d_ef(RING + 2 * SLOT + 16384, &mp.m_down, (bid & 15) * 64, (bid >> 4) * 448 + 128, B_DR + 8, EVICT_FIRST);
          e_tma2d_ef(RING + 2 * SLOT + 24576, &mp.m_down, (bid & 15) * 64, (bid >> 4) * 448 + 192, B_DR + 8, EVICT_FIRST);
        }
        STAMP2(r + 48 - NST);
        if (++s == NST) { s = 0; ph ^= 1; }
      }
    } else if (w == 13) {
      if (XS_EARLY < XS_FLY) mbar_wait(B_FULL + 8 * XS_GO, 0);
      front(XS_EARLY, 4);
      {
        const char* pd = mp.wd + (bid & 15) * 128 + ((bid >> 4) * 448 + lane) * 2048;
        mbar_wait(B_XS + 24, 0);
        __nanosleep(PF_WAIT);
#pragma unroll 1
        for (int i = 0; i < 14; i++, pd += 65536) {
          if (PF_GAP) asm volatile("prefetch.global.L2 [%0];" ::"l"(pd));
          if (PF_GAP) __nanosleep(PF_GAP);
        }
      }
      nb_sync(NB_Z, 160);
      const uint32_t ep = lds32(S_EPOCH);
      {
        float z[4] = {0.f, 0.f, 0.f, 0.f};
        e_signal(H_Z + tn, tm);
        await(H_Z + tn, 0xffffu, ep);
#pragma unroll 1
        for (int i = 0; i < 4; i++) {
          uint32_t p[16];
          poll_z(p, g_z + i * 4096 + tn * 128 + lane * 4, ep, 1u);
#pragma unroll
          for (int q = 0; q < 4; q++) z[q] += (__uint_as_float(p[q]) + __uint_as_float(p[4 + q])) + (__uint_as_float(p[8 + q]) + __uint_as_float(p[12 + q]));
        }
        const uint32_t z01 = pack(z[0], z[1]), z23 = pack(z[2], z[3]);
        if (bid < 112) mbar_wait(B_PFREE, 0);
#pragma unroll
        for (int i = 0; i < 4; i++) {
          const int n = 2 * i + (lane >> 4);
          asm volatile("st.shared.v2.u32 [%0], {%1,%2};" ::"r"(KVB_Z + n * 128 + ((((lane >> 1) & 7) ^ n) << 4) + (lane & 1) * 8), "r"(z01), "r"(z23) : "memory");
        }
        fence_async_smem();
        nb_arrive(NB_KVB, 288);
        STAMP_IF(lane == 0, 46);
      }
      nb_sync(NB_Q0, 192);
      e_store2d(&mp.m_os, tn * 128, tm * 128, STG);
      nb_sync(NB_OWN0, 288);
      e_store2d(&mp.m_os, tn * 128, tm * 128 + 64, STG + 8192);
      bulk_wait_read();
      e_signal(H_O + tm, 2 * tn);
      STAMP_IF(lane == 0, 4);
      nb_sync(NB_H1, 160);
      e_store2d(&mp.m_os, tn * 128 + 64, tm * 128, STG + 16384);
      e_store2d(&mp.m_os, tn * 128 + 64, tm * 128 + 64, STG + 24576);
      bulk_wait_read();
      e_signal(H_O + tm, 2 * tn + 1);
      STAMP_IF(lane == 0, 5);
      nb_arrive(NB_ST, 160);
    } else if (w == 14) {
      e_pfmap(&mp.m_gu); e_pfmap(&mp.m_o); e_pfmap(&mp.m_os); e_pfmap(&mp.m_wo); e_pfmap(&mp.m_down); e_pfmap(&mp.m_out);
      const uint32_t ep = ld_relaxed(&g_epoch) + 1;
      nb_sync(NB_FDONE, 416);
      {
        uint32_t c[4];
        poll_quad(c, g_csum + tn * 128 + lane * 4, ep, 1u);
        sts128(S_CSQ + lane * 16, c[0], c[1], c[2], c[3]);
        nb_arrive(NB_CSQ, 160);
        poll_quad(c, g_csum + 1024 + tn * 128 + lane * 4, ep, 1u);
        sts128(S_CSV + lane * 16, c[0], c[1], c[2], c[3]);
        __syncwarp();
        e_arrive(B_CSV);
      }
      nb_sync(NB_Q0, 192);
      uint32_t ready = 0;
      int s = 0, ph = 1;
#pragma unroll 1
      for (int r = 2; r < 16; r++) {
        const int kb = out_kblock(r, tn);
        if (!((ready >> kb) & 1)) {
          uint32_t f[1];
          poll0(f, g_sig + (H_O + tm) * 32, 0u - (ep & 1u), 1u << kb);
          ready = f[0] ^ ((ep & 1u) - 1u);
        }
        if (r == 4) mbar_wait(B_DND, 0);
        if (r == 5) mbar_wait(B_DND2, 0);
        mbar_wait(B_EMPTY + 8 * s, ph);
        e_tma2d(RING + s * SLOT + 16384, &mp.m_o, kb * 64, tm * 128, B_FULL + 8 * s);
        STAMP_IF(lane == 0 && r == 2, 2);
        STAMP_IF(lane == 0 && r == 9, 3);
        if (++s == NST) { s = 0; ph ^= 1; }
      }
    } else {
      uint32_t nsm = 132;
      if (BY_SMID) asm volatile("mov.u32 %0, %%nsmid;" : "=r"(nsm));
      asm volatile("{\n.reg .pred q;\nsetp.eq.u32 q, %0, 1156;\n@q bra LOK;\ntrap;\nLOK:\n}" ::"r"((uint32_t)__cvta_generic_to_shared(smem_raw) + nsm));
      const uint32_t ep = ld_relaxed(&g_epoch) + 1;
      mbar_wait(B_CSDN, 0);
#pragma unroll 1
      for (int n = 0; n < 5; n++) {
        __nanosleep(FFN_GAP);
        if (bid < 112) {
          e_expect(B_FR + 8 * n, 4096);
          e_tma3d_ef(GR + n * 4096, &mp.m_gu, bid * 32, n * 32, B_FR + 8 * n, EVICT_FIRST);
        }
      }
      uint32_t sel[2];
      poll_pair(sel, g_sel + (bid >> 4) * 16 + (lane >> 2), ep, 31u);
      const char* xs = mp.x + key_token(sel[0]) * 2048 + (lane & 3) * 16;
      const uint32_t xd = AUX + (lane >> 2) * 64 + (((lane & 3) ^ (lane >> 3)) << 4);
      auto slice = [&](int n, int p) {
        asm volatile("cp.async.cg.shared.global [%0], [%1], 16;\ncp.async.commit_group;" ::"r"(xd + p * 512), "l"(xs + n * 64) : "memory");
      };
      if ((lane & 3) == 0) sts64(S_SEL + lane * 2, sel[0], sel[1]);
      if (bid < 112) {
#pragma unroll
        for (int i = 0; i < 5; i++) slice(i, i + 9);
      }
      asm volatile("cp.async.wait_group 0;" ::: "memory");
      fence_async_smem();
      __syncwarp();
      e_arrive(B_SEL);
      if (bid < 112) {
#pragma unroll
        for (int i = 5; i < 23; i++) slice(i < 18 ? i : i + 9, i < 9 ? i + 9 : i < 18 ? i - 9 : i);
        int s = 0, ph = 0;
#pragma unroll 1
        for (int n = 5; n < 32; n++) {
          if (n == 5 || n == 9 || n == 18) {
            if (n == 5) asm volatile("cp.async.wait_group 14;" ::: "memory");
            else if (n == 9) asm volatile("cp.async.wait_group 4;" ::: "memory");
            else asm volatile("cp.async.wait_group 0;" ::: "memory");
            fence_async_smem();
            __syncwarp();
          }
          mbar_wait(B_FE + 8 * s, ph);
          e_expect(B_FR + 8 * s, 4096);
          e_tma3d_ef(GR + s * 4096, &mp.m_gu, bid * 32 , n * 32 , B_FR + 8 * s, EVICT_FIRST);
          if (n < 14) slice(n + 13, n + 4);
          STAMP2(64 + n);
          if (++s == 5) { s = 0; ph ^= 1; }
        }
      }
      e_expect(B_DR, 16384);
      if (bid < 112) mbar_wait(B_FE + 32, 1);
      e_tma2d_ef(FR + 8192, &mp.m_down, (bid & 15) * 64, (bid >> 4) * 448 + 64, B_DR, EVICT_FIRST);
      if (bid < 112) mbar_wait(B_FE + 8, 0);
      e_tma2d_ef(FR, &mp.m_down, (bid & 15) * 64, (bid >> 4) * 448, B_DR, EVICT_FIRST);
      mbar_wait(B_RESD, 0);
      e_expect(B_DR + 16, 24576);
      e_tma2d_ef(RING + 3 * SLOT + 16384, &mp.m_down, (bid & 15) * 64, (bid >> 4) * 448 + 256, B_DR + 16, EVICT_FIRST);
      e_tma2d_ef(RING + 3 * SLOT + 24576, &mp.m_down, (bid & 15) * 64, (bid >> 4) * 448 + 320, B_DR + 16, EVICT_FIRST);
      e_tma2d_ef(RING + 4 * SLOT + 16384, &mp.m_down, (bid & 15) * 64, (bid >> 4) * 448 + 384, B_DR + 16, EVICT_FIRST);
    }
  } else if (w >= 8) {
    asm volatile("setmaxnreg.dec.sync.aligned.u32 56;");
    const int t = tid - 256, ww = w - 8;
    const uint32_t ep = ld_relaxed(&g_epoch) + 1, par = ep & 1u;
    sts32(FONES + t * 4, 0x3f803f80u);
    {
      const int r0 = (lane >> 3) + (lane & 4);
      const uint32_t a = FR + (ww >> 1) * 8192 + r0 * 128 + ((((ww & 1) * 4 + (lane & 3)) ^ r0) << 4);
      float c[8];
      reg_zero(c);
      mbar_wait(B_WK, 0);
#pragma unroll 2
      for (int i = 0; i < 8; i++) {
        const uint4 v = lds128(a + i * 1024);
        c[0] += bf_lo(v.x); c[1] += bf_hi(v.x); c[2] += bf_lo(v.y); c[3] += bf_hi(v.y);
        c[4] += bf_lo(v.z); c[5] += bf_hi(v.z); c[6] += bf_lo(v.w); c[7] += bf_hi(v.w);
      }
      const bool u16 = lane & 16, u8 = lane & 8, u4 = lane & 4;
      const float d0 = xred(c[0], c[4], u16, 16), d1 = xred(c[1], c[5], u16, 16), d2 = xred(c[2], c[6], u16, 16), d3 = xred(c[3], c[7], u16, 16);
      fence_async_smem();
      e_arrive(B_CSDN);
      const float sum = xred(xred(d0, d2, u8, 8), xred(d1, d3, u8, 8), u4, 4);
      st_relaxed(g_csum + (2 + tm) * 1024 + tn * 128 + ww * 32 + (lane & 3) * 8 + (lane >> 2), tagf(sum, par));
      STAMP_IF(t == 0, 8);
      nb_sync(NB_WG2, 128);
      if (ww == 0) { e_signal(H_CS + tn, tm); await(H_CS + tn, 0xffffu, ep); }
      nb_sync(NB_WG2, 128);
      uint32_t p[16];
      poll16(p, g_csum + 2048 + tn * 128 + t, par, 1u);
      float tot = 0.f;
#pragma unroll
      for (int i = 0; i < 16; i += 4) tot += (__uint_as_float(p[i]) + __uint_as_float(p[i + 1])) + (__uint_as_float(p[i + 2]) + __uint_as_float(p[i + 3]));
      sts32(S_CSK + t * 4, __float_as_uint(tot));
      nb_arrive(NB_FDONE, 416);
      STAMP_IF(t == 0, 9);
    }
    const int ks = bid >> 4, nt = bid & 15;
    if (bid < 112) {
      float fg[8];
      reg_zero(fg);
      mbar_wait(B_SEL, 0);
      constexpr uint64_t DA0 = mkdesc(GR, 2048, 512, 2), DB0 = mkdesc(AUX, 16, FONES - AUX, 2), DBS = 32 - (32ull << 32);
      uint64_t da = DA0, db = DB0 + 9 * DBS;
      uint32_t bar = B_FR, ph = 0, prev = 0;
#pragma unroll 1
      for (int n = 0; n < 32; n++) {
        mbar_wait(bar, ph);
        wg_fence();
        wgmma_n16_ss<1, 0>(fg, da, db, 1);
        wgmma_n16_ss<1, 0>(fg, da + 64, db + 2, 1);
        wg_commit();
        const uint32_t rel = prev;
        const bool wrap = bar == B_FR + 32;
        prev = bar + (B_FE - B_FR);
        da = wrap ? DA0 : da + 256;
        db = n == 8 ? DB0 : db + DBS;
        bar = wrap ? B_FR : bar + 8;
        ph ^= wrap;
        wg_wait<1>();
        if (rel && t == 0) mbar_arrive(rel);
        if (n == 27 && t == 0) mbar_arrive(B_PFREE);
      }
      const uint4 st = lds128(S_SEL + (lane & 3) * 16);
      const float r0 = rcp(bf_lo(st.y)), r1 = rcp(bf_lo(st.w));
      wg_wait<0>();
      reg_fence(fg);
      if (t == 0) mbar_arrive(prev);
      const float fa[4] = {fmaf(-bf_hi(st.y), fg[4], fg[0]) * r0, fmaf(-bf_hi(st.w), fg[4], fg[1]) * r1,
                           fmaf(-bf_hi(st.y), fg[6], fg[2]) * r0, fmaf(-bf_hi(st.w), fg[6], fg[3]) * r1};
      STAMP_IF(t == 0, 12);
      const bool isup = (ww >> 1) != (mp.wu < mp.wg);
      if (isup) sts128f(GR + (t & 63) * 16, fa[0], fa[1], fa[2], fa[3]);
      nb_sync(NB_WG2, 128);
      if (!isup) {
        const float4 u = lds128f(GR + (t & 63) * 16);
        const float uu[4] = {u.x, u.y, u.z, u.w};
        uint32_t* hp = g_h + bid * 256 + (lane & 3) * 64 + (ww & 1) * 16 + (lane >> 2);
#pragma unroll
        for (int i = 0; i < 4; i++) {
          const float g = fa[i], hv = g * rcp(1.f + ex2(-g * LOG2E)) * uu[i];
          st_relaxed(hp + (i & 1) * 32 + (i >> 1) * 8, __byte_perm(pack(hv, hv), ep, 0x3254));
        }
      }
      nb_sync(NB_WG2, 128);
      if (ww == 0) e_signal(H_H + bid / 14, bid % 14);
    }
    {
      uint32_t v[28];
      if (ww == 0) await(H_H + ks, 0x3fffu, ep);
      nb_sync(NB_WG2, 128);
      poll7x4(v, g_h + ks * 3584 + t * 4, ep, 0xffffu);
#pragma unroll
      for (int q = 0; q < 7; q++)
        asm volatile("st.shared.v2.u32 [%0], {%1,%2};" ::"r"(HOP + q * 1024 + (t >> 3) * 64 + ((((t >> 1) & 3) ^ ((t >> 4) & 3)) << 4) + (t & 1) * 8),
                     "r"(__byte_perm(v[4 * q], v[4 * q + 1], 0x7632)), "r"(__byte_perm(v[4 * q + 2], v[4 * q + 3], 0x7632)) : "memory");
      fence_async_smem();
      nb_sync(NB_WG2, 128);
    }
    STAMP_IF(t == 0, 13);
    float fa[4] = {0.f, 0.f, 0.f, 0.f};
    auto down = [&](uint32_t a, int k0, int nk) {
#pragma unroll
      for (int q = 0; q < nk; q++) wgmma_n8_ss<1, 0>(fa, mkdesc(a + q * 2048, 4096, 1024, 1), mkdesc(HOP + ((k0 + q) >> 1) * 512 + (q & 1) * 32, 16, 512, 2), 1);
    };
    mbar_wait(B_DR + 8, 0);
    wg_fence();
    down(RING + 2 * SLOT + 16384, 8, 8);
    wg_commit();
    mbar_wait(B_DR, 0);
    wg_fence();
    down(FR, 0, 8);
    wg_commit();
    wg_wait<1>();
    if (t == 0) mbar_arrive(B_DND);
    mbar_wait(B_DR + 16, 0);
    wg_fence();
    down(RING + 3 * SLOT + 16384, 16, 8);
    down(RING + 4 * SLOT + 16384, 24, 4);
    wg_commit();
    wg_wait<0>();
    reg_fence(fa);
    if (t == 0) mbar_arrive(B_DND2);
    STAMP_IF(t == 0, 14);
    {
      uint32_t* yp = g_yp + (nt * 8 + ks) * 512 + (lane & 3) * 128 + ww * 16 + (lane >> 2);
#pragma unroll
      for (int i = 0; i < 4; i++) st_relaxed(yp + (i & 1) * 64 + (i >> 1) * 8, tagf(fa[i], par));
    }
    nb_sync(NB_WG2, 128);
    if (ww == 0) e_signal(H_Y + (nt >> 1), (nt & 1) * 8 + ks);
    mbar_wait(B_SEL, 0);
    const uint32_t mykey = lds32(S_SEL + (lane & 7) * 8);
    const uint32_t inmask = __ballot_sync(0xffffffffu, (key_token(mykey) >> 7) == tm) & 0xffu;
    if (inmask) {
      sts128(FR + t * 16, 0u, 0u, 0u, 0u);
      if (ww == 0) await(H_Y + tn, 0xffffu, ep);
      nb_sync(NB_WG2, 128);
      const float sg = rcp(1.f + ex2(-key_score(mykey) * LOG2E));
#pragma unroll 1
      for (uint32_t mine = __ballot_sync(0xffffffffu, ((inmask >> lane) & 1) && (__popc(inmask & ((1u << lane) - 1)) & 3) == ww); mine; mine &= mine - 1) {
        const int j = __ffs(mine) - 1;
        uint32_t p[32];
        poll8x4(p, g_yp + (tn * 2 + (lane >> 4)) * 4096 + j * 64 + (lane & 15) * 4, par, 1u);
        float y[4];
        const float sj = __shfl_sync(0xffffffffu, sg, j);
#pragma unroll
        for (int i = 0; i < 4; i++)
          y[i] = sj * (((__uint_as_float(p[i]) + __uint_as_float(p[4 + i])) + (__uint_as_float(p[8 + i]) + __uint_as_float(p[12 + i]))) +
                       ((__uint_as_float(p[16 + i]) + __uint_as_float(p[20 + i])) + (__uint_as_float(p[24 + i]) + __uint_as_float(p[28 + i]))));
        asm volatile("st.shared.v2.u32 [%0], {%1,%2};" ::"r"(FR + (lane >> 4) * 1024 + j * 128 + ((((lane >> 1) & 7) ^ j) << 4) + (lane & 1) * 8),
                     "r"(pack(y[0], y[1])), "r"(pack(y[2], y[3])) : "memory");
      }
      fence_async_smem();
      nb_arrive(NB_Y, 256);
    }
    STAMP_IF(t == 0, 15);
  } else if (w >= 4) {
    asm volatile("setmaxnreg.inc.sync.aligned.u32 208;");
    const int t = tid - 128, ww = w - 4, g = lane >> 2, t4 = lane & 3;
    const bool leader = t == 0;
    const uint32_t ep = ld_relaxed(&g_epoch) + 1, par = ep & 1u;
    {
      const uint4* wp = reinterpret_cast<const uint4*>(mp.w_r) + lane;
      uint4 w0 = __ldg(wp + (XS_ORD & 3) * 32), w1 = __ldg(wp + ((XS_ORD >> 4) & 3) * 32), w2 = __ldg(wp + ((XS_ORD >> 8) & 3) * 32), w3 = __ldg(wp + ((XS_ORD >> 12) & 3) * 32);
      if (leader) sts32(S_EPOCH, ep);
      if (KV_DIRECT && lane < 8) st_unit(g_kv + tn * 512 + tm * 32 + ww * 8 + lane, 0u, 0u, 0u, 0u, par ^ 1u);
      float s[4] = {0.f, 0.f, 0.f, 0.f}, q[4] = {0.f, 0.f, 0.f, 0.f}, d[4] = {0.f, 0.f, 0.f, 0.f}, wsum = 0.f;
#pragma unroll 1
      for (int c = 0; c < 4; c++) {
        const float wr[8] = {bf_lo(w0.x), bf_hi(w0.x), bf_lo(w0.y), bf_hi(w0.y), bf_lo(w0.z), bf_hi(w0.z), bf_lo(w0.w), bf_hi(w0.w)};
        w0 = w1; w1 = w2; w2 = w3;
        wsum += ((wr[0] + wr[1]) + (wr[2] + wr[3])) + ((wr[4] + wr[5]) + (wr[6] + wr[7]));
        mbar_wait(B_XS + 8 * c, 0);
#pragma unroll
        for (int r = 0; r < 4; r++) {
          const uint4 v = lds128(STG + c * 8192 + (ww * 4 + r) * 512 + lane * 16);
          const uint32_t xw[4] = {v.x, v.y, v.z, v.w};
#pragma unroll
          for (int i = 0; i < 4; i++) {
            const uint32_t dep = __float_as_uint(q[i ? r : (r + 3) & 3]);
            const float lo = POLITE ? __uint_as_float(prmt(xw[i], dep, 0x10ff)) : bf_lo(xw[i]), hi = POLITE ? __uint_as_float(prmt(xw[i], dep, 0x32ff)) : bf_hi(xw[i]);
            s[r] += lo; q[r] = fmaf(lo, lo, q[r]); d[r] = fmaf(lo, wr[2 * i], d[r]);
            s[r] += hi; q[r] = fmaf(hi, hi, q[r]); d[r] = fmaf(hi, wr[2 * i + 1], d[r]);
          }
        }
      }
      STAMP_IF(leader, 16);
      const bool u16 = lane & 16, u8 = lane & 8, u4 = lane & 4, u2 = lane & 2;
      const float s1 = xred(xred(s[0], s[2], u16, 16), xred(s[1], s[3], u16, 16), u8, 8);
      const float q1 = xred(xred(q[0], q[2], u16, 16), xred(q[1], q[3], u16, 16), u8, 8);
      const float d1 = xred(xred(d[0], d[2], u16, 16), xred(d[1], d[3], u16, 16), u8, 8);
      wsum += __shfl_xor_sync(0xffffffffu, wsum, 16);
      wsum += __shfl_xor_sync(0xffffffffu, wsum, 8);
      float tot = xred(xred(s1, d1, u4, 4), xred(q1, wsum, u4, 4), u2, 2);
      tot += __shfl_xor_sync(0xffffffffu, tot, 1);
      const float qq = __shfl_down_sync(0xffffffffu, tot, 2), dd = __shfl_down_sync(0xffffffffu, tot, 4), ws = __shfl_down_sync(0xffffffffu, tot, 6);
      if ((lane & 7) == 0) {
        const float mean = tot * (1.f / 1024.f);
        const float var = fmaxf(fmaf(-mean, mean, qq * (1.f / 1024.f)), 0.f);
        float sd;
        asm("sqrt.approx.ftz.f32 %0, %1;" : "=f"(sd) : "f"(bf_round(bf_round(var) + 1e-5f)));
        const uint32_t ms = pack(sd, mean);
        const int row = tm * 128 + tn * 16 + ww * 4 + (lane >> 3);
        const uint32_t rbits = pack(0.f, fmaf(-bf_hi(ms), ws, dd) * rcp(bf_lo(ms)));
        const uint32_t key = (rbits ^ (((int)rbits >> 31 & 0x7fff0000u) | 0x80000000u)) | ((2047 - row) << 5) | (ep & 31u);
        asm volatile("{\n.reg .b64 x;\nmov.b64 x, {%1,%2};\nst.relaxed.gpu.global.b64 [%0], x;\n}" ::"l"(g_keys + row), "r"(key), "r"(ms) : "memory");
      }
      STAMP_IF(leader, 17);
      __nanosleep(400);
      uint32_t st[2];
      poll_pair(st, g_keys + tm * 128 + t, ep, 31u);
      asm volatile("st.shared.v2.f32 [%0], {%1,%2};" ::"r"(S_KSTAT + t * 8), "f"(bf_hi(st[1])), "f"(rcp(bf_lo(st[1])) * LOG2E) : "memory");
      nb_arrive(NB_FDONE, 416);
      STAMP_IF(leader, 10);
    }
    float a0[64], a1[64];
    reg_zero(a0); reg_zero(a1); reg_fence(a0); reg_fence(a1);
    STAMP_IF(leader, 18);
    nb_sync(NB_KV, 256);
    mainloop<true>(a0, a1, 1, 1, NB_VQ, 0, leader);
    STAMP_IF(leader, 19);
    {
      uint32_t f0[32], f1[32];
#pragma unroll
      for (int i = 0; i < 32; i++) { f0[i] = pack(a0[2 * i], a0[2 * i + 1]); f1[i] = pack(a1[2 * i], a1[2 * i + 1]); }
      float c0[32], c1[32];
      reg_zero(c0); reg_zero(c1);
      nb_sync(NB_PK, 256);
      constexpr uint64_t db = mkdesc(STG, 16, 1024, 1);
      wg_fence();
#pragma unroll
      for (int k = 0; k < 8; k++) {
        wgmma_n64_rs<0>(c0, f0[4 * k], f0[4 * k + 1], f0[4 * k + 2], f0[4 * k + 3], db + (k >> 2) * 1024 + (k & 3) * 2, k != 0);
        wgmma_n64_rs<0>(c1, f1[4 * k], f1[4 * k + 1], f1[4 * k + 2], f1[4 * k + 3], db + (k >> 2) * 1024 + (k & 3) * 2 + 512, k != 0);
        if (GATE_KT && k == GATE_K) nb_arrive(NB_KV, 256);
      }
      wg_commit();
      const bool hp = ww >> 1;
      float c[4];
      float2 tt[8];
#pragma unroll
      for (int i = 0; i < 8; i++) tt[i] = lds64f(S_CSK + ((i >> 2) * 64 + hp * 32 + (i & 3) * 8 + 2 * t4) * 4);
      mbar_wait(B_CSV, 0);
#pragma unroll
      for (int i = 0; i < 4; i++) c[i] = -__uint_as_float(lds32(S_CSV + ((i >> 1) * 64 + ww * 16 + (i & 1) * 8 + g) * 4));
      wg_wait<0>();
      reg_fence(c0);
      reg_fence(c1);
      STAMP_IF(leader, 20);
      uint4* pp = g_kvp + (tn * 16 + tm) * 512 + t;
      auto put = [&](int q, const float* d) {
        const float ca = c[q & 2], cb = c[q | 1];
        const float2 ta = tt[2 * q], tb = tt[2 * q + 1];
        st_unit(pp + q * 128, pack(fmaf(ca, ta.x, d[0]), fmaf(ca, ta.y, d[1])), pack(fmaf(cb, ta.x, d[2]), fmaf(cb, ta.y, d[3])),
                pack(fmaf(ca, tb.x, d[4]), fmaf(ca, tb.y, d[5])), pack(fmaf(cb, tb.x, d[6]), fmaf(cb, tb.y, d[7])), par);
      };
      if (!hp) { put(0, c0); put(1, c0 + 8); put(2, c1); put(3, c1 + 8); }
      else { put(0, c0 + 16); put(1, c0 + 24); put(2, c1 + 16); put(3, c1 + 24); }
      STAMP_IF(leader, 47);
      {
        uint32_t p[16];
        nb_sync(NB_WG1, 128);
        if (ww == 0) { e_signal(H_KVP + tn, tm); await(H_KVP + tn, 0xffffu, ep); }
        nb_sync(NB_WG1, 128);
        STAMP_IF(leader, 1);
        poll_kvp(p, g_kvp + (tn * 16 + (lane >> 3) * 4) * 512 + tm * 32 + ww * 8 + (lane & 7), par, 1u);
        float r[8];
#pragma unroll
        for (int i = 0; i < 4; i++) {
          r[2 * i] = (bf_lo(p[i]) + bf_lo(p[4 + i])) + (bf_lo(p[8 + i]) + bf_lo(p[12 + i]));
          r[2 * i + 1] = (bf_hi(p[i]) + bf_hi(p[4 + i])) + (bf_hi(p[8 + i]) + bf_hi(p[12 + i]));
        }
#pragma unroll
        for (int i = 0; i < 8; i++) r[i] += __shfl_xor_sync(0xffffffffu, r[i], 8);
#pragma unroll
        for (int i = 0; i < 8; i++) r[i] += __shfl_xor_sync(0xffffffffu, r[i], 16);
        if (lane < 8) st_unit(g_kv + tn * 512 + tm * 32 + ww * 8 + lane, pack(r[0], r[1]), pack(r[2], r[3]), pack(r[4], r[5]), pack(r[6], r[7]), par);
      }
      STAMP_IF(leader, 21);
    }
    const uint32_t sx = lane & 7, sc = lane >> 4;
    const uint32_t sa = STG + (ww * 16 + (lane & 15)) * 128;
    const uint32_t sw[4] = {sa + ((sc ^ sx) << 4), sa + (((2 + sc) ^ sx) << 4), sa + (((4 + sc) ^ sx) << 4), sa + (((6 + sc) ^ sx) << 4)};
    {
      uint32_t v[16];
      if (!KV_DIRECT) {
        nb_sync(NB_WG1, 128);
        if (ww == 0) { e_signal(H_KV + tn, tm); await(H_KV + tn, 0xffffu, ep); }
        nb_sync(NB_WG1, 128);
      } else {
        __nanosleep(KV_DIRECT);
      }
      STAMP_IF(leader, 7);
      poll_kv(v, g_kv + tn * 512 + t, par, 1u);
      if (bid < 112) mbar_wait(B_PFREE, 0);
      STAMP_IF(leader, 23);
#pragma unroll
      for (int q = 0; q < 4; q++)
        stsm4((q < 2 ? KVB_P0 : KVB_P1) + ((ww & 1) * 16 + (lane & 15)) * 128 + ((((ww >> 1) * 4 + (q & 1) * 2 + sc) ^ sx) << 4),
              v[4 * q], v[4 * q + 1], v[4 * q + 2], v[4 * q + 3]);
      fence_async_smem();
      nb_arrive(NB_KVB, 288);
    }
    STAMP_IF(leader, 24);
    uint32_t oh[4];
    uint32_t inmask;
    {
      mbar_wait(B_SEL, 0);
      const int r0 = key_token(lds32(S_SEL + t4 * 16)) - tm * 128, r1 = key_token(lds32(S_SEL + t4 * 16 + 8)) - tm * 128;
#pragma unroll
      for (int i = 0; i < 4; i++) {
        const int row = (i >> 1) * 64 + ww * 16 + (i & 1) * 8 + g;
        oh[i] = (r0 == row ? 0x3f00u : 0u) | (r1 == row ? 0x3f000000u : 0u);
      }
      inmask = __ballot_sync(0xffffffffu, (unsigned)r0 < 128u || (unsigned)r1 < 128u);
    }
    uint32_t va = RING + 16384 + sc * 8192 + (ww * 16 + (lane & 8)) * 128 + sx * 16 + (lane >> 3) * 4;
    asm volatile("" : "+r"(va));
    {
      float ka[4], kb[4];
#pragma unroll
      for (int i = 0; i < 4; i++) {
        const float2 st = lds64f(S_KSTAT + ((i >> 1) * 64 + ww * 16 + (i & 1) * 8 + g) * 8);
        const float r = st.y * LN2;
        ka[i] = 1.f + r; kb[i] = -st.x * r;
      }
      constexpr uint32_t XOFF = RING + 3 * SLOT + 16384 - STG;
#pragma unroll
      for (int j = 0; j < 8; j++) {
        if ((j & 3) == 0) mbar_wait(B_XRES + 8 * (j >> 2), 0);
        const uint4 v = ldsm4(sw[j & 3] + XOFF + (j >> 2) * SLOT), u = ldsm4(sw[j & 3] + XOFF + (j >> 2) * SLOT + 8192);
        const uint32_t vv[4] = {v.x, v.y, v.z, v.w}, uu[4] = {u.x, u.y, u.z, u.w};
#pragma unroll
        for (int i = 0; i < 4; i++) {
          a0[8 * j + 2 * i] = fmaf(bf_lo(vv[i]), ka[i & 1], kb[i & 1]);
          a0[8 * j + 2 * i + 1] = fmaf(bf_hi(vv[i]), ka[i & 1], kb[i & 1]);
          a1[8 * j + 2 * i] = fmaf(bf_lo(uu[i]), ka[2 + (i & 1)], kb[2 + (i & 1)]);
          a1[8 * j + 2 * i + 1] = fmaf(bf_hi(uu[i]), ka[2 + (i & 1)], kb[2 + (i & 1)]);
        }
      }
      reg_fence(a0);
      reg_fence(a1);
      fence_async_smem();
      __syncwarp();
      e_arrive(B_RESD);
      STAMP_IF(leader, 22);
    }
    {
      auto own = [&](int r) {
        nb_sync(NB_OWN0 + r, r ? 256 : 288);
        mbar_wait(B_FULL + 8 * (3 + r), 1);
        STAMP_IF(leader, 25 + r);
        const uint64_t dw = mkdesc(RING + (3 + r) * SLOT, 8192, 1024, 1), dx = mkdesc(STG + r * 16384, 16, 1024, 1);
        wg_fence();
#pragma unroll
        for (int j = 0; j < 4; j++) {
          wgmma_n128_ss<0, 1>(a0, dx + j * 2, dw + j * 128, 1);
          wgmma_n128_ss<0, 1>(a1, dx + j * 2 + 512, dw + j * 128, 1);
        }
        wg_commit();
      };
      own(0);
      wg_wait<0>();
      if (leader) mbar_arrive(B_EMPTY + 24);
      own(1);
      int s = 0, ph = 0;
      uint32_t prev = B_EMPTY + 32;
#pragma unroll 1
      for (int r = 2; r < 16; r++) {
        mbar_wait(B_FULL + 8 * s, ph);
        {
          uint32_t bad;
          asm volatile("{\n.reg .u32 a, b, c, d, e, f, g, h;\n.reg .pred p;\n"
                       "ld.shared.u32 a, [%1];\nld.shared.u32 b, [%1+128];\nld.shared.u32 c, [%1+256];\nld.shared.u32 d, [%1+384];\n"
                       "ld.shared.u32 e, [%1+512];\nld.shared.u32 f, [%1+640];\nld.shared.u32 g, [%1+768];\nld.shared.u32 h, [%1+896];\n"
                       "lop3.b32 a, a, b, %2, 0x7e;\nlop3.b32 c, c, d, %2, 0x7e;\nlop3.b32 e, e, f, %2, 0x7e;\nlop3.b32 g, g, h, %2, 0x7e;\n"
                       "lop3.b32 a, a, c, e, 0xfe;\nlop3.b32 a, a, g, 1, 0xa8;\nsetp.ne.u32 p, a, 0;\nvote.sync.any.pred p, p, 0xffffffff;\nselp.u32 %0, 1, 0, p;\n}"
                       : "=r"(bad) : "r"(va + s * SLOT), "r"(par) : "memory");
          if (bad) {
            const uint4* src = reinterpret_cast<const uint4*>(g_o + (tm * 128 + sc * 64 + ww * 16 + (lane & 15)) * 1024 + out_kblock(r, tn) * 64);
#pragma unroll 1
            for (int i = 0; i < 8; i++) {
              uint32_t v[4];
              asm volatile("{\n.reg .b64 x, y;\n.reg .b128 z;\n.reg .pred p, q, h;\n.reg .u32 c, b;\nmov.u32 c, 0;\nsetp.ne.u32 h, %6, 0;\nLW:\n"
                           "ld.relaxed.gpu.global.b128 z, [%4];\nmov.b128 {x, y}, z;\nmov.b64 {%0,%1}, x;\nmov.b64 {%2,%3}, y;\n"
                           "selp.b64 x, y, x, h;\nshr.b64 x, x, %7;\ncvt.u32.u64 b, x;\nand.b32 b, b, 1;\nsetp.eq.u32 p, b, %5;\n"
                           "vote.sync.all.pred p, p, 0xffffffff;\n@p bra.uni LD;\nadd.u32 c, c, 1;\nsetp.lt.u32 q, c, 1000000;\n@q bra.uni LW;\ntrap;\nLD:\n}"
                           : "=&r"(v[0]), "=&r"(v[1]), "=&r"(v[2]), "=&r"(v[3]) : "l"(src + i), "r"(par), "r"(sc), "r"((lane & 8) * 4) : "memory");
              sts128(RING + 16384 + s * SLOT + sc * 8192 + (ww * 16 + (lane & 15)) * 128 + ((i ^ sx) << 4), v[0], v[1], v[2], v[3]);
            }
            fence_async_smem();
            __syncwarp();
          }
        }
        if (!LITE || ((LITE_MASK >> 27) & 1)) STAMP_IF(leader && r == 2, 27);
        const uint64_t dw = mkdesc(RING, 8192, 1024, 1) + s * (SLOT >> 4), dx = mkdesc(RING + 16384, 16, 1024, 1) + s * (SLOT >> 4);
        wg_fence();
#pragma unroll
        for (int j = 0; j < 4; j++) {
          wgmma_n128_ss<0, 1>(a0, dx + j * 2, dw + j * 128, 1);
          wgmma_n128_ss<0, 1>(a1, dx + j * 2 + 512, dw + j * 128, 1);
        }
        wg_commit();
        wg_wait<1>();
        if (leader) mbar_arrive(prev);
        prev = B_EMPTY + 8 * s;
        if (++s == NST) { s = 0; ph ^= 1; }
      }
      if (inmask) {
        nb_sync(NB_Y, 256);
        wg_fence();
        wgmma_n128_rs<1>(a0, oh[0], oh[1], oh[0], oh[1], mkdesc(FR, 1024, 0, 1), 1);
        wgmma_n128_rs<1>(a1, oh[2], oh[3], oh[2], oh[3], mkdesc(FR, 1024, 0, 1), 1);
        wg_commit();
      }
      nb_sync(NB_ST, 160);
      wg_wait<0>();
      reg_fence(a0);
      reg_fence(a1);
    }
    STAMP_IF(leader, 28);
#pragma unroll
    for (int c = 0; c < 2; c++) {
#pragma unroll
      for (int j = 4 * c; j < 4 * c + 4; j++) {
        stsm4(sw[j & 3] + c * 16384, pack(a0[8 * j], a0[8 * j + 1]), pack(a0[8 * j + 2], a0[8 * j + 3]), pack(a0[8 * j + 4], a0[8 * j + 5]), pack(a0[8 * j + 6], a0[8 * j + 7]));
        stsm4(sw[j & 3] + c * 16384 + 8192, pack(a1[8 * j], a1[8 * j + 1]), pack(a1[8 * j + 2], a1[8 * j + 3]), pack(a1[8 * j + 4], a1[8 * j + 5]), pack(a1[8 * j + 6], a1[8 * j + 7]));
      }
      fence_async_smem();
      e_store2d(&mp.m_out, tn * 128 + c * 64, tm * 128 + ww * 16, STG + c * 16384 + ww * 2048);
      e_store2d(&mp.m_out, tn * 128 + c * 64, tm * 128 + 64 + ww * 16, STG + c * 16384 + 8192 + ww * 2048);
    }
    bulk_wait_read();
    if (bid == 0 && leader) st_relaxed(&g_epoch, ep);
    STAMP_IF(leader, 29);
  } else {
    asm volatile("setmaxnreg.inc.sync.aligned.u32 216;");
    const int g = lane >> 2, t4 = lane & 3;
    const bool leader = tid == 0;
    const uint32_t sx = lane & 7, sc = lane >> 4;
    const uint32_t sa = STG + (w * 16 + (lane & 15)) * 128;
    const uint32_t sw[4] = {sa + ((sc ^ sx) << 4), sa + (((2 + sc) ^ sx) << 4), sa + (((4 + sc) ^ sx) << 4), sa + (((6 + sc) ^ sx) << 4)};
    float a0[64], a1[64];
    reg_zero(a0); reg_zero(a1); reg_fence(a0); reg_fence(a1);
    if (ALIGN) { uint32_t now; do { asm volatile("mov.u32 %0, %%clock;" : "=r"(now)); } while ((int)(now - ck0) < ALIGN); }
    mainloop<true>(a0, a1, 0, 0, NB_KV, 0, leader);
    STAMP_IF(leader, 33);
    {
      nb_sync(NB_FDONE, 416);
      STAMP_IF(leader, 34);
      float c[4], z[4] = {0.f, 0.f, 0.f, 0.f}, tt[4] = {0.f, 0.f, 0.f, 0.f};
#pragma unroll
      for (int i = 0; i < 4; i++) c[i] = -__uint_as_float(lds32(S_CSK + ((i >> 1) * 64 + w * 16 + (i & 1) * 8 + g) * 4));
#pragma unroll
      for (int j = 0; j < 8; j++) {
        const float4 s0 = lds128v(S_KSTAT + (j * 16 + 2 * t4) * 8), s1 = lds128v(S_KSTAT + (j * 16 + 8 + 2 * t4) * 8);
        const float mu[4] = {s0.x, s0.z, s1.x, s1.z}, rl[4] = {s0.y, s0.w, s1.y, s1.w};
#pragma unroll
        for (int m = 0; m < 2; m++) {
          float p[8];
#pragma unroll
          for (int i = 0; i < 8; i++) {
            const int r = m * 2 + ((i >> 1) & 1), cc = (i >> 2) * 2 + (i & 1);
            p[i] = phi2(fmaf(c[r], mu[cc], m ? a1[8 * j + i] : a0[8 * j + i]) * rl[cc]);
            z[r] += p[i];
            p[i] *= rl[cc];
            tt[r] = fmaf(p[i], mu[cc], tt[r]);
          }
          stsm4(sw[j & 3] + (j >> 2) * 16384 + m * 8192, pack(p[0], p[1]), pack(p[2], p[3]), pack(p[4], p[5]), pack(p[6], p[7]));
        }
      }
      const bool u2 = lane & 2, u1 = lane & 1;
      const float zz = xred(xred(z[0], z[2], u2, 2), xred(z[1], z[3], u2, 2), u1, 1);
      sts32(S_CSK + ((t4 >> 1) * 64 + w * 16 + (t4 & 1) * 8 + g) * 4, __float_as_uint(xred(xred(tt[0], tt[2], u2, 2), xred(tt[1], tt[3], u2, 2), u1, 1)));
      fence_async_smem();
      nb_arrive(NB_PK, 256);
      st_relaxed(g_z + tm * 1024 + tn * 128 + (t4 >> 1) * 64 + w * 16 + (t4 & 1) * 8 + g, tagf(zz * LOG2E, lds32(S_EPOCH) & 1u));
      nb_arrive(NB_Z, 160);
    }
    STAMP_IF(leader, 35);
    float rl0[2];
    const uint32_t ep = lds32(S_EPOCH);
    {
      nb_sync(NB_CSQ, 160);
      float mu[4];
#pragma unroll
      for (int i = 0; i < 4; i++) {
        const float2 st = lds64f(S_KSTAT + ((i >> 1) * 64 + w * 16 + (i & 1) * 8 + g) * 8);
        mu[i] = -st.x;
        if (i < 2) rl0[i] = st.y;
      }
#pragma unroll
      for (int j = 0; j < 16; j++) {
        const float2 c = lds64f(S_CSQ + (j * 8 + 2 * t4) * 4);
        a0[4 * j] = mu[0] * c.x; a0[4 * j + 1] = mu[0] * c.y; a0[4 * j + 2] = mu[1] * c.x; a0[4 * j + 3] = mu[1] * c.y;
        a1[4 * j] = mu[2] * c.x; a1[4 * j + 1] = mu[2] * c.y; a1[4 * j + 2] = mu[3] * c.x; a1[4 * j + 3] = mu[3] * c.y;
      }
      reg_fence(a0); reg_fence(a1);
    }
    STAMP_IF(leader, 40);
    nb_sync(NB_VQ, 256);
    mainloop<false>(a0, a1, 2, 0, 0, GATE_KT ? NB_KV : 0, leader);
    STAMP_IF(leader, 36);
    {
      uint32_t f[2][16];
      float oc[2][2][20];
      auto phi = [&](const float (&a)[64], int j, int m, uint32_t (&o)[16]) {
        float rl[2] = {rl0[0], rl0[1]};
        if (j | m) { rl[0] = lds32v(S_KSTAT + (m * 64 + w * 16 + g) * 8 + 4); rl[1] = lds32v(S_KSTAT + (m * 64 + w * 16 + 8 + g) * 8 + 4); }
#pragma unroll
        for (int i = 0; i < 16; i++) o[i] = pack(phi2(a[32 * j + 2 * i] * rl[i & 1]), phi2(a[32 * j + 2 * i + 1] * rl[i & 1]));
      };
      auto mma = [&](int j, const uint32_t (&a)[16], float (&o)[2][20]) {
        const uint64_t db = mkdesc(j ? KVB_Z : KVB_P0, 16, 1024, 1);
        reg_zero(o[0]); reg_zero(o[1]);
        wg_fence();
        wgmma_n40_rs<0>(o[0], a[0], a[1], a[2], a[3], db, 0);
        wgmma_n40_rs<0>(o[1], a[8], a[9], a[10], a[11], db + 4, 0);
        wgmma_n40_rs<0>(o[0], a[4], a[5], a[6], a[7], db + 2, 1);
        wgmma_n40_rs<0>(o[1], a[12], a[13], a[14], a[15], db + 6, 1);
        wg_commit();
      };
      auto fin = [&](int j, int m, float (&o)[2][20]) {
        const uint32_t m0 = t4 == 2 * m, m1 = t4 == 2 * m + 1;
#pragma unroll
        for (int h = 0; h < 2; h++) {
          const float r0 = rcp(o[h][j ? 1 : 16] + 1e-6f * LOG2E), r1 = rcp(o[h][j ? 3 : 18] + 1e-6f * LOG2E);
          const int b = j ? 4 : 0;
#pragma unroll
          for (int q = 0; q < 2; q++)
            stsm4(sw[h * 2 + q] + j * 16384 + m * 8192,
                  bsel(pack(o[h][b + 8 * q] * r0, o[h][b + 8 * q + 1] * r0), ep, m0), bsel(pack(o[h][b + 8 * q + 2] * r1, o[h][b + 8 * q + 3] * r1), ep, m1),
                  bsel(pack(o[h][b + 8 * q + 4] * r0, o[h][b + 8 * q + 5] * r0), ep, m0), bsel(pack(o[h][b + 8 * q + 6] * r1, o[h][b + 8 * q + 7] * r1), ep, m1));
        }
      };
#pragma unroll
      for (int j = 0; j < 2; j++) {
        phi(a0, j, 0, f[0]);
        if (j == 0) nb_sync(NB_KVB, 288);
        STAMP_IF(leader && j == 0, 37);
        mma(j, f[0], oc[0]);
        phi(a1, j, 1, f[1]);
        wg_wait<0>();
        reg_fence(oc[0][0]); reg_fence(oc[0][1]);
        mma(j, f[1], oc[1]);
        fin(j, 0, oc[0]);
        if (j == 0) { fence_async_smem(); nb_arrive(NB_Q0, 192); }
        wg_wait<0>();
        reg_fence(oc[1][0]); reg_fence(oc[1][1]);
        fin(j, 1, oc[1]);
        fence_async_smem();
        if (j == 0) nb_arrive(NB_OWN0, 288);
        else { nb_arrive(NB_OWN1, 256); nb_arrive(NB_H1, 160); }
        STAMP_IF(leader, 38 + j);
      }
    }
  }
}

#undef CK
typedef CUresult (*EncodeFn)(CUtensorMap*, CUtensorMapDataType, cuuint32_t, void*, const cuuint64_t*, const cuuint64_t*, const cuuint32_t*,
                             const cuuint32_t*, CUtensorMapInterleave, CUtensorMapSwizzle, CUtensorMapL2promotion, CUtensorMapFloatOOBfill);

void make_map(EncodeFn enc, CUtensorMap* m, const void* p, int rank, uint64_t d0, uint64_t d1, uint64_t d2, uint64_t s1, uint64_t s2,
              uint32_t b0, uint32_t b1, uint32_t b2, CUtensorMapSwizzle sw) {
  cuuint64_t gd[3] = {d0, d1, d2}, gs[2] = {s1, s2};
  cuuint32_t bd[3] = {b0, b1, b2}, es[3] = {1, 1, 1};
  enc(m, CU_TENSOR_MAP_DATA_TYPE_BFLOAT16, rank, const_cast<void*>(p), gd, gs, bd, es, CU_TENSOR_MAP_INTERLEAVE_NONE, sw,
      CU_TENSOR_MAP_L2_PROMOTION_L2_128B, CU_TENSOR_MAP_FLOAT_OOB_FILL_NONE);
}

}

extern "C" void kernel_launch(void* const* d_in, const int* in_sizes, int n_in, void* d_out, int out_size) {
  (void)in_sizes; (void)n_in; (void)out_size;
  void* fn = nullptr;
  cudaDriverEntryPointQueryResult qr;
  cudaGetDriverEntryPoint("cuTensorMapEncodeTiled", &fn, cudaEnableDefault, &qr);
  EncodeFn enc = (EncodeFn)fn;
  void* o;
  cudaGetSymbolAddress(&o, g_o);
  const CUtensorMapSwizzle S128 = CU_TENSOR_MAP_SWIZZLE_128B, S64 = CU_TENSOR_MAP_SWIZZLE_64B, S0 = CU_TENSOR_MAP_SWIZZLE_NONE;
  Params mp;
  mp.x = (const char*)d_in[0]; mp.wqkv = (const char*)d_in[1]; mp.w_r = (const char*)d_in[4];
  mp.wg = (const char*)d_in[5]; mp.wu = (const char*)d_in[6]; mp.wd = (const char*)d_in[7];
  make_map(enc, &mp.m_wqkv, d_in[1], 3, 64, 1024, 48, 6144, 128, 64, 64, 2, S128);
  make_map(enc, &mp.m_x, d_in[0], 2, 1024, 2048, 1, 2048, 0, 64, 128, 1, S128);
  make_map(enc, &mp.m_os, o, 2, 1024, 2048, 1, 2048, 0, 64, 64, 1, S128);
  make_map(enc, &mp.m_o, o, 2, 1024, 2048, 1, 2048, 0, 64, 128, 1, S128);
  make_map(enc, &mp.m_wo, d_in[2], 3, 64, 1024, 16, 2048, 128, 64, 64, 2, S128);
  make_map(enc, &mp.m_xs, d_in[0], 2, 1024, 2048, 1, 2048, 0, 256, 16, 1, S0);
  const char *wg = (const char*)d_in[5], *wu = (const char*)d_in[6];
  make_map(enc, &mp.m_gu, wu < wg ? wu : wg, 3, 3584, 1024, 2, 7168, (uint64_t)(wu < wg ? wg - wu : wu - wg), 32, 32, 2, S64);
  make_map(enc, &mp.m_down, d_in[7], 2, 1024, 3584, 1, 2048, 0, 64, 64, 1, S128);
  make_map(enc, &mp.m_out, d_out, 2, 1024, 2048, 1, 2048, 0, 64, 16, 1, S128);
  int dev = 0, sms = 0;
  cudaGetDevice(&dev);
  cudaDeviceGetAttribute(&sms, cudaDevAttrMultiProcessorCount, dev);
  auto kern = sms == 132 ? fused_kernel<true> : fused_kernel<false>;
  cudaFuncSetAttribute(kern, cudaFuncAttributeMaxDynamicSharedMemorySize, SMEM_BYTES);
  kern<<<132, 512, SMEM_BYTES>>>(mp);
}
```

```cpp
#include <cuda_runtime.h>
#include <cuda.h>
#include <cuda_bf16.h>
#include <stdint.h>

namespace {

template <int TA, int TB>
__device__ __forceinline__ void wgmma_n8_ss(float (&d)[4], uint64_t da, uint64_t db, int sc) {
  asm volatile("{\n.reg .pred p;\nsetp.ne.b32 p, %6, 0;\n"
    "wgmma.mma_async.sync.aligned.m64n8k16.f32.bf16.bf16 {%0, %1, %2, %3}, %4, %5, p, 1, 1, %7, %8;\n}\n"
    : "+f"(d[0]), "+f"(d[1]), "+f"(d[2]), "+f"(d[3])
    : "l"(da), "l"(db), "r"(sc), "n"(TA), "n"(TB));
}
template <int TA, int TB>
__device__ __forceinline__ void wgmma_n16_ss(float (&d)[8], uint64_t da, uint64_t db, int sc) {
  asm volatile("{\n.reg .pred p;\nsetp.ne.b32 p, %10, 0;\n"
    "wgmma.mma_async.sync.aligned.m64n16k16.f32.bf16.bf16 {%0, %1, %2, %3, %4, %5, %6, %7}, %8, %9, p, 1, 1, %11, %12;\n}\n"
    : "+f"(d[0]), "+f"(d[1]), "+f"(d[2]), "+f"(d[3]), "+f"(d[4]), "+f"(d[5]), "+f"(d[6]), "+f"(d[7])
    : "l"(da), "l"(db), "r"(sc), "n"(TA), "n"(TB));
}
template <int TB>
__device__ __forceinline__ void wgmma_n40_rs(float (&d)[20], uint32_t a0, uint32_t a1, uint32_t a2, uint32_t a3, uint64_t db, int sc) {
  asm volatile("{\n.reg .pred p;\nsetp.ne.b32 p, %25, 0;\n"
    "wgmma.mma_async.sync.aligned.m64n40k16.f32.bf16.bf16 {%0, %1, %2, %3, %4, %5, %6, %7, %8, %9, %10, %11, %12, %13, %14, %15, %16, %17, %18, %19}, {%20,%21,%22,%23}, %24, p, 1, 1, %26;\n}\n"
    : "+f"(d[0]), "+f"(d[1]), "+f"(d[2]), "+f"(d[3]), "+f"(d[4]), "+f"(d[5]), "+f"(d[6]), "+f"(d[7]),
      "+f"(d[8]), "+f"(d[9]), "+f"(d[10]), "+f"(d[11]), "+f"(d[12]), "+f"(d[13]), "+f"(d[14]), "+f"(d[15]),
      "+f"(d[16]), "+f"(d[17]), "+f"(d[18]), "+f"(d[19])
    : "r"(a0), "r"(a1), "r"(a2), "r"(a3), "l"(db), "r"(sc), "n"(TB));
}
template <int TB>
__device__ __forceinline__ void wgmma_n64_rs(float (&d)[32], uint32_t a0, uint32_t a1, uint32_t a2, uint32_t a3, uint64_t db, int sc) {
  asm volatile("{\n.reg .pred p;\nsetp.ne.b32 p, %37, 0;\n"
    "wgmma.mma_async.sync.aligned.m64n64k16.f32.bf16.bf16 {%0, %1, %2, %3, %4, %5, %6, %7, %8, %9, %10, %11, %12, %13, %14, %15, %16, %17, %18, %19, %20, %21, %22, %23, %24, %25, %26, %27, %28, %29, %30, %31}, {%32,%33,%34,%35}, %36, p, 1, 1, %38;\n}\n"
    : "+f"(d[0]), "+f"(d[1]), "+f"(d[2]), "+f"(d[3]), "+f"(d[4]), "+f"(d[5]), "+f"(d[6]), "+f"(d[7]),
      "+f"(d[8]), "+f"(d[9]), "+f"(d[10]), "+f"(d[11]), "+f"(d[12]), "+f"(d[13]), "+f"(d[14]), "+f"(d[15]),
      "+f"(d[16]), "+f"(d[17]), "+f"(d[18]), "+f"(d[19]), "+f"(d[20]), "+f"(d[21]), "+f"(d[22]), "+f"(d[23]),
      "+f"(d[24]), "+f"(d[25]), "+f"(d[26]), "+f"(d[27]), "+f"(d[28]), "+f"(d[29]), "+f"(d[30]), "+f"(d[31])
    : "r"(a0), "r"(a1), "r"(a2), "r"(a3), "l"(db), "r"(sc), "n"(TB));
}
template <int TA, int TB>
__device__ __forceinline__ void wgmma_n128_ss(float (&d)[64], uint64_t da, uint64_t db, int sc) {
  asm volatile("{\n.reg .pred p;\nsetp.ne.b32 p, %66, 0;\n"
    "wgmma.mma_async.sync.aligned.m64n128k16.f32.bf16.bf16 {%0, %1, %2, %3, %4, %5, %6, %7, %8, %9, %10, %11, %12, %13, %14, %15, %16, %17, %18, %19, %20, %21, %22, %23, %24, %25, %26, %27, %28, %29, %30, %31, %32, %33, %34, %35, %36, %37, %38, %39, %40, %41, %42, %43, %44, %45, %46, %47, %48, %49, %50, %51, %52, %53, %54, %55, %56, %57, %58, %59, %60, %61, %62, %63}, %64, %65, p, 1, 1, %67, %68;\n}\n"
    : "+f"(d[0]), "+f"(d[1]), "+f"(d[2]), "+f"(d[3]), "+f"(d[4]), "+f"(d[5]), "+f"(d[6]), "+f"(d[7]),
      "+f"(d[8]), "+f"(d[9]), "+f"(d[10]), "+f"(d[11]), "+f"(d[12]), "+f"(d[13]), "+f"(d[14]), "+f"(d[15]),
      "+f"(d[16]), "+f"(d[17]), "+f"(d[18]), "+f"(d[19]), "+f"(d[20]), "+f"(d[21]), "+f"(d[22]), "+f"(d[23]),
      "+f"(d[24]), "+f"(d[25]), "+f"(d[26]), "+f"(d[27]), "+f"(d[28]), "+f"(d[29]), "+f"(d[30]), "+f"(d[31]),
      "+f"(d[32]), "+f"(d[33]), "+f"(d[34]), "+f"(d[35]), "+f"(d[36]), "+f"(d[37]), "+f"(d[38]), "+f"(d[39]),
      "+f"(d[40]), "+f"(d[41]), "+f"(d[42]), "+f"(d[43]), "+f"(d[44]), "+f"(d[45]), "+f"(d[46]), "+f"(d[47]),
      "+f"(d[48]), "+f"(d[49]), "+f"(d[50]), "+f"(d[51]), "+f"(d[52]), "+f"(d[53]), "+f"(d[54]), "+f"(d[55]),
      "+f"(d[56]), "+f"(d[57]), "+f"(d[58]), "+f"(d[59]), "+f"(d[60]), "+f"(d[61]), "+f"(d[62]), "+f"(d[63])
    : "l"(da), "l"(db), "r"(sc), "n"(TA), "n"(TB));
}
template <int TB>
__device__ __forceinline__ void wgmma_n128_rs(float (&d)[64], uint32_t a0, uint32_t a1, uint32_t a2, uint32_t a3, uint64_t db, int sc) {
  asm volatile("{\n.reg .pred p;\nsetp.ne.b32 p, %69, 0;\n"
    "wgmma.mma_async.sync.aligned.m64n128k16.f32.bf16.bf16 {%0, %1, %2, %3, %4, %5, %6, %7, %8, %9, %10, %11, %12, %13, %14, %15, %16, %17, %18, %19, %20, %21, %22, %23, %24, %25, %26, %27, %28, %29, %30, %31, %32, %33, %34, %35, %36, %37, %38, %39, %40, %41, %42, %43, %44, %45, %46, %47, %48, %49, %50, %51, %52, %53, %54, %55, %56, %57, %58, %59, %60, %61, %62, %63}, {%64,%65,%66,%67}, %68, p, 1, 1, %70;\n}\n"
    : "+f"(d[0]), "+f"(d[1]), "+f"(d[2]), "+f"(d[3]), "+f"(d[4]), "+f"(d[5]), "+f"(d[6]), "+f"(d[7]),
      "+f"(d[8]), "+f"(d[9]), "+f"(d[10]), "+f"(d[11]), "+f"(d[12]), "+f"(d[13]), "+f"(d[14]), "+f"(d[15]),
      "+f"(d[16]), "+f"(d[17]), "+f"(d[18]), "+f"(d[19]), "+f"(d[20]), "+f"(d[21]), "+f"(d[22]), "+f"(d[23]),
      "+f"(d[24]), "+f"(d[25]), "+f"(d[26]), "+f"(d[27]), "+f"(d[28]), "+f"(d[29]), "+f"(d[30]), "+f"(d[31]),
      "+f"(d[32]), "+f"(d[33]), "+f"(d[34]), "+f"(d[35]), "+f"(d[36]), "+f"(d[37]), "+f"(d[38]), "+f"(d[39]),
      "+f"(d[40]), "+f"(d[41]), "+f"(d[42]), "+f"(d[43]), "+f"(d[44]), "+f"(d[45]), "+f"(d[46]), "+f"(d[47]),
      "+f"(d[48]), "+f"(d[49]), "+f"(d[50]), "+f"(d[51]), "+f"(d[52]), "+f"(d[53]), "+f"(d[54]), "+f"(d[55]),
      "+f"(d[56]), "+f"(d[57]), "+f"(d[58]), "+f"(d[59]), "+f"(d[60]), "+f"(d[61]), "+f"(d[62]), "+f"(d[63])
    : "r"(a0), "r"(a1), "r"(a2), "r"(a3), "l"(db), "r"(sc), "n"(TB));
}

__device__ __forceinline__ void poll1(uint32_t (&v)[1], const void* p, uint32_t tag, uint32_t mask) {
  asm volatile("{\n.reg .pred p, q;\n.reg .u32 c, b;\n.reg .b64 x, y;\n.reg .b128 z;\nmov.u32 c, 0;\nLW:\n"
               "ld.relaxed.gpu.global.u32 %0, [%1+0];\n"
               "xor.b32 b, %0, %2;\n"
               "and.b32 b, b, %3;\nsetp.eq.u32 p, b, 0;\nvote.sync.all.pred p, p, 0xffffffff;\n@p bra.uni LD;\n"
               "nanosleep.u32 100;\nadd.u32 c, c, 1;\nsetp.lt.u32 q, c, 1000000;\n@q bra.uni LW;\ntrap;\nLD:\n}"
               : "=&r"(v[0])
               : "l"(p), "r"(tag), "r"(mask) : "memory");
}
__device__ __forceinline__ void poll1f(uint32_t (&v)[1], const void* p, uint32_t tag, uint32_t mask) {
  asm volatile("{\n.reg .pred p, q;\n.reg .u32 c, b;\n.reg .b64 x, y;\n.reg .b128 z;\nmov.u32 c, 0;\nLW:\n"
               "ld.relaxed.gpu.global.u32 %0, [%1+0];\n"
               "xor.b32 b, %0, %2;\n"
               "and.b32 b, b, %3;\nsetp.eq.u32 p, b, 0;\nvote.sync.all.pred p, p, 0xffffffff;\n@p bra.uni LD;\n"
               "nanosleep.u32 50;\nadd.u32 c, c, 1;\nsetp.lt.u32 q, c, 1000000;\n@q bra.uni LW;\ntrap;\nLD:\n}"
               : "=&r"(v[0])
               : "l"(p), "r"(tag), "r"(mask) : "memory");
}
__device__ __forceinline__ void poll0(uint32_t (&v)[1], const void* p, uint32_t tag, uint32_t mask) {
  asm volatile("{\n.reg .pred p, q;\n.reg .u32 c, b;\n.reg .b64 x, y;\n.reg .b128 z;\nmov.u32 c, 0;\nLW:\n"
               "ld.relaxed.gpu.global.u32 %0, [%1+0];\n"
               "xor.b32 b, %0, %2;\n"
               "and.b32 b, b, %3;\nsetp.eq.u32 p, b, 0;\nvote.sync.all.pred p, p, 0xffffffff;\n@p bra.uni LD;\n"
               "add.u32 c, c, 1;\nsetp.lt.u32 q, c, 1000000;\n@q bra.uni LW;\ntrap;\nLD:\n}"
               : "=&r"(v[0])
               : "l"(p), "r"(tag), "r"(mask) : "memory");
}
__device__ __forceinline__ void poll_pair(uint32_t (&v)[2], const void* p, uint32_t tag, uint32_t mask) {
  asm volatile("{\n.reg .pred p, q;\n.reg .u32 c, b;\n.reg .b64 x, y;\n.reg .b128 z;\nmov.u32 c, 0;\nLW:\n"
               "ld.relaxed.gpu.global.b64 x, [%2+0];\nmov.b64 {%0,%1}, x;\n"
               "xor.b32 b, %0, %3;\n"
               "and.b32 b, b, %4;\nsetp.eq.u32 p, b, 0;\nvote.sync.all.pred p, p, 0xffffffff;\n@p bra.uni LD;\n"
               "nanosleep.u32 100;\nadd.u32 c, c, 1;\nsetp.lt.u32 q, c, 1000000;\n@q bra.uni LW;\ntrap;\nLD:\n}"
               : "=&r"(v[0]), "=&r"(v[1])
               : "l"(p), "r"(tag), "r"(mask) : "memory");
}
__device__ __forceinline__ void poll_quad(uint32_t (&v)[4], const void* p, uint32_t tag, uint32_t mask) {
  asm volatile("{\n.reg .pred p, q;\n.reg .u32 c, b;\n.reg .b64 x, y;\n.reg .b128 z;\nmov.u32 c, 0;\nLW:\n"
               "ld.relaxed.gpu.global.v4.u32 {%0,%1,%2,%3}, [%4+0];\n"
               "xor.b32 b, %0, %5;\n"
               "lop3.b32 b, b, %1, %5, 0xf6;\nlop3.b32 b, b, %2, %5, 0xf6;\nlop3.b32 b, b, %3, %5, 0xf6;\n"
               "and.b32 b, b, %6;\nsetp.eq.u32 p, b, 0;\nvote.sync.all.pred p, p, 0xffffffff;\n@p bra.uni LD;\n"
               "nanosleep.u32 200;\nadd.u32 c, c, 1;\nsetp.lt.u32 q, c, 1000000;\n@q bra.uni LW;\ntrap;\nLD:\n}"
               : "=&r"(v[0]), "=&r"(v[1]), "=&r"(v[2]), "=&r"(v[3])
               : "l"(p), "r"(tag), "r"(mask) : "memory");
}
__device__ __forceinline__ void poll8x4(uint32_t (&v)[32], const void* p, uint32_t tag, uint32_t mask) {
  asm volatile("{\n.reg .pred p, q;\n.reg .u32 c, b;\n.reg .b64 x, y;\n.reg .b128 z;\nmov.u32 c, 0;\nLW:\n"
               "ld.relaxed.gpu.global.v4.u32 {%0,%1,%2,%3}, [%32+0];\n"
               "ld.relaxed.gpu.global.v4.u32 {%4,%5,%6,%7}, [%32+2048];\n"
               "ld.relaxed.gpu.global.v4.u32 {%8,%9,%10,%11}, [%32+4096];\n"
               "ld.relaxed.gpu.global.v4.u32 {%12,%13,%14,%15}, [%32+6144];\n"
               "ld.relaxed.gpu.global.v4.u32 {%16,%17,%18,%19}, [%32+8192];\n"
               "ld.relaxed.gpu.global.v4.u32 {%20,%21,%22,%23}, [%32+10240];\n"
               "ld.relaxed.gpu.global.v4.u32 {%24,%25,%26,%27}, [%32+12288];\n"
               "ld.relaxed.gpu.global.v4.u32 {%28,%29,%30,%31}, [%32+14336];\n"
               "xor.b32 b, %0, %33;\n"
               "lop3.b32 b, b, %1, %33, 0xf6;\nlop3.b32 b, b, %2, %33, 0xf6;\nlop3.b32 b, b, %3, %33, 0xf6;\nlop3.b32 b, b, %4, %33, 0xf6;\n"
               "lop3.b32 b, b, %5, %33, 0xf6;\nlop3.b32 b, b, %6, %33, 0xf6;\nlop3.b32 b, b, %7, %33, 0xf6;\nlop3.b32 b, b, %8, %33, 0xf6;\n"
               "lop3.b32 b, b, %9, %33, 0xf6;\nlop3.b32 b, b, %10, %33, 0xf6;\nlop3.b32 b, b, %11, %33, 0xf6;\nlop3.b32 b, b, %12, %33, 0xf6;\n"
               "lop3.b32 b, b, %13, %33, 0xf6;\nlop3.b32 b, b, %14, %33, 0xf6;\nlop3.b32 b, b, %15, %33, 0xf6;\nlop3.b32 b, b, %16, %33, 0xf6;\n"
               "lop3.b32 b, b, %17, %33, 0xf6;\nlop3.b32 b, b, %18, %33, 0xf6;\nlop3.b32 b, b, %19, %33, 0xf6;\nlop3.b32 b, b, %20, %33, 0xf6;\n"
               "lop3.b32 b, b, %21, %33, 0xf6;\nlop3.b32 b, b, %22, %33, 0xf6;\nlop3.b32 b, b, %23, %33, 0xf6;\nlop3.b32 b, b, %24, %33, 0xf6;\n"
               "lop3.b32 b, b, %25, %33, 0xf6;\nlop3.b32 b, b, %26, %33, 0xf6;\nlop3.b32 b, b, %27, %33, 0xf6;\nlop3.b32 b, b, %28, %33, 0xf6;\n"
               "lop3.b32 b, b, %29, %33, 0xf6;\nlop3.b32 b, b, %30, %33, 0xf6;\nlop3.b32 b, b, %31, %33, 0xf6;\n"
               "and.b32 b, b, %34;\nsetp.eq.u32 p, b, 0;\nvote.sync.all.pred p, p, 0xffffffff;\n@p bra.uni LD;\n"
               "nanosleep.u32 50;\nadd.u32 c, c, 1;\nsetp.lt.u32 q, c, 1000000;\n@q bra.uni LW;\ntrap;\nLD:\n}"
               : "=&r"(v[0]), "=&r"(v[1]), "=&r"(v[2]), "=&r"(v[3]), "=&r"(v[4]), "=&r"(v[5]), "=&r"(v[6]), "=&r"(v[7]), "=&r"(v[8]), "=&r"(v[9]), "=&r"(v[10]), "=&r"(v[11]), "=&r"(v[12]), "=&r"(v[13]), "=&r"(v[14]), "=&r"(v[15]), "=&r"(v[16]), "=&r"(v[17]), "=&r"(v[18]), "=&r"(v[19]), "=&r"(v[20]), "=&r"(v[21]), "=&r"(v[22]), "=&r"(v[23]), "=&r"(v[24]), "=&r"(v[25]), "=&r"(v[26]), "=&r"(v[27]), "=&r"(v[28]), "=&r"(v[29]), "=&r"(v[30]), "=&r"(v[31])
               : "l"(p), "r"(tag), "r"(mask) : "memory");
}
__device__ __forceinline__ void poll16(uint32_t (&v)[16], const void* p, uint32_t tag, uint32_t mask) {
  asm volatile("{\n.reg .pred p, q;\n.reg .u32 c, b;\n.reg .b64 x, y;\n.reg .b128 z;\nmov.u32 c, 0;\nLW:\n"
               "ld.relaxed.gpu.global.u32 %0, [%16+0];\n"
               "ld.relaxed.gpu.global.u32 %1, [%16+4096];\n"
               "ld.relaxed.gpu.global.u32 %2, [%16+8192];\n"
               "ld.relaxed.gpu.global.u32 %3, [%16+12288];\n"
               "ld.relaxed.gpu.global.u32 %4, [%16+16384];\n"
               "ld.relaxed.gpu.global.u32 %5, [%16+20480];\n"
               "ld.relaxed.gpu.global.u32 %6, [%16+24576];\n"
               "ld.relaxed.gpu.global.u32 %7, [%16+28672];\n"
               "ld.relaxed.gpu.global.u32 %8, [%16+32768];\n"
               "ld.relaxed.gpu.global.u32 %9, [%16+36864];\n"
               "ld.relaxed.gpu.global.u32 %10, [%16+40960];\n"
               "ld.relaxed.gpu.global.u32 %11, [%16+45056];\n"
               "ld.relaxed.gpu.global.u32 %12, [%16+49152];\n"
               "ld.relaxed.gpu.global.u32 %13, [%16+53248];\n"
               "ld.relaxed.gpu.global.u32 %14, [%16+57344];\n"
               "ld.relaxed.gpu.global.u32 %15, [%16+61440];\n"
               "xor.b32 b, %0, %17;\n"
               "lop3.b32 b, b, %1, %17, 0xf6;\nlop3.b32 b, b, %2, %17, 0xf6;\nlop3.b32 b, b, %3, %17, 0xf6;\nlop3.b32 b, b, %4, %17, 0xf6;\n"
               "lop3.b32 b, b, %5, %17, 0xf6;\nlop3.b32 b, b, %6, %17, 0xf6;\nlop3.b32 b, b, %7, %17, 0xf6;\nlop3.b32 b, b, %8, %17, 0xf6;\n"
               "lop3.b32 b, b, %9, %17, 0xf6;\nlop3.b32 b, b, %10, %17, 0xf6;\nlop3.b32 b, b, %11, %17, 0xf6;\nlop3.b32 b, b, %12, %17, 0xf6;\n"
               "lop3.b32 b, b, %13, %17, 0xf6;\nlop3.b32 b, b, %14, %17, 0xf6;\nlop3.b32 b, b, %15, %17, 0xf6;\n"
               "and.b32 b, b, %18;\nsetp.eq.u32 p, b, 0;\nvote.sync.all.pred p, p, 0xffffffff;\n@p bra.uni LD;\n"
               "nanosleep.u32 200;\nadd.u32 c, c, 1;\nsetp.lt.u32 q, c, 1000000;\n@q bra.uni LW;\ntrap;\nLD:\n}"
               : "=&r"(v[0]), "=&r"(v[1]), "=&r"(v[2]), "=&r"(v[3]), "=&r"(v[4]), "=&r"(v[5]), "=&r"(v[6]), "=&r"(v[7]), "=&r"(v[8]), "=&r"(v[9]), "=&r"(v[10]), "=&r"(v[11]), "=&r"(v[12]), "=&r"(v[13]), "=&r"(v[14]), "=&r"(v[15])
               : "l"(p), "r"(tag), "r"(mask) : "memory");
}
__device__ __forceinline__ void poll_keys(uint32_t (&v)[16], const void* p, uint32_t tag, uint32_t mask) {
  asm volatile("{\n.reg .pred p, q;\n.reg .u32 c, b;\n.reg .b64 x, y;\n.reg .b128 z;\nmov.u32 c, 0;\nLW:\n"
               "ld.relaxed.gpu.global.v2.b64 {x, y}, [%16+0];\nmov.b64 {%0,%1}, x;\nmov.b64 {%2,%3}, y;\n"
               "ld.relaxed.gpu.global.v2.b64 {x, y}, [%16+4096];\nmov.b64 {%4,%5}, x;\nmov.b64 {%6,%7}, y;\n"
               "ld.relaxed.gpu.global.v2.b64 {x, y}, [%16+8192];\nmov.b64 {%8,%9}, x;\nmov.b64 {%10,%11}, y;\n"
               "ld.relaxed.gpu.global.v2.b64 {x, y}, [%16+12288];\nmov.b64 {%12,%13}, x;\nmov.b64 {%14,%15}, y;\n"
               "xor.b32 b, %0, %17;\n"
               "lop3.b32 b, b, %2, %17, 0xf6;\nlop3.b32 b, b, %4, %17, 0xf6;\nlop3.b32 b, b, %6, %17, 0xf6;\nlop3.b32 b, b, %8, %17, 0xf6;\n"
               "lop3.b32 b, b, %10, %17, 0xf6;\nlop3.b32 b, b, %12, %17, 0xf6;\nlop3.b32 b, b, %14, %17, 0xf6;\n"
               "and.b32 b, b, %18;\nsetp.eq.u32 p, b, 0;\nvote.sync.all.pred p, p, 0xffffffff;\n@p bra.uni LD;\n"
               "nanosleep.u32 20;\nadd.u32 c, c, 1;\nsetp.lt.u32 q, c, 1000000;\n@q bra.uni LW;\ntrap;\nLD:\n}"
               : "=&r"(v[0]), "=&r"(v[1]), "=&r"(v[2]), "=&r"(v[3]), "=&r"(v[4]), "=&r"(v[5]), "=&r"(v[6]), "=&r"(v[7]), "=&r"(v[8]), "=&r"(v[9]), "=&r"(v[10]), "=&r"(v[11]), "=&r"(v[12]), "=&r"(v[13]), "=&r"(v[14]), "=&r"(v[15])
               : "l"(p), "r"(tag), "r"(mask) : "memory");
}
__device__ __forceinline__ void poll_z(uint32_t (&v)[16], const void* p, uint32_t tag, uint32_t mask) {
  asm volatile("{\n.reg .pred p, q;\n.reg .u32 c, b;\n.reg .b64 x, y;\n.reg .b128 z;\nmov.u32 c, 0;\nLW:\n"
               "ld.relaxed.gpu.global.v4.u32 {%0,%1,%2,%3}, [%16+0];\n"
               "ld.relaxed.gpu.global.v4.u32 {%4,%5,%6,%7}, [%16+4096];\n"
               "ld.relaxed.gpu.global.v4.u32 {%8,%9,%10,%11}, [%16+8192];\n"
               "ld.relaxed.gpu.global.v4.u32 {%12,%13,%14,%15}, [%16+12288];\n"
               "xor.b32 b, %0, %17;\n"
               "lop3.b32 b, b, %1, %17, 0xf6;\nlop3.b32 b, b, %2, %17, 0xf6;\nlop3.b32 b, b, %3, %17, 0xf6;\nlop3.b32 b, b, %4, %17, 0xf6;\n"
               "lop3.b32 b, b, %5, %17, 0xf6;\nlop3.b32 b, b, %6, %17, 0xf6;\nlop3.b32 b, b, %7, %17, 0xf6;\nlop3.b32 b, b, %8, %17, 0xf6;\n"
               "lop3.b32 b, b, %9, %17, 0xf6;\nlop3.b32 b, b, %10, %17, 0xf6;\nlop3.b32 b, b, %11, %17, 0xf6;\nlop3.b32 b, b, %12, %17, 0xf6;\n"
               "lop3.b32 b, b, %13, %17, 0xf6;\nlop3.b32 b, b, %14, %17, 0xf6;\nlop3.b32 b, b, %15, %17, 0xf6;\n"
               "and.b32 b, b, %18;\nsetp.eq.u32 p, b, 0;\nvote.sync.all.pred p, p, 0xffffffff;\n@p bra.uni LD;\n"
               "nanosleep.u32 300;\nadd.u32 c, c, 1;\nsetp.lt.u32 q, c, 1000000;\n@q bra.uni LW;\ntrap;\nLD:\n}"
               : "=&r"(v[0]), "=&r"(v[1]), "=&r"(v[2]), "=&r"(v[3]), "=&r"(v[4]), "=&r"(v[5]), "=&r"(v[6]), "=&r"(v[7]), "=&r"(v[8]), "=&r"(v[9]), "=&r"(v[10]), "=&r"(v[11]), "=&r"(v[12]), "=&r"(v[13]), "=&r"(v[14]), "=&r"(v[15])
               : "l"(p), "r"(tag), "r"(mask) : "memory");
}
__device__ __forceinline__ void poll7x4(uint32_t (&v)[28], const void* p, uint32_t tag, uint32_t mask) {
  asm volatile("{\n.reg .pred p, q;\n.reg .u32 c, b;\n.reg .b64 x, y;\n.reg .b128 z;\nmov.u32 c, 0;\nLW:\n"
               "ld.relaxed.gpu.global.v4.u32 {%0,%1,%2,%3}, [%28+0];\n"
               "ld.relaxed.gpu.global.v4.u32 {%4,%5,%6,%7}, [%28+2048];\n"
               "ld.relaxed.gpu.global.v4.u32 {%8,%9,%10,%11}, [%28+4096];\n"
               "ld.relaxed.gpu.global.v4.u32 {%12,%13,%14,%15}, [%28+6144];\n"
               "ld.relaxed.gpu.global.v4.u32 {%16,%17,%18,%19}, [%28+8192];\n"
               "ld.relaxed.gpu.global.v4.u32 {%20,%21,%22,%23}, [%28+10240];\n"
               "ld.relaxed.gpu.global.v4.u32 {%24,%25,%26,%27}, [%28+12288];\n"
               "xor.b32 b, %0, %29;\n"
               "lop3.b32 b, b, %1, %29, 0xf6;\nlop3.b32 b, b, %2, %29, 0xf6;\nlop3.b32 b, b, %3, %29, 0xf6;\nlop3.b32 b, b, %4, %29, 0xf6;\n"
               "lop3.b32 b, b, %5, %29, 0xf6;\nlop3.b32 b, b, %6, %29, 0xf6;\nlop3.b32 b, b, %7, %29, 0xf6;\nlop3.b32 b, b, %8, %29, 0xf6;\n"
               "lop3.b32 b, b, %9, %29, 0xf6;\nlop3.b32 b, b, %10, %29, 0xf6;\nlop3.b32 b, b, %11, %29, 0xf6;\nlop3.b32 b, b, %12, %29, 0xf6;\n"
               "lop3.b32 b, b, %13, %29, 0xf6;\nlop3.b32 b, b, %14, %29, 0xf6;\nlop3.b32 b, b, %15, %29, 0xf6;\nlop3.b32 b, b, %16, %29, 0xf6;\n"
               "lop3.b32 b, b, %17, %29, 0xf6;\nlop3.b32 b, b, %18, %29, 0xf6;\nlop3.b32 b, b, %19, %29, 0xf6;\nlop3.b32 b, b, %20, %29, 0xf6;\n"
               "lop3.b32 b, b, %21, %29, 0xf6;\nlop3.b32 b, b, %22, %29, 0xf6;\nlop3.b32 b, b, %23, %29, 0xf6;\nlop3.b32 b, b, %24, %29, 0xf6;\n"
               "lop3.b32 b, b, %25, %29, 0xf6;\nlop3.b32 b, b, %26, %29, 0xf6;\nlop3.b32 b, b, %27, %29, 0xf6;\n"
               "and.b32 b, b, %30;\nsetp.eq.u32 p, b, 0;\nvote.sync.all.pred p, p, 0xffffffff;\n@p bra.uni LD;\n"
               "nanosleep.u32 50;\nadd.u32 c, c, 1;\nsetp.lt.u32 q, c, 1000000;\n@q bra.uni LW;\ntrap;\nLD:\n}"
               : "=&r"(v[0]), "=&r"(v[1]), "=&r"(v[2]), "=&r"(v[3]), "=&r"(v[4]), "=&r"(v[5]), "=&r"(v[6]), "=&r"(v[7]), "=&r"(v[8]), "=&r"(v[9]), "=&r"(v[10]), "=&r"(v[11]), "=&r"(v[12]), "=&r"(v[13]), "=&r"(v[14]), "=&r"(v[15]), "=&r"(v[16]), "=&r"(v[17]), "=&r"(v[18]), "=&r"(v[19]), "=&r"(v[20]), "=&r"(v[21]), "=&r"(v[22]), "=&r"(v[23]), "=&r"(v[24]), "=&r"(v[25]), "=&r"(v[26]), "=&r"(v[27])
               : "l"(p), "r"(tag), "r"(mask) : "memory");
}
__device__ __forceinline__ void poll_kvp(uint32_t (&v)[16], const void* p, uint32_t tag, uint32_t mask) {
  asm volatile("{\n.reg .pred p, q;\n.reg .u32 c, b;\n.reg .b64 x, y;\n.reg .b128 z;\nmov.u32 c, 0;\nLW:\n"
               "ld.relaxed.gpu.global.b128 z, [%16+0];\nmov.b128 {x, y}, z;\nmov.b64 {%0,%1}, x;\nmov.b64 {%2,%3}, y;\n"
               "ld.relaxed.gpu.global.b128 z, [%16+8192];\nmov.b128 {x, y}, z;\nmov.b64 {%4,%5}, x;\nmov.b64 {%6,%7}, y;\n"
               "ld.relaxed.gpu.global.b128 z, [%16+16384];\nmov.b128 {x, y}, z;\nmov.b64 {%8,%9}, x;\nmov.b64 {%10,%11}, y;\n"
               "ld.relaxed.gpu.global.b128 z, [%16+24576];\nmov.b128 {x, y}, z;\nmov.b64 {%12,%13}, x;\nmov.b64 {%14,%15}, y;\n"
               "xor.b32 b, %0, %17;\n"
               "lop3.b32 b, b, %4, %17, 0xf6;\nlop3.b32 b, b, %8, %17, 0xf6;\nlop3.b32 b, b, %12, %17, 0xf6;\n"
               "and.b32 b, b, %18;\nsetp.eq.u32 p, b, 0;\nvote.sync.all.pred p, p, 0xffffffff;\n@p bra.uni LD;\n"
               "nanosleep.u32 50;\nadd.u32 c, c, 1;\nsetp.lt.u32 q, c, 1000000;\n@q bra.uni LW;\ntrap;\nLD:\n}"
               : "=&r"(v[0]), "=&r"(v[1]), "=&r"(v[2]), "=&r"(v[3]), "=&r"(v[4]), "=&r"(v[5]), "=&r"(v[6]), "=&r"(v[7]), "=&r"(v[8]), "=&r"(v[9]), "=&r"(v[10]), "=&r"(v[11]), "=&r"(v[12]), "=&r"(v[13]), "=&r"(v[14]), "=&r"(v[15])
               : "l"(p), "r"(tag), "r"(mask) : "memory");
}
__device__ __forceinline__ void poll_kv(uint32_t (&v)[16], const void* p, uint32_t tag, uint32_t mask) {
  asm volatile("{\n.reg .pred p, q;\n.reg .u32 c, b;\n.reg .b64 x, y;\n.reg .b128 z;\nmov.u32 c, 0;\nLW:\n"
               "ld.relaxed.gpu.global.b128 z, [%16+0];\nmov.b128 {x, y}, z;\nmov.b64 {%0,%1}, x;\nmov.b64 {%2,%3}, y;\n"
               "ld.relaxed.gpu.global.b128 z, [%16+2048];\nmov.b128 {x, y}, z;\nmov.b64 {%4,%5}, x;\nmov.b64 {%6,%7}, y;\n"
               "ld.relaxed.gpu.global.b128 z, [%16+4096];\nmov.b128 {x, y}, z;\nmov.b64 {%8,%9}, x;\nmov.b64 {%10,%11}, y;\n"
               "ld.relaxed.gpu.global.b128 z, [%16+6144];\nmov.b128 {x, y}, z;\nmov.b64 {%12,%13}, x;\nmov.b64 {%14,%15}, y;\n"
               "xor.b32 b, %0, %17;\n"
               "lop3.b32 b, b, %4, %17, 0xf6;\nlop3.b32 b, b, %8, %17, 0xf6;\nlop3.b32 b, b, %12, %17, 0xf6;\n"
               "and.b32 b, b, %18;\nsetp.eq.u32 p, b, 0;\nvote.sync.all.pred p, p, 0xffffffff;\n@p bra.uni LD;\n"
               "nanosleep.u32 50;\nadd.u32 c, c, 1;\nsetp.lt.u32 q, c, 1000000;\n@q bra.uni LW;\ntrap;\nLD:\n}"
               : "=&r"(v[0]), "=&r"(v[1]), "=&r"(v[2]), "=&r"(v[3]), "=&r"(v[4]), "=&r"(v[5]), "=&r"(v[6]), "=&r"(v[7]), "=&r"(v[8]), "=&r"(v[9]), "=&r"(v[10]), "=&r"(v[11]), "=&r"(v[12]), "=&r"(v[13]), "=&r"(v[14]), "=&r"(v[15])
               : "l"(p), "r"(tag), "r"(mask) : "memory");
}

__device__ __align__(1024) __nv_bfloat16 g_o[2048 * 1024];
__device__ __align__(128) uint2 g_keys[2048];
__device__ __align__(128) uint32_t g_csum[18 * 1024];
__device__ __align__(128) uint32_t g_z[16 * 1024];
__device__ __align__(128) uint4 g_kvp[128 * 512];
__device__ __align__(128) uint4 g_kv[8 * 512];
__device__ __align__(128) uint32_t g_h[112 * 256];
__device__ __align__(128) uint32_t g_yp[128 * 512];
__device__ __align__(128) uint2 g_sel[8 * 16];
enum { H_CS = 0, H_KVP = 8, H_KV = 16, H_H = 24, H_Y = 32, H_O = 40, H_Z = 56 };
__device__ __align__(128) uint32_t g_sig[64 * 32];
__device__ uint32_t g_epoch;

constexpr uint32_t RING = 1024, SLOT = 32768, SMEM_BYTES = 232448;
constexpr int NST = 5, HST = 7;
constexpr uint32_t STG = RING + 163840, AUX = RING + 196608, FR = RING + 212992, MISC = RING + 229376;
constexpr uint32_t B_FULL = MISC, B_EMPTY = MISC + 56, B_XS = MISC + 112, B_SEL = MISC + 144, B_WK = MISC + 160, B_CSDN = MISC + 168,
                   B_FR = MISC + 176, B_FE = MISC + 200, B_DR = MISC + 224, B_CSV = MISC + 248,
                   B_DND = MISC + 256, B_XRES = MISC + 264, B_PFREE = MISC + 280, B_SFREE = MISC + 288, NBAR = 37;
constexpr uint32_t S_EPOCH = MISC + 352, S_NCAND = MISC + 356, S_SEL = MISC + 368, S_WMAX = MISC + 432,
                   S_KSTAT = MISC + 512, S_CSK = MISC + 1536, S_CSV = MISC + 2048, S_CSQ = MISC + 2560, S_ONES = MISC + 512;
constexpr uint32_t KVB_P0 = AUX, KVB_Z = AUX + 4096, KVB_P1 = AUX + 5120, HOP = AUX + 9216, FONES = AUX + 6144, GR = FR - 8192;
enum { NB_Z = 0, NB_KV = 1, NB_VQ = 2, NB_WG0 = 3, NB_FDONE = 4, NB_PK = 5, NB_KVB = 6, NB_WG1 = 7, NB_WG2 = 8, NB_CSQ = 9,
       NB_Y = 10, NB_ST = 11, NB_OWN0 = 12, NB_OWN1 = 13, NB_Q0 = 14, NB_H1 = 15 };

#define XS_ORD 0x3210
#define XS_GO 0
#define XS_FLY 2
#define XS_EARLY 0
#define H_DELAY 0
#define FFN_GAP 400
#define RES_FIRST 1
#define KV_DIRECT 1
#define ALIGN 0
#define PF_GAP 200
#define PF_WAIT 1000
#define POLITE 1
constexpr uint64_t EVICT_FIRST = 0x12f0000000000000ull;
constexpr float LOG2E = 1.4426950408889634f, LN2 = 0.6931471805599453f;

#define ELECT "{\n.reg .pred p;\nelect.sync _|p, 0xffffffff;\n"
#define TMA2D "cp.async.bulk.tensor.2d.shared::cluster.global.mbarrier::complete_tx::bytes"
#define TMA3D "cp.async.bulk.tensor.3d.shared::cluster.global.mbarrier::complete_tx::bytes"
__device__ __forceinline__ void e_expect(uint32_t b, uint32_t n) {
  asm volatile(ELECT "@p mbarrier.arrive.expect_tx.shared::cta.b64 _, [%0], %1;\n}" ::"r"(b), "r"(n) : "memory");
}
__device__ __forceinline__ void e_arrive(uint32_t b) { asm volatile(ELECT "@p mbarrier.arrive.shared::cta.b64 _, [%0];\n}" ::"r"(b) : "memory"); }
__device__ __forceinline__ void e_tma2d(uint32_t dst, const CUtensorMap* m, int c0, int c1, uint32_t bar) {
  asm volatile(ELECT "@p " TMA2D " [%0], [%1, {%3, %4}], [%2];\n}" ::"r"(dst), "l"(m), "r"(bar), "r"(c0), "r"(c1) : "memory");
}
__device__ __forceinline__ void e_tma2d_ef(uint32_t dst, const CUtensorMap* m, int c0, int c1, uint32_t bar, uint64_t pol) {
  asm volatile(ELECT "@p " TMA2D ".L2::cache_hint [%0], [%1, {%3, %4}], [%2], %5;\n}" ::"r"(dst), "l"(m), "r"(bar), "r"(c0), "r"(c1), "l"(pol) : "memory");
}
__device__ __forceinline__ void e_tma3d(uint32_t dst, const CUtensorMap* m, int c1, int c2, uint32_t bar) {
  asm volatile(ELECT "@p " TMA3D " [%0], [%1, {0, %3, %4}], [%2];\n}" ::"r"(dst), "l"(m), "r"(bar), "r"(c1), "r"(c2) : "memory");
}
__device__ __forceinline__ void e_store2d(const CUtensorMap* m, int c0, int c1, uint32_t src) {
  asm volatile(ELECT "@p cp.async.bulk.tensor.2d.global.shared::cta.bulk_group [%0, {%2, %3}], [%1];\n}" ::"l"(m), "r"(src), "r"(c0), "r"(c1) : "memory");
}
__device__ __forceinline__ void e_tma3d_ef(uint32_t dst, const CUtensorMap* m, int c0, int c1, uint32_t bar, uint64_t pol) {
  asm volatile(ELECT "@p " TMA3D ".L2::cache_hint [%0], [%1, {%3, %4, 0}], [%2], %5;\n}" ::"r"(dst), "l"(m), "r"(bar), "r"(c0), "r"(c1), "l"(pol) : "memory");
}
__device__ __forceinline__ void e_pfmap(const CUtensorMap* m) { asm volatile(ELECT "@p prefetch.tensormap [%0];\n}" ::"l"(m) : "memory"); }
__device__ __forceinline__ void bulk_wait_read() { asm volatile("cp.async.bulk.commit_group;\ncp.async.bulk.wait_group.read 0;" ::: "memory"); }
__device__ __forceinline__ void e_signal(int word, int bit) {
  asm volatile(ELECT "@p red.relaxed.gpu.global.xor.b32 [%0], %1;\n}" ::"l"(g_sig + word * 32), "r"(1u << bit) : "memory");
}
__device__ __forceinline__ void await(int word, uint32_t mask, uint32_t ep) {
  uint32_t f[1];
  poll1f(f, g_sig + word * 32, 0u - (ep & 1u), mask);
}

__device__ __forceinline__ void mbar_arrive(uint32_t b) { asm volatile("mbarrier.arrive.shared::cta.b64 _, [%0];" ::"r"(b) : "memory"); }
__device__ __forceinline__ void mbar_wait(uint32_t b, uint32_t ph) {
  asm volatile("{\n.reg .pred p, q;\n.reg .u32 c;\nmov.u32 c, 0;\nLW:\nmbarrier.try_wait.parity.shared::cta.b64 p, [%0], %1;\n@p bra LD;\n"
               "add.u32 c, c, 1;\nsetp.lt.u32 q, c, 100000;\n@q bra LW;\ntrap;\nLD:\n}" ::"r"(b), "r"(ph) : "memory");
}
__device__ __forceinline__ void nb_sync(int id, int n) { asm volatile("bar.sync %0, %1;" ::"r"(id), "r"(n) : "memory"); }
__device__ __forceinline__ void nb_arrive(int id, int n) { asm volatile("bar.arrive %0, %1;" ::"r"(id), "r"(n) : "memory"); }
__device__ __forceinline__ void wg_fence() { asm volatile("wgmma.fence.sync.aligned;" ::: "memory"); }
__device__ __forceinline__ void wg_commit() { asm volatile("wgmma.commit_group.sync.aligned;" ::: "memory"); }
template <int N> __device__ __forceinline__ void wg_wait() { asm volatile("wgmma.wait_group.sync.aligned %0;" ::"n"(N) : "memory"); }
template <int N> __device__ __forceinline__ void reg_fence(float (&a)[N]) {
#pragma unroll
  for (int i = 0; i < N; i++) asm volatile("" : "+f"(a[i])::"memory");
}
template <int N> __device__ __forceinline__ void reg_zero(float (&a)[N]) {
#pragma unroll
  for (int i = 0; i < N; i++) a[i] = 0.f;
}
__device__ __forceinline__ constexpr uint64_t mkdesc(uint32_t addr, uint32_t lbo, uint32_t sbo, uint32_t swz) {
  return (uint64_t)(addr >> 4) | ((uint64_t)(lbo >> 4) << 16) | ((uint64_t)(sbo >> 4) << 32) | ((uint64_t)swz << 62);
}
__device__ __forceinline__ void fence_async_smem() { asm volatile("fence.proxy.async.shared::cta;" ::: "memory"); }
__device__ __forceinline__ void st_relaxed(uint32_t* p, uint32_t v) { asm volatile("st.relaxed.gpu.global.u32 [%0], %1;" ::"l"(p), "r"(v) : "memory"); }
__device__ __forceinline__ uint32_t ld_relaxed(const uint32_t* p) { uint32_t v; asm volatile("ld.relaxed.gpu.global.u32 %0, [%1];" : "=r"(v) : "l"(p) : "memory"); return v; }
__device__ __forceinline__ void st_unit(uint4* p, uint32_t a, uint32_t b, uint32_t c, uint32_t d, uint32_t par) {
  asm volatile("{\n.reg .b64 x, y;\n.reg .b128 z;\nmov.b64 x, {%1,%2};\nmov.b64 y, {%3,%4};\nmov.b128 z, {x, y};\nst.relaxed.gpu.global.b128 [%0], z;\n}"
               ::"l"(p), "r"((a & ~1u) | par), "r"(b), "r"(c), "r"(d) : "memory");
}
__device__ __forceinline__ uint4 lds128(uint32_t a) { uint4 v; asm volatile("ld.shared.v4.u32 {%0,%1,%2,%3}, [%4];" : "=r"(v.x), "=r"(v.y), "=r"(v.z), "=r"(v.w) : "r"(a)); return v; }
__device__ __forceinline__ float4 lds128f(uint32_t a) { float4 v; asm volatile("ld.shared.v4.f32 {%0,%1,%2,%3}, [%4];" : "=f"(v.x), "=f"(v.y), "=f"(v.z), "=f"(v.w) : "r"(a)); return v; }
__device__ __forceinline__ float4 lds128v(uint32_t a) { float4 v; asm volatile("ld.volatile.shared.v4.f32 {%0,%1,%2,%3}, [%4];" : "=f"(v.x), "=f"(v.y), "=f"(v.z), "=f"(v.w) : "r"(a) : "memory"); return v; }
__device__ __forceinline__ float lds32v(uint32_t a) { float v; asm volatile("ld.volatile.shared.f32 %0, [%1];" : "=f"(v) : "r"(a) : "memory"); return v; }
__device__ __forceinline__ float2 lds64f(uint32_t a) { float2 v; asm volatile("ld.shared.v2.f32 {%0,%1}, [%2];" : "=f"(v.x), "=f"(v.y) : "r"(a)); return v; }
__device__ __forceinline__ uint32_t lds32(uint32_t a) { uint32_t v; asm volatile("ld.shared.u32 %0, [%1];" : "=r"(v) : "r"(a)); return v; }
__device__ __forceinline__ void sts128(uint32_t a, uint32_t x, uint32_t y, uint32_t z, uint32_t w) { asm volatile("st.shared.v4.u32 [%0], {%1,%2,%3,%4};" ::"r"(a), "r"(x), "r"(y), "r"(z), "r"(w) : "memory"); }
__device__ __forceinline__ void sts128f(uint32_t a, float x, float y, float z, float w) { asm volatile("st.shared.v4.f32 [%0], {%1,%2,%3,%4};" ::"r"(a), "f"(x), "f"(y), "f"(z), "f"(w) : "memory"); }
__device__ __forceinline__ void sts64(uint32_t a, uint32_t x, uint32_t y) { asm volatile("st.shared.v2.u32 [%0], {%1,%2};" ::"r"(a), "r"(x), "r"(y) : "memory"); }
__device__ __forceinline__ void sts32(uint32_t a, uint32_t x) { asm volatile("st.shared.u32 [%0], %1;" ::"r"(a), "r"(x) : "memory"); }
__device__ __forceinline__ void stsm4(uint32_t a, uint32_t r0, uint32_t r1, uint32_t r2, uint32_t r3) {
  asm volatile("stmatrix.sync.aligned.m8n8.x4.shared.b16 [%0], {%1,%2,%3,%4};" ::"r"(a), "r"(r0), "r"(r1), "r"(r2), "r"(r3) : "memory");
}
__device__ __forceinline__ uint4 ldsm4(uint32_t a) {
  uint4 v; asm volatile("ldmatrix.sync.aligned.m8n8.x4.shared.b16 {%0,%1,%2,%3}, [%4];" : "=r"(v.x), "=r"(v.y), "=r"(v.z), "=r"(v.w) : "r"(a) : "memory"); return v;
}
__device__ __forceinline__ uint32_t pack(float lo, float hi) { uint32_t r; asm("cvt.rn.bf16x2.f32 %0, %1, %2;" : "=r"(r) : "f"(hi), "f"(lo)); return r; }
__device__ __forceinline__ float bf_lo(uint32_t w) { return __uint_as_float(w << 16); }
__device__ __forceinline__ float bf_hi(uint32_t w) { return __uint_as_float(w & 0xffff0000u); }
__device__ __forceinline__ float bf_round(float x) { return bf_lo(pack(x, x)); }
__device__ __forceinline__ float ex2(float x) { float v; asm("ex2.approx.ftz.f32 %0, %1;" : "=f"(v) : "f"(x)); return v; }
__device__ __forceinline__ float rcp(float x) { float v; asm("rcp.approx.ftz.f32 %0, %1;" : "=f"(v) : "f"(x)); return v; }
__device__ __forceinline__ float addsat(float a, float b) { float v; asm("add.sat.f32 %0, %1, %2;" : "=f"(v) : "f"(a), "f"(b)); return v; }
__device__ __forceinline__ float phi2(float a) { return fmaf(fmaxf(a, 0.f), LN2, addsat(ex2(a), 1e-6f)); }
__device__ __forceinline__ float key_score(uint32_t key) { uint32_t u = key >> 16; u = (u & 0x8000u) ? (u & 0x7fffu) : (~u & 0xffffu); return __uint_as_float(u << 16); }
__device__ __forceinline__ int key_token(uint32_t key) { return 2047 - (int)((key >> 5) & 2047u); }
__device__ __forceinline__ uint32_t bsel(uint32_t a, uint32_t b, uint32_t m) { uint32_t r; asm("lop3.b32 %0, %1, %2, %3, 0xd8;" : "=r"(r) : "r"(a), "r"(b), "r"(m)); return r; }
__device__ __forceinline__ uint32_t prmt(uint32_t a, uint32_t b, uint32_t c) { uint32_t r; asm("prmt.b32 %0, %1, %2, %3;" : "=r"(r) : "r"(a), "r"(b), "r"(c)); return r; }
__device__ __forceinline__ uint32_t tagf(float v, uint32_t par) { return (__float_as_uint(v) & ~1u) | par; }
__device__ __forceinline__ float xred(float a, float b, bool up, int o) { return (up ? b : a) + __shfl_xor_sync(0xffffffffu, up ? a : b, o); }

#define STAMP(id)
#define STAMP_IF(c, id)
#define STAMP2(i)
#define LITE 1
#define LITE_MASK 0ull

template <bool TRANS>
__device__ __forceinline__ void mainloop(float (&a0)[64], float (&a1)[64], int s, int ph, int handoff, int xpair, bool leader) {
  uint32_t prev = 0;
#pragma unroll 1
  for (int kt = 0; kt < 16; kt++) {
    const bool xr = !TRANS && (kt >> 1) == xpair;
    mbar_wait(B_FULL + 8 * s, ph);
    const uint64_t dw = mkdesc(RING, 8192, 1024, 1) + s * (SLOT >> 4), dx = mkdesc(0, 16, 1024, 1) + (xr ? (STG >> 4) + (kt & 1) * 1024 : ((RING + 16384) >> 4) + s * (SLOT >> 4));
    if (xr) mbar_wait(B_XRES + 8 * (kt & 1), 0);
    wg_fence();
#pragma unroll
    for (int j = 0; j < 4; j++) {
      if (TRANS) {
        wgmma_n128_ss<1, 0>(a0, dw + j * 128, dx + j * 2, 1);
        wgmma_n128_ss<1, 0>(a1, dw + j * 128 + 512, dx + j * 2, 1);
      } else {
        wgmma_n128_ss<0, 1>(a0, dx + j * 2, dw + j * 128, 1);
        wgmma_n128_ss<0, 1>(a1, dx + j * 2 + 512, dw + j * 128, 1);
      }
    }
    wg_commit();
    if (handoff && kt == 15) nb_arrive(handoff, 256);
    wg_wait<1>();
    if (prev && leader) mbar_arrive(prev);
    prev = B_EMPTY + 8 * s;
    if (++s == NST) { s = 0; ph ^= 1; }
  }
  wg_wait<0>();
  if (leader) mbar_arrive(prev);
  reg_fence(a0);
  reg_fence(a1);
}

__device__ __forceinline__ int out_kblock(int r, int tn) {
  const int q = r - 2, half = q >= 7, pi = q - 7 * half;
  return r < 2 ? 2 * tn + r : 2 * (pi + (pi >= tn)) + half;
}

struct Params {
  const char *x, *wqkv, *w_r, *wg, *wu, *wd;
  CUtensorMap m_wqkv, m_x, m_xs, m_o, m_os, m_wo, m_gu, m_down, m_out;
};

template <bool BY_SMID>
__global__ void __launch_bounds__(512, 1) fused_kernel(const __grid_constant__ Params mp) {
  extern __shared__ __align__(1024) uint8_t smem_raw[];
#define CK(i)
  CK(0);
  uint32_t ck0 = 0;
  if (ALIGN) asm volatile("mov.u32 %0, %%clock;" : "=r"(ck0));
  const int tid = threadIdx.x, lane = tid & 31;
  const int w = __shfl_sync(0xffffffffu, tid >> 5, 0);
  int bid = blockIdx.x;
  if (BY_SMID) {
    uint32_t sm;
    asm volatile("mov.u32 %0, %%smid;" : "=r"(sm));
    const uint32_t p = sm >> 1, q = ((p - 32) * 37) >> 8;
    const uint32_t gpc = p < 32 ? p & 7 : p < 60 ? p - 31 - 7 * q : 0, tpc = p < 32 ? p >> 3 : p < 60 ? 4 + q : p - 58;
    bid = (p >> 1) == 30 ? 128 + ((0x9cu >> (2 * (sm & 3))) & 3) : ((0x75143620u >> (4 * gpc)) & 7) * 16 + tpc * 2 + (sm & 1);
  }
  const int tn = (bid & 3) + 4 * (bid >> 6), tm = (bid >> 2) & 15;

  CK(1);
  if (w == 0) {
#pragma unroll 1
    for (int s = 0; s < NST; s++) {
      asm volatile(ELECT "@p mbarrier.init.shared::cta.b64 [%0], 1;\n}" ::"r"(B_FULL + 8 * s) : "memory");
      if (bid < 128) {
        e_expect(B_FULL + 8 * s, 32768);
        e_tma2d(RING + s * SLOT + 16384, &mp.m_x, s * 64, tm * 128, B_FULL + 8 * s);
        e_tma3d(RING + s * SLOT, &mp.m_wqkv, s * 64, 16 + 2 * tn, B_FULL + 8 * s);
      }
      if (s == 0) CK(2);
    }
  }
  if (w == 1) e_pfmap(&mp.m_wqkv);
  if (w == 2) e_pfmap(&mp.m_xs);
  if (w >= 4) {
#pragma unroll 1
    for (uint32_t b = MISC + 8 * (w + 1); b < MISC + 8 * NBAR; b += 96)
      asm volatile(ELECT "@p mbarrier.init.shared::cta.b64 [%0], %1;\n}" ::"r"(b), "r"(b == B_CSDN ? 4 : 1) : "memory");
    if (w == 15) sts32(S_NCAND, 0);
  }
  CK(3);
  asm volatile("fence.mbarrier_init.release.cluster;" ::: "memory");
  __syncthreads();

  auto front = [&](int i0, int i1) {
#pragma unroll 1
    for (int i = i0; i < i1; i++) {
      const int c = (XS_ORD >> (4 * i)) & 3;
      if (i >= XS_FLY) mbar_wait(B_XS + 8 * (i - XS_FLY), 0);
      if (c == (tm >> 2)) {
        e_expect(B_WK, 16384);
        e_tma3d(FR, &mp.m_wqkv, tm * 64, 16 + 2 * tn, B_WK);
      }
      e_expect(B_XS + 8 * i, 8192);
      e_tma2d(STG + i * 8192, &mp.m_xs, c * 256, tm * 128 + tn * 16, B_XS + 8 * i);
    }
  };
  if (XS_EARLY && w == 5 && bid < 128) front(0, XS_EARLY);

  if (bid >= 128) {
    const int h0 = bid == 128 ? 14 : bid - 129, hs = bid == 128 ? 1 : 3, h1 = bid == 128 ? 16 : 14;
    if (w == 12) {
      int s = 0, ph = 1;
      if (bid == 128) mbar_wait(B_SEL, 0);
      else if (H_DELAY) __nanosleep(H_DELAY);
#pragma unroll 1
      for (int h = h0; h < h1; h += hs) {
        const int c = 2 * h + (h & 8) * 2;
#pragma unroll 1
        for (int kt = 0; kt < 16; kt += 2) {
          mbar_wait(B_EMPTY + 8 * s, ph);
          e_expect(B_FULL + 8 * s, 32768);
          e_tma3d(RING + s * SLOT, &mp.m_wqkv, kt * 64, c, B_FULL + 8 * s);
          e_tma3d(RING + s * SLOT + 16384, &mp.m_wqkv, kt * 64 + 64, c, B_FULL + 8 * s);
          if (++s == HST) { s = 0; ph ^= 1; }
        }
      }
    } else if (w < 4) {
      const uint32_t par = (ld_relaxed(&g_epoch) + 1) & 1u;
      sts32(S_ONES + tid * 4, 0x3f803f80u);
      fence_async_smem();
      nb_sync(NB_WG0, 128);
      int s = 0, ph = 0;
#pragma unroll 1
      for (int h = h0; h < h1; h += hs) {
        float c[4][4];
#pragma unroll
        for (int i = 0; i < 4; i++) reg_zero(c[i]);
        uint32_t prev = 0;
#pragma unroll 1
        for (int kt = 0; kt < 8; kt++) {
          mbar_wait(B_FULL + 8 * s, ph);
          const uint64_t dw = mkdesc(RING, 8192, 1024, 1) + s * (SLOT >> 4);
          wg_fence();
#pragma unroll
          for (int j = 0; j < 16; j++) wgmma_n8_ss<1, 0>(c[j & 3], dw + (j & 3) * 512 + (j >> 2) * 128, mkdesc(S_ONES, 128, 128, 0), 1);
          wg_commit();
          wg_wait<1>();
          if (prev && tid == 0) mbar_arrive(prev);
          prev = B_EMPTY + 8 * s;
          if (++s == HST) { s = 0; ph ^= 1; }
        }
        wg_wait<0>();
        if (tid == 0) mbar_arrive(prev);
#pragma unroll
        for (int i = 0; i < 4; i++) reg_fence(c[i]);
        const bool u2 = lane & 2, u1 = lane & 1;
        const float lo = u2 ? c[1][0] + c[3][0] : c[0][0] + c[2][0], hi = u2 ? c[1][2] + c[3][2] : c[0][2] + c[2][2];
        st_relaxed(g_csum + h * 128 + (lane & 2) * 32 + w * 16 + (lane & 1) * 8 + (lane >> 2), tagf(u1 ? hi : lo, par));
        STAMP_IF(tid == 0, h >= 8 ? 6 : 30);
      }
    } else if (w < 12 && bid == 128) {
      const int t = tid - 128, j = w - 4;
      const uint32_t ep = ld_relaxed(&g_epoch) + 1;
      uint32_t kk[16];
      poll_keys(kk, g_keys + t * 2, ep, 31u);
      STAMP_IF(t == 0, 42);
      const uint32_t m = __reduce_max_sync(0xffffffffu, max(max(max(kk[0], kk[2]), max(kk[4], kk[6])), max(max(kk[8], kk[10]), max(kk[12], kk[14]))));
      if (lane == 0) sts32(S_WMAX + j * 4, m);
      nb_sync(NB_WG1, 256);
      const uint32_t T = __reduce_min_sync(0xffffffffu, lds32(S_WMAX + (lane & 7) * 4));
      uint32_t cnt = 0;
#pragma unroll
      for (int i = 0; i < 8; i++) cnt += kk[2 * i] >= T;
      if (cnt) {
        uint32_t pos;
        asm volatile("atom.shared.add.u32 %0, [%1], %2;" : "=r"(pos) : "r"(S_NCAND), "r"(cnt * 8) : "memory");
#pragma unroll
        for (int i = 0; i < 8; i++)
          if (kk[2 * i] >= T) { sts64(AUX + pos, kk[2 * i], kk[2 * i + 1]); pos += 8; }
      }
      nb_sync(NB_WG1, 256);
      const uint32_t n8 = lds32(S_NCAND);
#pragma unroll 1
      for (uint32_t i = j * 8; i < n8; i += 64) {
        const float2 c = lds64f(AUX + i);
        uint32_t rank = 0;
#pragma unroll 1
        for (uint32_t q = lane * 8; q < n8 + lane * 8; q += 256) rank += __popc(__ballot_sync(0xffffffffu, q < n8 && lds32(AUX + q) > __float_as_uint(c.x)));
        if (rank < 8) sts64(S_SEL + rank * 8, __float_as_uint(c.x), __float_as_uint(c.y));
      }
      fence_async_smem();
      nb_sync(NB_WG1, 256);
      if (j == 0) {
        const uint4 v = lds128(S_SEL + (lane & 3) * 16);
        asm volatile("{\n.reg .b64 x, y;\nmov.b64 x, {%1,%2};\nmov.b64 y, {%3,%4};\nst.relaxed.gpu.global.v2.b64 [%0], {x, y};\n}"
                     ::"l"(g_sel + (lane >> 2) * 16 + (lane & 3) * 2), "r"(v.x), "r"(v.y), "r"(v.z), "r"(v.w) : "memory");
        e_arrive(B_SEL);
      }
      STAMP_IF(t == 0, 45);
    }
  } else if (w >= 12) {
    asm volatile("setmaxnreg.dec.sync.aligned.u32 32;");
    if (w == 12) {
      int s = 0, ph = 0;
#pragma unroll 1
      for (int it = NST; it < 48; it++) {
        const int c = (it < 32 ? (it & 16) + 16 : 0) + 2 * tn;
        const int k0 = ((it + (it >= 32 && tn < 4 ? 8 : 0)) & 15) * 64;
        const bool xr = (it >> 1) == 20 + (tn & 3);
        if (xr) { mbar_wait(B_SFREE, 0); e_expect(B_XRES + 8 * (it & 1), 16384); }
        mbar_wait(B_EMPTY + 8 * s, ph);
        e_expect(B_FULL + 8 * s, xr ? 16384 : 32768);
        e_tma3d(RING + s * SLOT, &mp.m_wqkv, k0, c, B_FULL + 8 * s);
        e_tma2d(xr ? STG + (it & 1) * 16384 : RING + s * SLOT + 16384, &mp.m_x, k0, tm * 128, xr ? B_XRES + 8 * (it & 1) : B_FULL + 8 * s);
        if (it >= NST) STAMP2(it - NST);
        if (++s == NST) { s = 0; ph ^= 1; }
      }
#pragma unroll 1
      for (int r = 0; r < 16; r++) {
        const int kb = out_kblock(r, tn);
        mbar_wait(B_EMPTY + 8 * s, ph);
        e_expect(B_FULL + 8 * s, r < 2 ? 16384 : 32768);
        e_tma3d(RING + s * SLOT, &mp.m_wo, kb * 64, 2 * tn, B_FULL + 8 * s);
        if (r < 2 || r == 4) {
          const uint32_t bar = B_DR + (r < 2 ? 16 : 8);
          const int k0 = (bid >> 4) * 448 + 128 + min(r, 2) * 128;
          if (r != 1) e_expect(bar, r ? 8192 : 32768);
          e_tma2d_ef(RING + s * SLOT + 16384, &mp.m_down, (bid & 15) * 64, k0, bar, EVICT_FIRST);
          if (r < 2) e_tma2d_ef(RING + s * SLOT + 24576, &mp.m_down, (bid & 15) * 64, k0 + 64, bar, EVICT_FIRST);
        }
        STAMP2(r + 48 - NST);
        if (++s == NST) { s = 0; ph ^= 1; }
      }
    } else if (w == 13) {
      if (XS_EARLY < XS_FLY) mbar_wait(B_FULL + 8 * XS_GO, 0);
      front(XS_EARLY, 4);
      {
        const char* pd = mp.wd + (bid & 15) * 128 + ((bid >> 4) * 448 + lane) * 2048;
        mbar_wait(B_XS + 24, 0);
        __nanosleep(PF_WAIT);
#pragma unroll 1
        for (int i = 0; i < 14; i++, pd += 65536) {
          if (PF_GAP) asm volatile("prefetch.global.L2 [%0];" ::"l"(pd));
          if (PF_GAP) __nanosleep(PF_GAP);
        }
      }
      nb_sync(NB_Z, 160);
      const uint32_t ep = lds32(S_EPOCH);
      {
        float z[4] = {0.f, 0.f, 0.f, 0.f};
        e_signal(H_Z + tn, tm);
        await(H_Z + tn, 0xffffu, ep);
#pragma unroll 1
        for (int i = 0; i < 4; i++) {
          uint32_t p[16];
          poll_z(p, g_z + i * 4096 + tn * 128 + lane * 4, ep, 1u);
#pragma unroll
          for (int q = 0; q < 4; q++) z[q] += (__uint_as_float(p[q]) + __uint_as_float(p[4 + q])) + (__uint_as_float(p[8 + q]) + __uint_as_float(p[12 + q]));
        }
        const uint32_t z01 = pack(z[0], z[1]), z23 = pack(z[2], z[3]);
        if (bid < 112) mbar_wait(B_PFREE, 0);
#pragma unroll
        for (int i = 0; i < 4; i++) {
          const int n = 2 * i + (lane >> 4);
          asm volatile("st.shared.v2.u32 [%0], {%1,%2};" ::"r"(KVB_Z + n * 128 + ((((lane >> 1) & 7) ^ n) << 4) + (lane & 1) * 8), "r"(z01), "r"(z23) : "memory");
        }
        fence_async_smem();
        nb_arrive(NB_KVB, 288);
        STAMP_IF(lane == 0, 46);
      }
      nb_sync(NB_Q0, 192);
      e_store2d(&mp.m_os, tn * 128, tm * 128, STG);
      nb_sync(NB_OWN0, 288);
      e_store2d(&mp.m_os, tn * 128, tm * 128 + 64, STG + 8192);
      bulk_wait_read();
      e_signal(H_O + tm, 2 * tn);
      STAMP_IF(lane == 0, 4);
      nb_sync(NB_H1, 160);
      e_store2d(&mp.m_os, tn * 128 + 64, tm * 128, STG + 16384);
      e_store2d(&mp.m_os, tn * 128 + 64, tm * 128 + 64, STG + 24576);
      bulk_wait_read();
      e_signal(H_O + tm, 2 * tn + 1);
      STAMP_IF(lane == 0, 5);
      nb_arrive(NB_ST, 160);
    } else if (w == 14) {
      e_pfmap(&mp.m_gu); e_pfmap(&mp.m_o); e_pfmap(&mp.m_os); e_pfmap(&mp.m_wo); e_pfmap(&mp.m_down); e_pfmap(&mp.m_out);
      const uint32_t ep = ld_relaxed(&g_epoch) + 1;
      nb_sync(NB_FDONE, 416);
      {
        uint32_t c[4];
        poll_quad(c, g_csum + tn * 128 + lane * 4, ep, 1u);
        sts128(S_CSQ + lane * 16, c[0], c[1], c[2], c[3]);
        nb_arrive(NB_CSQ, 160);
        poll_quad(c, g_csum + 1024 + tn * 128 + lane * 4, ep, 1u);
        sts128(S_CSV + lane * 16, c[0], c[1], c[2], c[3]);
        __syncwarp();
        e_arrive(B_CSV);
      }
      nb_sync(NB_Q0, 192);
      uint32_t ready = 0;
      int s = 0, ph = 1;
#pragma unroll 1
      for (int r = 2; r < 16; r++) {
        const int kb = out_kblock(r, tn);
        if (!((ready >> kb) & 1)) {
          uint32_t f[1];
          poll0(f, g_sig + (H_O + tm) * 32, 0u - (ep & 1u), 1u << kb);
          ready = f[0] ^ ((ep & 1u) - 1u);
        }
        if (r == 4) mbar_wait(B_DND, 0);
        mbar_wait(B_EMPTY + 8 * s, ph);
        e_tma2d(RING + s * SLOT + 16384, &mp.m_o, kb * 64, tm * 128, B_FULL + 8 * s);
        STAMP_IF(lane == 0 && r == 2, 2);
        STAMP_IF(lane == 0 && r == 9, 3);
        if (++s == NST) { s = 0; ph ^= 1; }
      }
    } else {
      uint32_t nsm = 132;
      if (BY_SMID) asm volatile("mov.u32 %0, %%nsmid;" : "=r"(nsm));
      asm volatile("{\n.reg .pred q;\nsetp.eq.u32 q, %0, 1156;\n@q bra LOK;\ntrap;\nLOK:\n}" ::"r"((uint32_t)__cvta_generic_to_shared(smem_raw) + nsm));
      const uint32_t ep = ld_relaxed(&g_epoch) + 1;
      mbar_wait(B_CSDN, 0);
#pragma unroll 1
      for (int n = 0; n < 3 && bid < 112; n++) {
        __nanosleep(FFN_GAP);
        e_expect(B_FR + 8 * n, 8192);
        e_tma3d_ef(GR + n * 8192, &mp.m_gu, bid * 32, n * 64, B_FR + 8 * n, EVICT_FIRST);
      }
      uint32_t sel[2];
      poll_pair(sel, g_sel + (bid >> 4) * 16 + (lane >> 2), ep, 31u);
      const char* xs = mp.x + key_token(sel[0]) * 2048 + (lane & 3) * 16;
      const uint32_t xd = AUX + (lane >> 2) * 64 + (((lane & 3) ^ (lane >> 3)) << 4);
      auto slices = [&](int n, int p) {
        asm volatile("cp.async.cg.shared.global [%0], [%1], 16;\ncp.async.cg.shared.global [%0+512], [%1+64], 16;\ncp.async.commit_group;"
                     ::"r"(xd + p * 1024), "l"(xs + n * 128) : "memory");
      };
      if ((lane & 3) == 0) sts64(S_SEL + lane * 2, sel[0], sel[1]);
      if (bid < 112) {
#pragma unroll
        for (int i = 0; i < 6; i++) slices(i, i);
      }
      asm volatile("cp.async.wait_group 2;" ::: "memory");
      fence_async_smem();
      __syncwarp();
      e_arrive(B_SEL);
      if (bid < 112) {
        int s = 0, ph = 0;
#pragma unroll 1
        for (int n = 3; n < 16; n++) {
          mbar_wait(B_FE + 8 * s, ph);
          e_expect(B_FR + 8 * s, 8192);
          e_tma3d_ef(GR + s * 8192, &mp.m_gu, bid * 32, n * 64, B_FR + 8 * s, EVICT_FIRST);
          STAMP2(64 + n);
          asm volatile("cp.async.wait_group 1;" ::: "memory");
          fence_async_smem();
          __syncwarp();
          if (n < 13) slices(n + 3, s + 3 * ph);
          else asm volatile("cp.async.commit_group;" ::: "memory");
          if (++s == 3) { s = 0; ph ^= 1; }
        }
      }
      e_expect(B_DR, 16384);
      if (bid < 112) mbar_wait(B_FE + 8, 0);
      e_tma2d_ef(FR, &mp.m_down, (bid & 15) * 64, (bid >> 4) * 448, B_DR, EVICT_FIRST);
      if (bid < 112) mbar_wait(B_FE + 16, 0);
      e_tma2d_ef(FR + 8192, &mp.m_down, (bid & 15) * 64, (bid >> 4) * 448 + 64, B_DR, EVICT_FIRST);
    }
  } else if (w >= 8) {
    asm volatile("setmaxnreg.dec.sync.aligned.u32 56;");
    const int t = tid - 256, ww = w - 8;
    const uint32_t ep = ld_relaxed(&g_epoch) + 1, par = ep & 1u;
    sts32(FONES + t * 4, 0x3f803f80u);
    {
      const int r0 = (lane >> 3) + (lane & 4);
      const uint32_t a = FR + (ww >> 1) * 8192 + r0 * 128 + ((((ww & 1) * 4 + (lane & 3)) ^ r0) << 4);
      float c[8];
      reg_zero(c);
      mbar_wait(B_WK, 0);
#pragma unroll 2
      for (int i = 0; i < 8; i++) {
        const uint4 v = lds128(a + i * 1024);
        c[0] += bf_lo(v.x); c[1] += bf_hi(v.x); c[2] += bf_lo(v.y); c[3] += bf_hi(v.y);
        c[4] += bf_lo(v.z); c[5] += bf_hi(v.z); c[6] += bf_lo(v.w); c[7] += bf_hi(v.w);
      }
      const bool u16 = lane & 16, u8 = lane & 8, u4 = lane & 4;
      const float d0 = xred(c[0], c[4], u16, 16), d1 = xred(c[1], c[5], u16, 16), d2 = xred(c[2], c[6], u16, 16), d3 = xred(c[3], c[7], u16, 16);
      fence_async_smem();
      e_arrive(B_CSDN);
      const float sum = xred(xred(d0, d2, u8, 8), xred(d1, d3, u8, 8), u4, 4);
      st_relaxed(g_csum + (2 + tm) * 1024 + tn * 128 + ww * 32 + (lane & 3) * 8 + (lane >> 2), tagf(sum, par));
      STAMP_IF(t == 0, 8);
      nb_sync(NB_WG2, 128);
      if (ww == 0) { e_signal(H_CS + tn, tm); await(H_CS + tn, 0xffffu, ep); }
      nb_sync(NB_WG2, 128);
      uint32_t p[16];
      poll16(p, g_csum + 2048 + tn * 128 + t, par, 1u);
      float tot = 0.f;
#pragma unroll
      for (int i = 0; i < 16; i += 4) tot += (__uint_as_float(p[i]) + __uint_as_float(p[i + 1])) + (__uint_as_float(p[i + 2]) + __uint_as_float(p[i + 3]));
      sts32(S_CSK + t * 4, __float_as_uint(tot));
      nb_arrive(NB_FDONE, 416);
      STAMP_IF(t == 0, 9);
    }
    const int ks = bid >> 4, nt = bid & 15;
    if (bid < 112) {
      float fg[8];
      reg_zero(fg);
      mbar_wait(B_SEL, 0);
      constexpr uint64_t DA0 = mkdesc(GR, 4096, 512, 2), DB0 = mkdesc(AUX, 16, FONES - AUX, 2), DBS = 32 - (32ull << 32);
      uint64_t da = DA0, db = DB0;
      uint32_t bar = B_FR, ph = 0;
#pragma unroll 1
      for (int n = 0; n < 16; n++) {
        mbar_wait(bar, ph);
        wg_fence();
#pragma unroll
        for (int q = 0; q < 4; q++) wgmma_n16_ss<1, 0>(fg, da + q * 64, db + (q >> 1) * DBS + (q & 1) * 2, 1);
        wg_commit();
        const uint32_t rel = bar + (B_FE - B_FR);
        const bool wrap = bar == B_FR + 16;
        da = wrap ? DA0 : da + 512;
        db = wrap && ph ? DB0 : db + 2 * DBS;
        bar = wrap ? B_FR : bar + 8;
        ph ^= wrap;
        wg_wait<0>();
        if (t == 0) mbar_arrive(rel);
      }
      if (t == 0) mbar_arrive(B_PFREE);
      const uint4 st = lds128(S_SEL + (lane & 3) * 16);
      const float r0 = rcp(bf_lo(st.y)), r1 = rcp(bf_lo(st.w));
      reg_fence(fg);
      const float fa[4] = {fmaf(-bf_hi(st.y), fg[4], fg[0]) * r0, fmaf(-bf_hi(st.w), fg[4], fg[1]) * r1,
                           fmaf(-bf_hi(st.y), fg[6], fg[2]) * r0, fmaf(-bf_hi(st.w), fg[6], fg[3]) * r1};
      STAMP_IF(t == 0, 12);
      const bool isup = (ww >> 1) != (mp.wu < mp.wg);
      nb_sync(NB_WG2, 128);
      if (isup) sts128f(HOP + (t & 63) * 16, fa[0], fa[1], fa[2], fa[3]);
      nb_sync(NB_WG2, 128);
      if (!isup) {
        const float4 u = lds128f(HOP + (t & 63) * 16);
        const float uu[4] = {u.x, u.y, u.z, u.w};
        uint32_t* hp = g_h + bid * 256 + (lane & 3) * 64 + (ww & 1) * 16 + (lane >> 2);
#pragma unroll
        for (int i = 0; i < 4; i++) {
          const float g = fa[i], hv = g * rcp(1.f + ex2(-g * LOG2E)) * uu[i];
          st_relaxed(hp + (i & 1) * 32 + (i >> 1) * 8, __byte_perm(pack(hv, hv), ep, 0x3254));
        }
      }
      nb_sync(NB_WG2, 128);
      if (ww == 0) e_signal(H_H + bid / 14, bid % 14);
    }
    {
      uint32_t v[28];
      if (ww == 0) await(H_H + ks, 0x3fffu, ep);
      nb_sync(NB_WG2, 128);
      poll7x4(v, g_h + ks * 3584 + t * 4, ep, 0xffffu);
#pragma unroll
      for (int q = 0; q < 7; q++)
        asm volatile("st.shared.v2.u32 [%0], {%1,%2};" ::"r"(HOP + q * 1024 + (t >> 3) * 64 + ((((t >> 1) & 3) ^ ((t >> 4) & 3)) << 4) + (t & 1) * 8),
                     "r"(__byte_perm(v[4 * q], v[4 * q + 1], 0x7632)), "r"(__byte_perm(v[4 * q + 2], v[4 * q + 3], 0x7632)) : "memory");
      fence_async_smem();
      nb_sync(NB_WG2, 128);
    }
    STAMP_IF(t == 0, 13);
    float fa[4] = {0.f, 0.f, 0.f, 0.f};
    auto down = [&](uint32_t a, int k0, int nk) {
#pragma unroll
      for (int q = 0; q < nk; q++) wgmma_n8_ss<1, 0>(fa, mkdesc(a + q * 2048, 4096, 1024, 1), mkdesc(HOP + ((k0 + q) >> 1) * 512 + (q & 1) * 32, 16, 512, 2), 1);
    };
    mbar_wait(B_DR, 0);
    mbar_wait(B_DR + 16, 0);
    mbar_wait(B_DR + 8, 0);
    wg_fence();
    down(RING + 2 * SLOT + 16384, 24, 4);
    down(RING + 3 * SLOT + 16384, 8, 8);
    down(RING + 4 * SLOT + 16384, 16, 8);
    wg_commit();
    wg_fence();
    down(FR, 0, 8);
    wg_commit();
    wg_wait<1>();
    if (t == 0) mbar_arrive(B_DND);
    wg_wait<0>();
    reg_fence(fa);
    STAMP_IF(t == 0, 14);
    {
      uint32_t* yp = g_yp + (nt * 8 + ks) * 512 + (lane & 3) * 128 + ww * 16 + (lane >> 2);
#pragma unroll
      for (int i = 0; i < 4; i++) st_relaxed(yp + (i & 1) * 64 + (i >> 1) * 8, tagf(fa[i], par));
    }
    nb_sync(NB_WG2, 128);
    if (ww == 0) e_signal(H_Y + (nt >> 1), (nt & 1) * 8 + ks);
    mbar_wait(B_SEL, 0);
    const uint32_t mykey = lds32(S_SEL + (lane & 7) * 8);
    const uint32_t inmask = __ballot_sync(0xffffffffu, (key_token(mykey) >> 7) == tm) & 0xffu;
    if (inmask) {
      sts128(FR + t * 16, 0u, 0u, 0u, 0u);
      if (ww == 0) await(H_Y + tn, 0xffffu, ep);
      nb_sync(NB_WG2, 128);
      const float sg = rcp(1.f + ex2(-key_score(mykey) * LOG2E));
#pragma unroll 1
      for (uint32_t mine = __ballot_sync(0xffffffffu, ((inmask >> lane) & 1) && (__popc(inmask & ((1u << lane) - 1)) & 3) == ww); mine; mine &= mine - 1) {
        const int j = __ffs(mine) - 1;
        uint32_t p[32];
        poll8x4(p, g_yp + (tn * 2 + (lane >> 4)) * 4096 + j * 64 + (lane & 15) * 4, par, 1u);
        float y[4];
        const float sj = __shfl_sync(0xffffffffu, sg, j);
#pragma unroll
        for (int i = 0; i < 4; i++)
          y[i] = sj * (((__uint_as_float(p[i]) + __uint_as_float(p[4 + i])) + (__uint_as_float(p[8 + i]) + __uint_as_float(p[12 + i]))) +
                       ((__uint_as_float(p[16 + i]) + __uint_as_float(p[20 + i])) + (__uint_as_float(p[24 + i]) + __uint_as_float(p[28 + i]))));
        asm volatile("st.shared.v2.u32 [%0], {%1,%2};" ::"r"(FR + (lane >> 4) * 1024 + j * 128 + ((((lane >> 1) & 7) ^ j) << 4) + (lane & 1) * 8),
                     "r"(pack(y[0], y[1])), "r"(pack(y[2], y[3])) : "memory");
      }
      fence_async_smem();
      nb_arrive(NB_Y, 256);
    }
    STAMP_IF(t == 0, 15);
  } else if (w >= 4) {
    asm volatile("setmaxnreg.inc.sync.aligned.u32 208;");
    const int t = tid - 128, ww = w - 4, g = lane >> 2, t4 = lane & 3;
    const bool leader = t == 0;
    const uint32_t ep = ld_relaxed(&g_epoch) + 1, par = ep & 1u;
    {
      const uint4* wp = reinterpret_cast<const uint4*>(mp.w_r) + lane;
      uint4 w0 = __ldg(wp + (XS_ORD & 3) * 32), w1 = __ldg(wp + ((XS_ORD >> 4) & 3) * 32), w2 = __ldg(wp + ((XS_ORD >> 8) & 3) * 32), w3 = __ldg(wp + ((XS_ORD >> 12) & 3) * 32);
      if (leader) sts32(S_EPOCH, ep);
      if (KV_DIRECT && lane < 8) st_unit(g_kv + tn * 512 + tm * 32 + ww * 8 + lane, 0u, 0u, 0u, 0u, par ^ 1u);
      float s[4] = {0.f, 0.f, 0.f, 0.f}, q[4] = {0.f, 0.f, 0.f, 0.f}, d[4] = {0.f, 0.f, 0.f, 0.f}, wsum = 0.f;
#pragma unroll 1
      for (int c = 0; c < 4; c++) {
        const float wr[8] = {bf_lo(w0.x), bf_hi(w0.x), bf_lo(w0.y), bf_hi(w0.y), bf_lo(w0.z), bf_hi(w0.z), bf_lo(w0.w), bf_hi(w0.w)};
        w0 = w1; w1 = w2; w2 = w3;
        wsum += ((wr[0] + wr[1]) + (wr[2] + wr[3])) + ((wr[4] + wr[5]) + (wr[6] + wr[7]));
        mbar_wait(B_XS + 8 * c, 0);
#pragma unroll
        for (int r = 0; r < 4; r++) {
          const uint4 v = lds128(STG + c * 8192 + (ww * 4 + r) * 512 + lane * 16);
          const uint32_t xw[4] = {v.x, v.y, v.z, v.w};
#pragma unroll
          for (int i = 0; i < 4; i++) {
            const uint32_t dep = __float_as_uint(q[i ? r : (r + 3) & 3]);
            const float lo = POLITE ? __uint_as_float(prmt(xw[i], dep, 0x10ff)) : bf_lo(xw[i]), hi = POLITE ? __uint_as_float(prmt(xw[i], dep, 0x32ff)) : bf_hi(xw[i]);
            s[r] += lo; q[r] = fmaf(lo, lo, q[r]); d[r] = fmaf(lo, wr[2 * i], d[r]);
            s[r] += hi; q[r] = fmaf(hi, hi, q[r]); d[r] = fmaf(hi, wr[2 * i + 1], d[r]);
          }
        }
      }
      STAMP_IF(leader, 16);
      const bool u16 = lane & 16, u8 = lane & 8, u4 = lane & 4, u2 = lane & 2;
      const float s1 = xred(xred(s[0], s[2], u16, 16), xred(s[1], s[3], u16, 16), u8, 8);
      const float q1 = xred(xred(q[0], q[2], u16, 16), xred(q[1], q[3], u16, 16), u8, 8);
      const float d1 = xred(xred(d[0], d[2], u16, 16), xred(d[1], d[3], u16, 16), u8, 8);
      wsum += __shfl_xor_sync(0xffffffffu, wsum, 16);
      wsum += __shfl_xor_sync(0xffffffffu, wsum, 8);
      float tot = xred(xred(s1, d1, u4, 4), xred(q1, wsum, u4, 4), u2, 2);
      tot += __shfl_xor_sync(0xffffffffu, tot, 1);
      const float qq = __shfl_down_sync(0xffffffffu, tot, 2), dd = __shfl_down_sync(0xffffffffu, tot, 4), ws = __shfl_down_sync(0xffffffffu, tot, 6);
      if ((lane & 7) == 0) {
        const float mean = tot * (1.f / 1024.f);
        const float var = fmaxf(fmaf(-mean, mean, qq * (1.f / 1024.f)), 0.f);
        float sd;
        asm("sqrt.approx.ftz.f32 %0, %1;" : "=f"(sd) : "f"(bf_round(bf_round(var) + 1e-5f)));
        const uint32_t ms = pack(sd, mean);
        const int row = tm * 128 + tn * 16 + ww * 4 + (lane >> 3);
        const uint32_t rbits = pack(0.f, fmaf(-bf_hi(ms), ws, dd) * rcp(bf_lo(ms)));
        const uint32_t key = (rbits ^ (((int)rbits >> 31 & 0x7fff0000u) | 0x80000000u)) | ((2047 - row) << 5) | (ep & 31u);
        asm volatile("{\n.reg .b64 x;\nmov.b64 x, {%1,%2};\nst.relaxed.gpu.global.b64 [%0], x;\n}" ::"l"(g_keys + row), "r"(key), "r"(ms) : "memory");
      }
      STAMP_IF(leader, 17);
      __nanosleep(400);
      uint32_t st[2];
      poll_pair(st, g_keys + tm * 128 + t, ep, 31u);
      asm volatile("st.shared.v2.f32 [%0], {%1,%2};" ::"r"(S_KSTAT + t * 8), "f"(bf_hi(st[1])), "f"(rcp(bf_lo(st[1])) * LOG2E) : "memory");
      nb_arrive(NB_FDONE, 416);
      STAMP_IF(leader, 10);
    }
    float a0[64], a1[64];
    reg_zero(a0); reg_zero(a1); reg_fence(a0); reg_fence(a1);
    STAMP_IF(leader, 18);
    nb_sync(NB_KV, 256);
    mainloop<true>(a0, a1, 1, 1, NB_VQ, 0, leader);
    STAMP_IF(leader, 19);
    {
      uint32_t f0[32], f1[32];
#pragma unroll
      for (int i = 0; i < 32; i++) { f0[i] = pack(a0[2 * i], a0[2 * i + 1]); f1[i] = pack(a1[2 * i], a1[2 * i + 1]); }
      float c0[32], c1[32];
      reg_zero(c0); reg_zero(c1);
      nb_sync(NB_PK, 256);
      constexpr uint64_t db = mkdesc(STG, 16, 1024, 1);
      wg_fence();
#pragma unroll
      for (int k = 0; k < 8; k++) {
        wgmma_n64_rs<0>(c0, f0[4 * k], f0[4 * k + 1], f0[4 * k + 2], f0[4 * k + 3], db + (k >> 2) * 1024 + (k & 3) * 2, k != 0);
        wgmma_n64_rs<0>(c1, f1[4 * k], f1[4 * k + 1], f1[4 * k + 2], f1[4 * k + 3], db + (k >> 2) * 1024 + (k & 3) * 2 + 512, k != 0);
      }
      wg_commit();
      const bool hp = ww >> 1;
      float c[4];
      float2 tt[8];
#pragma unroll
      for (int i = 0; i < 8; i++) tt[i] = lds64f(S_CSK + ((i >> 2) * 64 + hp * 32 + (i & 3) * 8 + 2 * t4) * 4);
      mbar_wait(B_CSV, 0);
#pragma unroll
      for (int i = 0; i < 4; i++) c[i] = -__uint_as_float(lds32(S_CSV + ((i >> 1) * 64 + ww * 16 + (i & 1) * 8 + g) * 4));
      wg_wait<0>();
      reg_fence(c0);
      reg_fence(c1);
      if (leader) mbar_arrive(B_SFREE);
      STAMP_IF(leader, 20);
      uint4* pp = g_kvp + (tn * 16 + tm) * 512 + t;
      auto put = [&](int q, const float* d) {
        const float ca = c[q & 2], cb = c[q | 1];
        const float2 ta = tt[2 * q], tb = tt[2 * q + 1];
        st_unit(pp + q * 128, pack(fmaf(ca, ta.x, d[0]), fmaf(ca, ta.y, d[1])), pack(fmaf(cb, ta.x, d[2]), fmaf(cb, ta.y, d[3])),
                pack(fmaf(ca, tb.x, d[4]), fmaf(ca, tb.y, d[5])), pack(fmaf(cb, tb.x, d[6]), fmaf(cb, tb.y, d[7])), par);
      };
      if (!hp) { put(0, c0); put(1, c0 + 8); put(2, c1); put(3, c1 + 8); }
      else { put(0, c0 + 16); put(1, c0 + 24); put(2, c1 + 16); put(3, c1 + 24); }
      STAMP_IF(leader, 47);
      {
        uint32_t p[16];
        nb_sync(NB_WG1, 128);
        if (ww == 0) { e_signal(H_KVP + tn, tm); await(H_KVP + tn, 0xffffu, ep); }
        nb_sync(NB_WG1, 128);
        STAMP_IF(leader, 1);
        poll_kvp(p, g_kvp + (tn * 16 + (lane >> 3) * 4) * 512 + tm * 32 + ww * 8 + (lane & 7), par, 1u);
        float r[8];
#pragma unroll
        for (int i = 0; i < 4; i++) {
          r[2 * i] = (bf_lo(p[i]) + bf_lo(p[4 + i])) + (bf_lo(p[8 + i]) + bf_lo(p[12 + i]));
          r[2 * i + 1] = (bf_hi(p[i]) + bf_hi(p[4 + i])) + (bf_hi(p[8 + i]) + bf_hi(p[12 + i]));
        }
#pragma unroll
        for (int i = 0; i < 8; i++) r[i] += __shfl_xor_sync(0xffffffffu, r[i], 8);
#pragma unroll
        for (int i = 0; i < 8; i++) r[i] += __shfl_xor_sync(0xffffffffu, r[i], 16);
        if (lane < 8) st_unit(g_kv + tn * 512 + tm * 32 + ww * 8 + lane, pack(r[0], r[1]), pack(r[2], r[3]), pack(r[4], r[5]), pack(r[6], r[7]), par);
      }
      STAMP_IF(leader, 21);
    }
    const uint32_t sx = lane & 7, sc = lane >> 4;
    const uint32_t sa = STG + (ww * 16 + (lane & 15)) * 128;
    const uint32_t sw[4] = {sa + ((sc ^ sx) << 4), sa + (((2 + sc) ^ sx) << 4), sa + (((4 + sc) ^ sx) << 4), sa + (((6 + sc) ^ sx) << 4)};
    auto residual = [&]() {
      float ka[4], kb[4];
#pragma unroll
      for (int i = 0; i < 4; i++) {
        const float2 st = lds64f(S_KSTAT + ((i >> 1) * 64 + ww * 16 + (i & 1) * 8 + g) * 8);
        const float r = st.y * LN2;
        ka[i] = 1.f + r; kb[i] = -st.x * r;
      }
#pragma unroll
      for (int j = 0; j < 8; j++) {
        if ((j & 3) == 0) mbar_wait(B_XRES + 8 * (j >> 2), 0);
        const uint4 v = ldsm4(sw[j & 3] + (j >> 2) * 16384), u = ldsm4(sw[j & 3] + (j >> 2) * 16384 + 8192);
        const uint32_t vv[4] = {v.x, v.y, v.z, v.w}, uu[4] = {u.x, u.y, u.z, u.w};
#pragma unroll
        for (int i = 0; i < 4; i++) {
          a0[8 * j + 2 * i] = fmaf(bf_lo(vv[i]), ka[i & 1], kb[i & 1]);
          a0[8 * j + 2 * i + 1] = fmaf(bf_hi(vv[i]), ka[i & 1], kb[i & 1]);
          a1[8 * j + 2 * i] = fmaf(bf_lo(uu[i]), ka[2 + (i & 1)], kb[2 + (i & 1)]);
          a1[8 * j + 2 * i + 1] = fmaf(bf_hi(uu[i]), ka[2 + (i & 1)], kb[2 + (i & 1)]);
        }
      }
      reg_fence(a0);
      reg_fence(a1);
      STAMP_IF(leader, 22);
    };
    if (RES_FIRST) residual();
    {
      uint32_t v[16];
      if (!KV_DIRECT) {
        nb_sync(NB_WG1, 128);
        if (ww == 0) { e_signal(H_KV + tn, tm); await(H_KV + tn, 0xffffu, ep); }
        nb_sync(NB_WG1, 128);
      } else {
        __nanosleep(KV_DIRECT);
      }
      STAMP_IF(leader, 7);
      poll_kv(v, g_kv + tn * 512 + t, par, 1u);
      if (bid < 112) mbar_wait(B_PFREE, 0);
      STAMP_IF(leader, 23);
#pragma unroll
      for (int q = 0; q < 4; q++)
        stsm4((q < 2 ? KVB_P0 : KVB_P1) + ((ww & 1) * 16 + (lane & 15)) * 128 + ((((ww >> 1) * 4 + (q & 1) * 2 + sc) ^ sx) << 4),
              v[4 * q], v[4 * q + 1], v[4 * q + 2], v[4 * q + 3]);
      fence_async_smem();
      nb_arrive(NB_KVB, 288);
    }
    STAMP_IF(leader, 24);
    if (!RES_FIRST) { residual(); nb_arrive(NB_KV, 256); }
    uint32_t oh[4];
    uint32_t inmask;
    {
      mbar_wait(B_SEL, 0);
      const int r0 = key_token(lds32(S_SEL + t4 * 16)) - tm * 128, r1 = key_token(lds32(S_SEL + t4 * 16 + 8)) - tm * 128;
#pragma unroll
      for (int i = 0; i < 4; i++) {
        const int row = (i >> 1) * 64 + ww * 16 + (i & 1) * 8 + g;
        oh[i] = (r0 == row ? 0x3f00u : 0u) | (r1 == row ? 0x3f000000u : 0u);
      }
      inmask = __ballot_sync(0xffffffffu, (unsigned)r0 < 128u || (unsigned)r1 < 128u);
    }
    uint32_t va = RING + 16384 + sc * 8192 + (ww * 16 + (lane & 8)) * 128 + sx * 16 + (lane >> 3) * 4;
    asm volatile("" : "+r"(va));
    {
      auto own = [&](int r) {
        nb_sync(NB_OWN0 + r, r ? 256 : 288);
        mbar_wait(B_FULL + 8 * (3 + r), 1);
        STAMP_IF(leader, 25 + r);
        const uint64_t dw = mkdesc(RING + (3 + r) * SLOT, 8192, 1024, 1), dx = mkdesc(STG + r * 16384, 16, 1024, 1);
        wg_fence();
#pragma unroll
        for (int j = 0; j < 4; j++) {
          wgmma_n128_ss<0, 1>(a0, dx + j * 2, dw + j * 128, 1);
          wgmma_n128_ss<0, 1>(a1, dx + j * 2 + 512, dw + j * 128, 1);
        }
        wg_commit();
      };
      own(0);
      wg_wait<0>();
      if (leader) mbar_arrive(B_EMPTY + 24);
      own(1);
      int s = 0, ph = 0;
      uint32_t prev = B_EMPTY + 32;
#pragma unroll 1
      for (int r = 2; r < 16; r++) {
        mbar_wait(B_FULL + 8 * s, ph);
        {
          uint32_t bad;
          asm volatile("{\n.reg .u32 a, b, c, d, e, f, g, h;\n.reg .pred p;\n"
                       "ld.shared.u32 a, [%1];\nld.shared.u32 b, [%1+128];\nld.shared.u32 c, [%1+256];\nld.shared.u32 d, [%1+384];\n"
                       "ld.shared.u32 e, [%1+512];\nld.shared.u32 f, [%1+640];\nld.shared.u32 g, [%1+768];\nld.shared.u32 h, [%1+896];\n"
                       "lop3.b32 a, a, b, %2, 0x7e;\nlop3.b32 c, c, d, %2, 0x7e;\nlop3.b32 e, e, f, %2, 0x7e;\nlop3.b32 g, g, h, %2, 0x7e;\n"
                       "lop3.b32 a, a, c, e, 0xfe;\nlop3.b32 a, a, g, 1, 0xa8;\nsetp.ne.u32 p, a, 0;\nvote.sync.any.pred p, p, 0xffffffff;\nselp.u32 %0, 1, 0, p;\n}"
                       : "=r"(bad) : "r"(va + s * SLOT), "r"(par) : "memory");
          if (bad) {
            const uint4* src = reinterpret_cast<const uint4*>(g_o + (tm * 128 + sc * 64 + ww * 16 + (lane & 15)) * 1024 + out_kblock(r, tn) * 64);
#pragma unroll 1
            for (int i = 0; i < 8; i++) {
              uint32_t v[4];
              asm volatile("{\n.reg .b64 x, y;\n.reg .b128 z;\n.reg .pred p, q, h;\n.reg .u32 c, b;\nmov.u32 c, 0;\nsetp.ne.u32 h, %6, 0;\nLW:\n"
                           "ld.relaxed.gpu.global.b128 z, [%4];\nmov.b128 {x, y}, z;\nmov.b64 {%0,%1}, x;\nmov.b64 {%2,%3}, y;\n"
                           "selp.b64 x, y, x, h;\nshr.b64 x, x, %7;\ncvt.u32.u64 b, x;\nand.b32 b, b, 1;\nsetp.eq.u32 p, b, %5;\n"
                           "vote.sync.all.pred p, p, 0xffffffff;\n@p bra.uni LD;\nadd.u32 c, c, 1;\nsetp.lt.u32 q, c, 1000000;\n@q bra.uni LW;\ntrap;\nLD:\n}"
                           : "=&r"(v[0]), "=&r"(v[1]), "=&r"(v[2]), "=&r"(v[3]) : "l"(src + i), "r"(par), "r"(sc), "r"((lane & 8) * 4) : "memory");
              sts128(RING + 16384 + s * SLOT + sc * 8192 + (ww * 16 + (lane & 15)) * 128 + ((i ^ sx) << 4), v[0], v[1], v[2], v[3]);
            }
            fence_async_smem();
            __syncwarp();
          }
        }
        if (!LITE || ((LITE_MASK >> 27) & 1)) STAMP_IF(leader && r == 2, 27);
        const uint64_t dw = mkdesc(RING, 8192, 1024, 1) + s * (SLOT >> 4), dx = mkdesc(RING + 16384, 16, 1024, 1) + s * (SLOT >> 4);
        wg_fence();
#pragma unroll
        for (int j = 0; j < 4; j++) {
          wgmma_n128_ss<0, 1>(a0, dx + j * 2, dw + j * 128, 1);
          wgmma_n128_ss<0, 1>(a1, dx + j * 2 + 512, dw + j * 128, 1);
        }
        wg_commit();
        wg_wait<1>();
        if (leader) mbar_arrive(prev);
        prev = B_EMPTY + 8 * s;
        if (++s == NST) { s = 0; ph ^= 1; }
      }
      if (inmask) {
        nb_sync(NB_Y, 256);
        wg_fence();
        wgmma_n128_rs<1>(a0, oh[0], oh[1], oh[0], oh[1], mkdesc(FR, 1024, 0, 1), 1);
        wgmma_n128_rs<1>(a1, oh[2], oh[3], oh[2], oh[3], mkdesc(FR, 1024, 0, 1), 1);
        wg_commit();
      }
      nb_sync(NB_ST, 160);
      wg_wait<0>();
      reg_fence(a0);
      reg_fence(a1);
    }
    STAMP_IF(leader, 28);
#pragma unroll
    for (int c = 0; c < 2; c++) {
#pragma unroll
      for (int j = 4 * c; j < 4 * c + 4; j++) {
        stsm4(sw[j & 3] + c * 16384, pack(a0[8 * j], a0[8 * j + 1]), pack(a0[8 * j + 2], a0[8 * j + 3]), pack(a0[8 * j + 4], a0[8 * j + 5]), pack(a0[8 * j + 6], a0[8 * j + 7]));
        stsm4(sw[j & 3] + c * 16384 + 8192, pack(a1[8 * j], a1[8 * j + 1]), pack(a1[8 * j + 2], a1[8 * j + 3]), pack(a1[8 * j + 4], a1[8 * j + 5]), pack(a1[8 * j + 6], a1[8 * j + 7]));
      }
      fence_async_smem();
      e_store2d(&mp.m_out, tn * 128 + c * 64, tm * 128 + ww * 16, STG + c * 16384 + ww * 2048);
      e_store2d(&mp.m_out, tn * 128 + c * 64, tm * 128 + 64 + ww * 16, STG + c * 16384 + 8192 + ww * 2048);
    }
    bulk_wait_read();
    if (bid == 0 && leader) st_relaxed(&g_epoch, ep);
    STAMP_IF(leader, 29);
  } else {
    asm volatile("setmaxnreg.inc.sync.aligned.u32 216;");
    const int g = lane >> 2, t4 = lane & 3;
    const bool leader = tid == 0;
    const uint32_t sx = lane & 7, sc = lane >> 4;
    const uint32_t sa = STG + (w * 16 + (lane & 15)) * 128;
    const uint32_t sw[4] = {sa + ((sc ^ sx) << 4), sa + (((2 + sc) ^ sx) << 4), sa + (((4 + sc) ^ sx) << 4), sa + (((6 + sc) ^ sx) << 4)};
    float a0[64], a1[64];
    reg_zero(a0); reg_zero(a1); reg_fence(a0); reg_fence(a1);
    if (ALIGN) { uint32_t now; do { asm volatile("mov.u32 %0, %%clock;" : "=r"(now)); } while ((int)(now - ck0) < ALIGN); }
    mainloop<true>(a0, a1, 0, 0, NB_KV, 0, leader);
    STAMP_IF(leader, 33);
    {
      nb_sync(NB_FDONE, 416);
      STAMP_IF(leader, 34);
      float c[4], z[4] = {0.f, 0.f, 0.f, 0.f}, tt[4] = {0.f, 0.f, 0.f, 0.f};
#pragma unroll
      for (int i = 0; i < 4; i++) c[i] = -__uint_as_float(lds32(S_CSK + ((i >> 1) * 64 + w * 16 + (i & 1) * 8 + g) * 4));
#pragma unroll
      for (int j = 0; j < 8; j++) {
        const float4 s0 = lds128v(S_KSTAT + (j * 16 + 2 * t4) * 8), s1 = lds128v(S_KSTAT + (j * 16 + 8 + 2 * t4) * 8);
        const float mu[4] = {s0.x, s0.z, s1.x, s1.z}, rl[4] = {s0.y, s0.w, s1.y, s1.w};
#pragma unroll
        for (int m = 0; m < 2; m++) {
          float p[8];
#pragma unroll
          for (int i = 0; i < 8; i++) {
            const int r = m * 2 + ((i >> 1) & 1), cc = (i >> 2) * 2 + (i & 1);
            p[i] = phi2(fmaf(c[r], mu[cc], m ? a1[8 * j + i] : a0[8 * j + i]) * rl[cc]);
            z[r] += p[i];
            p[i] *= rl[cc];
            tt[r] = fmaf(p[i], mu[cc], tt[r]);
          }
          stsm4(sw[j & 3] + (j >> 2) * 16384 + m * 8192, pack(p[0], p[1]), pack(p[2], p[3]), pack(p[4], p[5]), pack(p[6], p[7]));
        }
      }
      const bool u2 = lane & 2, u1 = lane & 1;
      const float zz = xred(xred(z[0], z[2], u2, 2), xred(z[1], z[3], u2, 2), u1, 1);
      sts32(S_CSK + ((t4 >> 1) * 64 + w * 16 + (t4 & 1) * 8 + g) * 4, __float_as_uint(xred(xred(tt[0], tt[2], u2, 2), xred(tt[1], tt[3], u2, 2), u1, 1)));
      fence_async_smem();
      nb_arrive(NB_PK, 256);
      st_relaxed(g_z + tm * 1024 + tn * 128 + (t4 >> 1) * 64 + w * 16 + (t4 & 1) * 8 + g, tagf(zz * LOG2E, lds32(S_EPOCH) & 1u));
      nb_arrive(NB_Z, 160);
    }
    STAMP_IF(leader, 35);
    float rl0[2];
    const uint32_t ep = lds32(S_EPOCH);
    {
      nb_sync(NB_CSQ, 160);
      float mu[4];
#pragma unroll
      for (int i = 0; i < 4; i++) {
        const float2 st = lds64f(S_KSTAT + ((i >> 1) * 64 + w * 16 + (i & 1) * 8 + g) * 8);
        mu[i] = -st.x;
        if (i < 2) rl0[i] = st.y;
      }
#pragma unroll
      for (int j = 0; j < 16; j++) {
        const float2 c = lds64f(S_CSQ + (j * 8 + 2 * t4) * 4);
        a0[4 * j] = mu[0] * c.x; a0[4 * j + 1] = mu[0] * c.y; a0[4 * j + 2] = mu[1] * c.x; a0[4 * j + 3] = mu[1] * c.y;
        a1[4 * j] = mu[2] * c.x; a1[4 * j + 1] = mu[2] * c.y; a1[4 * j + 2] = mu[3] * c.x; a1[4 * j + 3] = mu[3] * c.y;
      }
      reg_fence(a0); reg_fence(a1);
    }
    STAMP_IF(leader, 40);
    nb_sync(NB_VQ, 256);
    mainloop<false>(a0, a1, 2, 0, 0, 4 + (tn & 3), leader);
    STAMP_IF(leader, 36);
    {
      uint32_t f[2][16];
      float oc[2][2][20];
      auto phi = [&](const float (&a)[64], int j, int m, uint32_t (&o)[16]) {
        float rl[2] = {rl0[0], rl0[1]};
        if (j | m) { rl[0] = lds32v(S_KSTAT + (m * 64 + w * 16 + g) * 8 + 4); rl[1] = lds32v(S_KSTAT + (m * 64 + w * 16 + 8 + g) * 8 + 4); }
#pragma unroll
        for (int i = 0; i < 16; i++) o[i] = pack(phi2(a[32 * j + 2 * i] * rl[i & 1]), phi2(a[32 * j + 2 * i + 1] * rl[i & 1]));
      };
      auto mma = [&](int j, const uint32_t (&a)[16], float (&o)[2][20]) {
        const uint64_t db = mkdesc(j ? KVB_Z : KVB_P0, 16, 1024, 1);
        reg_zero(o[0]); reg_zero(o[1]);
        wg_fence();
        wgmma_n40_rs<0>(o[0], a[0], a[1], a[2], a[3], db, 0);
        wgmma_n40_rs<0>(o[1], a[8], a[9], a[10], a[11], db + 4, 0);
        wgmma_n40_rs<0>(o[0], a[4], a[5], a[6], a[7], db + 2, 1);
        wgmma_n40_rs<0>(o[1], a[12], a[13], a[14], a[15], db + 6, 1);
        wg_commit();
      };
      auto fin = [&](int j, int m, float (&o)[2][20]) {
        const uint32_t m0 = t4 == 2 * m, m1 = t4 == 2 * m + 1;
#pragma unroll
        for (int h = 0; h < 2; h++) {
          const float r0 = rcp(o[h][j ? 1 : 16] + 1e-6f * LOG2E), r1 = rcp(o[h][j ? 3 : 18] + 1e-6f * LOG2E);
          const int b = j ? 4 : 0;
#pragma unroll
          for (int q = 0; q < 2; q++)
            stsm4(sw[h * 2 + q] + j * 16384 + m * 8192,
                  bsel(pack(o[h][b + 8 * q] * r0, o[h][b + 8 * q + 1] * r0), ep, m0), bsel(pack(o[h][b + 8 * q + 2] * r1, o[h][b + 8 * q + 3] * r1), ep, m1),
                  bsel(pack(o[h][b + 8 * q + 4] * r0, o[h][b + 8 * q + 5] * r0), ep, m0), bsel(pack(o[h][b + 8 * q + 6] * r1, o[h][b + 8 * q + 7] * r1), ep, m1));
        }
      };
#pragma unroll
      for (int j = 0; j < 2; j++) {
        phi(a0, j, 0, f[0]);
        if (j == 0) nb_sync(NB_KVB, 288);
        STAMP_IF(leader && j == 0, 37);
        mma(j, f[0], oc[0]);
        phi(a1, j, 1, f[1]);
        wg_wait<0>();
        reg_fence(oc[0][0]); reg_fence(oc[0][1]);
        mma(j, f[1], oc[1]);
        if (!RES_FIRST && j == 0) nb_sync(NB_KV, 256);
        fin(j, 0, oc[0]);
        if (j == 0) { fence_async_smem(); nb_arrive(NB_Q0, 192); }
        wg_wait<0>();
        reg_fence(oc[1][0]); reg_fence(oc[1][1]);
        fin(j, 1, oc[1]);
        fence_async_smem();
        if (j == 0) nb_arrive(NB_OWN0, 288);
        else { nb_arrive(NB_OWN1, 256); nb_arrive(NB_H1, 160); }
        STAMP_IF(leader, 38 + j);
      }
    }
  }
}

#undef CK
typedef CUresult (*EncodeFn)(CUtensorMap*, CUtensorMapDataType, cuuint32_t, void*, const cuuint64_t*, const cuuint64_t*, const cuuint32_t*,
                             const cuuint32_t*, CUtensorMapInterleave, CUtensorMapSwizzle, CUtensorMapL2promotion, CUtensorMapFloatOOBfill);

void make_map(EncodeFn enc, CUtensorMap* m, const void* p, int rank, uint64_t d0, uint64_t d1, uint64_t d2, uint64_t s1, uint64_t s2,
              uint32_t b0, uint32_t b1, uint32_t b2, CUtensorMapSwizzle sw) {
  cuuint64_t gd[3] = {d0, d1, d2}, gs[2] = {s1, s2};
  cuuint32_t bd[3] = {b0, b1, b2}, es[3] = {1, 1, 1};
  enc(m, CU_TENSOR_MAP_DATA_TYPE_BFLOAT16, rank, const_cast<void*>(p), gd, gs, bd, es, CU_TENSOR_MAP_INTERLEAVE_NONE, sw,
      CU_TENSOR_MAP_L2_PROMOTION_L2_128B, CU_TENSOR_MAP_FLOAT_OOB_FILL_NONE);
}

}

extern "C" void kernel_launch(void* const* d_in, const int* in_sizes, int n_in, void* d_out, int out_size) {
  (void)in_sizes; (void)n_in; (void)out_size;
  void* fn = nullptr;
  cudaDriverEntryPointQueryResult qr;
  cudaGetDriverEntryPoint("cuTensorMapEncodeTiled", &fn, cudaEnableDefault, &qr);
  EncodeFn enc = (EncodeFn)fn;
  void* o;
  cudaGetSymbolAddress(&o, g_o);
  const CUtensorMapSwizzle S128 = CU_TENSOR_MAP_SWIZZLE_128B, S64 = CU_TENSOR_MAP_SWIZZLE_64B, S0 = CU_TENSOR_MAP_SWIZZLE_NONE;
  Params mp;
  mp.x = (const char*)d_in[0]; mp.wqkv = (const char*)d_in[1]; mp.w_r = (const char*)d_in[4];
  mp.wg = (const char*)d_in[5]; mp.wu = (const char*)d_in[6]; mp.wd = (const char*)d_in[7];
  make_map(enc, &mp.m_wqkv, d_in[1], 3, 64, 1024, 48, 6144, 128, 64, 64, 2, S128);
  make_map(enc, &mp.m_x, d_in[0], 2, 1024, 2048, 1, 2048, 0, 64, 128, 1, S128);
  make_map(enc, &mp.m_os, o, 2, 1024, 2048, 1, 2048, 0, 64, 64, 1, S128);
  make_map(enc, &mp.m_o, o, 2, 1024, 2048, 1, 2048, 0, 64, 128, 1, S128);
  make_map(enc, &mp.m_wo, d_in[2], 3, 64, 1024, 16, 2048, 128, 64, 64, 2, S128);
  make_map(enc, &mp.m_xs, d_in[0], 2, 1024, 2048, 1, 2048, 0, 256, 16, 1, S0);
  const char *wg = (const char*)d_in[5], *wu = (const char*)d_in[6];
  make_map(enc, &mp.m_gu, wu < wg ? wu : wg, 3, 3584, 1024, 2, 7168, (uint64_t)(wu < wg ? wg - wu : wu - wg), 32, 64, 2, S64);
  make_map(enc, &mp.m_down, d_in[7], 2, 1024, 3584, 1, 2048, 0, 64, 64, 1, S128);
  make_map(enc, &mp.m_out, d_out, 2, 1024, 2048, 1, 2048, 0, 64, 16, 1, S128);
  int dev = 0, sms = 0;
  cudaGetDevice(&dev);
  cudaDeviceGetAttribute(&sms, cudaDevAttrMultiProcessorCount, dev);
  auto kern = sms == 132 ? fused_kernel<true> : fused_kernel<false>;
  cudaFuncSetAttribute(kern, cudaFuncAttributeMaxDynamicSharedMemorySize, SMEM_BYTES);
  kern<<<132, 512, SMEM_BYTES>>>(mp);
}
```

```cpp
#include <cuda_runtime.h>
#include <cuda.h>
#include <cuda_bf16.h>
#include <stdint.h>

namespace {

template <int TA, int TB>
__device__ __forceinline__ void wgmma_n8_ss(float (&d)[4], uint64_t da, uint64_t db, int sc) {
  asm volatile("{\n.reg .pred p;\nsetp.ne.b32 p, %6, 0;\n"
    "wgmma.mma_async.sync.aligned.m64n8k16.f32.bf16.bf16 {%0, %1, %2, %3}, %4, %5, p, 1, 1, %7, %8;\n}\n"
    : "+f"(d[0]), "+f"(d[1]), "+f"(d[2]), "+f"(d[3])
    : "l"(da), "l"(db), "r"(sc), "n"(TA), "n"(TB));
}
template <int TA, int TB>
__device__ __forceinline__ void wgmma_n16_ss(float (&d)[8], uint64_t da, uint64_t db, int sc) {
  asm volatile("{\n.reg .pred p;\nsetp.ne.b32 p, %10, 0;\n"
    "wgmma.mma_async.sync.aligned.m64n16k16.f32.bf16.bf16 {%0, %1, %2, %3, %4, %5, %6, %7}, %8, %9, p, 1, 1, %11, %12;\n}\n"
    : "+f"(d[0]), "+f"(d[1]), "+f"(d[2]), "+f"(d[3]), "+f"(d[4]), "+f"(d[5]), "+f"(d[6]), "+f"(d[7])
    : "l"(da), "l"(db), "r"(sc), "n"(TA), "n"(TB));
}
template <int TB>
__device__ __forceinline__ void wgmma_n40_rs(float (&d)[20], uint32_t a0, uint32_t a1, uint32_t a2, uint32_t a3, uint64_t db, int sc) {
  asm volatile("{\n.reg .pred p;\nsetp.ne.b32 p, %25, 0;\n"
    "wgmma.mma_async.sync.aligned.m64n40k16.f32.bf16.bf16 {%0, %1, %2, %3, %4, %5, %6, %7, %8, %9, %10, %11, %12, %13, %14, %15, %16, %17, %18, %19}, {%20,%21,%22,%23}, %24, p, 1, 1, %26;\n}\n"
    : "+f"(d[0]), "+f"(d[1]), "+f"(d[2]), "+f"(d[3]), "+f"(d[4]), "+f"(d[5]), "+f"(d[6]), "+f"(d[7]),
      "+f"(d[8]), "+f"(d[9]), "+f"(d[10]), "+f"(d[11]), "+f"(d[12]), "+f"(d[13]), "+f"(d[14]), "+f"(d[15]),
      "+f"(d[16]), "+f"(d[17]), "+f"(d[18]), "+f"(d[19])
    : "r"(a0), "r"(a1), "r"(a2), "r"(a3), "l"(db), "r"(sc), "n"(TB));
}
template <int TB>
__device__ __forceinline__ void wgmma_n64_rs(float (&d)[32], uint32_t a0, uint32_t a1, uint32_t a2, uint32_t a3, uint64_t db, int sc) {
  asm volatile("{\n.reg .pred p;\nsetp.ne.b32 p, %37, 0;\n"
    "wgmma.mma_async.sync.aligned.m64n64k16.f32.bf16.bf16 {%0, %1, %2, %3, %4, %5, %6, %7, %8, %9, %10, %11, %12, %13, %14, %15, %16, %17, %18, %19, %20, %21, %22, %23, %24, %25, %26, %27, %28, %29, %30, %31}, {%32,%33,%34,%35}, %36, p, 1, 1, %38;\n}\n"
    : "+f"(d[0]), "+f"(d[1]), "+f"(d[2]), "+f"(d[3]), "+f"(d[4]), "+f"(d[5]), "+f"(d[6]), "+f"(d[7]),
      "+f"(d[8]), "+f"(d[9]), "+f"(d[10]), "+f"(d[11]), "+f"(d[12]), "+f"(d[13]), "+f"(d[14]), "+f"(d[15]),
      "+f"(d[16]), "+f"(d[17]), "+f"(d[18]), "+f"(d[19]), "+f"(d[20]), "+f"(d[21]), "+f"(d[22]), "+f"(d[23]),
      "+f"(d[24]), "+f"(d[25]), "+f"(d[26]), "+f"(d[27]), "+f"(d[28]), "+f"(d[29]), "+f"(d[30]), "+f"(d[31])
    : "r"(a0), "r"(a1), "r"(a2), "r"(a3), "l"(db), "r"(sc), "n"(TB));
}
template <int TA, int TB>
__device__ __forceinline__ void wgmma_n128_ss(float (&d)[64], uint64_t da, uint64_t db, int sc) {
  asm volatile("{\n.reg .pred p;\nsetp.ne.b32 p, %66, 0;\n"
    "wgmma.mma_async.sync.aligned.m64n128k16.f32.bf16.bf16 {%0, %1, %2, %3, %4, %5, %6, %7, %8, %9, %10, %11, %12, %13, %14, %15, %16, %17, %18, %19, %20, %21, %22, %23, %24, %25, %26, %27, %28, %29, %30, %31, %32, %33, %34, %35, %36, %37, %38, %39, %40, %41, %42, %43, %44, %45, %46, %47, %48, %49, %50, %51, %52, %53, %54, %55, %56, %57, %58, %59, %60, %61, %62, %63}, %64, %65, p, 1, 1, %67, %68;\n}\n"
    : "+f"(d[0]), "+f"(d[1]), "+f"(d[2]), "+f"(d[3]), "+f"(d[4]), "+f"(d[5]), "+f"(d[6]), "+f"(d[7]),
      "+f"(d[8]), "+f"(d[9]), "+f"(d[10]), "+f"(d[11]), "+f"(d[12]), "+f"(d[13]), "+f"(d[14]), "+f"(d[15]),
      "+f"(d[16]), "+f"(d[17]), "+f"(d[18]), "+f"(d[19]), "+f"(d[20]), "+f"(d[21]), "+f"(d[22]), "+f"(d[23]),
      "+f"(d[24]), "+f"(d[25]), "+f"(d[26]), "+f"(d[27]), "+f"(d[28]), "+f"(d[29]), "+f"(d[30]), "+f"(d[31]),
      "+f"(d[32]), "+f"(d[33]), "+f"(d[34]), "+f"(d[35]), "+f"(d[36]), "+f"(d[37]), "+f"(d[38]), "+f"(d[39]),
      "+f"(d[40]), "+f"(d[41]), "+f"(d[42]), "+f"(d[43]), "+f"(d[44]), "+f"(d[45]), "+f"(d[46]), "+f"(d[47]),
      "+f"(d[48]), "+f"(d[49]), "+f"(d[50]), "+f"(d[51]), "+f"(d[52]), "+f"(d[53]), "+f"(d[54]), "+f"(d[55]),
      "+f"(d[56]), "+f"(d[57]), "+f"(d[58]), "+f"(d[59]), "+f"(d[60]), "+f"(d[61]), "+f"(d[62]), "+f"(d[63])
    : "l"(da), "l"(db), "r"(sc), "n"(TA), "n"(TB));
}
template <int TB>
__device__ __forceinline__ void wgmma_n128_rs(float (&d)[64], uint32_t a0, uint32_t a1, uint32_t a2, uint32_t a3, uint64_t db, int sc) {
  asm volatile("{\n.reg .pred p;\nsetp.ne.b32 p, %69, 0;\n"
    "wgmma.mma_async.sync.aligned.m64n128k16.f32.bf16.bf16 {%0, %1, %2, %3, %4, %5, %6, %7, %8, %9, %10, %11, %12, %13, %14, %15, %16, %17, %18, %19, %20, %21, %22, %23, %24, %25, %26, %27, %28, %29, %30, %31, %32, %33, %34, %35, %36, %37, %38, %39, %40, %41, %42, %43, %44, %45, %46, %47, %48, %49, %50, %51, %52, %53, %54, %55, %56, %57, %58, %59, %60, %61, %62, %63}, {%64,%65,%66,%67}, %68, p, 1, 1, %70;\n}\n"
    : "+f"(d[0]), "+f"(d[1]), "+f"(d[2]), "+f"(d[3]), "+f"(d[4]), "+f"(d[5]), "+f"(d[6]), "+f"(d[7]),
      "+f"(d[8]), "+f"(d[9]), "+f"(d[10]), "+f"(d[11]), "+f"(d[12]), "+f"(d[13]), "+f"(d[14]), "+f"(d[15]),
      "+f"(d[16]), "+f"(d[17]), "+f"(d[18]), "+f"(d[19]), "+f"(d[20]), "+f"(d[21]), "+f"(d[22]), "+f"(d[23]),
      "+f"(d[24]), "+f"(d[25]), "+f"(d[26]), "+f"(d[27]), "+f"(d[28]), "+f"(d[29]), "+f"(d[30]), "+f"(d[31]),
      "+f"(d[32]), "+f"(d[33]), "+f"(d[34]), "+f"(d[35]), "+f"(d[36]), "+f"(d[37]), "+f"(d[38]), "+f"(d[39]),
      "+f"(d[40]), "+f"(d[41]), "+f"(d[42]), "+f"(d[43]), "+f"(d[44]), "+f"(d[45]), "+f"(d[46]), "+f"(d[47]),
      "+f"(d[48]), "+f"(d[49]), "+f"(d[50]), "+f"(d[51]), "+f"(d[52]), "+f"(d[53]), "+f"(d[54]), "+f"(d[55]),
      "+f"(d[56]), "+f"(d[57]), "+f"(d[58]), "+f"(d[59]), "+f"(d[60]), "+f"(d[61]), "+f"(d[62]), "+f"(d[63])
    : "r"(a0), "r"(a1), "r"(a2), "r"(a3), "l"(db), "r"(sc), "n"(TB));
}

__device__ __forceinline__ void poll1(uint32_t (&v)[1], const void* p, uint32_t tag, uint32_t mask) {
  asm volatile("{\n.reg .pred p, q;\n.reg .u32 c, b;\n.reg .b64 x, y;\n.reg .b128 z;\nmov.u32 c, 0;\nLW:\n"
               "ld.relaxed.gpu.global.u32 %0, [%1+0];\n"
               "xor.b32 b, %0, %2;\n"
               "and.b32 b, b, %3;\nsetp.eq.u32 p, b, 0;\nvote.sync.all.pred p, p, 0xffffffff;\n@p bra.uni LD;\n"
               "nanosleep.u32 100;\nadd.u32 c, c, 1;\nsetp.lt.u32 q, c, 1000000;\n@q bra.uni LW;\ntrap;\nLD:\n}"
               : "=&r"(v[0])
               : "l"(p), "r"(tag), "r"(mask) : "memory");
}
__device__ __forceinline__ void poll1f(uint32_t (&v)[1], const void* p, uint32_t tag, uint32_t mask) {
  asm volatile("{\n.reg .pred p, q;\n.reg .u32 c, b;\n.reg .b64 x, y;\n.reg .b128 z;\nmov.u32 c, 0;\nLW:\n"
               "ld.relaxed.gpu.global.u32 %0, [%1+0];\n"
               "xor.b32 b, %0, %2;\n"
               "and.b32 b, b, %3;\nsetp.eq.u32 p, b, 0;\nvote.sync.all.pred p, p, 0xffffffff;\n@p bra.uni LD;\n"
               "nanosleep.u32 50;\nadd.u32 c, c, 1;\nsetp.lt.u32 q, c, 1000000;\n@q bra.uni LW;\ntrap;\nLD:\n}"
               : "=&r"(v[0])
               : "l"(p), "r"(tag), "r"(mask) : "memory");
}
__device__ __forceinline__ void poll0(uint32_t (&v)[1], const void* p, uint32_t tag, uint32_t mask) {
  asm volatile("{\n.reg .pred p, q;\n.reg .u32 c, b;\n.reg .b64 x, y;\n.reg .b128 z;\nmov.u32 c, 0;\nLW:\n"
               "ld.relaxed.gpu.global.u32 %0, [%1+0];\n"
               "xor.b32 b, %0, %2;\n"
               "and.b32 b, b, %3;\nsetp.eq.u32 p, b, 0;\nvote.sync.all.pred p, p, 0xffffffff;\n@p bra.uni LD;\n"
               "add.u32 c, c, 1;\nsetp.lt.u32 q, c, 1000000;\n@q bra.uni LW;\ntrap;\nLD:\n}"
               : "=&r"(v[0])
               : "l"(p), "r"(tag), "r"(mask) : "memory");
}
__device__ __forceinline__ void poll_pair(uint32_t (&v)[2], const void* p, uint32_t tag, uint32_t mask) {
  asm volatile("{\n.reg .pred p, q;\n.reg .u32 c, b;\n.reg .b64 x, y;\n.reg .b128 z;\nmov.u32 c, 0;\nLW:\n"
               "ld.relaxed.gpu.global.b64 x, [%2+0];\nmov.b64 {%0,%1}, x;\n"
               "xor.b32 b, %0, %3;\n"
               "and.b32 b, b, %4;\nsetp.eq.u32 p, b, 0;\nvote.sync.all.pred p, p, 0xffffffff;\n@p bra.uni LD;\n"
               "nanosleep.u32 100;\nadd.u32 c, c, 1;\nsetp.lt.u32 q, c, 1000000;\n@q bra.uni LW;\ntrap;\nLD:\n}"
               : "=&r"(v[0]), "=&r"(v[1])
               : "l"(p), "r"(tag), "r"(mask) : "memory");
}
__device__ __forceinline__ void poll_quad(uint32_t (&v)[4], const void* p, uint32_t tag, uint32_t mask) {
  asm volatile("{\n.reg .pred p, q;\n.reg .u32 c, b;\n.reg .b64 x, y;\n.reg .b128 z;\nmov.u32 c, 0;\nLW:\n"
               "ld.relaxed.gpu.global.v4.u32 {%0,%1,%2,%3}, [%4+0];\n"
               "xor.b32 b, %0, %5;\n"
               "lop3.b32 b, b, %1, %5, 0xf6;\nlop3.b32 b, b, %2, %5, 0xf6;\nlop3.b32 b, b, %3, %5, 0xf6;\n"
               "and.b32 b, b, %6;\nsetp.eq.u32 p, b, 0;\nvote.sync.all.pred p, p, 0xffffffff;\n@p bra.uni LD;\n"
               "nanosleep.u32 200;\nadd.u32 c, c, 1;\nsetp.lt.u32 q, c, 1000000;\n@q bra.uni LW;\ntrap;\nLD:\n}"
               : "=&r"(v[0]), "=&r"(v[1]), "=&r"(v[2]), "=&r"(v[3])
               : "l"(p), "r"(tag), "r"(mask) : "memory");
}
__device__ __forceinline__ void poll8x4(uint32_t (&v)[32], const void* p, uint32_t tag, uint32_t mask) {
  asm volatile("{\n.reg .pred p, q;\n.reg .u32 c, b;\n.reg .b64 x, y;\n.reg .b128 z;\nmov.u32 c, 0;\nLW:\n"
               "ld.relaxed.gpu.global.v4.u32 {%0,%1,%2,%3}, [%32+0];\n"
               "ld.relaxed.gpu.global.v4.u32 {%4,%5,%6,%7}, [%32+2048];\n"
               "ld.relaxed.gpu.global.v4.u32 {%8,%9,%10,%11}, [%32+4096];\n"
               "ld.relaxed.gpu.global.v4.u32 {%12,%13,%14,%15}, [%32+6144];\n"
               "ld.relaxed.gpu.global.v4.u32 {%16,%17,%18,%19}, [%32+8192];\n"
               "ld.relaxed.gpu.global.v4.u32 {%20,%21,%22,%23}, [%32+10240];\n"
               "ld.relaxed.gpu.global.v4.u32 {%24,%25,%26,%27}, [%32+12288];\n"
               "ld.relaxed.gpu.global.v4.u32 {%28,%29,%30,%31}, [%32+14336];\n"
               "xor.b32 b, %0, %33;\n"
               "lop3.b32 b, b, %1, %33, 0xf6;\nlop3.b32 b, b, %2, %33, 0xf6;\nlop3.b32 b, b, %3, %33, 0xf6;\nlop3.b32 b, b, %4, %33, 0xf6;\n"
               "lop3.b32 b, b, %5, %33, 0xf6;\nlop3.b32 b, b, %6, %33, 0xf6;\nlop3.b32 b, b, %7, %33, 0xf6;\nlop3.b32 b, b, %8, %33, 0xf6;\n"
               "lop3.b32 b, b, %9, %33, 0xf6;\nlop3.b32 b, b, %10, %33, 0xf6;\nlop3.b32 b, b, %11, %33, 0xf6;\nlop3.b32 b, b, %12, %33, 0xf6;\n"
               "lop3.b32 b, b, %13, %33, 0xf6;\nlop3.b32 b, b, %14, %33, 0xf6;\nlop3.b32 b, b, %15, %33, 0xf6;\nlop3.b32 b, b, %16, %33, 0xf6;\n"
               "lop3.b32 b, b, %17, %33, 0xf6;\nlop3.b32 b, b, %18, %33, 0xf6;\nlop3.b32 b, b, %19, %33, 0xf6;\nlop3.b32 b, b, %20, %33, 0xf6;\n"
               "lop3.b32 b, b, %21, %33, 0xf6;\nlop3.b32 b, b, %22, %33, 0xf6;\nlop3.b32 b, b, %23, %33, 0xf6;\nlop3.b32 b, b, %24, %33, 0xf6;\n"
               "lop3.b32 b, b, %25, %33, 0xf6;\nlop3.b32 b, b, %26, %33, 0xf6;\nlop3.b32 b, b, %27, %33, 0xf6;\nlop3.b32 b, b, %28, %33, 0xf6;\n"
               "lop3.b32 b, b, %29, %33, 0xf6;\nlop3.b32 b, b, %30, %33, 0xf6;\nlop3.b32 b, b, %31, %33, 0xf6;\n"
               "and.b32 b, b, %34;\nsetp.eq.u32 p, b, 0;\nvote.sync.all.pred p, p, 0xffffffff;\n@p bra.uni LD;\n"
               "nanosleep.u32 50;\nadd.u32 c, c, 1;\nsetp.lt.u32 q, c, 1000000;\n@q bra.uni LW;\ntrap;\nLD:\n}"
               : "=&r"(v[0]), "=&r"(v[1]), "=&r"(v[2]), "=&r"(v[3]), "=&r"(v[4]), "=&r"(v[5]), "=&r"(v[6]), "=&r"(v[7]), "=&r"(v[8]), "=&r"(v[9]), "=&r"(v[10]), "=&r"(v[11]), "=&r"(v[12]), "=&r"(v[13]), "=&r"(v[14]), "=&r"(v[15]), "=&r"(v[16]), "=&r"(v[17]), "=&r"(v[18]), "=&r"(v[19]), "=&r"(v[20]), "=&r"(v[21]), "=&r"(v[22]), "=&r"(v[23]), "=&r"(v[24]), "=&r"(v[25]), "=&r"(v[26]), "=&r"(v[27]), "=&r"(v[28]), "=&r"(v[29]), "=&r"(v[30]), "=&r"(v[31])
               : "l"(p), "r"(tag), "r"(mask) : "memory");
}
__device__ __forceinline__ void poll16(uint32_t (&v)[16], const void* p, uint32_t tag, uint32_t mask) {
  asm volatile("{\n.reg .pred p, q;\n.reg .u32 c, b;\n.reg .b64 x, y;\n.reg .b128 z;\nmov.u32 c, 0;\nLW:\n"
               "ld.relaxed.gpu.global.u32 %0, [%16+0];\n"
               "ld.relaxed.gpu.global.u32 %1, [%16+4096];\n"
               "ld.relaxed.gpu.global.u32 %2, [%16+8192];\n"
               "ld.relaxed.gpu.global.u32 %3, [%16+12288];\n"
               "ld.relaxed.gpu.global.u32 %4, [%16+16384];\n"
               "ld.relaxed.gpu.global.u32 %5, [%16+20480];\n"
               "ld.relaxed.gpu.global.u32 %6, [%16+24576];\n"
               "ld.relaxed.gpu.global.u32 %7, [%16+28672];\n"
               "ld.relaxed.gpu.global.u32 %8, [%16+32768];\n"
               "ld.relaxed.gpu.global.u32 %9, [%16+36864];\n"
               "ld.relaxed.gpu.global.u32 %10, [%16+40960];\n"
               "ld.relaxed.gpu.global.u32 %11, [%16+45056];\n"
               "ld.relaxed.gpu.global.u32 %12, [%16+49152];\n"
               "ld.relaxed.gpu.global.u32 %13, [%16+53248];\n"
               "ld.relaxed.gpu.global.u32 %14, [%16+57344];\n"
               "ld.relaxed.gpu.global.u32 %15, [%16+61440];\n"
               "xor.b32 b, %0, %17;\n"
               "lop3.b32 b, b, %1, %17, 0xf6;\nlop3.b32 b, b, %2, %17, 0xf6;\nlop3.b32 b, b, %3, %17, 0xf6;\nlop3.b32 b, b, %4, %17, 0xf6;\n"
               "lop3.b32 b, b, %5, %17, 0xf6;\nlop3.b32 b, b, %6, %17, 0xf6;\nlop3.b32 b, b, %7, %17, 0xf6;\nlop3.b32 b, b, %8, %17, 0xf6;\n"
               "lop3.b32 b, b, %9, %17, 0xf6;\nlop3.b32 b, b, %10, %17, 0xf6;\nlop3.b32 b, b, %11, %17, 0xf6;\nlop3.b32 b, b, %12, %17, 0xf6;\n"
               "lop3.b32 b, b, %13, %17, 0xf6;\nlop3.b32 b, b, %14, %17, 0xf6;\nlop3.b32 b, b, %15, %17, 0xf6;\n"
               "and.b32 b, b, %18;\nsetp.eq.u32 p, b, 0;\nvote.sync.all.pred p, p, 0xffffffff;\n@p bra.uni LD;\n"
               "nanosleep.u32 200;\nadd.u32 c, c, 1;\nsetp.lt.u32 q, c, 1000000;\n@q bra.uni LW;\ntrap;\nLD:\n}"
               : "=&r"(v[0]), "=&r"(v[1]), "=&r"(v[2]), "=&r"(v[3]), "=&r"(v[4]), "=&r"(v[5]), "=&r"(v[6]), "=&r"(v[7]), "=&r"(v[8]), "=&r"(v[9]), "=&r"(v[10]), "=&r"(v[11]), "=&r"(v[12]), "=&r"(v[13]), "=&r"(v[14]), "=&r"(v[15])
               : "l"(p), "r"(tag), "r"(mask) : "memory");
}
__device__ __forceinline__ void poll_keys(uint32_t (&v)[16], const void* p, uint32_t tag, uint32_t mask) {
  asm volatile("{\n.reg .pred p, q;\n.reg .u32 c, b;\n.reg .b64 x, y;\n.reg .b128 z;\nmov.u32 c, 0;\nLW:\n"
               "ld.relaxed.gpu.global.v2.b64 {x, y}, [%16+0];\nmov.b64 {%0,%1}, x;\nmov.b64 {%2,%3}, y;\n"
               "ld.relaxed.gpu.global.v2.b64 {x, y}, [%16+4096];\nmov.b64 {%4,%5}, x;\nmov.b64 {%6,%7}, y;\n"
               "ld.relaxed.gpu.global.v2.b64 {x, y}, [%16+8192];\nmov.b64 {%8,%9}, x;\nmov.b64 {%10,%11}, y;\n"
               "ld.relaxed.gpu.global.v2.b64 {x, y}, [%16+12288];\nmov.b64 {%12,%13}, x;\nmov.b64 {%14,%15}, y;\n"
               "xor.b32 b, %0, %17;\n"
               "lop3.b32 b, b, %2, %17, 0xf6;\nlop3.b32 b, b, %4, %17, 0xf6;\nlop3.b32 b, b, %6, %17, 0xf6;\nlop3.b32 b, b, %8, %17, 0xf6;\n"
               "lop3.b32 b, b, %10, %17, 0xf6;\nlop3.b32 b, b, %12, %17, 0xf6;\nlop3.b32 b, b, %14, %17, 0xf6;\n"
               "and.b32 b, b, %18;\nsetp.eq.u32 p, b, 0;\nvote.sync.all.pred p, p, 0xffffffff;\n@p bra.uni LD;\n"
               "nanosleep.u32 20;\nadd.u32 c, c, 1;\nsetp.lt.u32 q, c, 1000000;\n@q bra.uni LW;\ntrap;\nLD:\n}"
               : "=&r"(v[0]), "=&r"(v[1]), "=&r"(v[2]), "=&r"(v[3]), "=&r"(v[4]), "=&r"(v[5]), "=&r"(v[6]), "=&r"(v[7]), "=&r"(v[8]), "=&r"(v[9]), "=&r"(v[10]), "=&r"(v[11]), "=&r"(v[12]), "=&r"(v[13]), "=&r"(v[14]), "=&r"(v[15])
               : "l"(p), "r"(tag), "r"(mask) : "memory");
}
__device__ __forceinline__ void poll_z(uint32_t (&v)[16], const void* p, uint32_t tag, uint32_t mask) {
  asm volatile("{\n.reg .pred p, q;\n.reg .u32 c, b;\n.reg .b64 x, y;\n.reg .b128 z;\nmov.u32 c, 0;\nLW:\n"
               "ld.relaxed.gpu.global.v4.u32 {%0,%1,%2,%3}, [%16+0];\n"
               "ld.relaxed.gpu.global.v4.u32 {%4,%5,%6,%7}, [%16+4096];\n"
               "ld.relaxed.gpu.global.v4.u32 {%8,%9,%10,%11}, [%16+8192];\n"
               "ld.relaxed.gpu.global.v4.u32 {%12,%13,%14,%15}, [%16+12288];\n"
               "xor.b32 b, %0, %17;\n"
               "lop3.b32 b, b, %1, %17, 0xf6;\nlop3.b32 b, b, %2, %17, 0xf6;\nlop3.b32 b, b, %3, %17, 0xf6;\nlop3.b32 b, b, %4, %17, 0xf6;\n"
               "lop3.b32 b, b, %5, %17, 0xf6;\nlop3.b32 b, b, %6, %17, 0xf6;\nlop3.b32 b, b, %7, %17, 0xf6;\nlop3.b32 b, b, %8, %17, 0xf6;\n"
               "lop3.b32 b, b, %9, %17, 0xf6;\nlop3.b32 b, b, %10, %17, 0xf6;\nlop3.b32 b, b, %11, %17, 0xf6;\nlop3.b32 b, b, %12, %17, 0xf6;\n"
               "lop3.b32 b, b, %13, %17, 0xf6;\nlop3.b32 b, b, %14, %17, 0xf6;\nlop3.b32 b, b, %15, %17, 0xf6;\n"
               "and.b32 b, b, %18;\nsetp.eq.u32 p, b, 0;\nvote.sync.all.pred p, p, 0xffffffff;\n@p bra.uni LD;\n"
               "nanosleep.u32 300;\nadd.u32 c, c, 1;\nsetp.lt.u32 q, c, 1000000;\n@q bra.uni LW;\ntrap;\nLD:\n}"
               : "=&r"(v[0]), "=&r"(v[1]), "=&r"(v[2]), "=&r"(v[3]), "=&r"(v[4]), "=&r"(v[5]), "=&r"(v[6]), "=&r"(v[7]), "=&r"(v[8]), "=&r"(v[9]), "=&r"(v[10]), "=&r"(v[11]), "=&r"(v[12]), "=&r"(v[13]), "=&r"(v[14]), "=&r"(v[15])
               : "l"(p), "r"(tag), "r"(mask) : "memory");
}
__device__ __forceinline__ void poll7x4(uint32_t (&v)[28], const void* p, uint32_t tag, uint32_t mask) {
  asm volatile("{\n.reg .pred p, q;\n.reg .u32 c, b;\n.reg .b64 x, y;\n.reg .b128 z;\nmov.u32 c, 0;\nLW:\n"
               "ld.relaxed.gpu.global.v4.u32 {%0,%1,%2,%3}, [%28+0];\n"
               "ld.relaxed.gpu.global.v4.u32 {%4,%5,%6,%7}, [%28+2048];\n"
               "ld.relaxed.gpu.global.v4.u32 {%8,%9,%10,%11}, [%28+4096];\n"
               "ld.relaxed.gpu.global.v4.u32 {%12,%13,%14,%15}, [%28+6144];\n"
               "ld.relaxed.gpu.global.v4.u32 {%16,%17,%18,%19}, [%28+8192];\n"
               "ld.relaxed.gpu.global.v4.u32 {%20,%21,%22,%23}, [%28+10240];\n"
               "ld.relaxed.gpu.global.v4.u32 {%24,%25,%26,%27}, [%28+12288];\n"
               "xor.b32 b, %0, %29;\n"
               "lop3.b32 b, b, %1, %29, 0xf6;\nlop3.b32 b, b, %2, %29, 0xf6;\nlop3.b32 b, b, %3, %29, 0xf6;\nlop3.b32 b, b, %4, %29, 0xf6;\n"
               "lop3.b32 b, b, %5, %29, 0xf6;\nlop3.b32 b, b, %6, %29, 0xf6;\nlop3.b32 b, b, %7, %29, 0xf6;\nlop3.b32 b, b, %8, %29, 0xf6;\n"
               "lop3.b32 b, b, %9, %29, 0xf6;\nlop3.b32 b, b, %10, %29, 0xf6;\nlop3.b32 b, b, %11, %29, 0xf6;\nlop3.b32 b, b, %12, %29, 0xf6;\n"
               "lop3.b32 b, b, %13, %29, 0xf6;\nlop3.b32 b, b, %14, %29, 0xf6;\nlop3.b32 b, b, %15, %29, 0xf6;\nlop3.b32 b, b, %16, %29, 0xf6;\n"
               "lop3.b32 b, b, %17, %29, 0xf6;\nlop3.b32 b, b, %18, %29, 0xf6;\nlop3.b32 b, b, %19, %29, 0xf6;\nlop3.b32 b, b, %20, %29, 0xf6;\n"
               "lop3.b32 b, b, %21, %29, 0xf6;\nlop3.b32 b, b, %22, %29, 0xf6;\nlop3.b32 b, b, %23, %29, 0xf6;\nlop3.b32 b, b, %24, %29, 0xf6;\n"
               "lop3.b32 b, b, %25, %29, 0xf6;\nlop3.b32 b, b, %26, %29, 0xf6;\nlop3.b32 b, b, %27, %29, 0xf6;\n"
               "and.b32 b, b, %30;\nsetp.eq.u32 p, b, 0;\nvote.sync.all.pred p, p, 0xffffffff;\n@p bra.uni LD;\n"
               "nanosleep.u32 50;\nadd.u32 c, c, 1;\nsetp.lt.u32 q, c, 1000000;\n@q bra.uni LW;\ntrap;\nLD:\n}"
               : "=&r"(v[0]), "=&r"(v[1]), "=&r"(v[2]), "=&r"(v[3]), "=&r"(v[4]), "=&r"(v[5]), "=&r"(v[6]), "=&r"(v[7]), "=&r"(v[8]), "=&r"(v[9]), "=&r"(v[10]), "=&r"(v[11]), "=&r"(v[12]), "=&r"(v[13]), "=&r"(v[14]), "=&r"(v[15]), "=&r"(v[16]), "=&r"(v[17]), "=&r"(v[18]), "=&r"(v[19]), "=&r"(v[20]), "=&r"(v[21]), "=&r"(v[22]), "=&r"(v[23]), "=&r"(v[24]), "=&r"(v[25]), "=&r"(v[26]), "=&r"(v[27])
               : "l"(p), "r"(tag), "r"(mask) : "memory");
}
__device__ __forceinline__ void poll_kvp(uint32_t (&v)[16], const void* p, uint32_t tag, uint32_t mask) {
  asm volatile("{\n.reg .pred p, q;\n.reg .u32 c, b;\n.reg .b64 x, y;\n.reg .b128 z;\nmov.u32 c, 0;\nLW:\n"
               "ld.relaxed.gpu.global.b128 z, [%16+0];\nmov.b128 {x, y}, z;\nmov.b64 {%0,%1}, x;\nmov.b64 {%2,%3}, y;\n"
               "ld.relaxed.gpu.global.b128 z, [%16+8192];\nmov.b128 {x, y}, z;\nmov.b64 {%4,%5}, x;\nmov.b64 {%6,%7}, y;\n"
               "ld.relaxed.gpu.global.b128 z, [%16+16384];\nmov.b128 {x, y}, z;\nmov.b64 {%8,%9}, x;\nmov.b64 {%10,%11}, y;\n"
               "ld.relaxed.gpu.global.b128 z, [%16+24576];\nmov.b128 {x, y}, z;\nmov.b64 {%12,%13}, x;\nmov.b64 {%14,%15}, y;\n"
               "xor.b32 b, %0, %17;\n"
               "lop3.b32 b, b, %4, %17, 0xf6;\nlop3.b32 b, b, %8, %17, 0xf6;\nlop3.b32 b, b, %12, %17, 0xf6;\n"
               "and.b32 b, b, %18;\nsetp.eq.u32 p, b, 0;\nvote.sync.all.pred p, p, 0xffffffff;\n@p bra.uni LD;\n"
               "nanosleep.u32 50;\nadd.u32 c, c, 1;\nsetp.lt.u32 q, c, 1000000;\n@q bra.uni LW;\ntrap;\nLD:\n}"
               : "=&r"(v[0]), "=&r"(v[1]), "=&r"(v[2]), "=&r"(v[3]), "=&r"(v[4]), "=&r"(v[5]), "=&r"(v[6]), "=&r"(v[7]), "=&r"(v[8]), "=&r"(v[9]), "=&r"(v[10]), "=&r"(v[11]), "=&r"(v[12]), "=&r"(v[13]), "=&r"(v[14]), "=&r"(v[15])
               : "l"(p), "r"(tag), "r"(mask) : "memory");
}
__device__ __forceinline__ void poll_kv(uint32_t (&v)[16], const void* p, uint32_t tag, uint32_t mask) {
  asm volatile("{\n.reg .pred p, q;\n.reg .u32 c, b;\n.reg .b64 x, y;\n.reg .b128 z;\nmov.u32 c, 0;\nLW:\n"
               "ld.relaxed.gpu.global.b128 z, [%16+0];\nmov.b128 {x, y}, z;\nmov.b64 {%0,%1}, x;\nmov.b64 {%2,%3}, y;\n"
               "ld.relaxed.gpu.global.b128 z, [%16+2048];\nmov.b128 {x, y}, z;\nmov.b64 {%4,%5}, x;\nmov.b64 {%6,%7}, y;\n"
               "ld.relaxed.gpu.global.b128 z, [%16+4096];\nmov.b128 {x, y}, z;\nmov.b64 {%8,%9}, x;\nmov.b64 {%10,%11}, y;\n"
               "ld.relaxed.gpu.global.b128 z, [%16+6144];\nmov.b128 {x, y}, z;\nmov.b64 {%12,%13}, x;\nmov.b64 {%14,%15}, y;\n"
               "xor.b32 b, %0, %17;\n"
               "lop3.b32 b, b, %4, %17, 0xf6;\nlop3.b32 b, b, %8, %17, 0xf6;\nlop3.b32 b, b, %12, %17, 0xf6;\n"
               "and.b32 b, b, %18;\nsetp.eq.u32 p, b, 0;\nvote.sync.all.pred p, p, 0xffffffff;\n@p bra.uni LD;\n"
               "nanosleep.u32 50;\nadd.u32 c, c, 1;\nsetp.lt.u32 q, c, 1000000;\n@q bra.uni LW;\ntrap;\nLD:\n}"
               : "=&r"(v[0]), "=&r"(v[1]), "=&r"(v[2]), "=&r"(v[3]), "=&r"(v[4]), "=&r"(v[5]), "=&r"(v[6]), "=&r"(v[7]), "=&r"(v[8]), "=&r"(v[9]), "=&r"(v[10]), "=&r"(v[11]), "=&r"(v[12]), "=&r"(v[13]), "=&r"(v[14]), "=&r"(v[15])
               : "l"(p), "r"(tag), "r"(mask) : "memory");
}

__device__ __align__(1024) __nv_bfloat16 g_o[2048 * 1024];
__device__ __align__(128) uint2 g_keys[2048];
__device__ __align__(128) uint32_t g_csum[18 * 1024];
__device__ __align__(128) uint32_t g_z[16 * 1024];
__device__ __align__(128) uint4 g_kvp[128 * 512];
__device__ __align__(128) uint4 g_kv[8 * 512];
__device__ __align__(128) uint32_t g_h[112 * 256];
__device__ __align__(128) uint32_t g_yp[128 * 512];
__device__ __align__(128) uint2 g_sel[8 * 16];
enum { H_CS = 0, H_KVP = 8, H_KV = 16, H_H = 24, H_Y = 32, H_O = 40, H_Z = 56 };
__device__ __align__(128) uint32_t g_sig[64 * 32];
__device__ uint32_t g_epoch;

constexpr uint32_t RING = 1024, SLOT = 32768, SMEM_BYTES = 232448;
constexpr int NST = 5, HST = 7;
constexpr uint32_t STG = RING + 163840, AUX = RING + 196608, FR = RING + 212992, MISC = RING + 229376;
constexpr uint32_t B_FULL = MISC, B_EMPTY = MISC + 56, B_XS = MISC + 112, B_SEL = MISC + 144, B_WK = MISC + 160, B_CSDN = MISC + 168,
                   B_FR = MISC + 176, B_FE = MISC + 200, B_DR = MISC + 224, B_CSV = MISC + 248,
                   B_DND = MISC + 256, B_XRES = MISC + 264, B_PFREE = MISC + 280, B_SFREE = MISC + 288, NBAR = 37;
constexpr uint32_t S_EPOCH = MISC + 352, S_NCAND = MISC + 356, S_SEL = MISC + 368, S_WMAX = MISC + 432,
                   S_KSTAT = MISC + 512, S_CSK = MISC + 1536, S_CSV = MISC + 2048, S_CSQ = MISC + 2560, S_ONES = MISC + 512;
constexpr uint32_t KVB_P0 = AUX, KVB_Z = AUX + 4096, KVB_P1 = AUX + 5120, HOP = AUX + 9216, FONES = AUX + 6144, GR = FR - 8192;
enum { NB_Z = 0, NB_KV = 1, NB_VQ = 2, NB_WG0 = 3, NB_FDONE = 4, NB_PK = 5, NB_KVB = 6, NB_WG1 = 7, NB_WG2 = 8, NB_CSQ = 9,
       NB_Y = 10, NB_ST = 11, NB_OWN0 = 12, NB_OWN1 = 13, NB_Q0 = 14, NB_H1 = 15 };

#define XS_FLY 2
#define FFN_GAP 400
#define RES_FIRST 1
#define KV_DIRECT 1
#define PF_GAP 200
#define PF_WAIT 1000
constexpr uint64_t EVICT_FIRST = 0x12f0000000000000ull;
constexpr float LOG2E = 1.4426950408889634f, LN2 = 0.6931471805599453f;

#define ELECT "{\n.reg .pred p;\nelect.sync _|p, 0xffffffff;\n"
#define TMA2D "cp.async.bulk.tensor.2d.shared::cluster.global.mbarrier::complete_tx::bytes"
#define TMA3D "cp.async.bulk.tensor.3d.shared::cluster.global.mbarrier::complete_tx::bytes"
__device__ __forceinline__ void e_expect(uint32_t b, uint32_t n) {
  asm volatile(ELECT "@p mbarrier.arrive.expect_tx.shared::cta.b64 _, [%0], %1;\n}" ::"r"(b), "r"(n) : "memory");
}
__device__ __forceinline__ void e_arrive(uint32_t b) { asm volatile(ELECT "@p mbarrier.arrive.shared::cta.b64 _, [%0];\n}" ::"r"(b) : "memory"); }
__device__ __forceinline__ void e_tma2d(uint32_t dst, const CUtensorMap* m, int c0, int c1, uint32_t bar) {
  asm volatile(ELECT "@p " TMA2D " [%0], [%1, {%3, %4}], [%2];\n}" ::"r"(dst), "l"(m), "r"(bar), "r"(c0), "r"(c1) : "memory");
}
__device__ __forceinline__ void e_tma2d_ef(uint32_t dst, const CUtensorMap* m, int c0, int c1, uint32_t bar, uint64_t pol) {
  asm volatile(ELECT "@p " TMA2D ".L2::cache_hint [%0], [%1, {%3, %4}], [%2], %5;\n}" ::"r"(dst), "l"(m), "r"(bar), "r"(c0), "r"(c1), "l"(pol) : "memory");
}
__device__ __forceinline__ void e_tma3d(uint32_t dst, const CUtensorMap* m, int c1, int c2, uint32_t bar) {
  asm volatile(ELECT "@p " TMA3D " [%0], [%1, {0, %3, %4}], [%2];\n}" ::"r"(dst), "l"(m), "r"(bar), "r"(c1), "r"(c2) : "memory");
}
__device__ __forceinline__ void e_store2d(const CUtensorMap* m, int c0, int c1, uint32_t src) {
  asm volatile(ELECT "@p cp.async.bulk.tensor.2d.global.shared::cta.bulk_group [%0, {%2, %3}], [%1];\n}" ::"l"(m), "r"(src), "r"(c0), "r"(c1) : "memory");
}
__device__ __forceinline__ void e_tma3d_ef(uint32_t dst, const CUtensorMap* m, int c0, int c1, uint32_t bar, uint64_t pol) {
  asm volatile(ELECT "@p " TMA3D ".L2::cache_hint [%0], [%1, {%3, %4, 0}], [%2], %5;\n}" ::"r"(dst), "l"(m), "r"(bar), "r"(c0), "r"(c1), "l"(pol) : "memory");
}
__device__ __forceinline__ void e_pfmap(const CUtensorMap* m) { asm volatile(ELECT "@p prefetch.tensormap [%0];\n}" ::"l"(m) : "memory"); }
__device__ __forceinline__ void bulk_wait_read() { asm volatile("cp.async.bulk.commit_group;\ncp.async.bulk.wait_group.read 0;" ::: "memory"); }
__device__ __forceinline__ void e_signal(int word, int bit) {
  asm volatile(ELECT "@p red.relaxed.gpu.global.xor.b32 [%0], %1;\n}" ::"l"(g_sig + word * 32), "r"(1u << bit) : "memory");
}
__device__ __forceinline__ void await(int word, uint32_t mask, uint32_t ep) {
  uint32_t f[1];
  poll1f(f, g_sig + word * 32, 0u - (ep & 1u), mask);
}

__device__ __forceinline__ void mbar_arrive(uint32_t b) { asm volatile("mbarrier.arrive.shared::cta.b64 _, [%0];" ::"r"(b) : "memory"); }
__device__ __forceinline__ void mbar_wait(uint32_t b, uint32_t ph) {
  asm volatile("{\n.reg .pred p, q;\n.reg .u32 c;\nmov.u32 c, 0;\nLW:\nmbarrier.try_wait.parity.shared::cta.b64 p, [%0], %1;\n@p bra LD;\n"
               "add.u32 c, c, 1;\nsetp.lt.u32 q, c, 100000;\n@q bra LW;\ntrap;\nLD:\n}" ::"r"(b), "r"(ph) : "memory");
}
__device__ __forceinline__ void nb_sync(int id, int n) { asm volatile("bar.sync %0, %1;" ::"r"(id), "r"(n) : "memory"); }
__device__ __forceinline__ void nb_arrive(int id, int n) { asm volatile("bar.arrive %0, %1;" ::"r"(id), "r"(n) : "memory"); }
__device__ __forceinline__ void wg_fence() { asm volatile("wgmma.fence.sync.aligned;" ::: "memory"); }
__device__ __forceinline__ void wg_commit() { asm volatile("wgmma.commit_group.sync.aligned;" ::: "memory"); }
template <int N> __device__ __forceinline__ void wg_wait() { asm volatile("wgmma.wait_group.sync.aligned %0;" ::"n"(N) : "memory"); }
template <int N> __device__ __forceinline__ void reg_fence(float (&a)[N]) {
#pragma unroll
  for (int i = 0; i < N; i++) asm volatile("" : "+f"(a[i])::"memory");
}
template <int N> __device__ __forceinline__ void reg_zero(float (&a)[N]) {
#pragma unroll
  for (int i = 0; i < N; i++) a[i] = 0.f;
}
__device__ __forceinline__ constexpr uint64_t mkdesc(uint32_t addr, uint32_t lbo, uint32_t sbo, uint32_t swz) {
  return (uint64_t)(addr >> 4) | ((uint64_t)(lbo >> 4) << 16) | ((uint64_t)(sbo >> 4) << 32) | ((uint64_t)swz << 62);
}
__device__ __forceinline__ void fence_async_smem() { asm volatile("fence.proxy.async.shared::cta;" ::: "memory"); }
__device__ __forceinline__ void st_relaxed(uint32_t* p, uint32_t v) { asm volatile("st.relaxed.gpu.global.u32 [%0], %1;" ::"l"(p), "r"(v) : "memory"); }
__device__ __forceinline__ uint32_t ld_relaxed(const uint32_t* p) { uint32_t v; asm volatile("ld.relaxed.gpu.global.u32 %0, [%1];" : "=r"(v) : "l"(p) : "memory"); return v; }
__device__ __forceinline__ void st_unit(uint4* p, uint32_t a, uint32_t b, uint32_t c, uint32_t d, uint32_t par) {
  asm volatile("{\n.reg .b64 x, y;\n.reg .b128 z;\nmov.b64 x, {%1,%2};\nmov.b64 y, {%3,%4};\nmov.b128 z, {x, y};\nst.relaxed.gpu.global.b128 [%0], z;\n}"
               ::"l"(p), "r"((a & ~1u) | par), "r"(b), "r"(c), "r"(d) : "memory");
}
__device__ __forceinline__ uint4 lds128(uint32_t a) { uint4 v; asm volatile("ld.shared.v4.u32 {%0,%1,%2,%3}, [%4];" : "=r"(v.x), "=r"(v.y), "=r"(v.z), "=r"(v.w) : "r"(a)); return v; }
__device__ __forceinline__ float4 lds128f(uint32_t a) { float4 v; asm volatile("ld.shared.v4.f32 {%0,%1,%2,%3}, [%4];" : "=f"(v.x), "=f"(v.y), "=f"(v.z), "=f"(v.w) : "r"(a)); return v; }
__device__ __forceinline__ float4 lds128v(uint32_t a) { float4 v; asm volatile("ld.volatile.shared.v4.f32 {%0,%1,%2,%3}, [%4];" : "=f"(v.x), "=f"(v.y), "=f"(v.z), "=f"(v.w) : "r"(a) : "memory"); return v; }
__device__ __forceinline__ float lds32v(uint32_t a) { float v; asm volatile("ld.volatile.shared.f32 %0, [%1];" : "=f"(v) : "r"(a) : "memory"); return v; }
__device__ __forceinline__ float2 lds64f(uint32_t a) { float2 v; asm volatile("ld.shared.v2.f32 {%0,%1}, [%2];" : "=f"(v.x), "=f"(v.y) : "r"(a)); return v; }
__device__ __forceinline__ uint32_t lds32(uint32_t a) { uint32_t v; asm volatile("ld.shared.u32 %0, [%1];" : "=r"(v) : "r"(a)); return v; }
__device__ __forceinline__ void sts128(uint32_t a, uint32_t x, uint32_t y, uint32_t z, uint32_t w) { asm volatile("st.shared.v4.u32 [%0], {%1,%2,%3,%4};" ::"r"(a), "r"(x), "r"(y), "r"(z), "r"(w) : "memory"); }
__device__ __forceinline__ void sts128f(uint32_t a, float x, float y, float z, float w) { asm volatile("st.shared.v4.f32 [%0], {%1,%2,%3,%4};" ::"r"(a), "f"(x), "f"(y), "f"(z), "f"(w) : "memory"); }
__device__ __forceinline__ void sts64(uint32_t a, uint32_t x, uint32_t y) { asm volatile("st.shared.v2.u32 [%0], {%1,%2};" ::"r"(a), "r"(x), "r"(y) : "memory"); }
__device__ __forceinline__ void sts32(uint32_t a, uint32_t x) { asm volatile("st.shared.u32 [%0], %1;" ::"r"(a), "r"(x) : "memory"); }
__device__ __forceinline__ void stsm4(uint32_t a, uint32_t r0, uint32_t r1, uint32_t r2, uint32_t r3) {
  asm volatile("stmatrix.sync.aligned.m8n8.x4.shared.b16 [%0], {%1,%2,%3,%4};" ::"r"(a), "r"(r0), "r"(r1), "r"(r2), "r"(r3) : "memory");
}
__device__ __forceinline__ uint4 ldsm4(uint32_t a) {
  uint4 v; asm volatile("ldmatrix.sync.aligned.m8n8.x4.shared.b16 {%0,%1,%2,%3}, [%4];" : "=r"(v.x), "=r"(v.y), "=r"(v.z), "=r"(v.w) : "r"(a) : "memory"); return v;
}
__device__ __forceinline__ uint32_t pack(float lo, float hi) { uint32_t r; asm("cvt.rn.bf16x2.f32 %0, %1, %2;" : "=r"(r) : "f"(hi), "f"(lo)); return r; }
__device__ __forceinline__ float bf_lo(uint32_t w) { return __uint_as_float(w << 16); }
__device__ __forceinline__ float bf_hi(uint32_t w) { return __uint_as_float(w & 0xffff0000u); }
__device__ __forceinline__ float bf_round(float x) { return bf_lo(pack(x, x)); }
__device__ __forceinline__ float ex2(float x) { float v; asm("ex2.approx.ftz.f32 %0, %1;" : "=f"(v) : "f"(x)); return v; }
__device__ __forceinline__ float rcp(float x) { float v; asm("rcp.approx.ftz.f32 %0, %1;" : "=f"(v) : "f"(x)); return v; }
__device__ __forceinline__ float addsat(float a, float b) { float v; asm("add.sat.f32 %0, %1, %2;" : "=f"(v) : "f"(a), "f"(b)); return v; }
__device__ __forceinline__ float phi2(float a) { return fmaf(fmaxf(a, 0.f), LN2, addsat(ex2(a), 1e-6f)); }
__device__ __forceinline__ float key_score(uint32_t key) { uint32_t u = key >> 16; u = (u & 0x8000u) ? (u & 0x7fffu) : (~u & 0xffffu); return __uint_as_float(u << 16); }
__device__ __forceinline__ int key_token(uint32_t key) { return 2047 - (int)((key >> 5) & 2047u); }
__device__ __forceinline__ uint32_t bsel(uint32_t a, uint32_t b, uint32_t m) { uint32_t r; asm("lop3.b32 %0, %1, %2, %3, 0xd8;" : "=r"(r) : "r"(a), "r"(b), "r"(m)); return r; }
__device__ __forceinline__ uint32_t prmt(uint32_t a, uint32_t b, uint32_t c) { uint32_t r; asm("prmt.b32 %0, %1, %2, %3;" : "=r"(r) : "r"(a), "r"(b), "r"(c)); return r; }
__device__ __forceinline__ uint32_t tagf(float v, uint32_t par) { return (__float_as_uint(v) & ~1u) | par; }
__device__ __forceinline__ float xred(float a, float b, bool up, int o) { return (up ? b : a) + __shfl_xor_sync(0xffffffffu, up ? a : b, o); }

#define STAMP(id)
#define STAMP_IF(c, id)
#define STAMP2(i)
#define LITE 1
#define LITE_MASK 0ull

template <bool TRANS>
__device__ __forceinline__ void mainloop(float (&a0)[64], float (&a1)[64], int s, int ph, int handoff, int xpair, bool leader) {
  uint32_t prev = 0;
#pragma unroll 1
  for (int kt = 0; kt < 16; kt++) {
    const bool xr = !TRANS && (kt >> 1) == xpair;
    mbar_wait(B_FULL + 8 * s, ph);
    const uint64_t dw = mkdesc(RING, 8192, 1024, 1) + s * (SLOT >> 4), dx = mkdesc(0, 16, 1024, 1) + (xr ? (STG >> 4) + (kt & 1) * 1024 : ((RING + 16384) >> 4) + s * (SLOT >> 4));
    if (xr) mbar_wait(B_XRES + 8 * (kt & 1), 0);
    wg_fence();
#pragma unroll
    for (int j = 0; j < 4; j++) {
      if (TRANS) {
        wgmma_n128_ss<1, 0>(a0, dw + j * 128, dx + j * 2, 1);
        wgmma_n128_ss<1, 0>(a1, dw + j * 128 + 512, dx + j * 2, 1);
      } else {
        wgmma_n128_ss<0, 1>(a0, dx + j * 2, dw + j * 128, 1);
        wgmma_n128_ss<0, 1>(a1, dx + j * 2 + 512, dw + j * 128, 1);
      }
    }
    wg_commit();
    if (handoff && kt == 15) nb_arrive(handoff, 256);
    wg_wait<1>();
    if (prev && leader) mbar_arrive(prev);
    prev = B_EMPTY + 8 * s;
    if (++s == NST) { s = 0; ph ^= 1; }
  }
  wg_wait<0>();
  if (leader) mbar_arrive(prev);
  reg_fence(a0);
  reg_fence(a1);
}

__device__ __forceinline__ int out_kblock(int r, int tn) {
  const int q = r - 2, half = q >= 7, pi = q - 7 * half;
  return r < 2 ? 2 * tn + r : 2 * (pi + (pi >= tn)) + half;
}

struct Params {
  const char *x, *wqkv, *w_r, *wg, *wu, *wd;
  CUtensorMap m_wqkv, m_x, m_xs, m_o, m_os, m_wo, m_gu, m_down, m_out;
};

template <bool BY_SMID>
__global__ void __launch_bounds__(512, 1) fused_kernel(const __grid_constant__ Params mp) {
  extern __shared__ __align__(1024) uint8_t smem_raw[];
#define CK(i)
  CK(0);
  const int tid = threadIdx.x, lane = tid & 31;
  const int w = __shfl_sync(0xffffffffu, tid >> 5, 0);
  int bid = blockIdx.x;
  if (BY_SMID) {
    uint32_t sm;
    asm volatile("mov.u32 %0, %%smid;" : "=r"(sm));
    const uint32_t p = sm >> 1, q = ((p - 32) * 37) >> 8;
    const uint32_t gpc = p < 32 ? p & 7 : p < 60 ? p - 31 - 7 * q : 0, tpc = p < 32 ? p >> 3 : p < 60 ? 4 + q : p - 58;
    bid = (p >> 1) == 30 ? 128 + ((0x9cu >> (2 * (sm & 3))) & 3) : ((0x75143620u >> (4 * gpc)) & 7) * 16 + tpc * 2 + (sm & 1);
  }
  const int tn = (bid & 3) + 4 * (bid >> 6), tm = (bid >> 2) & 15;

  CK(1);
  if (w == 0) {
#pragma unroll 1
    for (int s = 0; s < NST; s++) {
      asm volatile(ELECT "@p mbarrier.init.shared::cta.b64 [%0], 1;\n}" ::"r"(B_FULL + 8 * s) : "memory");
      if (bid < 128) {
        e_expect(B_FULL + 8 * s, 32768);
        e_tma2d(RING + s * SLOT + 16384, &mp.m_x, s * 64, tm * 128, B_FULL + 8 * s);
        e_tma3d(RING + s * SLOT, &mp.m_wqkv, s * 64, 16 + 2 * tn, B_FULL + 8 * s);
      }
      if (s == 0) CK(2);
    }
  }
  if (w == 1) e_pfmap(&mp.m_wqkv);
  if (w == 2) e_pfmap(&mp.m_xs);
  if (w >= 4) {
#pragma unroll 1
    for (uint32_t b = MISC + 8 * (w + 1); b < MISC + 8 * NBAR; b += 96)
      asm volatile(ELECT "@p mbarrier.init.shared::cta.b64 [%0], %1;\n}" ::"r"(b), "r"(b == B_CSDN ? 4 : 1) : "memory");
    if (w == 15) sts32(S_NCAND, 0);
  }
  CK(3);
  asm volatile("fence.mbarrier_init.release.cluster;" ::: "memory");
  __syncthreads();

  if (bid >= 128) {
    const int h0 = bid == 128 ? 14 : bid - 129, hs = bid == 128 ? 1 : 3, h1 = bid == 128 ? 16 : 14;
    if (w == 12) {
      int s = 0, ph = 1;
      if (bid == 128) mbar_wait(B_SEL, 0);
#pragma unroll 1
      for (int h = h0; h < h1; h += hs) {
        const int c = 2 * h + (h & 8) * 2;
#pragma unroll 1
        for (int kt = 0; kt < 16; kt += 2) {
          mbar_wait(B_EMPTY + 8 * s, ph);
          e_expect(B_FULL + 8 * s, 32768);
          e_tma3d(RING + s * SLOT, &mp.m_wqkv, kt * 64, c, B_FULL + 8 * s);
          e_tma3d(RING + s * SLOT + 16384, &mp.m_wqkv, kt * 64 + 64, c, B_FULL + 8 * s);
          if (++s == HST) { s = 0; ph ^= 1; }
        }
      }
    } else if (w < 4) {
      const uint32_t par = (ld_relaxed(&g_epoch) + 1) & 1u;
      sts32(S_ONES + tid * 4, 0x3f803f80u);
      fence_async_smem();
      nb_sync(NB_WG0, 128);
      int s = 0, ph = 0;
#pragma unroll 1
      for (int h = h0; h < h1; h += hs) {
        float c[4][4];
#pragma unroll
        for (int i = 0; i < 4; i++) reg_zero(c[i]);
        uint32_t prev = 0;
#pragma unroll 1
        for (int kt = 0; kt < 8; kt++) {
          mbar_wait(B_FULL + 8 * s, ph);
          const uint64_t dw = mkdesc(RING, 8192, 1024, 1) + s * (SLOT >> 4);
          wg_fence();
#pragma unroll
          for (int j = 0; j < 16; j++) wgmma_n8_ss<1, 0>(c[j & 3], dw + (j & 3) * 512 + (j >> 2) * 128, mkdesc(S_ONES, 128, 128, 0), 1);
          wg_commit();
          wg_wait<1>();
          if (prev && tid == 0) mbar_arrive(prev);
          prev = B_EMPTY + 8 * s;
          if (++s == HST) { s = 0; ph ^= 1; }
        }
        wg_wait<0>();
        if (tid == 0) mbar_arrive(prev);
#pragma unroll
        for (int i = 0; i < 4; i++) reg_fence(c[i]);
        const bool u2 = lane & 2, u1 = lane & 1;
        const float lo = u2 ? c[1][0] + c[3][0] : c[0][0] + c[2][0], hi = u2 ? c[1][2] + c[3][2] : c[0][2] + c[2][2];
        st_relaxed(g_csum + h * 128 + (lane & 2) * 32 + w * 16 + (lane & 1) * 8 + (lane >> 2), tagf(u1 ? hi : lo, par));
        STAMP_IF(tid == 0, h >= 8 ? 6 : 30);
      }
    } else if (w < 12 && bid == 128) {
      const int t = tid - 128, j = w - 4;
      const uint32_t ep = ld_relaxed(&g_epoch) + 1;
      uint32_t kk[16];
      poll_keys(kk, g_keys + t * 2, ep, 31u);
      STAMP_IF(t == 0, 42);
      const uint32_t m = __reduce_max_sync(0xffffffffu, max(max(max(kk[0], kk[2]), max(kk[4], kk[6])), max(max(kk[8], kk[10]), max(kk[12], kk[14]))));
      if (lane == 0) sts32(S_WMAX + j * 4, m);
      nb_sync(NB_WG1, 256);
      const uint32_t T = __reduce_min_sync(0xffffffffu, lds32(S_WMAX + (lane & 7) * 4));
      uint32_t cnt = 0;
#pragma unroll
      for (int i = 0; i < 8; i++) cnt += kk[2 * i] >= T;
      if (cnt) {
        uint32_t pos;
        asm volatile("atom.shared.add.u32 %0, [%1], %2;" : "=r"(pos) : "r"(S_NCAND), "r"(cnt * 8) : "memory");
#pragma unroll
        for (int i = 0; i < 8; i++)
          if (kk[2 * i] >= T) { sts64(AUX + pos, kk[2 * i], kk[2 * i + 1]); pos += 8; }
      }
      nb_sync(NB_WG1, 256);
      const uint32_t n8 = lds32(S_NCAND);
#pragma unroll 1
      for (uint32_t i = j * 8; i < n8; i += 64) {
        const float2 c = lds64f(AUX + i);
        uint32_t rank = 0;
#pragma unroll 1
        for (uint32_t q = lane * 8; q < n8 + lane * 8; q += 256) rank += __popc(__ballot_sync(0xffffffffu, q < n8 && lds32(AUX + q) > __float_as_uint(c.x)));
        if (rank < 8) sts64(S_SEL + rank * 8, __float_as_uint(c.x), __float_as_uint(c.y));
      }
      fence_async_smem();
      nb_sync(NB_WG1, 256);
      if (j == 0) {
        const uint4 v = lds128(S_SEL + (lane & 3) * 16);
        asm volatile("{\n.reg .b64 x, y;\nmov.b64 x, {%1,%2};\nmov.b64 y, {%3,%4};\nst.relaxed.gpu.global.v2.b64 [%0], {x, y};\n}"
                     ::"l"(g_sel + (lane >> 2) * 16 + (lane & 3) * 2), "r"(v.x), "r"(v.y), "r"(v.z), "r"(v.w) : "memory");
        e_arrive(B_SEL);
      }
      STAMP_IF(t == 0, 45);
    }
  } else if (w >= 12) {
    asm volatile("setmaxnreg.dec.sync.aligned.u32 32;");
    if (w == 12) {
      int s = 0, ph = 0;
#pragma unroll 1
      for (int it = NST; it < 48; it++) {
        const int c = (it < 32 ? (it & 16) + 16 : 0) + 2 * tn;
        const int k0 = ((it + (it >= 32 && tn < 4 ? 8 : 0)) & 15) * 64;
        const bool xr = (it >> 1) == 20 + (tn & 3);
        if (xr) { mbar_wait(B_SFREE, 0); e_expect(B_XRES + 8 * (it & 1), 16384); }
        mbar_wait(B_EMPTY + 8 * s, ph);
        e_expect(B_FULL + 8 * s, xr ? 16384 : 32768);
        e_tma3d(RING + s * SLOT, &mp.m_wqkv, k0, c, B_FULL + 8 * s);
        e_tma2d(xr ? STG + (it & 1) * 16384 : RING + s * SLOT + 16384, &mp.m_x, k0, tm * 128, xr ? B_XRES + 8 * (it & 1) : B_FULL + 8 * s);
        if (it >= NST) STAMP2(it - NST);
        if (++s == NST) { s = 0; ph ^= 1; }
      }
#pragma unroll 1
      for (int r = 0; r < 16; r++) {
        const int kb = out_kblock(r, tn);
        mbar_wait(B_EMPTY + 8 * s, ph);
        e_expect(B_FULL + 8 * s, r < 2 ? 16384 : 32768);
        e_tma3d(RING + s * SLOT, &mp.m_wo, kb * 64, 2 * tn, B_FULL + 8 * s);
        if (r < 2 || r == 4) {
          const uint32_t bar = B_DR + (r < 2 ? 16 : 8);
          const int k0 = (bid >> 4) * 448 + 128 + min(r, 2) * 128;
          if (r != 1) e_expect(bar, r ? 8192 : 32768);
          e_tma2d_ef(RING + s * SLOT + 16384, &mp.m_down, (bid & 15) * 64, k0, bar, EVICT_FIRST);
          if (r < 2) e_tma2d_ef(RING + s * SLOT + 24576, &mp.m_down, (bid & 15) * 64, k0 + 64, bar, EVICT_FIRST);
        }
        STAMP2(r + 48 - NST);
        if (++s == NST) { s = 0; ph ^= 1; }
      }
    } else if (w == 13) {
      mbar_wait(B_FULL, 0);
#pragma unroll 1
      for (int c = 0; c < 4; c++) {
        if (c >= XS_FLY) mbar_wait(B_XS + 8 * (c - XS_FLY), 0);
        if (c == (tm >> 2)) {
          e_expect(B_WK, 16384);
          e_tma3d(FR, &mp.m_wqkv, tm * 64, 16 + 2 * tn, B_WK);
        }
        e_expect(B_XS + 8 * c, 8192);
        e_tma2d(STG + c * 8192, &mp.m_xs, c * 256, tm * 128 + tn * 16, B_XS + 8 * c);
      }
      {
        const char* pd = mp.wd + (bid & 15) * 128 + ((bid >> 4) * 448 + lane) * 2048;
        mbar_wait(B_XS + 24, 0);
        __nanosleep(PF_WAIT);
#pragma unroll 1
        for (int i = 0; i < 14; i++, pd += 65536) {
          if (PF_GAP) asm volatile("prefetch.global.L2 [%0];" ::"l"(pd));
          if (PF_GAP) __nanosleep(PF_GAP);
        }
      }
      nb_sync(NB_Z, 160);
      const uint32_t ep = lds32(S_EPOCH);
      {
        float z[4] = {0.f, 0.f, 0.f, 0.f};
        e_signal(H_Z + tn, tm);
        await(H_Z + tn, 0xffffu, ep);
#pragma unroll 1
        for (int i = 0; i < 4; i++) {
          uint32_t p[16];
          poll_z(p, g_z + i * 4096 + tn * 128 + lane * 4, ep, 1u);
#pragma unroll
          for (int q = 0; q < 4; q++) z[q] += (__uint_as_float(p[q]) + __uint_as_float(p[4 + q])) + (__uint_as_float(p[8 + q]) + __uint_as_float(p[12 + q]));
        }
        const uint32_t z01 = pack(z[0], z[1]), z23 = pack(z[2], z[3]);
        if (bid < 112) mbar_wait(B_PFREE, 0);
#pragma unroll
        for (int i = 0; i < 4; i++) {
          const int n = 2 * i + (lane >> 4);
          asm volatile("st.shared.v2.u32 [%0], {%1,%2};" ::"r"(KVB_Z + n * 128 + ((((lane >> 1) & 7) ^ n) << 4) + (lane & 1) * 8), "r"(z01), "r"(z23) : "memory");
        }
        fence_async_smem();
        nb_arrive(NB_KVB, 288);
        STAMP_IF(lane == 0, 46);
      }
      nb_sync(NB_Q0, 192);
      e_store2d(&mp.m_os, tn * 128, tm * 128, STG);
      nb_sync(NB_OWN0, 288);
      e_store2d(&mp.m_os, tn * 128, tm * 128 + 64, STG + 8192);
      bulk_wait_read();
      e_signal(H_O + tm, 2 * tn);
      STAMP_IF(lane == 0, 4);
      nb_sync(NB_H1, 160);
      e_store2d(&mp.m_os, tn * 128 + 64, tm * 128, STG + 16384);
      e_store2d(&mp.m_os, tn * 128 + 64, tm * 128 + 64, STG + 24576);
      bulk_wait_read();
      e_signal(H_O + tm, 2 * tn + 1);
      STAMP_IF(lane == 0, 5);
      nb_arrive(NB_ST, 160);
    } else if (w == 14) {
      e_pfmap(&mp.m_gu); e_pfmap(&mp.m_o); e_pfmap(&mp.m_os); e_pfmap(&mp.m_wo); e_pfmap(&mp.m_down); e_pfmap(&mp.m_out);
      const uint32_t ep = ld_relaxed(&g_epoch) + 1;
      nb_sync(NB_FDONE, 416);
      {
        uint32_t c[4];
        poll_quad(c, g_csum + tn * 128 + lane * 4, ep, 1u);
        sts128(S_CSQ + lane * 16, c[0], c[1], c[2], c[3]);
        nb_arrive(NB_CSQ, 160);
        poll_quad(c, g_csum + 1024 + tn * 128 + lane * 4, ep, 1u);
        sts128(S_CSV + lane * 16, c[0], c[1], c[2], c[3]);
        __syncwarp();
        e_arrive(B_CSV);
      }
      nb_sync(NB_Q0, 192);
      uint32_t ready = 0;
      int s = 0, ph = 1;
#pragma unroll 1
      for (int r = 2; r < 16; r++) {
        const int kb = out_kblock(r, tn);
        if (!((ready >> kb) & 1)) {
          uint32_t f[1];
          poll0(f, g_sig + (H_O + tm) * 32, 0u - (ep & 1u), 1u << kb);
          ready = f[0] ^ ((ep & 1u) - 1u);
        }
        if (r == 4) mbar_wait(B_DND, 0);
        mbar_wait(B_EMPTY + 8 * s, ph);
        e_tma2d(RING + s * SLOT + 16384, &mp.m_o, kb * 64, tm * 128, B_FULL + 8 * s);
        STAMP_IF(lane == 0 && r == 2, 2);
        STAMP_IF(lane == 0 && r == 9, 3);
        if (++s == NST) { s = 0; ph ^= 1; }
      }
    } else {
      uint32_t nsm = 132;
      if (BY_SMID) asm volatile("mov.u32 %0, %%nsmid;" : "=r"(nsm));
      asm volatile("{\n.reg .pred q;\nsetp.eq.u32 q, %0, 1156;\n@q bra LOK;\ntrap;\nLOK:\n}" ::"r"((uint32_t)__cvta_generic_to_shared(smem_raw) + nsm));
      const uint32_t ep = ld_relaxed(&g_epoch) + 1;
      mbar_wait(B_CSDN, 0);
#pragma unroll 1
      for (int n = 0; n < 3 && bid < 112; n++) {
        __nanosleep(FFN_GAP);
        e_expect(B_FR + 8 * n, 8192);
        e_tma3d_ef(GR + n * 8192, &mp.m_gu, bid * 32, n * 64, B_FR + 8 * n, EVICT_FIRST);
      }
      uint32_t sel[2];
      poll_pair(sel, g_sel + (bid >> 4) * 16 + (lane >> 2), ep, 31u);
      const char* xs = mp.x + key_token(sel[0]) * 2048 + (lane & 3) * 16;
      const uint32_t xd = AUX + (lane >> 2) * 64 + (((lane & 3) ^ (lane >> 3)) << 4);
      auto slices = [&](int n, int p) {
        asm volatile("cp.async.cg.shared.global [%0], [%1], 16;\ncp.async.cg.shared.global [%0+512], [%1+64], 16;\ncp.async.commit_group;"
                     ::"r"(xd + p * 1024), "l"(xs + n * 128) : "memory");
      };
      if ((lane & 3) == 0) sts64(S_SEL + lane * 2, sel[0], sel[1]);
      if (bid < 112) {
#pragma unroll
        for (int i = 0; i < 6; i++) slices(i, i);
      }
      asm volatile("cp.async.wait_group 2;" ::: "memory");
      fence_async_smem();
      __syncwarp();
      e_arrive(B_SEL);
      if (bid < 112) {
        int s = 0, ph = 0;
#pragma unroll 1
        for (int n = 3; n < 16; n++) {
          mbar_wait(B_FE + 8 * s, ph);
          e_expect(B_FR + 8 * s, 8192);
          e_tma3d_ef(GR + s * 8192, &mp.m_gu, bid * 32, n * 64, B_FR + 8 * s, EVICT_FIRST);
          STAMP2(64 + n);
          asm volatile("cp.async.wait_group 1;" ::: "memory");
          fence_async_smem();
          __syncwarp();
          if (n < 13) slices(n + 3, s + 3 * ph);
          else asm volatile("cp.async.commit_group;" ::: "memory");
          if (++s == 3) { s = 0; ph ^= 1; }
        }
      }
      e_expect(B_DR, 16384);
      if (bid < 112) mbar_wait(B_FE + 8, 0);
      e_tma2d_ef(FR, &mp.m_down, (bid & 15) * 64, (bid >> 4) * 448, B_DR, EVICT_FIRST);
      if (bid < 112) mbar_wait(B_FE + 16, 0);
      e_tma2d_ef(FR + 8192, &mp.m_down, (bid & 15) * 64, (bid >> 4) * 448 + 64, B_DR, EVICT_FIRST);
    }
  } else if (w >= 8) {
    asm volatile("setmaxnreg.dec.sync.aligned.u32 56;");
    const int t = tid - 256, ww = w - 8;
    const uint32_t ep = ld_relaxed(&g_epoch) + 1, par = ep & 1u;
    sts32(FONES + t * 4, 0x3f803f80u);
    {
      const int r0 = (lane >> 3) + (lane & 4);
      const uint32_t a = FR + (ww >> 1) * 8192 + r0 * 128 + ((((ww & 1) * 4 + (lane & 3)) ^ r0) << 4);
      float c[8];
      reg_zero(c);
      mbar_wait(B_WK, 0);
#pragma unroll 2
      for (int i = 0; i < 8; i++) {
        const uint4 v = lds128(a + i * 1024);
        c[0] += bf_lo(v.x); c[1] += bf_hi(v.x); c[2] += bf_lo(v.y); c[3] += bf_hi(v.y);
        c[4] += bf_lo(v.z); c[5] += bf_hi(v.z); c[6] += bf_lo(v.w); c[7] += bf_hi(v.w);
      }
      const bool u16 = lane & 16, u8 = lane & 8, u4 = lane & 4;
      const float d0 = xred(c[0], c[4], u16, 16), d1 = xred(c[1], c[5], u16, 16), d2 = xred(c[2], c[6], u16, 16), d3 = xred(c[3], c[7], u16, 16);
      fence_async_smem();
      e_arrive(B_CSDN);
      const float sum = xred(xred(d0, d2, u8, 8), xred(d1, d3, u8, 8), u4, 4);
      st_relaxed(g_csum + (2 + tm) * 1024 + tn * 128 + ww * 32 + (lane & 3) * 8 + (lane >> 2), tagf(sum, par));
      STAMP_IF(t == 0, 8);
      nb_sync(NB_WG2, 128);
      if (ww == 0) { e_signal(H_CS + tn, tm); await(H_CS + tn, 0xffffu, ep); }
      nb_sync(NB_WG2, 128);
      uint32_t p[16];
      poll16(p, g_csum + 2048 + tn * 128 + t, par, 1u);
      float tot = 0.f;
#pragma unroll
      for (int i = 0; i < 16; i += 4) tot += (__uint_as_float(p[i]) + __uint_as_float(p[i + 1])) + (__uint_as_float(p[i + 2]) + __uint_as_float(p[i + 3]));
      sts32(S_CSK + t * 4, __float_as_uint(tot));
      nb_arrive(NB_FDONE, 416);
      STAMP_IF(t == 0, 9);
    }
    const int ks = bid >> 4, nt = bid & 15;
    if (bid < 112) {
      float fg[8];
      reg_zero(fg);
      mbar_wait(B_SEL, 0);
      constexpr uint64_t DA0 = mkdesc(GR, 4096, 512, 2), DB0 = mkdesc(AUX, 16, FONES - AUX, 2), DBS = 32 - (32ull << 32);
      uint64_t da = DA0, db = DB0;
      uint32_t bar = B_FR, ph = 0;
#pragma unroll 1
      for (int n = 0; n < 16; n++) {
        mbar_wait(bar, ph);
        wg_fence();
#pragma unroll
        for (int q = 0; q < 4; q++) wgmma_n16_ss<1, 0>(fg, da + q * 64, db + (q >> 1) * DBS + (q & 1) * 2, 1);
        wg_commit();
        const uint32_t rel = bar + (B_FE - B_FR);
        const bool wrap = bar == B_FR + 16;
        da = wrap ? DA0 : da + 512;
        db = wrap && ph ? DB0 : db + 2 * DBS;
        bar = wrap ? B_FR : bar + 8;
        ph ^= wrap;
        wg_wait<0>();
        if (t == 0) mbar_arrive(rel);
      }
      if (t == 0) mbar_arrive(B_PFREE);
      const uint4 st = lds128(S_SEL + (lane & 3) * 16);
      const float r0 = rcp(bf_lo(st.y)), r1 = rcp(bf_lo(st.w));
      reg_fence(fg);
      const float fa[4] = {fmaf(-bf_hi(st.y), fg[4], fg[0]) * r0, fmaf(-bf_hi(st.w), fg[4], fg[1]) * r1,
                           fmaf(-bf_hi(st.y), fg[6], fg[2]) * r0, fmaf(-bf_hi(st.w), fg[6], fg[3]) * r1};
      STAMP_IF(t == 0, 12);
      const bool isup = (ww >> 1) != (mp.wu < mp.wg);
      nb_sync(NB_WG2, 128);
      if (isup) sts128f(HOP + (t & 63) * 16, fa[0], fa[1], fa[2], fa[3]);
      nb_sync(NB_WG2, 128);
      if (!isup) {
        const float4 u = lds128f(HOP + (t & 63) * 16);
        const float uu[4] = {u.x, u.y, u.z, u.w};
        uint32_t* hp = g_h + bid * 256 + (lane & 3) * 64 + (ww & 1) * 16 + (lane >> 2);
#pragma unroll
        for (int i = 0; i < 4; i++) {
          const float g = fa[i], hv = g * rcp(1.f + ex2(-g * LOG2E)) * uu[i];
          st_relaxed(hp + (i & 1) * 32 + (i >> 1) * 8, __byte_perm(pack(hv, hv), ep, 0x3254));
        }
      }
      nb_sync(NB_WG2, 128);
      if (ww == 0) e_signal(H_H + bid / 14, bid % 14);
    }
    {
      uint32_t v[28];
      if (ww == 0) await(H_H + ks, 0x3fffu, ep);
      nb_sync(NB_WG2, 128);
      poll7x4(v, g_h + ks * 3584 + t * 4, ep, 0xffffu);
#pragma unroll
      for (int q = 0; q < 7; q++)
        asm volatile("st.shared.v2.u32 [%0], {%1,%2};" ::"r"(HOP + q * 1024 + (t >> 3) * 64 + ((((t >> 1) & 3) ^ ((t >> 4) & 3)) << 4) + (t & 1) * 8),
                     "r"(__byte_perm(v[4 * q], v[4 * q + 1], 0x7632)), "r"(__byte_perm(v[4 * q + 2], v[4 * q + 3], 0x7632)) : "memory");
      fence_async_smem();
      nb_sync(NB_WG2, 128);
    }
    STAMP_IF(t == 0, 13);
    float fa[4] = {0.f, 0.f, 0.f, 0.f};
    auto down = [&](uint32_t a, int k0, int nk) {
#pragma unroll
      for (int q = 0; q < nk; q++) wgmma_n8_ss<1, 0>(fa, mkdesc(a + q * 2048, 4096, 1024, 1), mkdesc(HOP + ((k0 + q) >> 1) * 512 + (q & 1) * 32, 16, 512, 2), 1);
    };
    mbar_wait(B_DR, 0);
    mbar_wait(B_DR + 16, 0);
    mbar_wait(B_DR + 8, 0);
    wg_fence();
    down(RING + 2 * SLOT + 16384, 24, 4);
    down(RING + 3 * SLOT + 16384, 8, 8);
    down(RING + 4 * SLOT + 16384, 16, 8);
    wg_commit();
    wg_fence();
    down(FR, 0, 8);
    wg_commit();
    wg_wait<1>();
    if (t == 0) mbar_arrive(B_DND);
    wg_wait<0>();
    reg_fence(fa);
    STAMP_IF(t == 0, 14);
    {
      uint32_t* yp = g_yp + (nt * 8 + ks) * 512 + (lane & 3) * 128 + ww * 16 + (lane >> 2);
#pragma unroll
      for (int i = 0; i < 4; i++) st_relaxed(yp + (i & 1) * 64 + (i >> 1) * 8, tagf(fa[i], par));
    }
    nb_sync(NB_WG2, 128);
    if (ww == 0) e_signal(H_Y + (nt >> 1), (nt & 1) * 8 + ks);
    mbar_wait(B_SEL, 0);
    const uint32_t mykey = lds32(S_SEL + (lane & 7) * 8);
    const uint32_t inmask = __ballot_sync(0xffffffffu, (key_token(mykey) >> 7) == tm) & 0xffu;
    if (inmask) {
      sts128(FR + t * 16, 0u, 0u, 0u, 0u);
      if (ww == 0) await(H_Y + tn, 0xffffu, ep);
      nb_sync(NB_WG2, 128);
      const float sg = rcp(1.f + ex2(-key_score(mykey) * LOG2E));
#pragma unroll 1
      for (uint32_t mine = __ballot_sync(0xffffffffu, ((inmask >> lane) & 1) && (__popc(inmask & ((1u << lane) - 1)) & 3) == ww); mine; mine &= mine - 1) {
        const int j = __ffs(mine) - 1;
        uint32_t p[32];
        poll8x4(p, g_yp + (tn * 2 + (lane >> 4)) * 4096 + j * 64 + (lane & 15) * 4, par, 1u);
        float y[4];
        const float sj = __shfl_sync(0xffffffffu, sg, j);
#pragma unroll
        for (int i = 0; i < 4; i++)
          y[i] = sj * (((__uint_as_float(p[i]) + __uint_as_float(p[4 + i])) + (__uint_as_float(p[8 + i]) + __uint_as_float(p[12 + i]))) +
                       ((__uint_as_float(p[16 + i]) + __uint_as_float(p[20 + i])) + (__uint_as_float(p[24 + i]) + __uint_as_float(p[28 + i]))));
        asm volatile("st.shared.v2.u32 [%0], {%1,%2};" ::"r"(FR + (lane >> 4) * 1024 + j * 128 + ((((lane >> 1) & 7) ^ j) << 4) + (lane & 1) * 8),
                     "r"(pack(y[0], y[1])), "r"(pack(y[2], y[3])) : "memory");
      }
      fence_async_smem();
      nb_arrive(NB_Y, 256);
    }
    STAMP_IF(t == 0, 15);
  } else if (w >= 4) {
    asm volatile("setmaxnreg.inc.sync.aligned.u32 208;");
    const int t = tid - 128, ww = w - 4, g = lane >> 2, t4 = lane & 3;
    const bool leader = t == 0;
    const uint32_t ep = ld_relaxed(&g_epoch) + 1, par = ep & 1u;
    {
      const uint4* wp = reinterpret_cast<const uint4*>(mp.w_r) + lane;
      uint4 w0 = __ldg(wp), w1 = __ldg(wp + 32), w2 = __ldg(wp + 64), w3 = __ldg(wp + 96);
      if (leader) sts32(S_EPOCH, ep);
      if (KV_DIRECT && lane < 8) st_unit(g_kv + tn * 512 + tm * 32 + ww * 8 + lane, 0u, 0u, 0u, 0u, par ^ 1u);
      float s[4] = {0.f, 0.f, 0.f, 0.f}, q[4] = {0.f, 0.f, 0.f, 0.f}, d[4] = {0.f, 0.f, 0.f, 0.f}, wsum = 0.f;
#pragma unroll 1
      for (int c = 0; c < 4; c++) {
        const float wr[8] = {bf_lo(w0.x), bf_hi(w0.x), bf_lo(w0.y), bf_hi(w0.y), bf_lo(w0.z), bf_hi(w0.z), bf_lo(w0.w), bf_hi(w0.w)};
        w0 = w1; w1 = w2; w2 = w3;
        wsum += ((wr[0] + wr[1]) + (wr[2] + wr[3])) + ((wr[4] + wr[5]) + (wr[6] + wr[7]));
        mbar_wait(B_XS + 8 * c, 0);
#pragma unroll
        for (int r = 0; r < 4; r++) {
          const uint4 v = lds128(STG + c * 8192 + (ww * 4 + r) * 512 + lane * 16);
          const uint32_t xw[4] = {v.x, v.y, v.z, v.w};
#pragma unroll
          for (int i = 0; i < 4; i++) {
            const uint32_t dep = __float_as_uint(q[i ? r : (r + 3) & 3]);
            const float lo = __uint_as_float(prmt(xw[i], dep, 0x10ff)), hi = __uint_as_float(prmt(xw[i], dep, 0x32ff));
            s[r] += lo; q[r] = fmaf(lo, lo, q[r]); d[r] = fmaf(lo, wr[2 * i], d[r]);
            s[r] += hi; q[r] = fmaf(hi, hi, q[r]); d[r] = fmaf(hi, wr[2 * i + 1], d[r]);
          }
        }
      }
      STAMP_IF(leader, 16);
      const bool u16 = lane & 16, u8 = lane & 8, u4 = lane & 4, u2 = lane & 2;
      const float s1 = xred(xred(s[0], s[2], u16, 16), xred(s[1], s[3], u16, 16), u8, 8);
      const float q1 = xred(xred(q[0], q[2], u16, 16), xred(q[1], q[3], u16, 16), u8, 8);
      const float d1 = xred(xred(d[0], d[2], u16, 16), xred(d[1], d[3], u16, 16), u8, 8);
      wsum += __shfl_xor_sync(0xffffffffu, wsum, 16);
      wsum += __shfl_xor_sync(0xffffffffu, wsum, 8);
      float tot = xred(xred(s1, d1, u4, 4), xred(q1, wsum, u4, 4), u2, 2);
      tot += __shfl_xor_sync(0xffffffffu, tot, 1);
      const float qq = __shfl_down_sync(0xffffffffu, tot, 2), dd = __shfl_down_sync(0xffffffffu, tot, 4), ws = __shfl_down_sync(0xffffffffu, tot, 6);
      if ((lane & 7) == 0) {
        const float mean = tot * (1.f / 1024.f);
        const float var = fmaxf(fmaf(-mean, mean, qq * (1.f / 1024.f)), 0.f);
        float sd;
        asm("sqrt.approx.ftz.f32 %0, %1;" : "=f"(sd) : "f"(bf_round(bf_round(var) + 1e-5f)));
        const uint32_t ms = pack(sd, mean);
        const int row = tm * 128 + tn * 16 + ww * 4 + (lane >> 3);
        const uint32_t rbits = pack(0.f, fmaf(-bf_hi(ms), ws, dd) * rcp(bf_lo(ms)));
        const uint32_t key = (rbits ^ (((int)rbits >> 31 & 0x7fff0000u) | 0x80000000u)) | ((2047 - row) << 5) | (ep & 31u);
        asm volatile("{\n.reg .b64 x;\nmov.b64 x, {%1,%2};\nst.relaxed.gpu.global.b64 [%0], x;\n}" ::"l"(g_keys + row), "r"(key), "r"(ms) : "memory");
      }
      STAMP_IF(leader, 17);
      __nanosleep(400);
      uint32_t st[2];
      poll_pair(st, g_keys + tm * 128 + t, ep, 31u);
      asm volatile("st.shared.v2.f32 [%0], {%1,%2};" ::"r"(S_KSTAT + t * 8), "f"(bf_hi(st[1])), "f"(rcp(bf_lo(st[1])) * LOG2E) : "memory");
      nb_arrive(NB_FDONE, 416);
      STAMP_IF(leader, 10);
    }
    float a0[64], a1[64];
    reg_zero(a0); reg_zero(a1); reg_fence(a0); reg_fence(a1);
    STAMP_IF(leader, 18);
    nb_sync(NB_KV, 256);
    mainloop<true>(a0, a1, 1, 1, NB_VQ, 0, leader);
    STAMP_IF(leader, 19);
    {
      uint32_t f0[32], f1[32];
#pragma unroll
      for (int i = 0; i < 32; i++) { f0[i] = pack(a0[2 * i], a0[2 * i + 1]); f1[i] = pack(a1[2 * i], a1[2 * i + 1]); }
      float c0[32], c1[32];
      reg_zero(c0); reg_zero(c1);
      nb_sync(NB_PK, 256);
      constexpr uint64_t db = mkdesc(STG, 16, 1024, 1);
      wg_fence();
#pragma unroll
      for (int k = 0; k < 8; k++) {
        wgmma_n64_rs<0>(c0, f0[4 * k], f0[4 * k + 1], f0[4 * k + 2], f0[4 * k + 3], db + (k >> 2) * 1024 + (k & 3) * 2, k != 0);
        wgmma_n64_rs<0>(c1, f1[4 * k], f1[4 * k + 1], f1[4 * k + 2], f1[4 * k + 3], db + (k >> 2) * 1024 + (k & 3) * 2 + 512, k != 0);
      }
      wg_commit();
      const bool hp = ww >> 1;
      float c[4];
      float2 tt[8];
#pragma unroll
      for (int i = 0; i < 8; i++) tt[i] = lds64f(S_CSK + ((i >> 2) * 64 + hp * 32 + (i & 3) * 8 + 2 * t4) * 4);
      mbar_wait(B_CSV, 0);
#pragma unroll
      for (int i = 0; i < 4; i++) c[i] = -__uint_as_float(lds32(S_CSV + ((i >> 1) * 64 + ww * 16 + (i & 1) * 8 + g) * 4));
      wg_wait<0>();
      reg_fence(c0);
      reg_fence(c1);
      if (leader) mbar_arrive(B_SFREE);
      STAMP_IF(leader, 20);
      uint4* pp = g_kvp + (tn * 16 + tm) * 512 + t;
      auto put = [&](int q, const float* d) {
        const float ca = c[q & 2], cb = c[q | 1];
        const float2 ta = tt[2 * q], tb = tt[2 * q + 1];
        st_unit(pp + q * 128, pack(fmaf(ca, ta.x, d[0]), fmaf(ca, ta.y, d[1])), pack(fmaf(cb, ta.x, d[2]), fmaf(cb, ta.y, d[3])),
                pack(fmaf(ca, tb.x, d[4]), fmaf(ca, tb.y, d[5])), pack(fmaf(cb, tb.x, d[6]), fmaf(cb, tb.y, d[7])), par);
      };
      if (!hp) { put(0, c0); put(1, c0 + 8); put(2, c1); put(3, c1 + 8); }
      else { put(0, c0 + 16); put(1, c0 + 24); put(2, c1 + 16); put(3, c1 + 24); }
      STAMP_IF(leader, 47);
      {
        uint32_t p[16];
        nb_sync(NB_WG1, 128);
        if (ww == 0) { e_signal(H_KVP + tn, tm); await(H_KVP + tn, 0xffffu, ep); }
        nb_sync(NB_WG1, 128);
        STAMP_IF(leader, 1);
        poll_kvp(p, g_kvp + (tn * 16 + (lane >> 3) * 4) * 512 + tm * 32 + ww * 8 + (lane & 7), par, 1u);
        float r[8];
#pragma unroll
        for (int i = 0; i < 4; i++) {
          r[2 * i] = (bf_lo(p[i]) + bf_lo(p[4 + i])) + (bf_lo(p[8 + i]) + bf_lo(p[12 + i]));
          r[2 * i + 1] = (bf_hi(p[i]) + bf_hi(p[4 + i])) + (bf_hi(p[8 + i]) + bf_hi(p[12 + i]));
        }
#pragma unroll
        for (int i = 0; i < 8; i++) r[i] += __shfl_xor_sync(0xffffffffu, r[i], 8);
#pragma unroll
        for (int i = 0; i < 8; i++) r[i] += __shfl_xor_sync(0xffffffffu, r[i], 16);
        if (lane < 8) st_unit(g_kv + tn * 512 + tm * 32 + ww * 8 + lane, pack(r[0], r[1]), pack(r[2], r[3]), pack(r[4], r[5]), pack(r[6], r[7]), par);
      }
      STAMP_IF(leader, 21);
    }
    const uint32_t sx = lane & 7, sc = lane >> 4;
    const uint32_t sa = STG + (ww * 16 + (lane & 15)) * 128;
    const uint32_t sw[4] = {sa + ((sc ^ sx) << 4), sa + (((2 + sc) ^ sx) << 4), sa + (((4 + sc) ^ sx) << 4), sa + (((6 + sc) ^ sx) << 4)};
    auto residual = [&]() {
      float ka[4], kb[4];
#pragma unroll
      for (int i = 0; i < 4; i++) {
        const float2 st = lds64f(S_KSTAT + ((i >> 1) * 64 + ww * 16 + (i & 1) * 8 + g) * 8);
        const float r = st.y * LN2;
        ka[i] = 1.f + r; kb[i] = -st.x * r;
      }
#pragma unroll
      for (int j = 0; j < 8; j++) {
        if ((j & 3) == 0) mbar_wait(B_XRES + 8 * (j >> 2), 0);
        const uint4 v = ldsm4(sw[j & 3] + (j >> 2) * 16384), u = ldsm4(sw[j & 3] + (j >> 2) * 16384 + 8192);
        const uint32_t vv[4] = {v.x, v.y, v.z, v.w}, uu[4] = {u.x, u.y, u.z, u.w};
#pragma unroll
        for (int i = 0; i < 4; i++) {
          a0[8 * j + 2 * i] = fmaf(bf_lo(vv[i]), ka[i & 1], kb[i & 1]);
          a0[8 * j + 2 * i + 1] = fmaf(bf_hi(vv[i]), ka[i & 1], kb[i & 1]);
          a1[8 * j + 2 * i] = fmaf(bf_lo(uu[i]), ka[2 + (i & 1)], kb[2 + (i & 1)]);
          a1[8 * j + 2 * i + 1] = fmaf(bf_hi(uu[i]), ka[2 + (i & 1)], kb[2 + (i & 1)]);
        }
      }
      reg_fence(a0);
      reg_fence(a1);
      STAMP_IF(leader, 22);
    };
    if (RES_FIRST) residual();
    {
      uint32_t v[16];
      if (!KV_DIRECT) {
        nb_sync(NB_WG1, 128);
        if (ww == 0) { e_signal(H_KV + tn, tm); await(H_KV + tn, 0xffffu, ep); }
        nb_sync(NB_WG1, 128);
      } else {
        __nanosleep(KV_DIRECT);
      }
      STAMP_IF(leader, 7);
      poll_kv(v, g_kv + tn * 512 + t, par, 1u);
      if (bid < 112) mbar_wait(B_PFREE, 0);
      STAMP_IF(leader, 23);
#pragma unroll
      for (int q = 0; q < 4; q++)
        stsm4((q < 2 ? KVB_P0 : KVB_P1) + ((ww & 1) * 16 + (lane & 15)) * 128 + ((((ww >> 1) * 4 + (q & 1) * 2 + sc) ^ sx) << 4),
              v[4 * q], v[4 * q + 1], v[4 * q + 2], v[4 * q + 3]);
      fence_async_smem();
      nb_arrive(NB_KVB, 288);
    }
    STAMP_IF(leader, 24);
    if (!RES_FIRST) { residual(); nb_arrive(NB_KV, 256); }
    uint32_t oh[4];
    uint32_t inmask;
    {
      mbar_wait(B_SEL, 0);
      const int r0 = key_token(lds32(S_SEL + t4 * 16)) - tm * 128, r1 = key_token(lds32(S_SEL + t4 * 16 + 8)) - tm * 128;
#pragma unroll
      for (int i = 0; i < 4; i++) {
        const int row = (i >> 1) * 64 + ww * 16 + (i & 1) * 8 + g;
        oh[i] = (r0 == row ? 0x3f00u : 0u) | (r1 == row ? 0x3f000000u : 0u);
      }
      inmask = __ballot_sync(0xffffffffu, (unsigned)r0 < 128u || (unsigned)r1 < 128u);
    }
    uint32_t va = RING + 16384 + sc * 8192 + (ww * 16 + (lane & 8)) * 128 + sx * 16 + (lane >> 3) * 4;
    asm volatile("" : "+r"(va));
    {
      auto own = [&](int r) {
        nb_sync(NB_OWN0 + r, r ? 256 : 288);
        mbar_wait(B_FULL + 8 * (3 + r), 1);
        STAMP_IF(leader, 25 + r);
        const uint64_t dw = mkdesc(RING + (3 + r) * SLOT, 8192, 1024, 1), dx = mkdesc(STG + r * 16384, 16, 1024, 1);
        wg_fence();
#pragma unroll
        for (int j = 0; j < 4; j++) {
          wgmma_n128_ss<0, 1>(a0, dx + j * 2, dw + j * 128, 1);
          wgmma_n128_ss<0, 1>(a1, dx + j * 2 + 512, dw + j * 128, 1);
        }
        wg_commit();
      };
      own(0);
      wg_wait<0>();
      if (leader) mbar_arrive(B_EMPTY + 24);
      own(1);
      auto check = [&](int r, int s) {
          uint32_t bad;
          asm volatile("{\n.reg .u32 a, b, c, d, e, f, g, h;\n.reg .pred p;\n"
                       "ld.shared.u32 a, [%1];\nld.shared.u32 b, [%1+128];\nld.shared.u32 c, [%1+256];\nld.shared.u32 d, [%1+384];\n"
                       "ld.shared.u32 e, [%1+512];\nld.shared.u32 f, [%1+640];\nld.shared.u32 g, [%1+768];\nld.shared.u32 h, [%1+896];\n"
                       "lop3.b32 a, a, b, %2, 0x7e;\nlop3.b32 c, c, d, %2, 0x7e;\nlop3.b32 e, e, f, %2, 0x7e;\nlop3.b32 g, g, h, %2, 0x7e;\n"
                       "lop3.b32 a, a, c, e, 0xfe;\nlop3.b32 a, a, g, 1, 0xa8;\nsetp.ne.u32 p, a, 0;\nvote.sync.any.pred p, p, 0xffffffff;\nselp.u32 %0, 1, 0, p;\n}"
                       : "=r"(bad) : "r"(va + s * SLOT), "r"(par) : "memory");
          if (bad) {
            const uint4* src = reinterpret_cast<const uint4*>(g_o + (tm * 128 + sc * 64 + ww * 16 + (lane & 15)) * 1024 + out_kblock(r, tn) * 64);
#pragma unroll 1
            for (int i = 0; i < 8; i++) {
              uint32_t v[4];
              asm volatile("{\n.reg .b64 x, y;\n.reg .b128 z;\n.reg .pred p, q, h;\n.reg .u32 c, b;\nmov.u32 c, 0;\nsetp.ne.u32 h, %6, 0;\nLW:\n"
                           "ld.relaxed.gpu.global.b128 z, [%4];\nmov.b128 {x, y}, z;\nmov.b64 {%0,%1}, x;\nmov.b64 {%2,%3}, y;\n"
                           "selp.b64 x, y, x, h;\nshr.b64 x, x, %7;\ncvt.u32.u64 b, x;\nand.b32 b, b, 1;\nsetp.eq.u32 p, b, %5;\n"
                           "vote.sync.all.pred p, p, 0xffffffff;\n@p bra.uni LD;\nadd.u32 c, c, 1;\nsetp.lt.u32 q, c, 1000000;\n@q bra.uni LW;\ntrap;\nLD:\n}"
                           : "=&r"(v[0]), "=&r"(v[1]), "=&r"(v[2]), "=&r"(v[3]) : "l"(src + i), "r"(par), "r"(sc), "r"((lane & 8) * 4) : "memory");
              sts128(RING + 16384 + s * SLOT + sc * 8192 + (ww * 16 + (lane & 15)) * 128 + ((i ^ sx) << 4), v[0], v[1], v[2], v[3]);
            }
            fence_async_smem();
            __syncwarp();
          }
      };
      int s = 0, ph = 0;
      uint32_t prev = B_EMPTY + 32;
#pragma unroll 1
      for (int r = 2; r < 12; r++) {
        mbar_wait(B_FULL + 8 * s, ph);
        check(r, s);
        if (!LITE || ((LITE_MASK >> 27) & 1)) STAMP_IF(leader && r == 2, 27);
        const uint64_t dw = mkdesc(RING, 8192, 1024, 1) + s * (SLOT >> 4), dx = mkdesc(RING + 16384, 16, 1024, 1) + s * (SLOT >> 4);
        wg_fence();
#pragma unroll
        for (int j = 0; j < 4; j++) {
          wgmma_n128_ss<0, 1>(a0, dx + j * 2, dw + j * 128, 1);
          wgmma_n128_ss<0, 1>(a1, dx + j * 2 + 512, dw + j * 128, 1);
        }
        wg_commit();
        wg_wait<1>();
        if (leader) mbar_arrive(prev);
        prev = B_EMPTY + 8 * s;
        if (++s == NST) { s = 0; ph ^= 1; }
      }
      auto half = [&](float (&a)[64], int s, int m) {
        const uint64_t dw = mkdesc(RING, 8192, 1024, 1) + s * (SLOT >> 4), dx = mkdesc(RING + 16384 + m * 8192, 16, 1024, 1) + s * (SLOT >> 4);
#pragma unroll
        for (int j = 0; j < 4; j++) wgmma_n128_ss<0, 1>(a, dx + j * 2, dw + j * 128, 1);
      };
      auto store = [&](float (&a)[64], int m) {
        reg_fence(a);
#pragma unroll
        for (int j = 0; j < 8; j++) {
          stsm4(sw[j & 3] + (j >> 2) * 16384 + m * 8192, pack(a[8 * j], a[8 * j + 1]), pack(a[8 * j + 2], a[8 * j + 3]), pack(a[8 * j + 4], a[8 * j + 5]), pack(a[8 * j + 6], a[8 * j + 7]));
          if ((j & 3) == 3) {
            fence_async_smem();
            e_store2d(&mp.m_out, tn * 128 + (j >> 2) * 64, tm * 128 + m * 64 + ww * 16, STG + (j >> 2) * 16384 + m * 8192 + ww * 2048);
          }
        }
      };
#pragma unroll 1
      for (int q = 0; q < 4; q++) {
        mbar_wait(B_FULL + 8 * q, 0);
        check(12 + q, q);
        wg_fence();
        half(a0, q, 0);
        wg_commit();
      }
      if (inmask) nb_sync(NB_Y, 256);
      nb_sync(NB_ST, 160);
      wg_fence();
      wgmma_n128_rs<1>(a0, oh[0], oh[1], oh[0], oh[1], mkdesc(FR, 1024, 0, 1), 1);
      wg_commit();
      wg_fence();
      half(a1, 0, 1);
      half(a1, 1, 1);
      wg_commit();
      wg_wait<1>();
      store(a0, 0);
      wg_fence();
      half(a1, 2, 1);
      half(a1, 3, 1);
      wgmma_n128_rs<1>(a1, oh[2], oh[3], oh[2], oh[3], mkdesc(FR, 1024, 0, 1), 1);
      wg_commit();
      wg_wait<0>();
      STAMP_IF(leader, 28);
      store(a1, 1);
    }
    bulk_wait_read();
    if (bid == 0 && leader) st_relaxed(&g_epoch, ep);
    STAMP_IF(leader, 29);
  } else {
    asm volatile("setmaxnreg.inc.sync.aligned.u32 216;");
    const int g = lane >> 2, t4 = lane & 3;
    const bool leader = tid == 0;
    const uint32_t sx = lane & 7, sc = lane >> 4;
    const uint32_t sa = STG + (w * 16 + (lane & 15)) * 128;
    const uint32_t sw[4] = {sa + ((sc ^ sx) << 4), sa + (((2 + sc) ^ sx) << 4), sa + (((4 + sc) ^ sx) << 4), sa + (((6 + sc) ^ sx) << 4)};
    float a0[64], a1[64];
    reg_zero(a0); reg_zero(a1); reg_fence(a0); reg_fence(a1);
    mainloop<true>(a0, a1, 0, 0, NB_KV, 0, leader);
    STAMP_IF(leader, 33);
    {
      nb_sync(NB_FDONE, 416);
      STAMP_IF(leader, 34);
      const uint32_t par = lds32(S_EPOCH) & 1u;
#pragma unroll 1
      for (int m = 0;; m++) {
        const uint32_t ca = S_CSK + (m * 64 + w * 16 + g) * 4;
        const float c[2] = {-lds32v(ca), -lds32v(ca + 32)};
        float z[2] = {0.f, 0.f}, tt[2] = {0.f, 0.f};
#pragma unroll
        for (int j = 0; j < 8; j++) {
          const float4 s0 = lds128v(S_KSTAT + (j * 16 + 2 * t4) * 8), s1 = lds128v(S_KSTAT + (j * 16 + 8 + 2 * t4) * 8);
          const float mu[4] = {s0.x, s0.z, s1.x, s1.z}, rl[4] = {s0.y, s0.w, s1.y, s1.w};
          float p[8];
#pragma unroll
          for (int i = 0; i < 8; i++) {
            const int r = (i >> 1) & 1, cc = (i >> 2) * 2 + (i & 1);
            p[i] = phi2(fmaf(c[r], mu[cc], a0[8 * j + i]) * rl[cc]);
            a0[8 * j + i] = a1[8 * j + i];
            z[r] += p[i];
            p[i] *= rl[cc];
            tt[r] = fmaf(p[i], mu[cc], tt[r]);
          }
          stsm4(sw[j & 3] + (j >> 2) * 16384 + m * 8192, pack(p[0], p[1]), pack(p[2], p[3]), pack(p[4], p[5]), pack(p[6], p[7]));
        }
        const bool u2 = lane & 2, u1 = lane & 1;
        const float v = xred(xred(z[0], tt[0], u2, 2), xred(z[1], tt[1], u2, 2), u1, 1);
        if (u2) sts32(ca + (t4 & 1) * 32, __float_as_uint(v));
        else st_relaxed(g_z + tm * 1024 + tn * 128 + m * 64 + w * 16 + t4 * 8 + g, tagf(v * LOG2E, par));
        if (m) break;
      }
      fence_async_smem();
      nb_arrive(NB_PK, 256);
      nb_arrive(NB_Z, 160);
    }
    STAMP_IF(leader, 35);
    float rl0[2];
    const uint32_t ep = lds32(S_EPOCH);
    {
      nb_sync(NB_CSQ, 160);
      float mu[4];
#pragma unroll
      for (int i = 0; i < 4; i++) {
        const float2 st = lds64f(S_KSTAT + ((i >> 1) * 64 + w * 16 + (i & 1) * 8 + g) * 8);
        mu[i] = -st.x;
        if (i < 2) rl0[i] = st.y;
      }
#pragma unroll
      for (int j = 0; j < 16; j++) {
        const float2 c = lds64f(S_CSQ + (j * 8 + 2 * t4) * 4);
        a0[4 * j] = mu[0] * c.x; a0[4 * j + 1] = mu[0] * c.y; a0[4 * j + 2] = mu[1] * c.x; a0[4 * j + 3] = mu[1] * c.y;
        a1[4 * j] = mu[2] * c.x; a1[4 * j + 1] = mu[2] * c.y; a1[4 * j + 2] = mu[3] * c.x; a1[4 * j + 3] = mu[3] * c.y;
      }
      reg_fence(a0); reg_fence(a1);
    }
    STAMP_IF(leader, 40);
    nb_sync(NB_VQ, 256);
    mainloop<false>(a0, a1, 2, 0, 0, 4 + (tn & 3), leader);
    STAMP_IF(leader, 36);
    {
      uint32_t f[2][16];
      float oc[2][2][20];
      auto phi = [&](const float (&a)[64], int j, int m, uint32_t (&o)[16]) {
        float rl[2] = {rl0[0], rl0[1]};
        if (j | m) { rl[0] = lds32v(S_KSTAT + (m * 64 + w * 16 + g) * 8 + 4); rl[1] = lds32v(S_KSTAT + (m * 64 + w * 16 + 8 + g) * 8 + 4); }
#pragma unroll
        for (int i = 0; i < 16; i++) o[i] = pack(phi2(a[32 * j + 2 * i] * rl[i & 1]), phi2(a[32 * j + 2 * i + 1] * rl[i & 1]));
      };
      auto mma = [&](int j, const uint32_t (&a)[16], float (&o)[2][20]) {
        const uint64_t db = mkdesc(j ? KVB_Z : KVB_P0, 16, 1024, 1);
        reg_zero(o[0]); reg_zero(o[1]);
        wg_fence();
        wgmma_n40_rs<0>(o[0], a[0], a[1], a[2], a[3], db, 0);
        wgmma_n40_rs<0>(o[1], a[8], a[9], a[10], a[11], db + 4, 0);
        wgmma_n40_rs<0>(o[0], a[4], a[5], a[6], a[7], db + 2, 1);
        wgmma_n40_rs<0>(o[1], a[12], a[13], a[14], a[15], db + 6, 1);
        wg_commit();
      };
      auto fin = [&](int j, int m, float (&o)[2][20]) {
        const uint32_t m0 = t4 == 2 * m, m1 = t4 == 2 * m + 1;
#pragma unroll
        for (int h = 0; h < 2; h++) {
          const float r0 = rcp(o[h][j ? 1 : 16] + 1e-6f * LOG2E), r1 = rcp(o[h][j ? 3 : 18] + 1e-6f * LOG2E);
          const int b = j ? 4 : 0;
#pragma unroll
          for (int q = 0; q < 2; q++)
            stsm4(sw[h * 2 + q] + j * 16384 + m * 8192,
                  bsel(pack(o[h][b + 8 * q] * r0, o[h][b + 8 * q + 1] * r0), ep, m0), bsel(pack(o[h][b + 8 * q + 2] * r1, o[h][b + 8 * q + 3] * r1), ep, m1),
                  bsel(pack(o[h][b + 8 * q + 4] * r0, o[h][b + 8 * q + 5] * r0), ep, m0), bsel(pack(o[h][b + 8 * q + 6] * r1, o[h][b + 8 * q + 7] * r1), ep, m1));
        }
      };
#pragma unroll
      for (int j = 0; j < 2; j++) {
        phi(a0, j, 0, f[0]);
        if (j == 0) nb_sync(NB_KVB, 288);
        STAMP_IF(leader && j == 0, 37);
        mma(j, f[0], oc[0]);
        phi(a1, j, 1, f[1]);
        wg_wait<0>();
        reg_fence(oc[0][0]); reg_fence(oc[0][1]);
        mma(j, f[1], oc[1]);
        if (!RES_FIRST && j == 0) nb_sync(NB_KV, 256);
        fin(j, 0, oc[0]);
        if (j == 0) { fence_async_smem(); nb_arrive(NB_Q0, 192); }
        wg_wait<0>();
        reg_fence(oc[1][0]); reg_fence(oc[1][1]);
        fin(j, 1, oc[1]);
        fence_async_smem();
        if (j == 0) nb_arrive(NB_OWN0, 288);
        else { nb_arrive(NB_OWN1, 256); nb_arrive(NB_H1, 160); }
        STAMP_IF(leader, 38 + j);
      }
    }
  }
}

#undef CK
typedef CUresult (*EncodeFn)(CUtensorMap*, CUtensorMapDataType, cuuint32_t, void*, const cuuint64_t*, const cuuint64_t*, const cuuint32_t*,
                             const cuuint32_t*, CUtensorMapInterleave, CUtensorMapSwizzle, CUtensorMapL2promotion, CUtensorMapFloatOOBfill);

void make_map(EncodeFn enc, CUtensorMap* m, const void* p, int rank, uint64_t d0, uint64_t d1, uint64_t d2, uint64_t s1, uint64_t s2,
              uint32_t b0, uint32_t b1, uint32_t b2, CUtensorMapSwizzle sw) {
  cuuint64_t gd[3] = {d0, d1, d2}, gs[2] = {s1, s2};
  cuuint32_t bd[3] = {b0, b1, b2}, es[3] = {1, 1, 1};
  enc(m, CU_TENSOR_MAP_DATA_TYPE_BFLOAT16, rank, const_cast<void*>(p), gd, gs, bd, es, CU_TENSOR_MAP_INTERLEAVE_NONE, sw,
      CU_TENSOR_MAP_L2_PROMOTION_L2_128B, CU_TENSOR_MAP_FLOAT_OOB_FILL_NONE);
}

}

extern "C" void kernel_launch(void* const* d_in, const int* in_sizes, int n_in, void* d_out, int out_size) {
  (void)in_sizes; (void)n_in; (void)out_size;
  void* fn = nullptr;
  cudaDriverEntryPointQueryResult qr;
  cudaGetDriverEntryPoint("cuTensorMapEncodeTiled", &fn, cudaEnableDefault, &qr);
  EncodeFn enc = (EncodeFn)fn;
  void* o;
  cudaGetSymbolAddress(&o, g_o);
  const CUtensorMapSwizzle S128 = CU_TENSOR_MAP_SWIZZLE_128B, S64 = CU_TENSOR_MAP_SWIZZLE_64B, S0 = CU_TENSOR_MAP_SWIZZLE_NONE;
  Params mp;
  mp.x = (const char*)d_in[0]; mp.wqkv = (const char*)d_in[1]; mp.w_r = (const char*)d_in[4];
  mp.wg = (const char*)d_in[5]; mp.wu = (const char*)d_in[6]; mp.wd = (const char*)d_in[7];
  make_map(enc, &mp.m_wqkv, d_in[1], 3, 64, 1024, 48, 6144, 128, 64, 64, 2, S128);
  make_map(enc, &mp.m_x, d_in[0], 2, 1024, 2048, 1, 2048, 0, 64, 128, 1, S128);
  make_map(enc, &mp.m_os, o, 2, 1024, 2048, 1, 2048, 0, 64, 64, 1, S128);
  make_map(enc, &mp.m_o, o, 2, 1024, 2048, 1, 2048, 0, 64, 128, 1, S128);
  make_map(enc, &mp.m_wo, d_in[2], 3, 64, 1024, 16, 2048, 128, 64, 64, 2, S128);
  make_map(enc, &mp.m_xs, d_in[0], 2, 1024, 2048, 1, 2048, 0, 256, 16, 1, S0);
  const char *wg = (const char*)d_in[5], *wu = (const char*)d_in[6];
  make_map(enc, &mp.m_gu, wu < wg ? wu : wg, 3, 3584, 1024, 2, 7168, (uint64_t)(wu < wg ? wg - wu : wu - wg), 32, 64, 2, S64);
  make_map(enc, &mp.m_down, d_in[7], 2, 1024, 3584, 1, 2048, 0, 64, 64, 1, S128);
  make_map(enc, &mp.m_out, d_out, 2, 1024, 2048, 1, 2048, 0, 64, 16, 1, S128);
  int dev = 0, sms = 0;
  cudaGetDevice(&dev);
  cudaDeviceGetAttribute(&sms, cudaDevAttrMultiProcessorCount, dev);
  auto kern = sms == 132 ? fused_kernel<true> : fused_kernel<false>;
  cudaFuncSetAttribute(kern, cudaFuncAttributeMaxDynamicSharedMemorySize, SMEM_BYTES);
  kern<<<132, 512, SMEM_BYTES>>>(mp);
}
```

```cpp
#include <cuda_runtime.h>
#include <cuda.h>
#include <cuda_bf16.h>
#include <stdint.h>

namespace {

template <int TA, int TB>
__device__ __forceinline__ void wgmma_n8_ss(float (&d)[4], uint64_t da, uint64_t db, int sc) {
  asm volatile("{\n.reg .pred p;\nsetp.ne.b32 p, %6, 0;\n"
    "wgmma.mma_async.sync.aligned.m64n8k16.f32.bf16.bf16 {%0, %1, %2, %3}, %4, %5, p, 1, 1, %7, %8;\n}\n"
    : "+f"(d[0]), "+f"(d[1]), "+f"(d[2]), "+f"(d[3])
    : "l"(da), "l"(db), "r"(sc), "n"(TA), "n"(TB));
}
template <int TA, int TB>
__device__ __forceinline__ void wgmma_n16_ss(float (&d)[8], uint64_t da, uint64_t db, int sc) {
  asm volatile("{\n.reg .pred p;\nsetp.ne.b32 p, %10, 0;\n"
    "wgmma.mma_async.sync.aligned.m64n16k16.f32.bf16.bf16 {%0, %1, %2, %3, %4, %5, %6, %7}, %8, %9, p, 1, 1, %11, %12;\n}\n"
    : "+f"(d[0]), "+f"(d[1]), "+f"(d[2]), "+f"(d[3]), "+f"(d[4]), "+f"(d[5]), "+f"(d[6]), "+f"(d[7])
    : "l"(da), "l"(db), "r"(sc), "n"(TA), "n"(TB));
}
template <int TB>
__device__ __forceinline__ void wgmma_n40_rs(float (&d)[20], uint32_t a0, uint32_t a1, uint32_t a2, uint32_t a3, uint64_t db, int sc) {
  asm volatile("{\n.reg .pred p;\nsetp.ne.b32 p, %25, 0;\n"
    "wgmma.mma_async.sync.aligned.m64n40k16.f32.bf16.bf16 {%0, %1, %2, %3, %4, %5, %6, %7, %8, %9, %10, %11, %12, %13, %14, %15, %16, %17, %18, %19}, {%20,%21,%22,%23}, %24, p, 1, 1, %26;\n}\n"
    : "+f"(d[0]), "+f"(d[1]), "+f"(d[2]), "+f"(d[3]), "+f"(d[4]), "+f"(d[5]), "+f"(d[6]), "+f"(d[7]),
      "+f"(d[8]), "+f"(d[9]), "+f"(d[10]), "+f"(d[11]), "+f"(d[12]), "+f"(d[13]), "+f"(d[14]), "+f"(d[15]),
      "+f"(d[16]), "+f"(d[17]), "+f"(d[18]), "+f"(d[19])
    : "r"(a0), "r"(a1), "r"(a2), "r"(a3), "l"(db), "r"(sc), "n"(TB));
}
template <int TB>
__device__ __forceinline__ void wgmma_n64_rs(float (&d)[32], uint32_t a0, uint32_t a1, uint32_t a2, uint32_t a3, uint64_t db, int sc) {
  asm volatile("{\n.reg .pred p;\nsetp.ne.b32 p, %37, 0;\n"
    "wgmma.mma_async.sync.aligned.m64n64k16.f32.bf16.bf16 {%0, %1, %2, %3, %4, %5, %6, %7, %8, %9, %10, %11, %12, %13, %14, %15, %16, %17, %18, %19, %20, %21, %22, %23, %24, %25, %26, %27, %28, %29, %30, %31}, {%32,%33,%34,%35}, %36, p, 1, 1, %38;\n}\n"
    : "+f"(d[0]), "+f"(d[1]), "+f"(d[2]), "+f"(d[3]), "+f"(d[4]), "+f"(d[5]), "+f"(d[6]), "+f"(d[7]),
      "+f"(d[8]), "+f"(d[9]), "+f"(d[10]), "+f"(d[11]), "+f"(d[12]), "+f"(d[13]), "+f"(d[14]), "+f"(d[15]),
      "+f"(d[16]), "+f"(d[17]), "+f"(d[18]), "+f"(d[19]), "+f"(d[20]), "+f"(d[21]), "+f"(d[22]), "+f"(d[23]),
      "+f"(d[24]), "+f"(d[25]), "+f"(d[26]), "+f"(d[27]), "+f"(d[28]), "+f"(d[29]), "+f"(d[30]), "+f"(d[31])
    : "r"(a0), "r"(a1), "r"(a2), "r"(a3), "l"(db), "r"(sc), "n"(TB));
}
template <int TA, int TB>
__device__ __forceinline__ void wgmma_n128_ss(float (&d)[64], uint64_t da, uint64_t db, int sc) {
  asm volatile("{\n.reg .pred p;\nsetp.ne.b32 p, %66, 0;\n"
    "wgmma.mma_async.sync.aligned.m64n128k16.f32.bf16.bf16 {%0, %1, %2, %3, %4, %5, %6, %7, %8, %9, %10, %11, %12, %13, %14, %15, %16, %17, %18, %19, %20, %21, %22, %23, %24, %25, %26, %27, %28, %29, %30, %31, %32, %33, %34, %35, %36, %37, %38, %39, %40, %41, %42, %43, %44, %45, %46, %47, %48, %49, %50, %51, %52, %53, %54, %55, %56, %57, %58, %59, %60, %61, %62, %63}, %64, %65, p, 1, 1, %67, %68;\n}\n"
    : "+f"(d[0]), "+f"(d[1]), "+f"(d[2]), "+f"(d[3]), "+f"(d[4]), "+f"(d[5]), "+f"(d[6]), "+f"(d[7]),
      "+f"(d[8]), "+f"(d[9]), "+f"(d[10]), "+f"(d[11]), "+f"(d[12]), "+f"(d[13]), "+f"(d[14]), "+f"(d[15]),
      "+f"(d[16]), "+f"(d[17]), "+f"(d[18]), "+f"(d[19]), "+f"(d[20]), "+f"(d[21]), "+f"(d[22]), "+f"(d[23]),
      "+f"(d[24]), "+f"(d[25]), "+f"(d[26]), "+f"(d[27]), "+f"(d[28]), "+f"(d[29]), "+f"(d[30]), "+f"(d[31]),
      "+f"(d[32]), "+f"(d[33]), "+f"(d[34]), "+f"(d[35]), "+f"(d[36]), "+f"(d[37]), "+f"(d[38]), "+f"(d[39]),
      "+f"(d[40]), "+f"(d[41]), "+f"(d[42]), "+f"(d[43]), "+f"(d[44]), "+f"(d[45]), "+f"(d[46]), "+f"(d[47]),
      "+f"(d[48]), "+f"(d[49]), "+f"(d[50]), "+f"(d[51]), "+f"(d[52]), "+f"(d[53]), "+f"(d[54]), "+f"(d[55]),
      "+f"(d[56]), "+f"(d[57]), "+f"(d[58]), "+f"(d[59]), "+f"(d[60]), "+f"(d[61]), "+f"(d[62]), "+f"(d[63])
    : "l"(da), "l"(db), "r"(sc), "n"(TA), "n"(TB));
}
template <int TB>
__device__ __forceinline__ void wgmma_n128_rs(float (&d)[64], uint32_t a0, uint32_t a1, uint32_t a2, uint32_t a3, uint64_t db, int sc) {
  asm volatile("{\n.reg .pred p;\nsetp.ne.b32 p, %69, 0;\n"
    "wgmma.mma_async.sync.aligned.m64n128k16.f32.bf16.bf16 {%0, %1, %2, %3, %4, %5, %6, %7, %8, %9, %10, %11, %12, %13, %14, %15, %16, %17, %18, %19, %20, %21, %22, %23, %24, %25, %26, %27, %28, %29, %30, %31, %32, %33, %34, %35, %36, %37, %38, %39, %40, %41, %42, %43, %44, %45, %46, %47, %48, %49, %50, %51, %52, %53, %54, %55, %56, %57, %58, %59, %60, %61, %62, %63}, {%64,%65,%66,%67}, %68, p, 1, 1, %70;\n}\n"
    : "+f"(d[0]), "+f"(d[1]), "+f"(d[2]), "+f"(d[3]), "+f"(d[4]), "+f"(d[5]), "+f"(d[6]), "+f"(d[7]),
      "+f"(d[8]), "+f"(d[9]), "+f"(d[10]), "+f"(d[11]), "+f"(d[12]), "+f"(d[13]), "+f"(d[14]), "+f"(d[15]),
      "+f"(d[16]), "+f"(d[17]), "+f"(d[18]), "+f"(d[19]), "+f"(d[20]), "+f"(d[21]), "+f"(d[22]), "+f"(d[23]),
      "+f"(d[24]), "+f"(d[25]), "+f"(d[26]), "+f"(d[27]), "+f"(d[28]), "+f"(d[29]), "+f"(d[30]), "+f"(d[31]),
      "+f"(d[32]), "+f"(d[33]), "+f"(d[34]), "+f"(d[35]), "+f"(d[36]), "+f"(d[37]), "+f"(d[38]), "+f"(d[39]),
      "+f"(d[40]), "+f"(d[41]), "+f"(d[42]), "+f"(d[43]), "+f"(d[44]), "+f"(d[45]), "+f"(d[46]), "+f"(d[47]),
      "+f"(d[48]), "+f"(d[49]), "+f"(d[50]), "+f"(d[51]), "+f"(d[52]), "+f"(d[53]), "+f"(d[54]), "+f"(d[55]),
      "+f"(d[56]), "+f"(d[57]), "+f"(d[58]), "+f"(d[59]), "+f"(d[60]), "+f"(d[61]), "+f"(d[62]), "+f"(d[63])
    : "r"(a0), "r"(a1), "r"(a2), "r"(a3), "l"(db), "r"(sc), "n"(TB));
}

__device__ __forceinline__ void poll1f(uint32_t (&v)[1], const void* p, uint32_t tag, uint32_t mask) {
  asm volatile("{\n.reg .pred p, q;\n.reg .u32 c, b;\n.reg .b64 x, y;\n.reg .b128 z;\nmov.u32 c, 0;\nLW:\n"
               "ld.relaxed.gpu.global.u32 %0, [%1+0];\n"
               "xor.b32 b, %0, %2;\n"
               "and.b32 b, b, %3;\nsetp.eq.u32 p, b, 0;\nvote.sync.all.pred p, p, 0xffffffff;\n@p bra.uni LD;\n"
               "nanosleep.u32 50;\nadd.u32 c, c, 1;\nsetp.lt.u32 q, c, 1000000;\n@q bra.uni LW;\ntrap;\nLD:\n}"
               : "=&r"(v[0])
               : "l"(p), "r"(tag), "r"(mask) : "memory");
}
__device__ __forceinline__ void poll0(uint32_t (&v)[1], const void* p, uint32_t tag, uint32_t mask) {
  asm volatile("{\n.reg .pred p, q;\n.reg .u32 c, b;\n.reg .b64 x, y;\n.reg .b128 z;\nmov.u32 c, 0;\nLW:\n"
               "ld.relaxed.gpu.global.u32 %0, [%1+0];\n"
               "xor.b32 b, %0, %2;\n"
               "and.b32 b, b, %3;\nsetp.eq.u32 p, b, 0;\nvote.sync.all.pred p, p, 0xffffffff;\n@p bra.uni LD;\n"
               "add.u32 c, c, 1;\nsetp.lt.u32 q, c, 1000000;\n@q bra.uni LW;\ntrap;\nLD:\n}"
               : "=&r"(v[0])
               : "l"(p), "r"(tag), "r"(mask) : "memory");
}
__device__ __forceinline__ void poll_pair(uint32_t (&v)[2], const void* p, uint32_t tag, uint32_t mask) {
  asm volatile("{\n.reg .pred p, q;\n.reg .u32 c, b;\n.reg .b64 x, y;\n.reg .b128 z;\nmov.u32 c, 0;\nLW:\n"
               "ld.relaxed.gpu.global.b64 x, [%2+0];\nmov.b64 {%0,%1}, x;\n"
               "xor.b32 b, %0, %3;\n"
               "and.b32 b, b, %4;\nsetp.eq.u32 p, b, 0;\nvote.sync.all.pred p, p, 0xffffffff;\n@p bra.uni LD;\n"
               "nanosleep.u32 100;\nadd.u32 c, c, 1;\nsetp.lt.u32 q, c, 1000000;\n@q bra.uni LW;\ntrap;\nLD:\n}"
               : "=&r"(v[0]), "=&r"(v[1])
               : "l"(p), "r"(tag), "r"(mask) : "memory");
}
__device__ __forceinline__ void poll_quad(uint32_t (&v)[4], const void* p, uint32_t tag, uint32_t mask) {
  asm volatile("{\n.reg .pred p, q;\n.reg .u32 c, b;\n.reg .b64 x, y;\n.reg .b128 z;\nmov.u32 c, 0;\nLW:\n"
               "ld.relaxed.gpu.global.v4.u32 {%0,%1,%2,%3}, [%4+0];\n"
               "xor.b32 b, %0, %5;\n"
               "lop3.b32 b, b, %1, %5, 0xf6;\nlop3.b32 b, b, %2, %5, 0xf6;\nlop3.b32 b, b, %3, %5, 0xf6;\n"
               "and.b32 b, b, %6;\nsetp.eq.u32 p, b, 0;\nvote.sync.all.pred p, p, 0xffffffff;\n@p bra.uni LD;\n"
               "nanosleep.u32 200;\nadd.u32 c, c, 1;\nsetp.lt.u32 q, c, 1000000;\n@q bra.uni LW;\ntrap;\nLD:\n}"
               : "=&r"(v[0]), "=&r"(v[1]), "=&r"(v[2]), "=&r"(v[3])
               : "l"(p), "r"(tag), "r"(mask) : "memory");
}
__device__ __forceinline__ void poll8x4(uint32_t (&v)[32], const void* p, uint32_t tag, uint32_t mask) {
  asm volatile("{\n.reg .pred p, q;\n.reg .u32 c, b;\n.reg .b64 x, y;\n.reg .b128 z;\nmov.u32 c, 0;\nLW:\n"
               "ld.relaxed.gpu.global.v4.u32 {%0,%1,%2,%3}, [%32+0];\n"
               "ld.relaxed.gpu.global.v4.u32 {%4,%5,%6,%7}, [%32+2048];\n"
               "ld.relaxed.gpu.global.v4.u32 {%8,%9,%10,%11}, [%32+4096];\n"
               "ld.relaxed.gpu.global.v4.u32 {%12,%13,%14,%15}, [%32+6144];\n"
               "ld.relaxed.gpu.global.v4.u32 {%16,%17,%18,%19}, [%32+8192];\n"
               "ld.relaxed.gpu.global.v4.u32 {%20,%21,%22,%23}, [%32+10240];\n"
               "ld.relaxed.gpu.global.v4.u32 {%24,%25,%26,%27}, [%32+12288];\n"
               "ld.relaxed.gpu.global.v4.u32 {%28,%29,%30,%31}, [%32+14336];\n"
               "xor.b32 b, %0, %33;\n"
               "lop3.b32 b, b, %1, %33, 0xf6;\nlop3.b32 b, b, %2, %33, 0xf6;\nlop3.b32 b, b, %3, %33, 0xf6;\nlop3.b32 b, b, %4, %33, 0xf6;\n"
               "lop3.b32 b, b, %5, %33, 0xf6;\nlop3.b32 b, b, %6, %33, 0xf6;\nlop3.b32 b, b, %7, %33, 0xf6;\nlop3.b32 b, b, %8, %33, 0xf6;\n"
               "lop3.b32 b, b, %9, %33, 0xf6;\nlop3.b32 b, b, %10, %33, 0xf6;\nlop3.b32 b, b, %11, %33, 0xf6;\nlop3.b32 b, b, %12, %33, 0xf6;\n"
               "lop3.b32 b, b, %13, %33, 0xf6;\nlop3.b32 b, b, %14, %33, 0xf6;\nlop3.b32 b, b, %15, %33, 0xf6;\nlop3.b32 b, b, %16, %33, 0xf6;\n"
               "lop3.b32 b, b, %17, %33, 0xf6;\nlop3.b32 b, b, %18, %33, 0xf6;\nlop3.b32 b, b, %19, %33, 0xf6;\nlop3.b32 b, b, %20, %33, 0xf6;\n"
               "lop3.b32 b, b, %21, %33, 0xf6;\nlop3.b32 b, b, %22, %33, 0xf6;\nlop3.b32 b, b, %23, %33, 0xf6;\nlop3.b32 b, b, %24, %33, 0xf6;\n"
               "lop3.b32 b, b, %25, %33, 0xf6;\nlop3.b32 b, b, %26, %33, 0xf6;\nlop3.b32 b, b, %27, %33, 0xf6;\nlop3.b32 b, b, %28, %33, 0xf6;\n"
               "lop3.b32 b, b, %29, %33, 0xf6;\nlop3.b32 b, b, %30, %33, 0xf6;\nlop3.b32 b, b, %31, %33, 0xf6;\n"
               "and.b32 b, b, %34;\nsetp.eq.u32 p, b, 0;\nvote.sync.all.pred p, p, 0xffffffff;\n@p bra.uni LD;\n"
               "nanosleep.u32 50;\nadd.u32 c, c, 1;\nsetp.lt.u32 q, c, 1000000;\n@q bra.uni LW;\ntrap;\nLD:\n}"
               : "=&r"(v[0]), "=&r"(v[1]), "=&r"(v[2]), "=&r"(v[3]), "=&r"(v[4]), "=&r"(v[5]), "=&r"(v[6]), "=&r"(v[7]), "=&r"(v[8]), "=&r"(v[9]), "=&r"(v[10]), "=&r"(v[11]), "=&r"(v[12]), "=&r"(v[13]), "=&r"(v[14]), "=&r"(v[15]), "=&r"(v[16]), "=&r"(v[17]), "=&r"(v[18]), "=&r"(v[19]), "=&r"(v[20]), "=&r"(v[21]), "=&r"(v[22]), "=&r"(v[23]), "=&r"(v[24]), "=&r"(v[25]), "=&r"(v[26]), "=&r"(v[27]), "=&r"(v[28]), "=&r"(v[29]), "=&r"(v[30]), "=&r"(v[31])
               : "l"(p), "r"(tag), "r"(mask) : "memory");
}
__device__ __forceinline__ void poll16(uint32_t (&v)[16], const void* p, uint32_t tag, uint32_t mask) {
  asm volatile("{\n.reg .pred p, q;\n.reg .u32 c, b;\n.reg .b64 x, y;\n.reg .b128 z;\nmov.u32 c, 0;\nLW:\n"
               "ld.relaxed.gpu.global.u32 %0, [%16+0];\n"
               "ld.relaxed.gpu.global.u32 %1, [%16+4096];\n"
               "ld.relaxed.gpu.global.u32 %2, [%16+8192];\n"
               "ld.relaxed.gpu.global.u32 %3, [%16+12288];\n"
               "ld.relaxed.gpu.global.u32 %4, [%16+16384];\n"
               "ld.relaxed.gpu.global.u32 %5, [%16+20480];\n"
               "ld.relaxed.gpu.global.u32 %6, [%16+24576];\n"
               "ld.relaxed.gpu.global.u32 %7, [%16+28672];\n"
               "ld.relaxed.gpu.global.u32 %8, [%16+32768];\n"
               "ld.relaxed.gpu.global.u32 %9, [%16+36864];\n"
               "ld.relaxed.gpu.global.u32 %10, [%16+40960];\n"
               "ld.relaxed.gpu.global.u32 %11, [%16+45056];\n"
               "ld.relaxed.gpu.global.u32 %12, [%16+49152];\n"
               "ld.relaxed.gpu.global.u32 %13, [%16+53248];\n"
               "ld.relaxed.gpu.global.u32 %14, [%16+57344];\n"
               "ld.relaxed.gpu.global.u32 %15, [%16+61440];\n"
               "xor.b32 b, %0, %17;\n"
               "lop3.b32 b, b, %1, %17, 0xf6;\nlop3.b32 b, b, %2, %17, 0xf6;\nlop3.b32 b, b, %3, %17, 0xf6;\nlop3.b32 b, b, %4, %17, 0xf6;\n"
               "lop3.b32 b, b, %5, %17, 0xf6;\nlop3.b32 b, b, %6, %17, 0xf6;\nlop3.b32 b, b, %7, %17, 0xf6;\nlop3.b32 b, b, %8, %17, 0xf6;\n"
               "lop3.b32 b, b, %9, %17, 0xf6;\nlop3.b32 b, b, %10, %17, 0xf6;\nlop3.b32 b, b, %11, %17, 0xf6;\nlop3.b32 b, b, %12, %17, 0xf6;\n"
               "lop3.b32 b, b, %13, %17, 0xf6;\nlop3.b32 b, b, %14, %17, 0xf6;\nlop3.b32 b, b, %15, %17, 0xf6;\n"
               "and.b32 b, b, %18;\nsetp.eq.u32 p, b, 0;\nvote.sync.all.pred p, p, 0xffffffff;\n@p bra.uni LD;\n"
               "nanosleep.u32 200;\nadd.u32 c, c, 1;\nsetp.lt.u32 q, c, 1000000;\n@q bra.uni LW;\ntrap;\nLD:\n}"
               : "=&r"(v[0]), "=&r"(v[1]), "=&r"(v[2]), "=&r"(v[3]), "=&r"(v[4]), "=&r"(v[5]), "=&r"(v[6]), "=&r"(v[7]), "=&r"(v[8]), "=&r"(v[9]), "=&r"(v[10]), "=&r"(v[11]), "=&r"(v[12]), "=&r"(v[13]), "=&r"(v[14]), "=&r"(v[15])
               : "l"(p), "r"(tag), "r"(mask) : "memory");
}
__device__ __forceinline__ void poll_keys(uint32_t (&v)[16], const void* p, uint32_t tag, uint32_t mask) {
  asm volatile("{\n.reg .pred p, q;\n.reg .u32 c, b;\n.reg .b64 x, y;\n.reg .b128 z;\nmov.u32 c, 0;\nLW:\n"
               "ld.relaxed.gpu.global.v2.b64 {x, y}, [%16+0];\nmov.b64 {%0,%1}, x;\nmov.b64 {%2,%3}, y;\n"
               "ld.relaxed.gpu.global.v2.b64 {x, y}, [%16+4096];\nmov.b64 {%4,%5}, x;\nmov.b64 {%6,%7}, y;\n"
               "ld.relaxed.gpu.global.v2.b64 {x, y}, [%16+8192];\nmov.b64 {%8,%9}, x;\nmov.b64 {%10,%11}, y;\n"
               "ld.relaxed.gpu.global.v2.b64 {x, y}, [%16+12288];\nmov.b64 {%12,%13}, x;\nmov.b64 {%14,%15}, y;\n"
               "xor.b32 b, %0, %17;\n"
               "lop3.b32 b, b, %2, %17, 0xf6;\nlop3.b32 b, b, %4, %17, 0xf6;\nlop3.b32 b, b, %6, %17, 0xf6;\nlop3.b32 b, b, %8, %17, 0xf6;\n"
               "lop3.b32 b, b, %10, %17, 0xf6;\nlop3.b32 b, b, %12, %17, 0xf6;\nlop3.b32 b, b, %14, %17, 0xf6;\n"
               "and.b32 b, b, %18;\nsetp.eq.u32 p, b, 0;\nvote.sync.all.pred p, p, 0xffffffff;\n@p bra.uni LD;\n"
               "nanosleep.u32 20;\nadd.u32 c, c, 1;\nsetp.lt.u32 q, c, 1000000;\n@q bra.uni LW;\ntrap;\nLD:\n}"
               : "=&r"(v[0]), "=&r"(v[1]), "=&r"(v[2]), "=&r"(v[3]), "=&r"(v[4]), "=&r"(v[5]), "=&r"(v[6]), "=&r"(v[7]), "=&r"(v[8]), "=&r"(v[9]), "=&r"(v[10]), "=&r"(v[11]), "=&r"(v[12]), "=&r"(v[13]), "=&r"(v[14]), "=&r"(v[15])
               : "l"(p), "r"(tag), "r"(mask) : "memory");
}
__device__ __forceinline__ void poll_z(uint32_t (&v)[16], const void* p, uint32_t tag, uint32_t mask) {
  asm volatile("{\n.reg .pred p, q;\n.reg .u32 c, b;\n.reg .b64 x, y;\n.reg .b128 z;\nmov.u32 c, 0;\nLW:\n"
               "ld.relaxed.gpu.global.v4.u32 {%0,%1,%2,%3}, [%16+0];\n"
               "ld.relaxed.gpu.global.v4.u32 {%4,%5,%6,%7}, [%16+4096];\n"
               "ld.relaxed.gpu.global.v4.u32 {%8,%9,%10,%11}, [%16+8192];\n"
               "ld.relaxed.gpu.global.v4.u32 {%12,%13,%14,%15}, [%16+12288];\n"
               "xor.b32 b, %0, %17;\n"
               "lop3.b32 b, b, %1, %17, 0xf6;\nlop3.b32 b, b, %2, %17, 0xf6;\nlop3.b32 b, b, %3, %17, 0xf6;\nlop3.b32 b, b, %4, %17, 0xf6;\n"
               "lop3.b32 b, b, %5, %17, 0xf6;\nlop3.b32 b, b, %6, %17, 0xf6;\nlop3.b32 b, b, %7, %17, 0xf6;\nlop3.b32 b, b, %8, %17, 0xf6;\n"
               "lop3.b32 b, b, %9, %17, 0xf6;\nlop3.b32 b, b, %10, %17, 0xf6;\nlop3.b32 b, b, %11, %17, 0xf6;\nlop3.b32 b, b, %12, %17, 0xf6;\n"
               "lop3.b32 b, b, %13, %17, 0xf6;\nlop3.b32 b, b, %14, %17, 0xf6;\nlop3.b32 b, b, %15, %17, 0xf6;\n"
               "and.b32 b, b, %18;\nsetp.eq.u32 p, b, 0;\nvote.sync.all.pred p, p, 0xffffffff;\n@p bra.uni LD;\n"
               "nanosleep.u32 300;\nadd.u32 c, c, 1;\nsetp.lt.u32 q, c, 1000000;\n@q bra.uni LW;\ntrap;\nLD:\n}"
               : "=&r"(v[0]), "=&r"(v[1]), "=&r"(v[2]), "=&r"(v[3]), "=&r"(v[4]), "=&r"(v[5]), "=&r"(v[6]), "=&r"(v[7]), "=&r"(v[8]), "=&r"(v[9]), "=&r"(v[10]), "=&r"(v[11]), "=&r"(v[12]), "=&r"(v[13]), "=&r"(v[14]), "=&r"(v[15])
               : "l"(p), "r"(tag), "r"(mask) : "memory");
}
__device__ __forceinline__ void poll7x4(uint32_t (&v)[28], const void* p, uint32_t tag, uint32_t mask) {
  asm volatile("{\n.reg .pred p, q;\n.reg .u32 c, b;\n.reg .b64 x, y;\n.reg .b128 z;\nmov.u32 c, 0;\nLW:\n"
               "ld.relaxed.gpu.global.v4.u32 {%0,%1,%2,%3}, [%28+0];\n"
               "ld.relaxed.gpu.global.v4.u32 {%4,%5,%6,%7}, [%28+2048];\n"
               "ld.relaxed.gpu.global.v4.u32 {%8,%9,%10,%11}, [%28+4096];\n"
               "ld.relaxed.gpu.global.v4.u32 {%12,%13,%14,%15}, [%28+6144];\n"
               "ld.relaxed.gpu.global.v4.u32 {%16,%17,%18,%19}, [%28+8192];\n"
               "ld.relaxed.gpu.global.v4.u32 {%20,%21,%22,%23}, [%28+10240];\n"
               "ld.relaxed.gpu.global.v4.u32 {%24,%25,%26,%27}, [%28+12288];\n"
               "xor.b32 b, %0, %29;\n"
               "lop3.b32 b, b, %1, %29, 0xf6;\nlop3.b32 b, b, %2, %29, 0xf6;\nlop3.b32 b, b, %3, %29, 0xf6;\nlop3.b32 b, b, %4, %29, 0xf6;\n"
               "lop3.b32 b, b, %5, %29, 0xf6;\nlop3.b32 b, b, %6, %29, 0xf6;\nlop3.b32 b, b, %7, %29, 0xf6;\nlop3.b32 b, b, %8, %29, 0xf6;\n"
               "lop3.b32 b, b, %9, %29, 0xf6;\nlop3.b32 b, b, %10, %29, 0xf6;\nlop3.b32 b, b, %11, %29, 0xf6;\nlop3.b32 b, b, %12, %29, 0xf6;\n"
               "lop3.b32 b, b, %13, %29, 0xf6;\nlop3.b32 b, b, %14, %29, 0xf6;\nlop3.b32 b, b, %15, %29, 0xf6;\nlop3.b32 b, b, %16, %29, 0xf6;\n"
               "lop3.b32 b, b, %17, %29, 0xf6;\nlop3.b32 b, b, %18, %29, 0xf6;\nlop3.b32 b, b, %19, %29, 0xf6;\nlop3.b32 b, b, %20, %29, 0xf6;\n"
               "lop3.b32 b, b, %21, %29, 0xf6;\nlop3.b32 b, b, %22, %29, 0xf6;\nlop3.b32 b, b, %23, %29, 0xf6;\nlop3.b32 b, b, %24, %29, 0xf6;\n"
               "lop3.b32 b, b, %25, %29, 0xf6;\nlop3.b32 b, b, %26, %29, 0xf6;\nlop3.b32 b, b, %27, %29, 0xf6;\n"
               "and.b32 b, b, %30;\nsetp.eq.u32 p, b, 0;\nvote.sync.all.pred p, p, 0xffffffff;\n@p bra.uni LD;\n"
               "nanosleep.u32 50;\nadd.u32 c, c, 1;\nsetp.lt.u32 q, c, 1000000;\n@q bra.uni LW;\ntrap;\nLD:\n}"
               : "=&r"(v[0]), "=&r"(v[1]), "=&r"(v[2]), "=&r"(v[3]), "=&r"(v[4]), "=&r"(v[5]), "=&r"(v[6]), "=&r"(v[7]), "=&r"(v[8]), "=&r"(v[9]), "=&r"(v[10]), "=&r"(v[11]), "=&r"(v[12]), "=&r"(v[13]), "=&r"(v[14]), "=&r"(v[15]), "=&r"(v[16]), "=&r"(v[17]), "=&r"(v[18]), "=&r"(v[19]), "=&r"(v[20]), "=&r"(v[21]), "=&r"(v[22]), "=&r"(v[23]), "=&r"(v[24]), "=&r"(v[25]), "=&r"(v[26]), "=&r"(v[27])
               : "l"(p), "r"(tag), "r"(mask) : "memory");
}
__device__ __forceinline__ void poll_kvp(uint32_t (&v)[16], const void* p, uint32_t tag, uint32_t mask) {
  asm volatile("{\n.reg .pred p, q;\n.reg .u32 c, b;\n.reg .b64 x, y;\n.reg .b128 z;\nmov.u32 c, 0;\nLW:\n"
               "ld.relaxed.gpu.global.b128 z, [%16+0];\nmov.b128 {x, y}, z;\nmov.b64 {%0,%1}, x;\nmov.b64 {%2,%3}, y;\n"
               "ld.relaxed.gpu.global.b128 z, [%16+8192];\nmov.b128 {x, y}, z;\nmov.b64 {%4,%5}, x;\nmov.b64 {%6,%7}, y;\n"
               "ld.relaxed.gpu.global.b128 z, [%16+16384];\nmov.b128 {x, y}, z;\nmov.b64 {%8,%9}, x;\nmov.b64 {%10,%11}, y;\n"
               "ld.relaxed.gpu.global.b128 z, [%16+24576];\nmov.b128 {x, y}, z;\nmov.b64 {%12,%13}, x;\nmov.b64 {%14,%15}, y;\n"
               "xor.b32 b, %0, %17;\n"
               "lop3.b32 b, b, %4, %17, 0xf6;\nlop3.b32 b, b, %8, %17, 0xf6;\nlop3.b32 b, b, %12, %17, 0xf6;\n"
               "and.b32 b, b, %18;\nsetp.eq.u32 p, b, 0;\nvote.sync.all.pred p, p, 0xffffffff;\n@p bra.uni LD;\n"
               "nanosleep.u32 50;\nadd.u32 c, c, 1;\nsetp.lt.u32 q, c, 1000000;\n@q bra.uni LW;\ntrap;\nLD:\n}"
               : "=&r"(v[0]), "=&r"(v[1]), "=&r"(v[2]), "=&r"(v[3]), "=&r"(v[4]), "=&r"(v[5]), "=&r"(v[6]), "=&r"(v[7]), "=&r"(v[8]), "=&r"(v[9]), "=&r"(v[10]), "=&r"(v[11]), "=&r"(v[12]), "=&r"(v[13]), "=&r"(v[14]), "=&r"(v[15])
               : "l"(p), "r"(tag), "r"(mask) : "memory");
}

__device__ __align__(1024) __nv_bfloat16 g_o[2048 * 1024];
__device__ __align__(128) uint2 g_keys[2048];
__device__ __align__(128) uint32_t g_csum[18 * 1024];
__device__ __align__(128) uint32_t g_z[16 * 1024];
__device__ __align__(128) uint4 g_kvp[128 * 512];
__device__ __align__(128) uint4 g_kv[8 * 512];
__device__ __align__(128) uint32_t g_h[112 * 256];
__device__ __align__(128) uint32_t g_yp[128 * 512];
__device__ __align__(128) uint2 g_sel[8 * 16];
enum { H_CS = 0, H_KVP = 8, H_KV = 16, H_H = 24, H_Y = 32, H_O = 40, H_Z = 56 };
__device__ __align__(128) uint32_t g_sig[64 * 32];
__device__ uint32_t g_epoch;

constexpr uint32_t RING = 1024, SLOT = 32768, SMEM_BYTES = 232448;
constexpr int NST = 5, HST = 7;
constexpr uint32_t STG = RING + 163840, AUX = RING + 196608, FR = RING + 212992, MISC = RING + 229376;
constexpr uint32_t B_FULL = MISC, B_EMPTY = MISC + 56, B_XS = MISC + 112, B_SEL = MISC + 144, B_WK = MISC + 160, B_CSDN = MISC + 168,
                   B_FR = MISC + 176, B_FE = MISC + 200, B_DR = MISC + 224, B_CSV = MISC + 248,
                   B_DND = MISC + 256, B_XRES = MISC + 264, B_PFREE = MISC + 280, B_SFREE = MISC + 288, B_KVL = MISC + 296, NBAR = 38;
constexpr uint32_t S_EPOCH = MISC + 352, S_NCAND = MISC + 356, S_SEL = MISC + 368, S_WMAX = MISC + 432,
                   S_KSTAT = MISC + 512, S_CSK = MISC + 1536, S_CSV = MISC + 2048, S_CSQ = MISC + 2560, S_ONES = MISC + 512;
constexpr uint32_t KVB = AUX, HOP = AUX + 10240, FONES = AUX + 6144, GR = FR - 8192;
enum { NB_Z = 0, NB_KV = 1, NB_VQ = 2, NB_WG0 = 3, NB_FDONE = 4, NB_PK = 5, NB_KVB = 6, NB_WG1 = 7, NB_WG2 = 8, NB_CSQ = 9,
       NB_Y = 10, NB_ST = 11, NB_OWN0 = 12, NB_OWN1 = 13, NB_Q0 = 14, NB_H1 = 15 };

#define XS_FLY 2
#define FFN_GAP 400
#define PF_GAP 200
#define PF_WAIT 1000
#define GPCMAP 0x75143620u
#define KV_SPEC 0
#define HAND_K 2
constexpr uint64_t EVICT_FIRST = 0x12f0000000000000ull;
constexpr float LOG2E = 1.4426950408889634f, LN2 = 0.6931471805599453f;

#define ELECT "{\n.reg .pred p;\nelect.sync _|p, 0xffffffff;\n"
#define TMA2D "cp.async.bulk.tensor.2d.shared::cluster.global.mbarrier::complete_tx::bytes"
#define TMA3D "cp.async.bulk.tensor.3d.shared::cluster.global.mbarrier::complete_tx::bytes"
__device__ __forceinline__ void e_expect(uint32_t b, uint32_t n) {
  asm volatile(ELECT "@p mbarrier.arrive.expect_tx.shared::cta.b64 _, [%0], %1;\n}" ::"r"(b), "r"(n) : "memory");
}
__device__ __forceinline__ void e_arrive(uint32_t b) { asm volatile(ELECT "@p mbarrier.arrive.shared::cta.b64 _, [%0];\n}" ::"r"(b) : "memory"); }
__device__ __forceinline__ void e_tma2d(uint32_t dst, const CUtensorMap* m, int c0, int c1, uint32_t bar) {
  asm volatile(ELECT "@p " TMA2D " [%0], [%1, {%3, %4}], [%2];\n}" ::"r"(dst), "l"(m), "r"(bar), "r"(c0), "r"(c1) : "memory");
}
__device__ __forceinline__ void e_tma2d_ef(uint32_t dst, const CUtensorMap* m, int c0, int c1, uint32_t bar, uint64_t pol) {
  asm volatile(ELECT "@p " TMA2D ".L2::cache_hint [%0], [%1, {%3, %4}], [%2], %5;\n}" ::"r"(dst), "l"(m), "r"(bar), "r"(c0), "r"(c1), "l"(pol) : "memory");
}
__device__ __forceinline__ void e_tma3d(uint32_t dst, const CUtensorMap* m, int c1, int c2, uint32_t bar) {
  asm volatile(ELECT "@p " TMA3D " [%0], [%1, {0, %3, %4}], [%2];\n}" ::"r"(dst), "l"(m), "r"(bar), "r"(c1), "r"(c2) : "memory");
}
__device__ __forceinline__ void e_store2d(const CUtensorMap* m, int c0, int c1, uint32_t src) {
  asm volatile(ELECT "@p cp.async.bulk.tensor.2d.global.shared::cta.bulk_group [%0, {%2, %3}], [%1];\n}" ::"l"(m), "r"(src), "r"(c0), "r"(c1) : "memory");
}
__device__ __forceinline__ void e_tma3d_ef(uint32_t dst, const CUtensorMap* m, int c0, int c1, uint32_t bar, uint64_t pol) {
  asm volatile(ELECT "@p " TMA3D ".L2::cache_hint [%0], [%1, {%3, %4, 0}], [%2], %5;\n}" ::"r"(dst), "l"(m), "r"(bar), "r"(c0), "r"(c1), "l"(pol) : "memory");
}
__device__ __forceinline__ void e_load(uint32_t dst, const void* src, uint32_t n, uint32_t bar) {
  asm volatile(ELECT "@p cp.async.bulk.shared::cluster.global.mbarrier::complete_tx::bytes [%0], [%1], %2, [%3];\n}" ::"r"(dst), "l"(src), "r"(n), "r"(bar) : "memory");
}
__device__ __forceinline__ void e_pfmap(const CUtensorMap* m) { asm volatile(ELECT "@p prefetch.tensormap [%0];\n}" ::"l"(m) : "memory"); }
__device__ __forceinline__ void bulk_wait_read() { asm volatile("cp.async.bulk.commit_group;\ncp.async.bulk.wait_group.read 0;" ::: "memory"); }
__device__ __forceinline__ void e_signal(int word, int bit) {
  asm volatile(ELECT "@p red.relaxed.gpu.global.xor.b32 [%0], %1;\n}" ::"l"(g_sig + word * 32), "r"(1u << bit) : "memory");
}
__device__ __forceinline__ void await(int word, uint32_t mask, uint32_t ep) {
  uint32_t f[1];
  poll1f(f, g_sig + word * 32, 0u - (ep & 1u), mask);
}

__device__ __forceinline__ void mbar_arrive(uint32_t b) { asm volatile("mbarrier.arrive.shared::cta.b64 _, [%0];" ::"r"(b) : "memory"); }
__device__ __forceinline__ void mbar_wait(uint32_t b, uint32_t ph) {
  asm volatile("{\n.reg .pred p, q;\n.reg .u32 c;\nmov.u32 c, 0;\nLW:\nmbarrier.try_wait.parity.shared::cta.b64 p, [%0], %1;\n@p bra LD;\n"
               "add.u32 c, c, 1;\nsetp.lt.u32 q, c, 100000;\n@q bra LW;\ntrap;\nLD:\n}" ::"r"(b), "r"(ph) : "memory");
}
__device__ __forceinline__ void nb_sync(int id, int n) { asm volatile("bar.sync %0, %1;" ::"r"(id), "r"(n) : "memory"); }
__device__ __forceinline__ void nb_arrive(int id, int n) { asm volatile("bar.arrive %0, %1;" ::"r"(id), "r"(n) : "memory"); }
__device__ __forceinline__ void wg_fence() { asm volatile("wgmma.fence.sync.aligned;" ::: "memory"); }
__device__ __forceinline__ void wg_commit() { asm volatile("wgmma.commit_group.sync.aligned;" ::: "memory"); }
template <int N> __device__ __forceinline__ void wg_wait() { asm volatile("wgmma.wait_group.sync.aligned %0;" ::"n"(N) : "memory"); }
template <int N> __device__ __forceinline__ void reg_fence(float (&a)[N]) {
#pragma unroll
  for (int i = 0; i < N; i++) asm volatile("" : "+f"(a[i])::"memory");
}
template <int N> __device__ __forceinline__ void reg_zero(float (&a)[N]) {
#pragma unroll
  for (int i = 0; i < N; i++) a[i] = 0.f;
}
__device__ __forceinline__ constexpr uint64_t mkdesc(uint32_t addr, uint32_t lbo, uint32_t sbo, uint32_t swz) {
  return (uint64_t)(addr >> 4) | ((uint64_t)(lbo >> 4) << 16) | ((uint64_t)(sbo >> 4) << 32) | ((uint64_t)swz << 62);
}
__device__ __forceinline__ void fence_async_smem() { asm volatile("fence.proxy.async.shared::cta;" ::: "memory"); }
__device__ __forceinline__ void st_relaxed(uint32_t* p, uint32_t v) { asm volatile("st.relaxed.gpu.global.u32 [%0], %1;" ::"l"(p), "r"(v) : "memory"); }
__device__ __forceinline__ uint32_t ld_relaxed(const uint32_t* p) { uint32_t v; asm volatile("ld.relaxed.gpu.global.u32 %0, [%1];" : "=r"(v) : "l"(p) : "memory"); return v; }
__device__ __forceinline__ void st_unit(uint4* p, uint32_t a, uint32_t b, uint32_t c, uint32_t d, uint32_t par) {
  asm volatile("{\n.reg .b64 x, y;\n.reg .b128 z;\nmov.b64 x, {%1,%2};\nmov.b64 y, {%3,%4};\nmov.b128 z, {x, y};\nst.relaxed.gpu.global.b128 [%0], z;\n}"
               ::"l"(p), "r"((a & ~1u) | par), "r"(b), "r"(c), "r"(d) : "memory");
}
__device__ __forceinline__ uint4 lds128(uint32_t a) { uint4 v; asm volatile("ld.shared.v4.u32 {%0,%1,%2,%3}, [%4];" : "=r"(v.x), "=r"(v.y), "=r"(v.z), "=r"(v.w) : "r"(a)); return v; }
__device__ __forceinline__ float4 lds128f(uint32_t a) { float4 v; asm volatile("ld.shared.v4.f32 {%0,%1,%2,%3}, [%4];" : "=f"(v.x), "=f"(v.y), "=f"(v.z), "=f"(v.w) : "r"(a)); return v; }
__device__ __forceinline__ float4 lds128v(uint32_t a) { float4 v; asm volatile("ld.volatile.shared.v4.f32 {%0,%1,%2,%3}, [%4];" : "=f"(v.x), "=f"(v.y), "=f"(v.z), "=f"(v.w) : "r"(a) : "memory"); return v; }
__device__ __forceinline__ float lds32v(uint32_t a) { float v; asm volatile("ld.volatile.shared.f32 %0, [%1];" : "=f"(v) : "r"(a) : "memory"); return v; }
__device__ __forceinline__ float2 lds64f(uint32_t a) { float2 v; asm volatile("ld.shared.v2.f32 {%0,%1}, [%2];" : "=f"(v.x), "=f"(v.y) : "r"(a)); return v; }
__device__ __forceinline__ uint32_t lds32(uint32_t a) { uint32_t v; asm volatile("ld.shared.u32 %0, [%1];" : "=r"(v) : "r"(a)); return v; }
__device__ __forceinline__ void sts128(uint32_t a, uint32_t x, uint32_t y, uint32_t z, uint32_t w) { asm volatile("st.shared.v4.u32 [%0], {%1,%2,%3,%4};" ::"r"(a), "r"(x), "r"(y), "r"(z), "r"(w) : "memory"); }
__device__ __forceinline__ void sts128f(uint32_t a, float x, float y, float z, float w) { asm volatile("st.shared.v4.f32 [%0], {%1,%2,%3,%4};" ::"r"(a), "f"(x), "f"(y), "f"(z), "f"(w) : "memory"); }
__device__ __forceinline__ void sts64(uint32_t a, uint32_t x, uint32_t y) { asm volatile("st.shared.v2.u32 [%0], {%1,%2};" ::"r"(a), "r"(x), "r"(y) : "memory"); }
__device__ __forceinline__ void sts32(uint32_t a, uint32_t x) { asm volatile("st.shared.u32 [%0], %1;" ::"r"(a), "r"(x) : "memory"); }
__device__ __forceinline__ void stsm4(uint32_t a, uint32_t r0, uint32_t r1, uint32_t r2, uint32_t r3) {
  asm volatile("stmatrix.sync.aligned.m8n8.x4.shared.b16 [%0], {%1,%2,%3,%4};" ::"r"(a), "r"(r0), "r"(r1), "r"(r2), "r"(r3) : "memory");
}
__device__ __forceinline__ uint4 ldsm4(uint32_t a) {
  uint4 v; asm volatile("ldmatrix.sync.aligned.m8n8.x4.shared.b16 {%0,%1,%2,%3}, [%4];" : "=r"(v.x), "=r"(v.y), "=r"(v.z), "=r"(v.w) : "r"(a) : "memory"); return v;
}
__device__ __forceinline__ uint32_t pack(float lo, float hi) { uint32_t r; asm("cvt.rn.bf16x2.f32 %0, %1, %2;" : "=r"(r) : "f"(hi), "f"(lo)); return r; }
__device__ __forceinline__ float bf_lo(uint32_t w) { return __uint_as_float(w << 16); }
__device__ __forceinline__ float bf_hi(uint32_t w) { return __uint_as_float(w & 0xffff0000u); }
__device__ __forceinline__ float bf_round(float x) { return bf_lo(pack(x, x)); }
__device__ __forceinline__ float ex2(float x) { float v; asm("ex2.approx.ftz.f32 %0, %1;" : "=f"(v) : "f"(x)); return v; }
__device__ __forceinline__ float rcp(float x) { float v; asm("rcp.approx.ftz.f32 %0, %1;" : "=f"(v) : "f"(x)); return v; }
__device__ __forceinline__ float addsat(float a, float b) { float v; asm("add.sat.f32 %0, %1, %2;" : "=f"(v) : "f"(a), "f"(b)); return v; }
__device__ __forceinline__ float phi2(float a) { return fmaf(fmaxf(a, 0.f), LN2, addsat(ex2(a), 1e-6f)); }
__device__ __forceinline__ float key_score(uint32_t key) { uint32_t u = key >> 16; u = (u & 0x8000u) ? (u & 0x7fffu) : (~u & 0xffffu); return __uint_as_float(u << 16); }
__device__ __forceinline__ int key_token(uint32_t key) { return 2047 - (int)((key >> 5) & 2047u); }
__device__ __forceinline__ uint32_t bsel(uint32_t a, uint32_t b, uint32_t m) { uint32_t r; asm("lop3.b32 %0, %1, %2, %3, 0xd8;" : "=r"(r) : "r"(a), "r"(b), "r"(m)); return r; }
__device__ __forceinline__ uint32_t prmt(uint32_t a, uint32_t b, uint32_t c) { uint32_t r; asm("prmt.b32 %0, %1, %2, %3;" : "=r"(r) : "r"(a), "r"(b), "r"(c)); return r; }
__device__ __forceinline__ uint32_t tagf(float v, uint32_t par) { return (__float_as_uint(v) & ~1u) | par; }
__device__ __forceinline__ float xred(float a, float b, bool up, int o) { return (up ? b : a) + __shfl_xor_sync(0xffffffffu, up ? a : b, o); }

#define STAMP(id)
#define STAMP_IF(c, id)
#define STAMP2(i)
#define LITE 1
#define LITE_MASK 0ull

template <bool TRANS, int NK = 16>
__device__ __forceinline__ void mainloop(float (&a0)[64], float (&a1)[64], int s, int ph, int handoff, int xpair, bool leader) {
  uint32_t prev = 0;
#pragma unroll 1
  for (int kt = 0; kt < NK; kt++) {
    const bool xr = !TRANS && (kt >> 1) == xpair;
    mbar_wait(B_FULL + 8 * s, ph);
    const uint64_t dw = mkdesc(RING, 8192, 1024, 1) + s * (SLOT >> 4), dx = mkdesc(0, 16, 1024, 1) + (xr ? (STG >> 4) + (kt & 1) * 1024 : ((RING + 16384) >> 4) + s * (SLOT >> 4));
    if (xr) mbar_wait(B_XRES + 8 * (kt & 1), 0);
    wg_fence();
#pragma unroll
    for (int j = 0; j < 4; j++) {
      if (TRANS) {
        wgmma_n128_ss<1, 0>(a0, dw + j * 128, dx + j * 2, 1);
        wgmma_n128_ss<1, 0>(a1, dw + j * 128 + 512, dx + j * 2, 1);
      } else {
        wgmma_n128_ss<0, 1>(a0, dx + j * 2, dw + j * 128, 1);
        wgmma_n128_ss<0, 1>(a1, dx + j * 2 + 512, dw + j * 128, 1);
      }
    }
    wg_commit();
    if (handoff && kt == 15) nb_arrive(handoff, 256);
    wg_wait<1>();
    if (prev && leader) mbar_arrive(prev);
    prev = B_EMPTY + 8 * s;
    if (++s == NST) { s = 0; ph ^= 1; }
  }
  if (NK < 16) return;
  wg_wait<0>();
  if (leader) mbar_arrive(prev);
  reg_fence(a0);
  reg_fence(a1);
}

__device__ __forceinline__ int out_kblock(int r, int tn) {
  const int q = r - 2, half = q >= 7, pi = q - 7 * half;
  return r < 2 ? 2 * tn + r : 2 * ((pi + (pi >= (tn & 3))) ^ (tn & 4)) + half;
}

struct Params {
  const char *x, *wqkv, *w_r, *wg, *wu, *wd;
  CUtensorMap m_wqkv, m_x, m_xs, m_o, m_os, m_wo, m_gu, m_down, m_out;
};

template <bool BY_SMID>
__global__ void __launch_bounds__(512, 1) fused_kernel(const __grid_constant__ Params mp) {
  extern __shared__ __align__(1024) uint8_t smem_raw[];
#define CK(i)
  CK(0);
  const int tid = threadIdx.x, lane = tid & 31;
  const int w = __shfl_sync(0xffffffffu, tid >> 5, 0);
  int bid = blockIdx.x;
  if (BY_SMID) {
    uint32_t sm;
    asm volatile("mov.u32 %0, %%smid;" : "=r"(sm));
    const uint32_t p = sm >> 1, q = ((p - 32) * 37) >> 8;
    const uint32_t gpc = p < 32 ? p & 7 : p < 60 ? p - 31 - 7 * q : 0, tpc = p < 32 ? p >> 3 : p < 60 ? 4 + q : p - 58;
    bid = (p >> 1) == 30 ? 128 + ((0x9cu >> (2 * (sm & 3))) & 3) : ((GPCMAP >> (4 * gpc)) & 7) * 16 + tpc * 2 + (sm & 1);
  }
  const int tn = (bid & 3) + 4 * (bid >> 6), tm = (bid >> 2) & 15;

  CK(1);
  if (w == 0) {
#pragma unroll 1
    for (int s = 0; s < NST; s++) {
      asm volatile(ELECT "@p mbarrier.init.shared::cta.b64 [%0], 1;\n}" ::"r"(B_FULL + 8 * s) : "memory");
      if (bid < 128) {
        e_expect(B_FULL + 8 * s, 32768);
        e_tma2d(RING + s * SLOT + 16384, &mp.m_x, s * 64, tm * 128, B_FULL + 8 * s);
        e_tma3d(RING + s * SLOT, &mp.m_wqkv, s * 64, 16 + 2 * tn, B_FULL + 8 * s);
      }
      if (s == 0) CK(2);
    }
  }
  if (w == 1) e_pfmap(&mp.m_wqkv);
  if (w == 2) e_pfmap(&mp.m_xs);
  if (w >= 4) {
#pragma unroll 1
    for (uint32_t b = MISC + 8 * (w + 1); b < MISC + 8 * NBAR; b += 96)
      asm volatile(ELECT "@p mbarrier.init.shared::cta.b64 [%0], %1;\n}" ::"r"(b), "r"(b == B_CSDN ? 4 : 1) : "memory");
    if (w == 15) sts32(S_NCAND, 0);
  }
  CK(3);
  asm volatile("fence.mbarrier_init.release.cluster;" ::: "memory");
  __syncthreads();

  if (bid >= 128) {
    const int h0 = bid - 128, hs = 4, h1 = 16;
    if (w == 12) {
      int s = 0, ph = 1;
#pragma unroll 1
      for (int h = h0; h < h1; h += hs) {
        const int c = 2 * h + (h & 8) * 2;
        if (h == 8) mbar_wait(B_SEL, 0);
#pragma unroll 1
        for (int kt = 0; kt < 16; kt += 2) {
          mbar_wait(B_EMPTY + 8 * s, ph);
          e_expect(B_FULL + 8 * s, 32768);
          e_tma3d(RING + s * SLOT, &mp.m_wqkv, kt * 64, c, B_FULL + 8 * s);
          e_tma3d(RING + s * SLOT + 16384, &mp.m_wqkv, kt * 64 + 64, c, B_FULL + 8 * s);
          if (++s == HST) { s = 0; ph ^= 1; }
        }
      }
    } else if (w < 4) {
      const uint32_t par = (ld_relaxed(&g_epoch) + 1) & 1u;
      sts32(S_ONES + tid * 4, 0x3f803f80u);
      fence_async_smem();
      nb_sync(NB_WG0, 128);
      int s = 0, ph = 0;
#pragma unroll 1
      for (int h = h0; h < h1; h += hs) {
        float c[4][4];
#pragma unroll
        for (int i = 0; i < 4; i++) reg_zero(c[i]);
        uint32_t prev = 0;
#pragma unroll 1
        for (int kt = 0; kt < 8; kt++) {
          mbar_wait(B_FULL + 8 * s, ph);
          const uint64_t dw = mkdesc(RING, 8192, 1024, 1) + s * (SLOT >> 4);
          wg_fence();
#pragma unroll
          for (int j = 0; j < 16; j++) wgmma_n8_ss<1, 0>(c[j & 3], dw + (j & 3) * 512 + (j >> 2) * 128, mkdesc(S_ONES, 128, 128, 0), 1);
          wg_commit();
          wg_wait<1>();
          if (prev && tid == 0) mbar_arrive(prev);
          prev = B_EMPTY + 8 * s;
          if (++s == HST) { s = 0; ph ^= 1; }
        }
        wg_wait<0>();
        if (tid == 0) mbar_arrive(prev);
        if (tid == 0 && h == 4) mbar_arrive(B_XRES);
#pragma unroll
        for (int i = 0; i < 4; i++) reg_fence(c[i]);
        const bool u2 = lane & 2, u1 = lane & 1;
        const float lo = u2 ? c[1][0] + c[3][0] : c[0][0] + c[2][0], hi = u2 ? c[1][2] + c[3][2] : c[0][2] + c[2][2];
        st_relaxed(g_csum + h * 128 + (lane & 2) * 32 + w * 16 + (lane & 1) * 8 + (lane >> 2), tagf(u1 ? hi : lo, par));
        STAMP_IF(tid == 0, h >= 8 ? 6 : 30);
      }
    } else if (w < 12 && bid == 128) {
      const int t = tid - 128, j = w - 4;
      const uint32_t ep = ld_relaxed(&g_epoch) + 1;
      uint32_t kk[16];
      poll_keys(kk, g_keys + t * 2, ep, 31u);
      STAMP_IF(t == 0, 42);
      const uint32_t m = __reduce_max_sync(0xffffffffu, max(max(max(kk[0], kk[2]), max(kk[4], kk[6])), max(max(kk[8], kk[10]), max(kk[12], kk[14]))));
      if (lane == 0) sts32(S_WMAX + j * 4, m);
      mbar_wait(B_XRES, 0);
      nb_sync(NB_WG1, 256);
      const uint32_t T = __reduce_min_sync(0xffffffffu, lds32(S_WMAX + (lane & 7) * 4));
      uint32_t cnt = 0;
#pragma unroll
      for (int i = 0; i < 8; i++) cnt += kk[2 * i] >= T;
      if (cnt) {
        uint32_t pos;
        asm volatile("atom.shared.add.u32 %0, [%1], %2;" : "=r"(pos) : "r"(S_NCAND), "r"(cnt * 8) : "memory");
#pragma unroll
        for (int i = 0; i < 8; i++)
          if (kk[2 * i] >= T) { sts64(AUX + pos, kk[2 * i], kk[2 * i + 1]); pos += 8; }
      }
      nb_sync(NB_WG1, 256);
      const uint32_t n8 = lds32(S_NCAND);
#pragma unroll 1
      for (uint32_t i = j * 8; i < n8; i += 64) {
        const float2 c = lds64f(AUX + i);
        uint32_t rank = 0;
#pragma unroll 1
        for (uint32_t q = lane * 8; q < n8 + lane * 8; q += 256) rank += __popc(__ballot_sync(0xffffffffu, q < n8 && lds32(AUX + q) > __float_as_uint(c.x)));
        if (rank < 8) sts64(S_SEL + rank * 8, __float_as_uint(c.x), __float_as_uint(c.y));
      }
      fence_async_smem();
      nb_sync(NB_WG1, 256);
      if (j == 0) {
        const uint4 v = lds128(S_SEL + (lane & 3) * 16);
        asm volatile("{\n.reg .b64 x, y;\nmov.b64 x, {%1,%2};\nmov.b64 y, {%3,%4};\nst.relaxed.gpu.global.v2.b64 [%0], {x, y};\n}"
                     ::"l"(g_sel + (lane >> 2) * 16 + (lane & 3) * 2), "r"(v.x), "r"(v.y), "r"(v.z), "r"(v.w) : "memory");
        e_arrive(B_SEL);
      }
      STAMP_IF(t == 0, 45);
    }
  } else if (w >= 12) {
    asm volatile("setmaxnreg.dec.sync.aligned.u32 32;");
    if (w == 12) {
      int s = 0, ph = 0;
#pragma unroll 1
      for (int it = NST; it < 48; it++) {
        const int c = (it < 32 ? (it & 16) + 16 : 0) + 2 * tn;
        const int k0 = ((it + (it >= 32 && tn < 4 ? 8 : 0)) & 15) * 64;
        const bool xr = (it >> 1) == 20 + (tn & 3);
        if (xr) { mbar_wait(B_SFREE, 0); e_expect(B_XRES + 8 * (it & 1), 16384); }
        mbar_wait(B_EMPTY + 8 * s, ph);
        e_expect(B_FULL + 8 * s, xr ? 16384 : 32768);
        e_tma3d(RING + s * SLOT, &mp.m_wqkv, k0, c, B_FULL + 8 * s);
        e_tma2d(xr ? STG + (it & 1) * 16384 : RING + s * SLOT + 16384, &mp.m_x, k0, tm * 128, xr ? B_XRES + 8 * (it & 1) : B_FULL + 8 * s);
        if (it >= NST) STAMP2(it - NST);
        if (++s == NST) { s = 0; ph ^= 1; }
      }
#pragma unroll 1
      for (int r = 0; r < 16; r++) {
        const int kb = out_kblock(r, tn);
        mbar_wait(B_EMPTY + 8 * s, ph);
        e_expect(B_FULL + 8 * s, r < 2 ? 16384 : 32768);
        e_tma3d(RING + s * SLOT, &mp.m_wo, kb * 64, 2 * tn, B_FULL + 8 * s);
        if (r < 2 || r == 4) {
          const uint32_t bar = B_DR + (r < 2 ? 16 : 8);
          const int k0 = (bid >> 4) * 448 + 128 + min(r, 2) * 128;
          if (r != 1) e_expect(bar, r ? 8192 : 32768);
          e_tma2d_ef(RING + s * SLOT + 16384, &mp.m_down, (bid & 15) * 64, k0, bar, EVICT_FIRST);
          if (r < 2) e_tma2d_ef(RING + s * SLOT + 24576, &mp.m_down, (bid & 15) * 64, k0 + 64, bar, EVICT_FIRST);
        }
        STAMP2(r + 48 - NST);
        if (++s == NST) { s = 0; ph ^= 1; }
      }
    } else if (w == 13) {
      mbar_wait(B_FULL, 0);
#pragma unroll 1
      for (int c = 0; c < 4; c++) {
        if (c >= XS_FLY) mbar_wait(B_XS + 8 * (c - XS_FLY), 0);
        if (c == (tm >> 2)) {
          e_expect(B_WK, 16384);
          e_tma3d(FR, &mp.m_wqkv, tm * 64, 16 + 2 * tn, B_WK);
        }
        e_expect(B_XS + 8 * c, 8192);
        e_tma2d(STG + c * 8192, &mp.m_xs, c * 256, tm * 128 + tn * 16, B_XS + 8 * c);
      }
      {
        const char* pd = mp.wd + (bid & 15) * 128 + ((bid >> 4) * 448 + lane) * 2048;
        mbar_wait(B_XS + 24, 0);
        __nanosleep(PF_WAIT);
#pragma unroll 1
        for (int i = 0; i < 14; i++, pd += 65536) {
          if (PF_GAP) asm volatile("prefetch.global.L2 [%0];" ::"l"(pd));
          if (PF_GAP) __nanosleep(PF_GAP);
        }
      }
      nb_sync(NB_Z, 160);
      const uint32_t ep = lds32(S_EPOCH);
      {
        float z[4] = {0.f, 0.f, 0.f, 0.f};
        e_signal(H_Z + tn, tm);
        await(H_Z + tn, 0xffffu, ep);
#pragma unroll 1
        for (int i = 0; i < 4; i++) {
          uint32_t p[16];
          poll_z(p, g_z + i * 4096 + tn * 128 + lane * 4, ep, 1u);
#pragma unroll
          for (int q = 0; q < 4; q++) z[q] += (__uint_as_float(p[q]) + __uint_as_float(p[4 + q])) + (__uint_as_float(p[8 + q]) + __uint_as_float(p[12 + q]));
        }
        const uint32_t z01 = pack(z[0], z[1]), z23 = pack(z[2], z[3]);
        if (bid < 112) mbar_wait(B_PFREE, 0);
#pragma unroll
        for (int n = 0; n < 8; n++) sts64(KVB + (lane >> 4) * 5120 + n * 128 + ((((lane >> 1) & 7) ^ n) << 4) + (lane & 1) * 8, z01, z23);
        fence_async_smem();
        nb_arrive(NB_KVB, 320);
        STAMP_IF(lane == 0, 46);
      }
      nb_sync(NB_Q0, 192);
      e_store2d(&mp.m_os, tn * 128, tm * 128, STG);
      nb_sync(NB_OWN0, 288);
      e_store2d(&mp.m_os, tn * 128, tm * 128 + 64, STG + 8192);
      bulk_wait_read();
      e_signal(H_O + tm, 2 * tn);
      STAMP_IF(lane == 0, 4);
      nb_sync(NB_H1, 160);
      e_store2d(&mp.m_os, tn * 128 + 64, tm * 128, STG + 16384);
      e_store2d(&mp.m_os, tn * 128 + 64, tm * 128 + 64, STG + 24576);
      bulk_wait_read();
      e_signal(H_O + tm, 2 * tn + 1);
      STAMP_IF(lane == 0, 5);
      nb_arrive(NB_ST, 288);
    } else if (w == 14) {
      e_pfmap(&mp.m_gu); e_pfmap(&mp.m_o); e_pfmap(&mp.m_os); e_pfmap(&mp.m_wo); e_pfmap(&mp.m_down); e_pfmap(&mp.m_out);
      const uint32_t ep = ld_relaxed(&g_epoch) + 1;
      nb_sync(NB_FDONE, 416);
      {
        uint32_t c[4];
        poll_quad(c, g_csum + tn * 128 + lane * 4, ep, 1u);
        sts128(S_CSQ + lane * 16, c[0], c[1], c[2], c[3]);
        nb_arrive(NB_CSQ, 160);
        poll_quad(c, g_csum + 1024 + tn * 128 + lane * 4, ep, 1u);
        sts128(S_CSV + lane * 16, c[0], c[1], c[2], c[3]);
        __syncwarp();
        e_arrive(B_CSV);
      }
      {
        mbar_wait(B_WK, 1);
        if (KV_SPEC) __nanosleep(KV_SPEC); else await(H_KV + tn, 0xffffu, ep);
        STAMP_IF(lane == 0, 7);
        if (bid < 112) mbar_wait(B_PFREE, 0);
        STAMP_IF(lane == 0, 23);
        uint32_t bad, ph = 0;
        do {
          e_expect(B_KVL, 8192);
          e_load(KVB + 1024, g_kv + tn * 512, 4096, B_KVL);
          e_load(KVB + 6144, g_kv + tn * 512 + 256, 4096, B_KVL);
          mbar_wait(B_KVL, ph & 1);
          bad = 0;
#pragma unroll
          for (int i = 0; i < 16; i++) bad |= __float_as_uint(lds32v(KVB + 1024 + (i & 8) * 128 + i * 512 + lane * 16)) ^ ep;
          bad = __any_sync(0xffffffffu, bad & 1u);
          if (bad) fence_async_smem();
        } while (bad && ++ph < 100000);
        nb_arrive(NB_KVB, 320);
        STAMP_IF(lane == 0, 24);
      }
      nb_sync(NB_Q0, 192);
      uint32_t ready = 0;
      int s = 0, ph = 1;
#pragma unroll 1
      for (int r = 2; r < 16; r++) {
        const int kb = out_kblock(r, tn);
        if (!((ready >> kb) & 1)) {
          uint32_t f[1];
          poll0(f, g_sig + (H_O + tm) * 32, 0u - (ep & 1u), 1u << kb);
          ready = f[0] ^ ((ep & 1u) - 1u);
        }
        if (r == 4) mbar_wait(B_DND, 0);
        mbar_wait(B_EMPTY + 8 * s, ph);
        e_tma2d(RING + s * SLOT + 16384, &mp.m_o, kb * 64, tm * 128, B_FULL + 8 * s);
        STAMP_IF(lane == 0 && r == 2, 2);
        STAMP_IF(lane == 0 && r == 9, 3);
        if (++s == NST) { s = 0; ph ^= 1; }
      }
    } else {
      uint32_t nsm = 132;
      if (BY_SMID) asm volatile("mov.u32 %0, %%nsmid;" : "=r"(nsm));
      asm volatile("{\n.reg .pred q;\nsetp.eq.u32 q, %0, 1156;\n@q bra LOK;\ntrap;\nLOK:\n}" ::"r"((uint32_t)__cvta_generic_to_shared(smem_raw) + nsm));
      const uint32_t ep = ld_relaxed(&g_epoch) + 1;
      mbar_wait(B_CSDN, 0);
#pragma unroll 1
      for (int n = 0; n < 3 && bid < 112; n++) {
        __nanosleep(FFN_GAP);
        e_expect(B_FR + 8 * n, 8192);
        e_tma3d_ef(GR + n * 8192, &mp.m_gu, bid * 32, n * 64, B_FR + 8 * n, EVICT_FIRST);
      }
      uint32_t sel[2];
      poll_pair(sel, g_sel + (bid >> 4) * 16 + (lane >> 2), ep, 31u);
      const char* xs = mp.x + key_token(sel[0]) * 2048 + (lane & 3) * 16;
      const uint32_t xd = AUX + (lane >> 2) * 64 + (((lane & 3) ^ (lane >> 3)) << 4);
      auto slices = [&](int n, int p) {
        asm volatile("cp.async.cg.shared.global [%0], [%1], 16;\ncp.async.cg.shared.global [%0+512], [%1+64], 16;\ncp.async.commit_group;"
                     ::"r"(xd + p * 1024), "l"(xs + n * 128) : "memory");
      };
      if ((lane & 3) == 0) sts64(S_SEL + lane * 2, sel[0], sel[1]);
      if (bid < 112) {
#pragma unroll
        for (int i = 0; i < 6; i++) slices(i, i);
      }
      asm volatile("cp.async.wait_group 2;" ::: "memory");
      fence_async_smem();
      __syncwarp();
      e_arrive(B_SEL);
      if (bid < 112) {
        int s = 0, ph = 0;
#pragma unroll 1
        for (int n = 3; n < 16; n++) {
          mbar_wait(B_FE + 8 * s, ph);
          e_expect(B_FR + 8 * s, 8192);
          e_tma3d_ef(GR + s * 8192, &mp.m_gu, bid * 32, n * 64, B_FR + 8 * s, EVICT_FIRST);
          STAMP2(64 + n);
          asm volatile("cp.async.wait_group 1;" ::: "memory");
          fence_async_smem();
          __syncwarp();
          if (n < 13) slices(n + 3, s + 3 * ph);
          else asm volatile("cp.async.commit_group;" ::: "memory");
          if (++s == 3) { s = 0; ph ^= 1; }
        }
      }
      e_expect(B_DR, 16384);
      if (bid < 112) mbar_wait(B_FE + 8, 0);
      e_tma2d_ef(FR, &mp.m_down, (bid & 15) * 64, (bid >> 4) * 448, B_DR, EVICT_FIRST);
      if (bid < 112) mbar_wait(B_FE + 16, 0);
      e_tma2d_ef(FR + 8192, &mp.m_down, (bid & 15) * 64, (bid >> 4) * 448 + 64, B_DR, EVICT_FIRST);
    }
  } else if (w >= 8) {
    asm volatile("setmaxnreg.dec.sync.aligned.u32 56;");
    const int t = tid - 256, ww = w - 8;
    const uint32_t ep = ld_relaxed(&g_epoch) + 1, par = ep & 1u;
    sts32(FONES + t * 4, 0x3f803f80u);
    {
      const int r0 = (lane >> 3) + (lane & 4);
      const uint32_t a = FR + (ww >> 1) * 8192 + r0 * 128 + ((((ww & 1) * 4 + (lane & 3)) ^ r0) << 4);
      float c[8];
      reg_zero(c);
      mbar_wait(B_WK, 0);
#pragma unroll 2
      for (int i = 0; i < 8; i++) {
        const uint4 v = lds128(a + i * 1024);
        c[0] += bf_lo(v.x); c[1] += bf_hi(v.x); c[2] += bf_lo(v.y); c[3] += bf_hi(v.y);
        c[4] += bf_lo(v.z); c[5] += bf_hi(v.z); c[6] += bf_lo(v.w); c[7] += bf_hi(v.w);
      }
      const bool u16 = lane & 16, u8 = lane & 8, u4 = lane & 4;
      const float d0 = xred(c[0], c[4], u16, 16), d1 = xred(c[1], c[5], u16, 16), d2 = xred(c[2], c[6], u16, 16), d3 = xred(c[3], c[7], u16, 16);
      fence_async_smem();
      e_arrive(B_CSDN);
      const float sum = xred(xred(d0, d2, u8, 8), xred(d1, d3, u8, 8), u4, 4);
      st_relaxed(g_csum + (2 + tm) * 1024 + tn * 128 + ww * 32 + (lane & 3) * 8 + (lane >> 2), tagf(sum, par));
      STAMP_IF(t == 0, 8);
      nb_sync(NB_WG2, 128);
      if (ww == 0) { e_signal(H_CS + tn, tm); await(H_CS + tn, 0xffffu, ep); }
      nb_sync(NB_WG2, 128);
      uint32_t p[16];
      poll16(p, g_csum + 2048 + tn * 128 + t, par, 1u);
      float tot = 0.f;
#pragma unroll
      for (int i = 0; i < 16; i += 4) tot += (__uint_as_float(p[i]) + __uint_as_float(p[i + 1])) + (__uint_as_float(p[i + 2]) + __uint_as_float(p[i + 3]));
      sts32(S_CSK + t * 4, __float_as_uint(tot));
      nb_arrive(NB_FDONE, 416);
      STAMP_IF(t == 0, 9);
    }
    const int ks = bid >> 4, nt = bid & 15;
    if (bid < 112) {
      float fg[8];
      reg_zero(fg);
      mbar_wait(B_SEL, 0);
      constexpr uint64_t DA0 = mkdesc(GR, 4096, 512, 2), DB0 = mkdesc(AUX, 16, FONES - AUX, 2), DBS = 32 - (32ull << 32);
      uint64_t da = DA0, db = DB0;
      uint32_t bar = B_FR, ph = 0;
#pragma unroll 1
      for (int n = 0; n < 16; n++) {
        mbar_wait(bar, ph);
        wg_fence();
#pragma unroll
        for (int q = 0; q < 4; q++) wgmma_n16_ss<1, 0>(fg, da + q * 64, db + (q >> 1) * DBS + (q & 1) * 2, 1);
        wg_commit();
        const uint32_t rel = bar + (B_FE - B_FR);
        const bool wrap = bar == B_FR + 16;
        da = wrap ? DA0 : da + 512;
        db = wrap && ph ? DB0 : db + 2 * DBS;
        bar = wrap ? B_FR : bar + 8;
        ph ^= wrap;
        wg_wait<0>();
        if (t == 0) mbar_arrive(rel);
      }
      if (t == 0) mbar_arrive(B_PFREE);
      const uint4 st = lds128(S_SEL + (lane & 3) * 16);
      const float r0 = rcp(bf_lo(st.y)), r1 = rcp(bf_lo(st.w));
      reg_fence(fg);
      const float fa[4] = {fmaf(-bf_hi(st.y), fg[4], fg[0]) * r0, fmaf(-bf_hi(st.w), fg[4], fg[1]) * r1,
                           fmaf(-bf_hi(st.y), fg[6], fg[2]) * r0, fmaf(-bf_hi(st.w), fg[6], fg[3]) * r1};
      STAMP_IF(t == 0, 12);
      const bool isup = (ww >> 1) != (mp.wu < mp.wg);
      nb_sync(NB_WG2, 128);
      if (isup) sts128f(HOP + (t & 63) * 16, fa[0], fa[1], fa[2], fa[3]);
      nb_sync(NB_WG2, 128);
      if (!isup) {
        const float4 u = lds128f(HOP + (t & 63) * 16);
        const float uu[4] = {u.x, u.y, u.z, u.w};
        uint32_t* hp = g_h + bid * 256 + (lane & 3) * 64 + (ww & 1) * 16 + (lane >> 2);
#pragma unroll
        for (int i = 0; i < 4; i++) {
          const float g = fa[i], hv = g * rcp(1.f + ex2(-g * LOG2E)) * uu[i];
          st_relaxed(hp + (i & 1) * 32 + (i >> 1) * 8, __byte_perm(pack(hv, hv), ep, 0x3254));
        }
      }
      nb_sync(NB_WG2, 128);
      if (ww == 0) e_signal(H_H + bid / 14, bid % 14);
    }
    {
      uint32_t v[28];
      if (ww == 0) await(H_H + ks, 0x3fffu, ep);
      nb_sync(NB_WG2, 128);
      poll7x4(v, g_h + ks * 3584 + t * 4, ep, 0xffffu);
      mbar_wait(B_WK, 1);
#pragma unroll
      for (int q = 0; q < 7; q++)
        asm volatile("st.shared.v2.u32 [%0], {%1,%2};" ::"r"((q < 6 ? HOP + q * 1024 : S_CSK) + (t >> 3) * 64 + ((((t >> 1) & 3) ^ ((t >> 4) & 3)) << 4) + (t & 1) * 8),
                     "r"(__byte_perm(v[4 * q], v[4 * q + 1], 0x7632)), "r"(__byte_perm(v[4 * q + 2], v[4 * q + 3], 0x7632)) : "memory");
      fence_async_smem();
      nb_sync(NB_WG2, 128);
    }
    STAMP_IF(t == 0, 13);
    float fa[4] = {0.f, 0.f, 0.f, 0.f};
    auto down = [&](uint32_t a, int k0, int nk) {
#pragma unroll
      for (int q = 0; q < nk; q++) wgmma_n8_ss<1, 0>(fa, mkdesc(a + q * 2048, 4096, 1024, 1), mkdesc((k0 < 24 ? HOP : S_CSK - 6144) + ((k0 + q) >> 1) * 512 + (q & 1) * 32, 16, 512, 2), 1);
    };
    mbar_wait(B_DR, 0);
    mbar_wait(B_DR + 16, 0);
    mbar_wait(B_DR + 8, 0);
    wg_fence();
    down(RING + 2 * SLOT + 16384, 24, 4);
    down(RING + 3 * SLOT + 16384, 8, 8);
    down(RING + 4 * SLOT + 16384, 16, 8);
    wg_commit();
    wg_fence();
    down(FR, 0, 8);
    wg_commit();
    wg_wait<1>();
    if (t == 0) mbar_arrive(B_DND);
    wg_wait<0>();
    reg_fence(fa);
    STAMP_IF(t == 0, 14);
    {
      uint32_t* yp = g_yp + (nt * 8 + ks) * 512 + (lane & 3) * 128 + ww * 16 + (lane >> 2);
#pragma unroll
      for (int i = 0; i < 4; i++) st_relaxed(yp + (i & 1) * 64 + (i >> 1) * 8, tagf(fa[i], par));
    }
    nb_sync(NB_WG2, 128);
    if (ww == 0) e_signal(H_Y + (nt >> 1), (nt & 1) * 8 + ks);
    mbar_wait(B_SEL, 0);
    const uint32_t mykey = lds32(S_SEL + (lane & 7) * 8);
    const uint32_t inmask = __ballot_sync(0xffffffffu, (key_token(mykey) >> 7) == tm) & 0xffu;
    sts128(FR + t * 16, 0u, 0u, 0u, 0u);
    if (inmask) {
      if (ww == 0) await(H_Y + tn, 0xffffu, ep);
      nb_sync(NB_WG2, 128);
      const float sg = rcp(1.f + ex2(-key_score(mykey) * LOG2E));
#pragma unroll 1
      for (uint32_t mine = __ballot_sync(0xffffffffu, ((inmask >> lane) & 1) && (__popc(inmask & ((1u << lane) - 1)) & 3) == ww); mine; mine &= mine - 1) {
        const int j = __ffs(mine) - 1;
        uint32_t p[32];
        poll8x4(p, g_yp + (tn * 2 + (lane >> 4)) * 4096 + j * 64 + (lane & 15) * 4, par, 1u);
        float y[4];
        const float sj = __shfl_sync(0xffffffffu, sg, j);
#pragma unroll
        for (int i = 0; i < 4; i++)
          y[i] = sj * (((__uint_as_float(p[i]) + __uint_as_float(p[4 + i])) + (__uint_as_float(p[8 + i]) + __uint_as_float(p[12 + i]))) +
                       ((__uint_as_float(p[16 + i]) + __uint_as_float(p[20 + i])) + (__uint_as_float(p[24 + i]) + __uint_as_float(p[28 + i]))));
        asm volatile("st.shared.v2.u32 [%0], {%1,%2};" ::"r"(FR + (lane >> 4) * 1024 + j * 128 + ((((lane >> 1) & 7) ^ j) << 4) + (lane & 1) * 8),
                     "r"(pack(y[0], y[1])), "r"(pack(y[2], y[3])) : "memory");
      }
    }
    fence_async_smem();
    nb_arrive(NB_ST, 288);
    STAMP_IF(t == 0, 15);
  } else if (w >= 4) {
    asm volatile("setmaxnreg.inc.sync.aligned.u32 208;");
    const int t = tid - 128, ww = w - 4, g = lane >> 2, t4 = lane & 3;
    const bool leader = t == 0;
    const uint32_t ep = ld_relaxed(&g_epoch) + 1, par = ep & 1u;
    {
      const uint4* wp = reinterpret_cast<const uint4*>(mp.w_r) + lane;
      uint4 w0 = __ldg(wp), w1 = __ldg(wp + 32), w2 = __ldg(wp + 64), w3 = __ldg(wp + 96);
      if (leader) sts32(S_EPOCH, ep);
      if (KV_SPEC && t4 == 0) {
        const int grp = (tm & 1) * 2 + ((lane >> 3) & 1), row = ww * 2 + ((lane >> 2) & 1);
        st_unit(g_kv + tn * 512 + ((tm >> 3) * 4 + grp) * 64 + row * 8 + (((tm & 2) * 2 + ((tm >> 1) & 2) + (lane >> 4)) ^ row), 0u, 0u, 0u, 0u, par ^ 1u);
      }
      float s[4] = {0.f, 0.f, 0.f, 0.f}, q[4] = {0.f, 0.f, 0.f, 0.f}, d[4] = {0.f, 0.f, 0.f, 0.f}, wsum = 0.f;
#pragma unroll 1
      for (int c = 0; c < 4; c++) {
        const float wr[8] = {bf_lo(w0.x), bf_hi(w0.x), bf_lo(w0.y), bf_hi(w0.y), bf_lo(w0.z), bf_hi(w0.z), bf_lo(w0.w), bf_hi(w0.w)};
        w0 = w1; w1 = w2; w2 = w3;
        wsum += ((wr[0] + wr[1]) + (wr[2] + wr[3])) + ((wr[4] + wr[5]) + (wr[6] + wr[7]));
        mbar_wait(B_XS + 8 * c, 0);
#pragma unroll
        for (int r = 0; r < 4; r++) {
          const uint4 v = lds128(STG + c * 8192 + (ww * 4 + r) * 512 + lane * 16);
          const uint32_t xw[4] = {v.x, v.y, v.z, v.w};
#pragma unroll
          for (int i = 0; i < 4; i++) {
            const uint32_t dep = __float_as_uint(q[i ? r : (r + 3) & 3]);
            const float lo = __uint_as_float(prmt(xw[i], dep, 0x10ff)), hi = __uint_as_float(prmt(xw[i], dep, 0x32ff));
            s[r] += lo; q[r] = fmaf(lo, lo, q[r]); d[r] = fmaf(lo, wr[2 * i], d[r]);
            s[r] += hi; q[r] = fmaf(hi, hi, q[r]); d[r] = fmaf(hi, wr[2 * i + 1], d[r]);
          }
        }
      }
      STAMP_IF(leader, 16);
      const bool u16 = lane & 16, u8 = lane & 8, u4 = lane & 4, u2 = lane & 2;
      const float s1 = xred(xred(s[0], s[2], u16, 16), xred(s[1], s[3], u16, 16), u8, 8);
      const float q1 = xred(xred(q[0], q[2], u16, 16), xred(q[1], q[3], u16, 16), u8, 8);
      const float d1 = xred(xred(d[0], d[2], u16, 16), xred(d[1], d[3], u16, 16), u8, 8);
      wsum += __shfl_xor_sync(0xffffffffu, wsum, 16);
      wsum += __shfl_xor_sync(0xffffffffu, wsum, 8);
      float tot = xred(xred(s1, d1, u4, 4), xred(q1, wsum, u4, 4), u2, 2);
      tot += __shfl_xor_sync(0xffffffffu, tot, 1);
      const float qq = __shfl_down_sync(0xffffffffu, tot, 2), dd = __shfl_down_sync(0xffffffffu, tot, 4), ws = __shfl_down_sync(0xffffffffu, tot, 6);
      if ((lane & 7) == 0) {
        const float mean = tot * (1.f / 1024.f);
        const float var = fmaxf(fmaf(-mean, mean, qq * (1.f / 1024.f)), 0.f);
        float sd;
        asm("sqrt.approx.ftz.f32 %0, %1;" : "=f"(sd) : "f"(bf_round(bf_round(var) + 1e-5f)));
        const uint32_t ms = pack(sd, mean);
        const int row = tm * 128 + tn * 16 + ww * 4 + (lane >> 3);
        const uint32_t rbits = pack(0.f, fmaf(-bf_hi(ms), ws, dd) * rcp(bf_lo(ms)));
        const uint32_t key = (rbits ^ (((int)rbits >> 31 & 0x7fff0000u) | 0x80000000u)) | ((2047 - row) << 5) | (ep & 31u);
        asm volatile("{\n.reg .b64 x;\nmov.b64 x, {%1,%2};\nst.relaxed.gpu.global.b64 [%0], x;\n}" ::"l"(g_keys + row), "r"(key), "r"(ms) : "memory");
      }
      STAMP_IF(leader, 17);
      __nanosleep(400);
      uint32_t st[2];
      poll_pair(st, g_keys + tm * 128 + t, ep, 31u);
      asm volatile("st.shared.v2.f32 [%0], {%1,%2};" ::"r"(S_KSTAT + t * 8), "f"(bf_hi(st[1])), "f"(rcp(bf_lo(st[1])) * LOG2E) : "memory");
      nb_arrive(NB_FDONE, 416);
      STAMP_IF(leader, 10);
    }
    float a0[64], a1[64];
    reg_zero(a0); reg_zero(a1); reg_fence(a0); reg_fence(a1);
    STAMP_IF(leader, 18);
    nb_sync(NB_KV, 256);
    mainloop<true, 14>(a0, a1, 1, 1, 0, 0, leader);
    {
      auto half = [&](float (&a)[64], int s, int m) {
#pragma unroll
        for (int j = 0; j < 4; j++)
          wgmma_n128_ss<1, 0>(a, mkdesc(RING + s * SLOT + m * 8192 + j * 2048, 8192, 1024, 1), mkdesc(RING + s * SLOT + 16384 + j * 32, 16, 1024, 1), 1);
      };
      auto kvmma = [&](float (&a)[64], float (&c)[32], int m) {
        reg_fence(a);
        uint32_t f[32];
#pragma unroll
        for (int i = 0; i < 32; i++) f[i] = pack(a[2 * i], a[2 * i + 1]);
        reg_zero(c);
        wg_fence();
#pragma unroll
        for (int k = 0; k < 8; k++) {
          wgmma_n64_rs<0>(c, f[4 * k], f[4 * k + 1], f[4 * k + 2], f[4 * k + 3], mkdesc(STG + (k >> 2) * 16384 + m * 8192 + (k & 3) * 32, 16, 1024, 1), k != 0);
          if (m && k == HAND_K) nb_arrive(NB_VQ, 256);
        }
        wg_commit();
      };
      float c0[32], c1[32];
      mbar_wait(B_FULL, 0);
      wg_fence();
      half(a0, 0, 0);
      wg_commit();
      mbar_wait(B_FULL + 8, 0);
      wg_fence();
      half(a0, 1, 0);
      wg_commit();
      wg_wait<2>();
      if (leader) mbar_arrive(B_EMPTY + 32);
      wg_fence();
      half(a1, 0, 1);
      half(a1, 1, 1);
      wg_commit();
      nb_sync(NB_PK, 256);
      wg_wait<1>();
      kvmma(a0, c0, 0);
      wg_wait<1>();
      if (leader) { mbar_arrive(B_EMPTY); mbar_arrive(B_EMPTY + 8); }
      STAMP_IF(leader, 19);
      kvmma(a1, c1, 1);
      const bool hp = ww >> 1;
      float c[4];
      float2 tt[8];
#pragma unroll
      for (int i = 0; i < 8; i++) tt[i] = lds64f(S_CSK + ((i >> 2) * 64 + hp * 32 + (i & 3) * 8 + 2 * t4) * 4);
      mbar_wait(B_CSV, 0);
#pragma unroll
      for (int i = 0; i < 4; i++) c[i] = -__uint_as_float(lds32(S_CSV + ((i >> 1) * 64 + ww * 16 + (i & 1) * 8 + g) * 4));
      wg_wait<0>();
      reg_fence(c0);
      reg_fence(c1);
      if (leader) mbar_arrive(B_SFREE);
      STAMP_IF(leader, 20);
      uint4* pp = g_kvp + (tn * 16 + tm) * 512 + t;
      auto put = [&](int q, const float* d) {
        const float ca = c[q & 2], cb = c[q | 1];
        const float2 ta = tt[2 * q], tb = tt[2 * q + 1];
        st_unit(pp + q * 128, pack(fmaf(ca, ta.x, d[0]), fmaf(ca, ta.y, d[1])), pack(fmaf(cb, ta.x, d[2]), fmaf(cb, ta.y, d[3])),
                pack(fmaf(ca, tb.x, d[4]), fmaf(ca, tb.y, d[5])), pack(fmaf(cb, tb.x, d[6]), fmaf(cb, tb.y, d[7])), par);
      };
      if (!hp) { put(0, c0); put(1, c0 + 8); put(2, c1); put(3, c1 + 8); }
      else { put(0, c0 + 16); put(1, c0 + 24); put(2, c1 + 16); put(3, c1 + 24); }
      STAMP_IF(leader, 47);
      {
        uint32_t p[16];
        nb_sync(NB_WG1, 128);
        if (ww == 0) { e_signal(H_KVP + tn, tm); await(H_KVP + tn, 0xffffu, ep); }
        nb_sync(NB_WG1, 128);
        STAMP_IF(leader, 1);
        poll_kvp(p, g_kvp + (tn * 16 + (lane >> 3) * 4) * 512 + tm * 32 + ww * 8 + (lane & 7), par, 1u);
        float r[8];
#pragma unroll
        for (int i = 0; i < 4; i++) {
          r[2 * i] = (bf_lo(p[i]) + bf_lo(p[4 + i])) + (bf_lo(p[8 + i]) + bf_lo(p[12 + i]));
          r[2 * i + 1] = (bf_hi(p[i]) + bf_hi(p[4 + i])) + (bf_hi(p[8 + i]) + bf_hi(p[12 + i]));
        }
        const bool u16 = lane & 16, u8 = lane & 8;
        const uint32_t wd = pack(xred(xred(r[0], r[4], u16, 16), xred(r[2], r[6], u16, 16), u8, 8), xred(xred(r[1], r[5], u16, 16), xred(r[3], r[7], u16, 16), u8, 8));
        const uint32_t w1 = __shfl_down_sync(0xffffffffu, wd, 1), w2 = __shfl_down_sync(0xffffffffu, wd, 2), w3 = __shfl_down_sync(0xffffffffu, wd, 3);
        const int grp = (tm & 1) * 2 + ((lane >> 3) & 1), row = ww * 2 + ((lane >> 2) & 1);
        if (t4 == 0) st_unit(g_kv + tn * 512 + ((tm >> 3) * 4 + grp) * 64 + row * 8 + (((tm & 2) * 2 + ((tm >> 1) & 2) + (lane >> 4)) ^ row), wd, w1, w2, w3, par);
        nb_sync(NB_WG1, 128);
        if (ww == 0) { if (!KV_SPEC) e_signal(H_KV + tn, tm); e_arrive(B_WK); }
      }
      STAMP_IF(leader, 21);
    }
    const uint32_t sx = lane & 7, sc = lane >> 4;
    const uint32_t sa = STG + (ww * 16 + (lane & 15)) * 128;
    const uint32_t sw[4] = {sa + ((sc ^ sx) << 4), sa + (((2 + sc) ^ sx) << 4), sa + (((4 + sc) ^ sx) << 4), sa + (((6 + sc) ^ sx) << 4)};
    auto residual = [&]() {
      float ka[4], kb[4];
#pragma unroll
      for (int i = 0; i < 4; i++) {
        const float2 st = lds64f(S_KSTAT + ((i >> 1) * 64 + ww * 16 + (i & 1) * 8 + g) * 8);
        const float r = st.y * LN2;
        ka[i] = 1.f + r; kb[i] = -st.x * r;
      }
#pragma unroll
      for (int j = 0; j < 8; j++) {
        if ((j & 3) == 0) mbar_wait(B_XRES + 8 * (j >> 2), 0);
        const uint4 v = ldsm4(sw[j & 3] + (j >> 2) * 16384), u = ldsm4(sw[j & 3] + (j >> 2) * 16384 + 8192);
        const uint32_t vv[4] = {v.x, v.y, v.z, v.w}, uu[4] = {u.x, u.y, u.z, u.w};
#pragma unroll
        for (int i = 0; i < 4; i++) {
          a0[8 * j + 2 * i] = fmaf(bf_lo(vv[i]), ka[i & 1], kb[i & 1]);
          a0[8 * j + 2 * i + 1] = fmaf(bf_hi(vv[i]), ka[i & 1], kb[i & 1]);
          a1[8 * j + 2 * i] = fmaf(bf_lo(uu[i]), ka[2 + (i & 1)], kb[2 + (i & 1)]);
          a1[8 * j + 2 * i + 1] = fmaf(bf_hi(uu[i]), ka[2 + (i & 1)], kb[2 + (i & 1)]);
        }
      }
      reg_fence(a0);
      reg_fence(a1);
      STAMP_IF(leader, 22);
    };
    residual();
    nb_arrive(NB_KVB, 320);
    uint32_t oh[4];
    {
      mbar_wait(B_SEL, 0);
      const int r0 = key_token(lds32(S_SEL + t4 * 16)) - tm * 128, r1 = key_token(lds32(S_SEL + t4 * 16 + 8)) - tm * 128;
#pragma unroll
      for (int i = 0; i < 4; i++) {
        const int row = (i >> 1) * 64 + ww * 16 + (i & 1) * 8 + g;
        oh[i] = (r0 == row ? 0x3f00u : 0u) | (r1 == row ? 0x3f000000u : 0u);
      }
    }
    uint32_t va = RING + 16384 + sc * 8192 + (ww * 16 + (lane & 8)) * 128 + sx * 16 + (lane >> 3) * 4;
    asm volatile("" : "+r"(va));
    {
      auto own = [&](int r) {
        nb_sync(NB_OWN0 + r, r ? 256 : 288);
        mbar_wait(B_FULL + 8 * (3 + r), 1);
        STAMP_IF(leader, 25 + r);
        const uint64_t dw = mkdesc(RING + (3 + r) * SLOT, 8192, 1024, 1), dx = mkdesc(STG + r * 16384, 16, 1024, 1);
        wg_fence();
#pragma unroll
        for (int j = 0; j < 4; j++) {
          wgmma_n128_ss<0, 1>(a0, dx + j * 2, dw + j * 128, 1);
          wgmma_n128_ss<0, 1>(a1, dx + j * 2 + 512, dw + j * 128, 1);
        }
        wg_commit();
      };
      own(0);
      wg_wait<0>();
      if (leader) mbar_arrive(B_EMPTY + 24);
      own(1);
      auto check = [&](int r, int s) {
          uint32_t bad;
          asm volatile("{\n.reg .u32 a, b, c, d, e, f, g, h;\n.reg .pred p;\n"
                       "ld.shared.u32 a, [%1];\nld.shared.u32 b, [%1+128];\nld.shared.u32 c, [%1+256];\nld.shared.u32 d, [%1+384];\n"
                       "ld.shared.u32 e, [%1+512];\nld.shared.u32 f, [%1+640];\nld.shared.u32 g, [%1+768];\nld.shared.u32 h, [%1+896];\n"
                       "lop3.b32 a, a, b, %2, 0x7e;\nlop3.b32 c, c, d, %2, 0x7e;\nlop3.b32 e, e, f, %2, 0x7e;\nlop3.b32 g, g, h, %2, 0x7e;\n"
                       "lop3.b32 a, a, c, e, 0xfe;\nlop3.b32 a, a, g, 1, 0xa8;\nsetp.ne.u32 p, a, 0;\nvote.sync.any.pred p, p, 0xffffffff;\nselp.u32 %0, 1, 0, p;\n}"
                       : "=r"(bad) : "r"(va + s * SLOT), "r"(par) : "memory");
          if (bad) {
            const uint4* src = reinterpret_cast<const uint4*>(g_o + (tm * 128 + sc * 64 + ww * 16 + (lane & 15)) * 1024 + out_kblock(r, tn) * 64);
#pragma unroll 1
            for (int i = 0; i < 8; i++) {
              uint32_t v[4];
              asm volatile("{\n.reg .b64 x, y;\n.reg .b128 z;\n.reg .pred p, q, h;\n.reg .u32 c, b;\nmov.u32 c, 0;\nsetp.ne.u32 h, %6, 0;\nLW:\n"
                           "ld.relaxed.gpu.global.b128 z, [%4];\nmov.b128 {x, y}, z;\nmov.b64 {%0,%1}, x;\nmov.b64 {%2,%3}, y;\n"
                           "selp.b64 x, y, x, h;\nshr.b64 x, x, %7;\ncvt.u32.u64 b, x;\nand.b32 b, b, 1;\nsetp.eq.u32 p, b, %5;\n"
                           "vote.sync.all.pred p, p, 0xffffffff;\n@p bra.uni LD;\nadd.u32 c, c, 1;\nsetp.lt.u32 q, c, 1000000;\n@q bra.uni LW;\ntrap;\nLD:\n}"
                           : "=&r"(v[0]), "=&r"(v[1]), "=&r"(v[2]), "=&r"(v[3]) : "l"(src + i), "r"(par), "r"(sc), "r"((lane & 8) * 4) : "memory");
              sts128(RING + 16384 + s * SLOT + sc * 8192 + (ww * 16 + (lane & 15)) * 128 + ((i ^ sx) << 4), v[0], v[1], v[2], v[3]);
            }
            fence_async_smem();
            __syncwarp();
          }
      };
      int s = 0, ph = 0;
      uint32_t prev = B_EMPTY + 32;
#pragma unroll 1
      for (int r = 2; r < 12; r++) {
        mbar_wait(B_FULL + 8 * s, ph);
        check(r, s);
        if (!LITE || ((LITE_MASK >> 27) & 1)) STAMP_IF(leader && r == 2, 27);
        const uint64_t dw = mkdesc(RING, 8192, 1024, 1) + s * (SLOT >> 4), dx = mkdesc(RING + 16384, 16, 1024, 1) + s * (SLOT >> 4);
        wg_fence();
#pragma unroll
        for (int j = 0; j < 4; j++) {
          wgmma_n128_ss<0, 1>(a0, dx + j * 2, dw + j * 128, 1);
          wgmma_n128_ss<0, 1>(a1, dx + j * 2 + 512, dw + j * 128, 1);
        }
        wg_commit();
        wg_wait<1>();
        if (leader) mbar_arrive(prev);
        prev = B_EMPTY + 8 * s;
        if (++s == NST) { s = 0; ph ^= 1; }
      }
      auto half = [&](float (&a)[64], int s, int m) {
        const uint64_t dw = mkdesc(RING, 8192, 1024, 1) + s * (SLOT >> 4), dx = mkdesc(RING + 16384 + m * 8192, 16, 1024, 1) + s * (SLOT >> 4);
#pragma unroll
        for (int j = 0; j < 4; j++) wgmma_n128_ss<0, 1>(a, dx + j * 2, dw + j * 128, 1);
      };
      auto store = [&](float (&a)[64], int m) {
        reg_fence(a);
#pragma unroll
        for (int j = 0; j < 8; j++) {
          stsm4(sw[j & 3] + (j >> 2) * 16384 + m * 8192, pack(a[8 * j], a[8 * j + 1]), pack(a[8 * j + 2], a[8 * j + 3]), pack(a[8 * j + 4], a[8 * j + 5]), pack(a[8 * j + 6], a[8 * j + 7]));
          if ((j & 3) == 3) {
            fence_async_smem();
            e_store2d(&mp.m_out, tn * 128 + (j >> 2) * 64, tm * 128 + m * 64 + ww * 16, STG + (j >> 2) * 16384 + m * 8192 + ww * 2048);
          }
        }
      };
#pragma unroll 1
      for (int q = 0; q < 4; q++) {
        mbar_wait(B_FULL + 8 * q, 0);
        check(12 + q, q);
        wg_fence();
        half(a0, q, 0);
        wg_commit();
      }
      nb_sync(NB_ST, 288);
      wg_fence();
      wgmma_n128_rs<1>(a0, oh[0], oh[1], oh[0], oh[1], mkdesc(FR, 1024, 0, 1), 1);
      wg_commit();
      wg_fence();
      half(a1, 0, 1);
      half(a1, 1, 1);
      wg_commit();
      wg_wait<1>();
      store(a0, 0);
      wg_fence();
      half(a1, 2, 1);
      half(a1, 3, 1);
      wgmma_n128_rs<1>(a1, oh[2], oh[3], oh[2], oh[3], mkdesc(FR, 1024, 0, 1), 1);
      wg_commit();
      wg_wait<0>();
      STAMP_IF(leader, 28);
      store(a1, 1);
    }
    bulk_wait_read();
    if (bid == 0 && leader) st_relaxed(&g_epoch, ep);
    STAMP_IF(leader, 29);
  } else {
    asm volatile("setmaxnreg.inc.sync.aligned.u32 216;");
    const int g = lane >> 2, t4 = lane & 3;
    const bool leader = tid == 0;
    const uint32_t sx = lane & 7, sc = lane >> 4;
    const uint32_t sa = STG + (w * 16 + (lane & 15)) * 128;
    const uint32_t sw[4] = {sa + ((sc ^ sx) << 4), sa + (((2 + sc) ^ sx) << 4), sa + (((4 + sc) ^ sx) << 4), sa + (((6 + sc) ^ sx) << 4)};
    float a0[64], a1[64];
    reg_zero(a0); reg_zero(a1); reg_fence(a0); reg_fence(a1);
    mainloop<true>(a0, a1, 0, 0, NB_KV, 0, leader);
    STAMP_IF(leader, 33);
    {
      nb_sync(NB_FDONE, 416);
      STAMP_IF(leader, 34);
      const uint32_t par = lds32(S_EPOCH) & 1u;
#pragma unroll 1
      for (int m = 0;; m++) {
        const uint32_t ca = S_CSK + (m * 64 + w * 16 + g) * 4;
        const float c[2] = {-lds32v(ca), -lds32v(ca + 32)};
        float z[2] = {0.f, 0.f}, tt[2] = {0.f, 0.f};
#pragma unroll
        for (int j = 0; j < 8; j++) {
          const float4 s0 = lds128v(S_KSTAT + (j * 16 + 2 * t4) * 8), s1 = lds128v(S_KSTAT + (j * 16 + 8 + 2 * t4) * 8);
          const float mu[4] = {s0.x, s0.z, s1.x, s1.z}, rl[4] = {s0.y, s0.w, s1.y, s1.w};
          float p[8];
#pragma unroll
          for (int i = 0; i < 8; i++) {
            const int r = (i >> 1) & 1, cc = (i >> 2) * 2 + (i & 1);
            p[i] = phi2(fmaf(c[r], mu[cc], a0[8 * j + i]) * rl[cc]);
            a0[8 * j + i] = a1[8 * j + i];
            z[r] += p[i];
            p[i] *= rl[cc];
            tt[r] = fmaf(p[i], mu[cc], tt[r]);
          }
          stsm4(sw[j & 3] + (j >> 2) * 16384 + m * 8192, pack(p[0], p[1]), pack(p[2], p[3]), pack(p[4], p[5]), pack(p[6], p[7]));
        }
        const bool u2 = lane & 2, u1 = lane & 1;
        const float v = xred(xred(z[0], tt[0], u2, 2), xred(z[1], tt[1], u2, 2), u1, 1);
        if (u2) sts32(ca + (t4 & 1) * 32, __float_as_uint(v));
        else st_relaxed(g_z + tm * 1024 + tn * 128 + m * 64 + w * 16 + t4 * 8 + g, tagf(v * LOG2E, par));
        if (m) break;
      }
      fence_async_smem();
      nb_arrive(NB_PK, 256);
      nb_arrive(NB_Z, 160);
    }
    STAMP_IF(leader, 35);
    float rl0[2];
    const uint32_t ep = lds32(S_EPOCH);
    {
      nb_sync(NB_CSQ, 160);
      float mu[4];
#pragma unroll
      for (int i = 0; i < 4; i++) {
        const float2 st = lds64f(S_KSTAT + ((i >> 1) * 64 + w * 16 + (i & 1) * 8 + g) * 8);
        mu[i] = -st.x;
        if (i < 2) rl0[i] = st.y;
      }
#pragma unroll
      for (int j = 0; j < 16; j++) {
        const float2 c = lds64f(S_CSQ + (j * 8 + 2 * t4) * 4);
        a0[4 * j] = mu[0] * c.x; a0[4 * j + 1] = mu[0] * c.y; a0[4 * j + 2] = mu[1] * c.x; a0[4 * j + 3] = mu[1] * c.y;
        a1[4 * j] = mu[2] * c.x; a1[4 * j + 1] = mu[2] * c.y; a1[4 * j + 2] = mu[3] * c.x; a1[4 * j + 3] = mu[3] * c.y;
      }
      reg_fence(a0); reg_fence(a1);
    }
    STAMP_IF(leader, 40);
    nb_sync(NB_VQ, 256);
    mainloop<false>(a0, a1, 2, 0, 0, 4 + (tn & 3), leader);
    STAMP_IF(leader, 36);
    {
      const uint32_t mk[4] = {t4 == 0, t4 == 1, t4 == 2, t4 == 3};
      uint64_t db = mkdesc(KVB, 16, 1024, 1);
      uint32_t so = 0;
#pragma unroll 1
      for (int j = 0;; j++) {
        uint32_t f[2][16];
        float oc[2][2][20];
        auto phi = [&](const float (&a)[64], float r0, float r1, uint32_t (&o)[16]) {
#pragma unroll
          for (int i = 0; i < 16; i++) o[i] = pack(phi2(a[2 * i] * (i & 1 ? r1 : r0)), phi2(a[2 * i + 1] * (i & 1 ? r1 : r0)));
        };
        auto mma = [&](const uint32_t (&a)[16], float (&o)[2][20]) {
          reg_zero(o[0]); reg_zero(o[1]);
          wg_fence();
          wgmma_n40_rs<0>(o[0], a[0], a[1], a[2], a[3], db, 0);
          wgmma_n40_rs<0>(o[1], a[8], a[9], a[10], a[11], db + 4, 0);
          wgmma_n40_rs<0>(o[0], a[4], a[5], a[6], a[7], db + 2, 1);
          wgmma_n40_rs<0>(o[1], a[12], a[13], a[14], a[15], db + 6, 1);
          wg_commit();
        };
        auto fin = [&](int m, float (&o)[2][20]) {
          const uint32_t m0 = mk[2 * m], m1 = mk[2 * m + 1];
#pragma unroll
          for (int h = 0; h < 2; h++) {
            const float r0 = rcp(o[h][0] + 1e-6f * LOG2E), r1 = rcp(o[h][2] + 1e-6f * LOG2E);
#pragma unroll
            for (int q = 0; q < 2; q++)
              stsm4(sw[h * 2 + q] + so + m * 8192,
                    bsel(pack(o[h][4 + 8 * q] * r0, o[h][5 + 8 * q] * r0), ep, m0), bsel(pack(o[h][6 + 8 * q] * r1, o[h][7 + 8 * q] * r1), ep, m1),
                    bsel(pack(o[h][8 + 8 * q] * r0, o[h][9 + 8 * q] * r0), ep, m0), bsel(pack(o[h][10 + 8 * q] * r1, o[h][11 + 8 * q] * r1), ep, m1));
          }
        };
        phi(a0, rl0[0], rl0[1], f[0]);
        if (j == 0) nb_sync(NB_KVB, 320);
        STAMP_IF(leader && j == 0, 37);
        const float r2 = lds32v(S_KSTAT + (64 + w * 16 + g) * 8 + 4), r3 = lds32v(S_KSTAT + (72 + w * 16 + g) * 8 + 4);
        mma(f[0], oc[0]);
        phi(a1, r2, r3, f[1]);
        wg_wait<0>();
        reg_fence(oc[0][0]); reg_fence(oc[0][1]);
        mma(f[1], oc[1]);
        fin(0, oc[0]);
        if (j == 0) { fence_async_smem(); nb_arrive(NB_Q0, 192); }
        wg_wait<0>();
        reg_fence(oc[1][0]); reg_fence(oc[1][1]);
        fin(1, oc[1]);
        fence_async_smem();
        if (j) break;
        nb_arrive(NB_OWN0, 288);
        STAMP_IF(leader, 38);
#pragma unroll
        for (int i = 0; i < 32; i++) { a0[i] = a0[32 + i]; a1[i] = a1[32 + i]; }
        db = mkdesc(KVB + 5120, 16, 1024, 1);
        so = 16384;
      }
      nb_arrive(NB_OWN1, 256);
      nb_arrive(NB_H1, 160);
      STAMP_IF(leader, 39);
    }
  }
}

#undef CK
typedef CUresult (*EncodeFn)(CUtensorMap*, CUtensorMapDataType, cuuint32_t, void*, const cuuint64_t*, const cuuint64_t*, const cuuint32_t*,
                             const cuuint32_t*, CUtensorMapInterleave, CUtensorMapSwizzle, CUtensorMapL2promotion, CUtensorMapFloatOOBfill);

void make_map(EncodeFn enc, CUtensorMap* m, const void* p, int rank, uint64_t d0, uint64_t d1, uint64_t d2, uint64_t s1, uint64_t s2,
              uint32_t b0, uint32_t b1, uint32_t b2, CUtensorMapSwizzle sw) {
  cuuint64_t gd[3] = {d0, d1, d2}, gs[2] = {s1, s2};
  cuuint32_t bd[3] = {b0, b1, b2}, es[3] = {1, 1, 1};
  enc(m, CU_TENSOR_MAP_DATA_TYPE_BFLOAT16, rank, const_cast<void*>(p), gd, gs, bd, es, CU_TENSOR_MAP_INTERLEAVE_NONE, sw,
      CU_TENSOR_MAP_L2_PROMOTION_L2_128B, CU_TENSOR_MAP_FLOAT_OOB_FILL_NONE);
}

}

extern "C" void kernel_launch(void* const* d_in, const int* in_sizes, int n_in, void* d_out, int out_size) {
  (void)in_sizes; (void)n_in; (void)out_size;
  void* fn = nullptr;
  cudaDriverEntryPointQueryResult qr;
  cudaGetDriverEntryPoint("cuTensorMapEncodeTiled", &fn, cudaEnableDefault, &qr);
  EncodeFn enc = (EncodeFn)fn;
  void* o;
  cudaGetSymbolAddress(&o, g_o);
  const CUtensorMapSwizzle S128 = CU_TENSOR_MAP_SWIZZLE_128B, S64 = CU_TENSOR_MAP_SWIZZLE_64B, S0 = CU_TENSOR_MAP_SWIZZLE_NONE;
  Params mp;
  mp.x = (const char*)d_in[0]; mp.wqkv = (const char*)d_in[1]; mp.w_r = (const char*)d_in[4];
  mp.wg = (const char*)d_in[5]; mp.wu = (const char*)d_in[6]; mp.wd = (const char*)d_in[7];
  make_map(enc, &mp.m_wqkv, d_in[1], 3, 64, 1024, 48, 6144, 128, 64, 64, 2, S128);
  make_map(enc, &mp.m_x, d_in[0], 2, 1024, 2048, 1, 2048, 0, 64, 128, 1, S128);
  make_map(enc, &mp.m_os, o, 2, 1024, 2048, 1, 2048, 0, 64, 64, 1, S128);
  make_map(enc, &mp.m_o, o, 2, 1024, 2048, 1, 2048, 0, 64, 128, 1, S128);
  make_map(enc, &mp.m_wo, d_in[2], 3, 64, 1024, 16, 2048, 128, 64, 64, 2, S128);
  make_map(enc, &mp.m_xs, d_in[0], 2, 1024, 2048, 1, 2048, 0, 256, 16, 1, S0);
  const char *wg = (const char*)d_in[5], *wu = (const char*)d_in[6];
  make_map(enc, &mp.m_gu, wu < wg ? wu : wg, 3, 3584, 1024, 2, 7168, (uint64_t)(wu < wg ? wg - wu : wu - wg), 32, 64, 2, S64);
  make_map(enc, &mp.m_down, d_in[7], 2, 1024, 3584, 1, 2048, 0, 64, 64, 1, S128);
  make_map(enc, &mp.m_out, d_out, 2, 1024, 2048, 1, 2048, 0, 64, 16, 1, S128);
  int dev = 0, sms = 0;
  cudaGetDevice(&dev);
  cudaDeviceGetAttribute(&sms, cudaDevAttrMultiProcessorCount, dev);
  auto kern = sms == 132 ? fused_kernel<true> : fused_kernel<false>;
  cudaFuncSetAttribute(kern, cudaFuncAttributeMaxDynamicSharedMemorySize, SMEM_BYTES);
  kern<<<132, 512, SMEM_BYTES>>>(mp);
}
```

```cpp
#include <cuda_runtime.h>
#include <cuda.h>
#include <cuda_bf16.h>
#include <stdint.h>

namespace {

template <int TA, int TB>
__device__ __forceinline__ void wgmma_n8_ss(float (&d)[4], uint64_t da, uint64_t db, int sc) {
  asm volatile("{\n.reg .pred p;\nsetp.ne.b32 p, %6, 0;\n"
    "wgmma.mma_async.sync.aligned.m64n8k16.f32.bf16.bf16 {%0, %1, %2, %3}, %4, %5, p, 1, 1, %7, %8;\n}\n"
    : "+f"(d[0]), "+f"(d[1]), "+f"(d[2]), "+f"(d[3])
    : "l"(da), "l"(db), "r"(sc), "n"(TA), "n"(TB));
}
template <int TA, int TB>
__device__ __forceinline__ void wgmma_n16_ss(float (&d)[8], uint64_t da, uint64_t db, int sc) {
  asm volatile("{\n.reg .pred p;\nsetp.ne.b32 p, %10, 0;\n"
    "wgmma.mma_async.sync.aligned.m64n16k16.f32.bf16.bf16 {%0, %1, %2, %3, %4, %5, %6, %7}, %8, %9, p, 1, 1, %11, %12;\n}\n"
    : "+f"(d[0]), "+f"(d[1]), "+f"(d[2]), "+f"(d[3]), "+f"(d[4]), "+f"(d[5]), "+f"(d[6]), "+f"(d[7])
    : "l"(da), "l"(db), "r"(sc), "n"(TA), "n"(TB));
}
template <int TB>
__device__ __forceinline__ void wgmma_n40_rs(float (&d)[20], uint32_t a0, uint32_t a1, uint32_t a2, uint32_t a3, uint64_t db, int sc) {
  asm volatile("{\n.reg .pred p;\nsetp.ne.b32 p, %25, 0;\n"
    "wgmma.mma_async.sync.aligned.m64n40k16.f32.bf16.bf16 {%0, %1, %2, %3, %4, %5, %6, %7, %8, %9, %10, %11, %12, %13, %14, %15, %16, %17, %18, %19}, {%20,%21,%22,%23}, %24, p, 1, 1, %26;\n}\n"
    : "+f"(d[0]), "+f"(d[1]), "+f"(d[2]), "+f"(d[3]), "+f"(d[4]), "+f"(d[5]), "+f"(d[6]), "+f"(d[7]),
      "+f"(d[8]), "+f"(d[9]), "+f"(d[10]), "+f"(d[11]), "+f"(d[12]), "+f"(d[13]), "+f"(d[14]), "+f"(d[15]),
      "+f"(d[16]), "+f"(d[17]), "+f"(d[18]), "+f"(d[19])
    : "r"(a0), "r"(a1), "r"(a2), "r"(a3), "l"(db), "r"(sc), "n"(TB));
}
template <int TB>
__device__ __forceinline__ void wgmma_n64_rs(float (&d)[32], uint32_t a0, uint32_t a1, uint32_t a2, uint32_t a3, uint64_t db, int sc) {
  asm volatile("{\n.reg .pred p;\nsetp.ne.b32 p, %37, 0;\n"
    "wgmma.mma_async.sync.aligned.m64n64k16.f32.bf16.bf16 {%0, %1, %2, %3, %4, %5, %6, %7, %8, %9, %10, %11, %12, %13, %14, %15, %16, %17, %18, %19, %20, %21, %22, %23, %24, %25, %26, %27, %28, %29, %30, %31}, {%32,%33,%34,%35}, %36, p, 1, 1, %38;\n}\n"
    : "+f"(d[0]), "+f"(d[1]), "+f"(d[2]), "+f"(d[3]), "+f"(d[4]), "+f"(d[5]), "+f"(d[6]), "+f"(d[7]),
      "+f"(d[8]), "+f"(d[9]), "+f"(d[10]), "+f"(d[11]), "+f"(d[12]), "+f"(d[13]), "+f"(d[14]), "+f"(d[15]),
      "+f"(d[16]), "+f"(d[17]), "+f"(d[18]), "+f"(d[19]), "+f"(d[20]), "+f"(d[21]), "+f"(d[22]), "+f"(d[23]),
      "+f"(d[24]), "+f"(d[25]), "+f"(d[26]), "+f"(d[27]), "+f"(d[28]), "+f"(d[29]), "+f"(d[30]), "+f"(d[31])
    : "r"(a0), "r"(a1), "r"(a2), "r"(a3), "l"(db), "r"(sc), "n"(TB));
}
template <int TA, int TB>
__device__ __forceinline__ void wgmma_n128_ss(float (&d)[64], uint64_t da, uint64_t db, int sc) {
  asm volatile("{\n.reg .pred p;\nsetp.ne.b32 p, %66, 0;\n"
    "wgmma.mma_async.sync.aligned.m64n128k16.f32.bf16.bf16 {%0, %1, %2, %3, %4, %5, %6, %7, %8, %9, %10, %11, %12, %13, %14, %15, %16, %17, %18, %19, %20, %21, %22, %23, %24, %25, %26, %27, %28, %29, %30, %31, %32, %33, %34, %35, %36, %37, %38, %39, %40, %41, %42, %43, %44, %45, %46, %47, %48, %49, %50, %51, %52, %53, %54, %55, %56, %57, %58, %59, %60, %61, %62, %63}, %64, %65, p, 1, 1, %67, %68;\n}\n"
    : "+f"(d[0]), "+f"(d[1]), "+f"(d[2]), "+f"(d[3]), "+f"(d[4]), "+f"(d[5]), "+f"(d[6]), "+f"(d[7]),
      "+f"(d[8]), "+f"(d[9]), "+f"(d[10]), "+f"(d[11]), "+f"(d[12]), "+f"(d[13]), "+f"(d[14]), "+f"(d[15]),
      "+f"(d[16]), "+f"(d[17]), "+f"(d[18]), "+f"(d[19]), "+f"(d[20]), "+f"(d[21]), "+f"(d[22]), "+f"(d[23]),
      "+f"(d[24]), "+f"(d[25]), "+f"(d[26]), "+f"(d[27]), "+f"(d[28]), "+f"(d[29]), "+f"(d[30]), "+f"(d[31]),
      "+f"(d[32]), "+f"(d[33]), "+f"(d[34]), "+f"(d[35]), "+f"(d[36]), "+f"(d[37]), "+f"(d[38]), "+f"(d[39]),
      "+f"(d[40]), "+f"(d[41]), "+f"(d[42]), "+f"(d[43]), "+f"(d[44]), "+f"(d[45]), "+f"(d[46]), "+f"(d[47]),
      "+f"(d[48]), "+f"(d[49]), "+f"(d[50]), "+f"(d[51]), "+f"(d[52]), "+f"(d[53]), "+f"(d[54]), "+f"(d[55]),
      "+f"(d[56]), "+f"(d[57]), "+f"(d[58]), "+f"(d[59]), "+f"(d[60]), "+f"(d[61]), "+f"(d[62]), "+f"(d[63])
    : "l"(da), "l"(db), "r"(sc), "n"(TA), "n"(TB));
}
template <int TB>
__device__ __forceinline__ void wgmma_n128_rs(float (&d)[64], uint32_t a0, uint32_t a1, uint32_t a2, uint32_t a3, uint64_t db, int sc) {
  asm volatile("{\n.reg .pred p;\nsetp.ne.b32 p, %69, 0;\n"
    "wgmma.mma_async.sync.aligned.m64n128k16.f32.bf16.bf16 {%0, %1, %2, %3, %4, %5, %6, %7, %8, %9, %10, %11, %12, %13, %14, %15, %16, %17, %18, %19, %20, %21, %22, %23, %24, %25, %26, %27, %28, %29, %30, %31, %32, %33, %34, %35, %36, %37, %38, %39, %40, %41, %42, %43, %44, %45, %46, %47, %48, %49, %50, %51, %52, %53, %54, %55, %56, %57, %58, %59, %60, %61, %62, %63}, {%64,%65,%66,%67}, %68, p, 1, 1, %70;\n}\n"
    : "+f"(d[0]), "+f"(d[1]), "+f"(d[2]), "+f"(d[3]), "+f"(d[4]), "+f"(d[5]), "+f"(d[6]), "+f"(d[7]),
      "+f"(d[8]), "+f"(d[9]), "+f"(d[10]), "+f"(d[11]), "+f"(d[12]), "+f"(d[13]), "+f"(d[14]), "+f"(d[15]),
      "+f"(d[16]), "+f"(d[17]), "+f"(d[18]), "+f"(d[19]), "+f"(d[20]), "+f"(d[21]), "+f"(d[22]), "+f"(d[23]),
      "+f"(d[24]), "+f"(d[25]), "+f"(d[26]), "+f"(d[27]), "+f"(d[28]), "+f"(d[29]), "+f"(d[30]), "+f"(d[31]),
      "+f"(d[32]), "+f"(d[33]), "+f"(d[34]), "+f"(d[35]), "+f"(d[36]), "+f"(d[37]), "+f"(d[38]), "+f"(d[39]),
      "+f"(d[40]), "+f"(d[41]), "+f"(d[42]), "+f"(d[43]), "+f"(d[44]), "+f"(d[45]), "+f"(d[46]), "+f"(d[47]),
      "+f"(d[48]), "+f"(d[49]), "+f"(d[50]), "+f"(d[51]), "+f"(d[52]), "+f"(d[53]), "+f"(d[54]), "+f"(d[55]),
      "+f"(d[56]), "+f"(d[57]), "+f"(d[58]), "+f"(d[59]), "+f"(d[60]), "+f"(d[61]), "+f"(d[62]), "+f"(d[63])
    : "r"(a0), "r"(a1), "r"(a2), "r"(a3), "l"(db), "r"(sc), "n"(TB));
}

__device__ __forceinline__ void poll1f(uint32_t (&v)[1], const void* p, uint32_t tag, uint32_t mask) {
  asm volatile("{\n.reg .pred p, q;\n.reg .u32 c, b;\n.reg .b64 x, y;\n.reg .b128 z;\nmov.u32 c, 0;\nLW:\n"
               "ld.relaxed.gpu.global.u32 %0, [%1+0];\n"
               "xor.b32 b, %0, %2;\n"
               "and.b32 b, b, %3;\nsetp.eq.u32 p, b, 0;\nvote.sync.all.pred p, p, 0xffffffff;\n@p bra.uni LD;\n"
               "nanosleep.u32 50;\nadd.u32 c, c, 1;\nsetp.lt.u32 q, c, 1000000;\n@q bra.uni LW;\ntrap;\nLD:\n}"
               : "=&r"(v[0])
               : "l"(p), "r"(tag), "r"(mask) : "memory");
}
__device__ __forceinline__ void poll0(uint32_t (&v)[1], const void* p, uint32_t tag, uint32_t mask) {
  asm volatile("{\n.reg .pred p, q;\n.reg .u32 c, b;\n.reg .b64 x, y;\n.reg .b128 z;\nmov.u32 c, 0;\nLW:\n"
               "ld.relaxed.gpu.global.u32 %0, [%1+0];\n"
               "xor.b32 b, %0, %2;\n"
               "and.b32 b, b, %3;\nsetp.eq.u32 p, b, 0;\nvote.sync.all.pred p, p, 0xffffffff;\n@p bra.uni LD;\n"
               "add.u32 c, c, 1;\nsetp.lt.u32 q, c, 1000000;\n@q bra.uni LW;\ntrap;\nLD:\n}"
               : "=&r"(v[0])
               : "l"(p), "r"(tag), "r"(mask) : "memory");
}
__device__ __forceinline__ void poll_pair(uint32_t (&v)[2], const void* p, uint32_t tag, uint32_t mask) {
  asm volatile("{\n.reg .pred p, q;\n.reg .u32 c, b;\n.reg .b64 x, y;\n.reg .b128 z;\nmov.u32 c, 0;\nLW:\n"
               "ld.relaxed.gpu.global.b64 x, [%2+0];\nmov.b64 {%0,%1}, x;\n"
               "xor.b32 b, %0, %3;\n"
               "and.b32 b, b, %4;\nsetp.eq.u32 p, b, 0;\nvote.sync.all.pred p, p, 0xffffffff;\n@p bra.uni LD;\n"
               "nanosleep.u32 100;\nadd.u32 c, c, 1;\nsetp.lt.u32 q, c, 1000000;\n@q bra.uni LW;\ntrap;\nLD:\n}"
               : "=&r"(v[0]), "=&r"(v[1])
               : "l"(p), "r"(tag), "r"(mask) : "memory");
}
__device__ __forceinline__ void poll_quad(uint32_t (&v)[4], const void* p, uint32_t tag, uint32_t mask) {
  asm volatile("{\n.reg .pred p, q;\n.reg .u32 c, b;\n.reg .b64 x, y;\n.reg .b128 z;\nmov.u32 c, 0;\nLW:\n"
               "ld.relaxed.gpu.global.v4.u32 {%0,%1,%2,%3}, [%4+0];\n"
               "xor.b32 b, %0, %5;\n"
               "lop3.b32 b, b, %1, %5, 0xf6;\nlop3.b32 b, b, %2, %5, 0xf6;\nlop3.b32 b, b, %3, %5, 0xf6;\n"
               "and.b32 b, b, %6;\nsetp.eq.u32 p, b, 0;\nvote.sync.all.pred p, p, 0xffffffff;\n@p bra.uni LD;\n"
               "nanosleep.u32 200;\nadd.u32 c, c, 1;\nsetp.lt.u32 q, c, 1000000;\n@q bra.uni LW;\ntrap;\nLD:\n}"
               : "=&r"(v[0]), "=&r"(v[1]), "=&r"(v[2]), "=&r"(v[3])
               : "l"(p), "r"(tag), "r"(mask) : "memory");
}
__device__ __forceinline__ void poll8x4(uint32_t (&v)[32], const void* p, uint32_t tag, uint32_t mask) {
  asm volatile("{\n.reg .pred p, q;\n.reg .u32 c, b;\n.reg .b64 x, y;\n.reg .b128 z;\nmov.u32 c, 0;\nLW:\n"
               "ld.relaxed.gpu.global.v4.u32 {%0,%1,%2,%3}, [%32+0];\n"
               "ld.relaxed.gpu.global.v4.u32 {%4,%5,%6,%7}, [%32+2048];\n"
               "ld.relaxed.gpu.global.v4.u32 {%8,%9,%10,%11}, [%32+4096];\n"
               "ld.relaxed.gpu.global.v4.u32 {%12,%13,%14,%15}, [%32+6144];\n"
               "ld.relaxed.gpu.global.v4.u32 {%16,%17,%18,%19}, [%32+8192];\n"
               "ld.relaxed.gpu.global.v4.u32 {%20,%21,%22,%23}, [%32+10240];\n"
               "ld.relaxed.gpu.global.v4.u32 {%24,%25,%26,%27}, [%32+12288];\n"
               "ld.relaxed.gpu.global.v4.u32 {%28,%29,%30,%31}, [%32+14336];\n"
               "xor.b32 b, %0, %33;\n"
               "lop3.b32 b, b, %1, %33, 0xf6;\nlop3.b32 b, b, %2, %33, 0xf6;\nlop3.b32 b, b, %3, %33, 0xf6;\nlop3.b32 b, b, %4, %33, 0xf6;\n"
               "lop3.b32 b, b, %5, %33, 0xf6;\nlop3.b32 b, b, %6, %33, 0xf6;\nlop3.b32 b, b, %7, %33, 0xf6;\nlop3.b32 b, b, %8, %33, 0xf6;\n"
               "lop3.b32 b, b, %9, %33, 0xf6;\nlop3.b32 b, b, %10, %33, 0xf6;\nlop3.b32 b, b, %11, %33, 0xf6;\nlop3.b32 b, b, %12, %33, 0xf6;\n"
               "lop3.b32 b, b, %13, %33, 0xf6;\nlop3.b32 b, b, %14, %33, 0xf6;\nlop3.b32 b, b, %15, %33, 0xf6;\nlop3.b32 b, b, %16, %33, 0xf6;\n"
               "lop3.b32 b, b, %17, %33, 0xf6;\nlop3.b32 b, b, %18, %33, 0xf6;\nlop3.b32 b, b, %19, %33, 0xf6;\nlop3.b32 b, b, %20, %33, 0xf6;\n"
               "lop3.b32 b, b, %21, %33, 0xf6;\nlop3.b32 b, b, %22, %33, 0xf6;\nlop3.b32 b, b, %23, %33, 0xf6;\nlop3.b32 b, b, %24, %33, 0xf6;\n"
               "lop3.b32 b, b, %25, %33, 0xf6;\nlop3.b32 b, b, %26, %33, 0xf6;\nlop3.b32 b, b, %27, %33, 0xf6;\nlop3.b32 b, b, %28, %33, 0xf6;\n"
               "lop3.b32 b, b, %29, %33, 0xf6;\nlop3.b32 b, b, %30, %33, 0xf6;\nlop3.b32 b, b, %31, %33, 0xf6;\n"
               "and.b32 b, b, %34;\nsetp.eq.u32 p, b, 0;\nvote.sync.all.pred p, p, 0xffffffff;\n@p bra.uni LD;\n"
               "nanosleep.u32 50;\nadd.u32 c, c, 1;\nsetp.lt.u32 q, c, 1000000;\n@q bra.uni LW;\ntrap;\nLD:\n}"
               : "=&r"(v[0]), "=&r"(v[1]), "=&r"(v[2]), "=&r"(v[3]), "=&r"(v[4]), "=&r"(v[5]), "=&r"(v[6]), "=&r"(v[7]), "=&r"(v[8]), "=&r"(v[9]), "=&r"(v[10]), "=&r"(v[11]), "=&r"(v[12]), "=&r"(v[13]), "=&r"(v[14]), "=&r"(v[15]), "=&r"(v[16]), "=&r"(v[17]), "=&r"(v[18]), "=&r"(v[19]), "=&r"(v[20]), "=&r"(v[21]), "=&r"(v[22]), "=&r"(v[23]), "=&r"(v[24]), "=&r"(v[25]), "=&r"(v[26]), "=&r"(v[27]), "=&r"(v[28]), "=&r"(v[29]), "=&r"(v[30]), "=&r"(v[31])
               : "l"(p), "r"(tag), "r"(mask) : "memory");
}
__device__ __forceinline__ void poll16(uint32_t (&v)[16], const void* p, uint32_t tag, uint32_t mask) {
  asm volatile("{\n.reg .pred p, q;\n.reg .u32 c, b;\n.reg .b64 x, y;\n.reg .b128 z;\nmov.u32 c, 0;\nLW:\n"
               "ld.relaxed.gpu.global.u32 %0, [%16+0];\n"
               "ld.relaxed.gpu.global.u32 %1, [%16+4096];\n"
               "ld.relaxed.gpu.global.u32 %2, [%16+8192];\n"
               "ld.relaxed.gpu.global.u32 %3, [%16+12288];\n"
               "ld.relaxed.gpu.global.u32 %4, [%16+16384];\n"
               "ld.relaxed.gpu.global.u32 %5, [%16+20480];\n"
               "ld.relaxed.gpu.global.u32 %6, [%16+24576];\n"
               "ld.relaxed.gpu.global.u32 %7, [%16+28672];\n"
               "ld.relaxed.gpu.global.u32 %8, [%16+32768];\n"
               "ld.relaxed.gpu.global.u32 %9, [%16+36864];\n"
               "ld.relaxed.gpu.global.u32 %10, [%16+40960];\n"
               "ld.relaxed.gpu.global.u32 %11, [%16+45056];\n"
               "ld.relaxed.gpu.global.u32 %12, [%16+49152];\n"
               "ld.relaxed.gpu.global.u32 %13, [%16+53248];\n"
               "ld.relaxed.gpu.global.u32 %14, [%16+57344];\n"
               "ld.relaxed.gpu.global.u32 %15, [%16+61440];\n"
               "xor.b32 b, %0, %17;\n"
               "lop3.b32 b, b, %1, %17, 0xf6;\nlop3.b32 b, b, %2, %17, 0xf6;\nlop3.b32 b, b, %3, %17, 0xf6;\nlop3.b32 b, b, %4, %17, 0xf6;\n"
               "lop3.b32 b, b, %5, %17, 0xf6;\nlop3.b32 b, b, %6, %17, 0xf6;\nlop3.b32 b, b, %7, %17, 0xf6;\nlop3.b32 b, b, %8, %17, 0xf6;\n"
               "lop3.b32 b, b, %9, %17, 0xf6;\nlop3.b32 b, b, %10, %17, 0xf6;\nlop3.b32 b, b, %11, %17, 0xf6;\nlop3.b32 b, b, %12, %17, 0xf6;\n"
               "lop3.b32 b, b, %13, %17, 0xf6;\nlop3.b32 b, b, %14, %17, 0xf6;\nlop3.b32 b, b, %15, %17, 0xf6;\n"
               "and.b32 b, b, %18;\nsetp.eq.u32 p, b, 0;\nvote.sync.all.pred p, p, 0xffffffff;\n@p bra.uni LD;\n"
               "nanosleep.u32 200;\nadd.u32 c, c, 1;\nsetp.lt.u32 q, c, 1000000;\n@q bra.uni LW;\ntrap;\nLD:\n}"
               : "=&r"(v[0]), "=&r"(v[1]), "=&r"(v[2]), "=&r"(v[3]), "=&r"(v[4]), "=&r"(v[5]), "=&r"(v[6]), "=&r"(v[7]), "=&r"(v[8]), "=&r"(v[9]), "=&r"(v[10]), "=&r"(v[11]), "=&r"(v[12]), "=&r"(v[13]), "=&r"(v[14]), "=&r"(v[15])
               : "l"(p), "r"(tag), "r"(mask) : "memory");
}
__device__ __forceinline__ void poll_keys(uint32_t (&v)[16], const void* p, uint32_t tag, uint32_t mask) {
  asm volatile("{\n.reg .pred p, q;\n.reg .u32 c, b;\n.reg .b64 x, y;\n.reg .b128 z;\nmov.u32 c, 0;\nLW:\n"
               "ld.relaxed.gpu.global.v2.b64 {x, y}, [%16+0];\nmov.b64 {%0,%1}, x;\nmov.b64 {%2,%3}, y;\n"
               "ld.relaxed.gpu.global.v2.b64 {x, y}, [%16+4096];\nmov.b64 {%4,%5}, x;\nmov.b64 {%6,%7}, y;\n"
               "ld.relaxed.gpu.global.v2.b64 {x, y}, [%16+8192];\nmov.b64 {%8,%9}, x;\nmov.b64 {%10,%11}, y;\n"
               "ld.relaxed.gpu.global.v2.b64 {x, y}, [%16+12288];\nmov.b64 {%12,%13}, x;\nmov.b64 {%14,%15}, y;\n"
               "xor.b32 b, %0, %17;\n"
               "lop3.b32 b, b, %2, %17, 0xf6;\nlop3.b32 b, b, %4, %17, 0xf6;\nlop3.b32 b, b, %6, %17, 0xf6;\nlop3.b32 b, b, %8, %17, 0xf6;\n"
               "lop3.b32 b, b, %10, %17, 0xf6;\nlop3.b32 b, b, %12, %17, 0xf6;\nlop3.b32 b, b, %14, %17, 0xf6;\n"
               "and.b32 b, b, %18;\nsetp.eq.u32 p, b, 0;\nvote.sync.all.pred p, p, 0xffffffff;\n@p bra.uni LD;\n"
               "nanosleep.u32 20;\nadd.u32 c, c, 1;\nsetp.lt.u32 q, c, 1000000;\n@q bra.uni LW;\ntrap;\nLD:\n}"
               : "=&r"(v[0]), "=&r"(v[1]), "=&r"(v[2]), "=&r"(v[3]), "=&r"(v[4]), "=&r"(v[5]), "=&r"(v[6]), "=&r"(v[7]), "=&r"(v[8]), "=&r"(v[9]), "=&r"(v[10]), "=&r"(v[11]), "=&r"(v[12]), "=&r"(v[13]), "=&r"(v[14]), "=&r"(v[15])
               : "l"(p), "r"(tag), "r"(mask) : "memory");
}
__device__ __forceinline__ void poll_z(uint32_t (&v)[16], const void* p, uint32_t tag, uint32_t mask) {
  asm volatile("{\n.reg .pred p, q;\n.reg .u32 c, b;\n.reg .b64 x, y;\n.reg .b128 z;\nmov.u32 c, 0;\nLW:\n"
               "ld.relaxed.gpu.global.v4.u32 {%0,%1,%2,%3}, [%16+0];\n"
               "ld.relaxed.gpu.global.v4.u32 {%4,%5,%6,%7}, [%16+4096];\n"
               "ld.relaxed.gpu.global.v4.u32 {%8,%9,%10,%11}, [%16+8192];\n"
               "ld.relaxed.gpu.global.v4.u32 {%12,%13,%14,%15}, [%16+12288];\n"
               "xor.b32 b, %0, %17;\n"
               "lop3.b32 b, b, %1, %17, 0xf6;\nlop3.b32 b, b, %2, %17, 0xf6;\nlop3.b32 b, b, %3, %17, 0xf6;\nlop3.b32 b, b, %4, %17, 0xf6;\n"
               "lop3.b32 b, b, %5, %17, 0xf6;\nlop3.b32 b, b, %6, %17, 0xf6;\nlop3.b32 b, b, %7, %17, 0xf6;\nlop3.b32 b, b, %8, %17, 0xf6;\n"
               "lop3.b32 b, b, %9, %17, 0xf6;\nlop3.b32 b, b, %10, %17, 0xf6;\nlop3.b32 b, b, %11, %17, 0xf6;\nlop3.b32 b, b, %12, %17, 0xf6;\n"
               "lop3.b32 b, b, %13, %17, 0xf6;\nlop3.b32 b, b, %14, %17, 0xf6;\nlop3.b32 b, b, %15, %17, 0xf6;\n"
               "and.b32 b, b, %18;\nsetp.eq.u32 p, b, 0;\nvote.sync.all.pred p, p, 0xffffffff;\n@p bra.uni LD;\n"
               "nanosleep.u32 300;\nadd.u32 c, c, 1;\nsetp.lt.u32 q, c, 1000000;\n@q bra.uni LW;\ntrap;\nLD:\n}"
               : "=&r"(v[0]), "=&r"(v[1]), "=&r"(v[2]), "=&r"(v[3]), "=&r"(v[4]), "=&r"(v[5]), "=&r"(v[6]), "=&r"(v[7]), "=&r"(v[8]), "=&r"(v[9]), "=&r"(v[10]), "=&r"(v[11]), "=&r"(v[12]), "=&r"(v[13]), "=&r"(v[14]), "=&r"(v[15])
               : "l"(p), "r"(tag), "r"(mask) : "memory");
}
__device__ __forceinline__ void poll7x4(uint32_t (&v)[28], const void* p, uint32_t tag, uint32_t mask) {
  asm volatile("{\n.reg .pred p, q;\n.reg .u32 c, b;\n.reg .b64 x, y;\n.reg .b128 z;\nmov.u32 c, 0;\nLW:\n"
               "ld.relaxed.gpu.global.v4.u32 {%0,%1,%2,%3}, [%28+0];\n"
               "ld.relaxed.gpu.global.v4.u32 {%4,%5,%6,%7}, [%28+2048];\n"
               "ld.relaxed.gpu.global.v4.u32 {%8,%9,%10,%11}, [%28+4096];\n"
               "ld.relaxed.gpu.global.v4.u32 {%12,%13,%14,%15}, [%28+6144];\n"
               "ld.relaxed.gpu.global.v4.u32 {%16,%17,%18,%19}, [%28+8192];\n"
               "ld.relaxed.gpu.global.v4.u32 {%20,%21,%22,%23}, [%28+10240];\n"
               "ld.relaxed.gpu.global.v4.u32 {%24,%25,%26,%27}, [%28+12288];\n"
               "xor.b32 b, %0, %29;\n"
               "lop3.b32 b, b, %1, %29, 0xf6;\nlop3.b32 b, b, %2, %29, 0xf6;\nlop3.b32 b, b, %3, %29, 0xf6;\nlop3.b32 b, b, %4, %29, 0xf6;\n"
               "lop3.b32 b, b, %5, %29, 0xf6;\nlop3.b32 b, b, %6, %29, 0xf6;\nlop3.b32 b, b, %7, %29, 0xf6;\nlop3.b32 b, b, %8, %29, 0xf6;\n"
               "lop3.b32 b, b, %9, %29, 0xf6;\nlop3.b32 b, b, %10, %29, 0xf6;\nlop3.b32 b, b, %11, %29, 0xf6;\nlop3.b32 b, b, %12, %29, 0xf6;\n"
               "lop3.b32 b, b, %13, %29, 0xf6;\nlop3.b32 b, b, %14, %29, 0xf6;\nlop3.b32 b, b, %15, %29, 0xf6;\nlop3.b32 b, b, %16, %29, 0xf6;\n"
               "lop3.b32 b, b, %17, %29, 0xf6;\nlop3.b32 b, b, %18, %29, 0xf6;\nlop3.b32 b, b, %19, %29, 0xf6;\nlop3.b32 b, b, %20, %29, 0xf6;\n"
               "lop3.b32 b, b, %21, %29, 0xf6;\nlop3.b32 b, b, %22, %29, 0xf6;\nlop3.b32 b, b, %23, %29, 0xf6;\nlop3.b32 b, b, %24, %29, 0xf6;\n"
               "lop3.b32 b, b, %25, %29, 0xf6;\nlop3.b32 b, b, %26, %29, 0xf6;\nlop3.b32 b, b, %27, %29, 0xf6;\n"
               "and.b32 b, b, %30;\nsetp.eq.u32 p, b, 0;\nvote.sync.all.pred p, p, 0xffffffff;\n@p bra.uni LD;\n"
               "nanosleep.u32 50;\nadd.u32 c, c, 1;\nsetp.lt.u32 q, c, 1000000;\n@q bra.uni LW;\ntrap;\nLD:\n}"
               : "=&r"(v[0]), "=&r"(v[1]), "=&r"(v[2]), "=&r"(v[3]), "=&r"(v[4]), "=&r"(v[5]), "=&r"(v[6]), "=&r"(v[7]), "=&r"(v[8]), "=&r"(v[9]), "=&r"(v[10]), "=&r"(v[11]), "=&r"(v[12]), "=&r"(v[13]), "=&r"(v[14]), "=&r"(v[15]), "=&r"(v[16]), "=&r"(v[17]), "=&r"(v[18]), "=&r"(v[19]), "=&r"(v[20]), "=&r"(v[21]), "=&r"(v[22]), "=&r"(v[23]), "=&r"(v[24]), "=&r"(v[25]), "=&r"(v[26]), "=&r"(v[27])
               : "l"(p), "r"(tag), "r"(mask) : "memory");
}
__device__ __forceinline__ void poll_kvp(uint32_t (&v)[16], const void* p, uint32_t tag, uint32_t mask) {
  asm volatile("{\n.reg .pred p, q;\n.reg .u32 c, b;\n.reg .b64 x, y;\n.reg .b128 z;\nmov.u32 c, 0;\nLW:\n"
               "ld.relaxed.gpu.global.b128 z, [%16+0];\nmov.b128 {x, y}, z;\nmov.b64 {%0,%1}, x;\nmov.b64 {%2,%3}, y;\n"
               "ld.relaxed.gpu.global.b128 z, [%16+8192];\nmov.b128 {x, y}, z;\nmov.b64 {%4,%5}, x;\nmov.b64 {%6,%7}, y;\n"
               "ld.relaxed.gpu.global.b128 z, [%16+16384];\nmov.b128 {x, y}, z;\nmov.b64 {%8,%9}, x;\nmov.b64 {%10,%11}, y;\n"
               "ld.relaxed.gpu.global.b128 z, [%16+24576];\nmov.b128 {x, y}, z;\nmov.b64 {%12,%13}, x;\nmov.b64 {%14,%15}, y;\n"
               "xor.b32 b, %0, %17;\n"
               "lop3.b32 b, b, %4, %17, 0xf6;\nlop3.b32 b, b, %8, %17, 0xf6;\nlop3.b32 b, b, %12, %17, 0xf6;\n"
               "and.b32 b, b, %18;\nsetp.eq.u32 p, b, 0;\nvote.sync.all.pred p, p, 0xffffffff;\n@p bra.uni LD;\n"
               "nanosleep.u32 50;\nadd.u32 c, c, 1;\nsetp.lt.u32 q, c, 1000000;\n@q bra.uni LW;\ntrap;\nLD:\n}"
               : "=&r"(v[0]), "=&r"(v[1]), "=&r"(v[2]), "=&r"(v[3]), "=&r"(v[4]), "=&r"(v[5]), "=&r"(v[6]), "=&r"(v[7]), "=&r"(v[8]), "=&r"(v[9]), "=&r"(v[10]), "=&r"(v[11]), "=&r"(v[12]), "=&r"(v[13]), "=&r"(v[14]), "=&r"(v[15])
               : "l"(p), "r"(tag), "r"(mask) : "memory");
}

__device__ __align__(1024) __nv_bfloat16 g_o[2048 * 1024];
__device__ __align__(128) uint2 g_keys[2048];
__device__ __align__(128) uint32_t g_csum[18 * 1024];
__device__ __align__(128) uint32_t g_z[16 * 1024];
__device__ __align__(128) uint4 g_kvp[128 * 512];
__device__ __align__(128) uint4 g_kv[8 * 512];
__device__ __align__(128) uint32_t g_h[112 * 256];
__device__ __align__(128) uint32_t g_yp[128 * 512];
__device__ __align__(128) uint2 g_sel[8 * 16];
enum { H_CS = 0, H_KVP = 8, H_KV = 16, H_H = 24, H_Y = 32, H_O = 40, H_Z = 56 };
__device__ __align__(128) uint32_t g_sig[64 * 32];
__device__ uint32_t g_epoch;

constexpr uint32_t RING = 1024, SLOT = 32768, SMEM_BYTES = 232448;
constexpr int NST = 5, HST = 7;
constexpr uint32_t STG = RING + 163840, AUX = RING + 196608, FR = RING + 212992, MISC = RING + 229376;
constexpr uint32_t B_FULL = MISC, B_EMPTY = MISC + 56, B_XS = MISC + 112, B_SEL = MISC + 144, B_WK = MISC + 160, B_CSDN = MISC + 168,
                   B_FR = MISC + 176, B_FE = MISC + 200, B_DR = MISC + 224, B_CSV = MISC + 248,
                   B_DND = MISC + 256, B_XRES = MISC + 264, B_PFREE = MISC + 280, B_SFREE = MISC + 288, B_KVL = MISC + 296, NBAR = 38;
constexpr uint32_t S_EPOCH = MISC + 352, S_NCAND = MISC + 356, S_SEL = MISC + 368, S_WMAX = MISC + 432,
                   S_KSTAT = MISC + 512, S_CSK = MISC + 1536, S_CSV = MISC + 2048, S_CSQ = MISC + 2560, S_ONES = MISC + 512;
constexpr uint32_t KVB = AUX, HOP = AUX + 10240, FONES = AUX + 6144, GR = FR - 8192;
enum { NB_Z = 0, NB_KV = 1, NB_VQ = 2, NB_WG0 = 3, NB_FDONE = 4, NB_PK = 5, NB_KVB = 6, NB_WG1 = 7, NB_WG2 = 8, NB_CSQ = 9,
       NB_Y = 10, NB_ST = 11, NB_OWN0 = 12, NB_OWN1 = 13, NB_Q0 = 14, NB_H1 = 15 };

#define XS_FLY 2
#define FFN_GAP 400
#define PF_GAP 200
#define PF_WAIT 1000
#define GPCMAP 0x75143620u
#define KV_SPEC 200
#define HAND_K 5
constexpr uint64_t EVICT_FIRST = 0x12f0000000000000ull;
constexpr float LOG2E = 1.4426950408889634f, LN2 = 0.6931471805599453f;

#define ELECT "{\n.reg .pred p;\nelect.sync _|p, 0xffffffff;\n"
#define TMA2D "cp.async.bulk.tensor.2d.shared::cluster.global.mbarrier::complete_tx::bytes"
#define TMA3D "cp.async.bulk.tensor.3d.shared::cluster.global.mbarrier::complete_tx::bytes"
__device__ __forceinline__ void e_expect(uint32_t b, uint32_t n) {
  asm volatile(ELECT "@p mbarrier.arrive.expect_tx.shared::cta.b64 _, [%0], %1;\n}" ::"r"(b), "r"(n) : "memory");
}
__device__ __forceinline__ void e_arrive(uint32_t b) { asm volatile(ELECT "@p mbarrier.arrive.shared::cta.b64 _, [%0];\n}" ::"r"(b) : "memory"); }
__device__ __forceinline__ void e_tma2d(uint32_t dst, const CUtensorMap* m, int c0, int c1, uint32_t bar) {
  asm volatile(ELECT "@p " TMA2D " [%0], [%1, {%3, %4}], [%2];\n}" ::"r"(dst), "l"(m), "r"(bar), "r"(c0), "r"(c1) : "memory");
}
__device__ __forceinline__ void e_tma2d_ef(uint32_t dst, const CUtensorMap* m, int c0, int c1, uint32_t bar, uint64_t pol) {
  asm volatile(ELECT "@p " TMA2D ".L2::cache_hint [%0], [%1, {%3, %4}], [%2], %5;\n}" ::"r"(dst), "l"(m), "r"(bar), "r"(c0), "r"(c1), "l"(pol) : "memory");
}
__device__ __forceinline__ void e_tma3d(uint32_t dst, const CUtensorMap* m, int c1, int c2, uint32_t bar) {
  asm volatile(ELECT "@p " TMA3D " [%0], [%1, {0, %3, %4}], [%2];\n}" ::"r"(dst), "l"(m), "r"(bar), "r"(c1), "r"(c2) : "memory");
}
__device__ __forceinline__ void e_store2d(const CUtensorMap* m, int c0, int c1, uint32_t src) {
  asm volatile(ELECT "@p cp.async.bulk.tensor.2d.global.shared::cta.bulk_group [%0, {%2, %3}], [%1];\n}" ::"l"(m), "r"(src), "r"(c0), "r"(c1) : "memory");
}
__device__ __forceinline__ void e_tma3d_ef(uint32_t dst, const CUtensorMap* m, int c0, int c1, uint32_t bar, uint64_t pol) {
  asm volatile(ELECT "@p " TMA3D ".L2::cache_hint [%0], [%1, {%3, %4, 0}], [%2], %5;\n}" ::"r"(dst), "l"(m), "r"(bar), "r"(c0), "r"(c1), "l"(pol) : "memory");
}
__device__ __forceinline__ void e_load(uint32_t dst, const void* src, uint32_t n, uint32_t bar) {
  asm volatile(ELECT "@p cp.async.bulk.shared::cluster.global.mbarrier::complete_tx::bytes [%0], [%1], %2, [%3];\n}" ::"r"(dst), "l"(src), "r"(n), "r"(bar) : "memory");
}
__device__ __forceinline__ void e_pfmap(const CUtensorMap* m) { asm volatile(ELECT "@p prefetch.tensormap [%0];\n}" ::"l"(m) : "memory"); }
__device__ __forceinline__ void bulk_wait_read() { asm volatile("cp.async.bulk.commit_group;\ncp.async.bulk.wait_group.read 0;" ::: "memory"); }
__device__ __forceinline__ void e_signal(int word, int bit) {
  asm volatile(ELECT "@p red.relaxed.gpu.global.xor.b32 [%0], %1;\n}" ::"l"(g_sig + word * 32), "r"(1u << bit) : "memory");
}
__device__ __forceinline__ void await(int word, uint32_t mask, uint32_t ep) {
  uint32_t f[1];
  poll1f(f, g_sig + word * 32, 0u - (ep & 1u), mask);
}

__device__ __forceinline__ void mbar_arrive(uint32_t b) { asm volatile("mbarrier.arrive.shared::cta.b64 _, [%0];" ::"r"(b) : "memory"); }
__device__ __forceinline__ void mbar_wait(uint32_t b, uint32_t ph) {
  asm volatile("{\n.reg .pred p, q;\n.reg .u32 c;\nmov.u32 c, 0;\nLW:\nmbarrier.try_wait.parity.shared::cta.b64 p, [%0], %1;\n@p bra LD;\n"
               "add.u32 c, c, 1;\nsetp.lt.u32 q, c, 100000;\n@q bra LW;\ntrap;\nLD:\n}" ::"r"(b), "r"(ph) : "memory");
}
__device__ __forceinline__ void nb_sync(int id, int n) { asm volatile("bar.sync %0, %1;" ::"r"(id), "r"(n) : "memory"); }
__device__ __forceinline__ void nb_arrive(int id, int n) { asm volatile("bar.arrive %0, %1;" ::"r"(id), "r"(n) : "memory"); }
__device__ __forceinline__ void wg_fence() { asm volatile("wgmma.fence.sync.aligned;" ::: "memory"); }
__device__ __forceinline__ void wg_commit() { asm volatile("wgmma.commit_group.sync.aligned;" ::: "memory"); }
template <int N> __device__ __forceinline__ void wg_wait() { asm volatile("wgmma.wait_group.sync.aligned %0;" ::"n"(N) : "memory"); }
template <int N> __device__ __forceinline__ void reg_fence(float (&a)[N]) {
#pragma unroll
  for (int i = 0; i < N; i++) asm volatile("" : "+f"(a[i])::"memory");
}
template <int N> __device__ __forceinline__ void reg_zero(float (&a)[N]) {
#pragma unroll
  for (int i = 0; i < N; i++) a[i] = 0.f;
}
__device__ __forceinline__ constexpr uint64_t mkdesc(uint32_t addr, uint32_t lbo, uint32_t sbo, uint32_t swz) {
  return (uint64_t)(addr >> 4) | ((uint64_t)(lbo >> 4) << 16) | ((uint64_t)(sbo >> 4) << 32) | ((uint64_t)swz << 62);
}
__device__ __forceinline__ void fence_async_smem() { asm volatile("fence.proxy.async.shared::cta;" ::: "memory"); }
__device__ __forceinline__ void st_relaxed(uint32_t* p, uint32_t v) { asm volatile("st.relaxed.gpu.global.u32 [%0], %1;" ::"l"(p), "r"(v) : "memory"); }
__device__ __forceinline__ uint32_t ld_relaxed(const uint32_t* p) { uint32_t v; asm volatile("ld.relaxed.gpu.global.u32 %0, [%1];" : "=r"(v) : "l"(p) : "memory"); return v; }
__device__ __forceinline__ void st_unit(uint4* p, uint32_t a, uint32_t b, uint32_t c, uint32_t d, uint32_t par) {
  asm volatile("{\n.reg .b64 x, y;\n.reg .b128 z;\nmov.b64 x, {%1,%2};\nmov.b64 y, {%3,%4};\nmov.b128 z, {x, y};\nst.relaxed.gpu.global.b128 [%0], z;\n}"
               ::"l"(p), "r"((a & ~1u) | par), "r"(b), "r"(c), "r"(d) : "memory");
}
__device__ __forceinline__ uint4 lds128(uint32_t a) { uint4 v; asm volatile("ld.shared.v4.u32 {%0,%1,%2,%3}, [%4];" : "=r"(v.x), "=r"(v.y), "=r"(v.z), "=r"(v.w) : "r"(a)); return v; }
__device__ __forceinline__ float4 lds128f(uint32_t a) { float4 v; asm volatile("ld.shared.v4.f32 {%0,%1,%2,%3}, [%4];" : "=f"(v.x), "=f"(v.y), "=f"(v.z), "=f"(v.w) : "r"(a)); return v; }
__device__ __forceinline__ float4 lds128v(uint32_t a) { float4 v; asm volatile("ld.volatile.shared.v4.f32 {%0,%1,%2,%3}, [%4];" : "=f"(v.x), "=f"(v.y), "=f"(v.z), "=f"(v.w) : "r"(a) : "memory"); return v; }
__device__ __forceinline__ float lds32v(uint32_t a) { float v; asm volatile("ld.volatile.shared.f32 %0, [%1];" : "=f"(v) : "r"(a) : "memory"); return v; }
__device__ __forceinline__ float2 lds64f(uint32_t a) { float2 v; asm volatile("ld.shared.v2.f32 {%0,%1}, [%2];" : "=f"(v.x), "=f"(v.y) : "r"(a)); return v; }
__device__ __forceinline__ uint32_t lds32(uint32_t a) { uint32_t v; asm volatile("ld.shared.u32 %0, [%1];" : "=r"(v) : "r"(a)); return v; }
__device__ __forceinline__ void sts128(uint32_t a, uint32_t x, uint32_t y, uint32_t z, uint32_t w) { asm volatile("st.shared.v4.u32 [%0], {%1,%2,%3,%4};" ::"r"(a), "r"(x), "r"(y), "r"(z), "r"(w) : "memory"); }
__device__ __forceinline__ void sts128f(uint32_t a, float x, float y, float z, float w) { asm volatile("st.shared.v4.f32 [%0], {%1,%2,%3,%4};" ::"r"(a), "f"(x), "f"(y), "f"(z), "f"(w) : "memory"); }
__device__ __forceinline__ void sts64(uint32_t a, uint32_t x, uint32_t y) { asm volatile("st.shared.v2.u32 [%0], {%1,%2};" ::"r"(a), "r"(x), "r"(y) : "memory"); }
__device__ __forceinline__ void sts32(uint32_t a, uint32_t x) { asm volatile("st.shared.u32 [%0], %1;" ::"r"(a), "r"(x) : "memory"); }
__device__ __forceinline__ void stsm4(uint32_t a, uint32_t r0, uint32_t r1, uint32_t r2, uint32_t r3) {
  asm volatile("stmatrix.sync.aligned.m8n8.x4.shared.b16 [%0], {%1,%2,%3,%4};" ::"r"(a), "r"(r0), "r"(r1), "r"(r2), "r"(r3) : "memory");
}
__device__ __forceinline__ uint4 ldsm4(uint32_t a) {
  uint4 v; asm volatile("ldmatrix.sync.aligned.m8n8.x4.shared.b16 {%0,%1,%2,%3}, [%4];" : "=r"(v.x), "=r"(v.y), "=r"(v.z), "=r"(v.w) : "r"(a) : "memory"); return v;
}
__device__ __forceinline__ uint32_t pack(float lo, float hi) { uint32_t r; asm("cvt.rn.bf16x2.f32 %0, %1, %2;" : "=r"(r) : "f"(hi), "f"(lo)); return r; }
__device__ __forceinline__ float bf_lo(uint32_t w) { return __uint_as_float(w << 16); }
__device__ __forceinline__ float bf_hi(uint32_t w) { return __uint_as_float(w & 0xffff0000u); }
__device__ __forceinline__ float bf_round(float x) { return bf_lo(pack(x, x)); }
__device__ __forceinline__ float ex2(float x) { float v; asm("ex2.approx.ftz.f32 %0, %1;" : "=f"(v) : "f"(x)); return v; }
__device__ __forceinline__ float rcp(float x) { float v; asm("rcp.approx.ftz.f32 %0, %1;" : "=f"(v) : "f"(x)); return v; }
__device__ __forceinline__ float addsat(float a, float b) { float v; asm("add.sat.f32 %0, %1, %2;" : "=f"(v) : "f"(a), "f"(b)); return v; }
__device__ __forceinline__ float phi2(float a) { return fmaf(fmaxf(a, 0.f), LN2, addsat(ex2(a), 1e-6f)); }
__device__ __forceinline__ float key_score(uint32_t key) { uint32_t u = key >> 16; u = (u & 0x8000u) ? (u & 0x7fffu) : (~u & 0xffffu); return __uint_as_float(u << 16); }
__device__ __forceinline__ int key_token(uint32_t key) { return 2047 - (int)((key >> 5) & 2047u); }
__device__ __forceinline__ uint32_t bsel(uint32_t a, uint32_t b, uint32_t m) { uint32_t r; asm("lop3.b32 %0, %1, %2, %3, 0xd8;" : "=r"(r) : "r"(a), "r"(b), "r"(m)); return r; }
__device__ __forceinline__ uint32_t prmt(uint32_t a, uint32_t b, uint32_t c) { uint32_t r; asm("prmt.b32 %0, %1, %2, %3;" : "=r"(r) : "r"(a), "r"(b), "r"(c)); return r; }
__device__ __forceinline__ uint32_t tagf(float v, uint32_t par) { return (__float_as_uint(v) & ~1u) | par; }
__device__ __forceinline__ float xred(float a, float b, bool up, int o) { return (up ? b : a) + __shfl_xor_sync(0xffffffffu, up ? a : b, o); }

#define STAMP(id)
#define STAMP_IF(c, id)
#define STAMP2(i)
#define LITE 1
#define LITE_MASK 0ull

template <bool TRANS, int NK = 16>
__device__ __forceinline__ void mainloop(float (&a0)[64], float (&a1)[64], int s, int ph, int handoff, int xpair, bool leader) {
  uint32_t prev = 0;
#pragma unroll 1
  for (int kt = 0; kt < NK; kt++) {
    const bool xr = !TRANS && (kt >> 1) == xpair;
    mbar_wait(B_FULL + 8 * s, ph);
    const uint64_t dw = mkdesc(RING, 8192, 1024, 1) + s * (SLOT >> 4), dx = mkdesc(0, 16, 1024, 1) + (xr ? (STG >> 4) + (kt & 1) * 1024 : ((RING + 16384) >> 4) + s * (SLOT >> 4));
    if (xr) mbar_wait(B_XRES + 8 * (kt & 1), 0);
    wg_fence();
#pragma unroll
    for (int j = 0; j < 4; j++) {
      if (TRANS) {
        wgmma_n128_ss<1, 0>(a0, dw + j * 128, dx + j * 2, 1);
        wgmma_n128_ss<1, 0>(a1, dw + j * 128 + 512, dx + j * 2, 1);
      } else {
        wgmma_n128_ss<0, 1>(a0, dx + j * 2, dw + j * 128, 1);
        wgmma_n128_ss<0, 1>(a1, dx + j * 2 + 512, dw + j * 128, 1);
      }
    }
    wg_commit();
    if (handoff && kt == 15) nb_arrive(handoff, 256);
    wg_wait<1>();
    if (prev && leader) mbar_arrive(prev);
    prev = B_EMPTY + 8 * s;
    if (++s == NST) { s = 0; ph ^= 1; }
  }
  if (NK < 16) return;
  wg_wait<0>();
  if (leader) mbar_arrive(prev);
  reg_fence(a0);
  reg_fence(a1);
}

__device__ __forceinline__ int out_kblock(int r, int tn) {
  const int q = r - 2, half = q >= 7, pi = q - 7 * half;
  return r < 2 ? 2 * tn + r : 2 * ((pi + (pi >= (tn & 3))) ^ (tn & 4)) + half;
}

struct Params {
  const char *x, *wqkv, *w_r, *wg, *wu, *wd;
  CUtensorMap m_wqkv, m_x, m_xs, m_o, m_os, m_wo, m_gu, m_down, m_out;
};

template <bool BY_SMID>
__global__ void __launch_bounds__(512, 1) fused_kernel(const __grid_constant__ Params mp) {
  extern __shared__ __align__(1024) uint8_t smem_raw[];
#define CK(i)
  CK(0);
  const int tid = threadIdx.x, lane = tid & 31;
  const int w = __shfl_sync(0xffffffffu, tid >> 5, 0);
  int bid = blockIdx.x;
  if (BY_SMID) {
    uint32_t sm;
    asm volatile("mov.u32 %0, %%smid;" : "=r"(sm));
    const uint32_t p = sm >> 1, q = ((p - 32) * 37) >> 8;
    const uint32_t gpc = p < 32 ? p & 7 : p < 60 ? p - 31 - 7 * q : 0, tpc = p < 32 ? p >> 3 : p < 60 ? 4 + q : p - 58;
    bid = (p >> 1) == 30 ? 128 + ((0x9cu >> (2 * (sm & 3))) & 3) : ((GPCMAP >> (4 * gpc)) & 7) * 16 + tpc * 2 + (sm & 1);
  }
  const int tn = (bid & 3) + 4 * (bid >> 6), tm = (bid >> 2) & 15;

  CK(1);
  if (w == 0) {
#pragma unroll 1
    for (int s = 0; s < NST; s++) {
      asm volatile(ELECT "@p mbarrier.init.shared::cta.b64 [%0], 1;\n}" ::"r"(B_FULL + 8 * s) : "memory");
      if (bid < 128) {
        e_expect(B_FULL + 8 * s, 32768);
        e_tma2d(RING + s * SLOT + 16384, &mp.m_x, s * 64, tm * 128, B_FULL + 8 * s);
        e_tma3d(RING + s * SLOT, &mp.m_wqkv, s * 64, 16 + 2 * tn, B_FULL + 8 * s);
      }
      if (s == 0) CK(2);
    }
  }
  if (w == 1) e_pfmap(&mp.m_wqkv);
  if (w == 2) e_pfmap(&mp.m_xs);
  if (w >= 4) {
#pragma unroll 1
    for (uint32_t b = MISC + 8 * (w + 1); b < MISC + 8 * NBAR; b += 96)
      asm volatile(ELECT "@p mbarrier.init.shared::cta.b64 [%0], %1;\n}" ::"r"(b), "r"(b == B_CSDN ? 4 : 1) : "memory");
    if (w == 15) sts32(S_NCAND, 0);
  }
  CK(3);
  asm volatile("fence.mbarrier_init.release.cluster;" ::: "memory");
  __syncthreads();

  if (bid >= 128) {
    const int h0 = bid == 128 ? 14 : bid - 129, hs = bid == 128 ? 1 : 3, h1 = bid == 128 ? 16 : 14;
    if (w == 12) {
      int s = 0, ph = 1;
#pragma unroll 1
      for (int h = h0; h < h1; h += hs) {
        const int c = 2 * h + (h & 8) * 2;
        if (h == 14) mbar_wait(B_SEL, 0);
#pragma unroll 1
        for (int kt = 0; kt < 16; kt += 2) {
          mbar_wait(B_EMPTY + 8 * s, ph);
          e_expect(B_FULL + 8 * s, 32768);
          e_tma3d(RING + s * SLOT, &mp.m_wqkv, kt * 64, c, B_FULL + 8 * s);
          e_tma3d(RING + s * SLOT + 16384, &mp.m_wqkv, kt * 64 + 64, c, B_FULL + 8 * s);
          if (++s == HST) { s = 0; ph ^= 1; }
        }
      }
    } else if (w < 4) {
      const uint32_t par = (ld_relaxed(&g_epoch) + 1) & 1u;
      sts32(S_ONES + tid * 4, 0x3f803f80u);
      fence_async_smem();
      nb_sync(NB_WG0, 128);
      int s = 0, ph = 0;
#pragma unroll 1
      for (int h = h0; h < h1; h += hs) {
        float c[4][4];
#pragma unroll
        for (int q = 0; q < 4; q++) reg_zero(c[q]);
        uint32_t prev = 0;
#pragma unroll 1
        for (int kt = 0; kt < 8; kt++) {
          mbar_wait(B_FULL + 8 * s, ph);
          const uint64_t dw = mkdesc(RING, 8192, 1024, 1) + s * (SLOT >> 4);
          wg_fence();
#pragma unroll
          for (int j = 0; j < 16; j++) wgmma_n8_ss<1, 0>(c[j & 3], dw + (j & 3) * 512 + (j >> 2) * 128, mkdesc(S_ONES, 128, 128, 0), 1);
          wg_commit();
          wg_wait<1>();
          if (prev && tid == 0) mbar_arrive(prev);
          prev = B_EMPTY + 8 * s;
          if (++s == HST) { s = 0; ph ^= 1; }
        }
        wg_wait<0>();
        if (tid == 0) mbar_arrive(prev);
#pragma unroll
        for (int q = 0; q < 4; q++) reg_fence(c[q]);
        const bool u2 = lane & 2, u1 = lane & 1;
        const float lo = u2 ? c[1][0] + c[3][0] : c[0][0] + c[2][0], hi = u2 ? c[1][2] + c[3][2] : c[0][2] + c[2][2];
        st_relaxed(g_csum + h * 128 + (lane & 2) * 32 + w * 16 + (lane & 1) * 8 + (lane >> 2), tagf(u1 ? hi : lo, par));
        STAMP_IF(tid == 0, h >= 8 ? 6 : 30);
      }
    } else if (w < 12 && bid == 128) {
      const int t = tid - 128, j = w - 4;
      const uint32_t ep = ld_relaxed(&g_epoch) + 1;
      uint32_t kk[16];
      poll_keys(kk, g_keys + t * 2, ep, 31u);
      STAMP_IF(t == 0, 42);
      const uint32_t m = __reduce_max_sync(0xffffffffu, max(max(max(kk[0], kk[2]), max(kk[4], kk[6])), max(max(kk[8], kk[10]), max(kk[12], kk[14]))));
      if (lane == 0) sts32(S_WMAX + j * 4, m);
      nb_sync(NB_WG1, 256);
      const uint32_t T = __reduce_min_sync(0xffffffffu, lds32(S_WMAX + (lane & 7) * 4));
      uint32_t cnt = 0;
#pragma unroll
      for (int i = 0; i < 8; i++) cnt += kk[2 * i] >= T;
      if (cnt) {
        uint32_t pos;
        asm volatile("atom.shared.add.u32 %0, [%1], %2;" : "=r"(pos) : "r"(S_NCAND), "r"(cnt * 8) : "memory");
#pragma unroll
        for (int i = 0; i < 8; i++)
          if (kk[2 * i] >= T) { sts64(AUX + pos, kk[2 * i], kk[2 * i + 1]); pos += 8; }
      }
      nb_sync(NB_WG1, 256);
      const uint32_t n8 = lds32(S_NCAND);
#pragma unroll 1
      for (uint32_t i = j * 8; i < n8; i += 64) {
        const float2 c = lds64f(AUX + i);
        uint32_t rank = 0;
#pragma unroll 1
        for (uint32_t q = lane * 8; q < n8 + lane * 8; q += 256) rank += __popc(__ballot_sync(0xffffffffu, q < n8 && lds32(AUX + q) > __float_as_uint(c.x)));
        if (rank < 8) sts64(S_SEL + rank * 8, __float_as_uint(c.x), __float_as_uint(c.y));
      }
      fence_async_smem();
      nb_sync(NB_WG1, 256);
      if (j == 0) {
        const uint4 v = lds128(S_SEL + (lane & 3) * 16);
        asm volatile("{\n.reg .b64 x, y;\nmov.b64 x, {%1,%2};\nmov.b64 y, {%3,%4};\nst.relaxed.gpu.global.v2.b64 [%0], {x, y};\n}"
                     ::"l"(g_sel + (lane >> 2) * 16 + (lane & 3) * 2), "r"(v.x), "r"(v.y), "r"(v.z), "r"(v.w) : "memory");
        e_arrive(B_SEL);
      }
      STAMP_IF(t == 0, 45);
    }
  } else if (w >= 12) {
    asm volatile("setmaxnreg.dec.sync.aligned.u32 32;");
    if (w == 12) {
      int s = 0, ph = 0;
#pragma unroll 1
      for (int it = NST; it < 48; it++) {
        const int c = (it < 32 ? (it & 16) + 16 : 0) + 2 * tn;
        const int k0 = ((it + (it >= 32 && tn < 4 ? 8 : 0)) & 15) * 64;
        const bool xr = (it >> 1) == 20 + (tn & 3);
        if (xr) { mbar_wait(B_SFREE, 0); e_expect(B_XRES + 8 * (it & 1), 16384); }
        mbar_wait(B_EMPTY + 8 * s, ph);
        e_expect(B_FULL + 8 * s, xr ? 16384 : 32768);
        e_tma3d(RING + s * SLOT, &mp.m_wqkv, k0, c, B_FULL + 8 * s);
        e_tma2d(xr ? STG + (it & 1) * 16384 : RING + s * SLOT + 16384, &mp.m_x, k0, tm * 128, xr ? B_XRES + 8 * (it & 1) : B_FULL + 8 * s);
        if (it >= NST) STAMP2(it - NST);
        if (++s == NST) { s = 0; ph ^= 1; }
      }
#pragma unroll 1
      for (int r = 0; r < 16; r++) {
        const int kb = out_kblock(r, tn);
        mbar_wait(B_EMPTY + 8 * s, ph);
        e_expect(B_FULL + 8 * s, r < 2 ? 16384 : 32768);
        e_tma3d(RING + s * SLOT, &mp.m_wo, kb * 64, 2 * tn, B_FULL + 8 * s);
        if (r < 2 || r == 4) {
          const uint32_t bar = B_DR + (r < 2 ? 16 : 8);
          const int k0 = (bid >> 4) * 448 + 128 + min(r, 2) * 128;
          if (r != 1) e_expect(bar, r ? 8192 : 32768);
          e_tma2d_ef(RING + s * SLOT + 16384, &mp.m_down, (bid & 15) * 64, k0, bar, EVICT_FIRST);
          if (r < 2) e_tma2d_ef(RING + s * SLOT + 24576, &mp.m_down, (bid & 15) * 64, k0 + 64, bar, EVICT_FIRST);
        }
        STAMP2(r + 48 - NST);
        if (++s == NST) { s = 0; ph ^= 1; }
      }
    } else if (w == 13) {
      mbar_wait(B_FULL, 0);
#pragma unroll 1
      for (int c = 0; c < 4; c++) {
        if (c >= XS_FLY) mbar_wait(B_XS + 8 * (c - XS_FLY), 0);
        if (c == (tm >> 2)) {
          e_expect(B_WK, 16384);
          e_tma3d(FR, &mp.m_wqkv, tm * 64, 16 + 2 * tn, B_WK);
        }
        e_expect(B_XS + 8 * c, 8192);
        e_tma2d(STG + c * 8192, &mp.m_xs, c * 256, tm * 128 + tn * 16, B_XS + 8 * c);
      }
      {
        const char* pd = mp.wd + (bid & 15) * 128 + ((bid >> 4) * 448 + lane) * 2048;
        mbar_wait(B_XS + 24, 0);
        __nanosleep(PF_WAIT);
#pragma unroll 1
        for (int i = 0; i < 14; i++, pd += 65536) {
          if (PF_GAP) asm volatile("prefetch.global.L2 [%0];" ::"l"(pd));
          if (PF_GAP) __nanosleep(PF_GAP);
        }
      }
      nb_sync(NB_Z, 160);
      const uint32_t ep = lds32(S_EPOCH);
      {
        float z[4] = {0.f, 0.f, 0.f, 0.f};
        e_signal(H_Z + tn, tm);
        await(H_Z + tn, 0xffffu, ep);
#pragma unroll 1
        for (int i = 0; i < 4; i++) {
          uint32_t p[16];
          poll_z(p, g_z + i * 4096 + tn * 128 + lane * 4, ep, 1u);
#pragma unroll
          for (int q = 0; q < 4; q++) z[q] += (__uint_as_float(p[q]) + __uint_as_float(p[4 + q])) + (__uint_as_float(p[8 + q]) + __uint_as_float(p[12 + q]));
        }
        const uint32_t z01 = pack(z[0], z[1]), z23 = pack(z[2], z[3]);
        if (bid < 112) mbar_wait(B_PFREE, 0);
#pragma unroll
        for (int n = 0; n < 8; n++) sts64(KVB + (lane >> 4) * 5120 + n * 128 + ((((lane >> 1) & 7) ^ n) << 4) + (lane & 1) * 8, z01, z23);
        fence_async_smem();
        nb_arrive(NB_KVB, 320);
        STAMP_IF(lane == 0, 46);
      }
      nb_sync(NB_Q0, 192);
      e_store2d(&mp.m_os, tn * 128, tm * 128, STG);
      nb_sync(NB_OWN0, 288);
      e_store2d(&mp.m_os, tn * 128, tm * 128 + 64, STG + 8192);
      bulk_wait_read();
      e_signal(H_O + tm, 2 * tn);
      STAMP_IF(lane == 0, 4);
      nb_sync(NB_H1, 160);
      e_store2d(&mp.m_os, tn * 128 + 64, tm * 128, STG + 16384);
      e_store2d(&mp.m_os, tn * 128 + 64, tm * 128 + 64, STG + 24576);
      bulk_wait_read();
      e_signal(H_O + tm, 2 * tn + 1);
      STAMP_IF(lane == 0, 5);
      nb_arrive(NB_ST, 288);
    } else if (w == 14) {
      e_pfmap(&mp.m_gu); e_pfmap(&mp.m_o); e_pfmap(&mp.m_os); e_pfmap(&mp.m_wo); e_pfmap(&mp.m_down); e_pfmap(&mp.m_out);
      const uint32_t ep = ld_relaxed(&g_epoch) + 1;
      nb_sync(NB_FDONE, 416);
      {
        uint32_t c[4];
        poll_quad(c, g_csum + tn * 128 + lane * 4, ep, 1u);
        sts128(S_CSQ + lane * 16, c[0], c[1], c[2], c[3]);
        nb_arrive(NB_CSQ, 160);
        poll_quad(c, g_csum + 1024 + tn * 128 + lane * 4, ep, 1u);
        sts128(S_CSV + lane * 16, c[0], c[1], c[2], c[3]);
        __syncwarp();
        e_arrive(B_CSV);
      }
      {
        mbar_wait(B_WK, 1);
        if (KV_SPEC) __nanosleep(KV_SPEC); else await(H_KV + tn, 0xffffu, ep);
        STAMP_IF(lane == 0, 7);
        if (bid < 112) mbar_wait(B_PFREE, 0);
        STAMP_IF(lane == 0, 23);
        uint32_t bad, ph = 0;
        do {
          e_expect(B_KVL, 8192);
          e_load(KVB + 1024, g_kv + tn * 512, 4096, B_KVL);
          e_load(KVB + 6144, g_kv + tn * 512 + 256, 4096, B_KVL);
          mbar_wait(B_KVL, ph & 1);
          bad = 0;
#pragma unroll
          for (int i = 0; i < 16; i++) bad |= __float_as_uint(lds32v(KVB + 1024 + (i & 8) * 128 + i * 512 + lane * 16)) ^ ep;
          bad = __any_sync(0xffffffffu, bad & 1u);
          if (bad) fence_async_smem();
        } while (bad && ++ph < 100000);
        nb_arrive(NB_KVB, 320);
        STAMP_IF(lane == 0, 24);
      }
      nb_sync(NB_Q0, 192);
      uint32_t ready = 0;
      int s = 0, ph = 1;
#pragma unroll 1
      for (int r = 2; r < 16; r++) {
        const int kb = out_kblock(r, tn);
        if (!((ready >> kb) & 1)) {
          uint32_t f[1];
          poll0(f, g_sig + (H_O + tm) * 32, 0u - (ep & 1u), 1u << kb);
          ready = f[0] ^ ((ep & 1u) - 1u);
        }
        if (r == 4) mbar_wait(B_DND, 0);
        mbar_wait(B_EMPTY + 8 * s, ph);
        e_tma2d(RING + s * SLOT + 16384, &mp.m_o, kb * 64, tm * 128, B_FULL + 8 * s);
        STAMP_IF(lane == 0 && r == 2, 2);
        STAMP_IF(lane == 0 && r == 9, 3);
        if (++s == NST) { s = 0; ph ^= 1; }
      }
    } else {
      uint32_t nsm = 132;
      if (BY_SMID) asm volatile("mov.u32 %0, %%nsmid;" : "=r"(nsm));
      asm volatile("{\n.reg .pred q;\nsetp.eq.u32 q, %0, 1156;\n@q bra LOK;\ntrap;\nLOK:\n}" ::"r"((uint32_t)__cvta_generic_to_shared(smem_raw) + nsm));
      const uint32_t ep = ld_relaxed(&g_epoch) + 1;
      mbar_wait(B_CSDN, 0);
#pragma unroll 1
      for (int n = 0; n < 3 && bid < 112; n++) {
        __nanosleep(FFN_GAP);
        e_expect(B_FR + 8 * n, 8192);
        e_tma3d_ef(GR + n * 8192, &mp.m_gu, bid * 32, n * 64, B_FR + 8 * n, EVICT_FIRST);
      }
      uint32_t sel[2];
      poll_pair(sel, g_sel + (bid >> 4) * 16 + (lane >> 2), ep, 31u);
      const char* xs = mp.x + key_token(sel[0]) * 2048 + (lane & 3) * 16;
      const uint32_t xd = AUX + (lane >> 2) * 64 + (((lane & 3) ^ (lane >> 3)) << 4);
      auto slices = [&](int n, int p) {
        asm volatile("cp.async.cg.shared.global [%0], [%1], 16;\ncp.async.cg.shared.global [%0+512], [%1+64], 16;\ncp.async.commit_group;"
                     ::"r"(xd + p * 1024), "l"(xs + n * 128) : "memory");
      };
      if ((lane & 3) == 0) sts64(S_SEL + lane * 2, sel[0], sel[1]);
      if (bid < 112) {
#pragma unroll
        for (int i = 0; i < 6; i++) slices(i, i);
      }
      asm volatile("cp.async.wait_group 2;" ::: "memory");
      fence_async_smem();
      __syncwarp();
      e_arrive(B_SEL);
      if (bid < 112) {
        int s = 0, ph = 0;
#pragma unroll 1
        for (int n = 3; n < 16; n++) {
          mbar_wait(B_FE + 8 * s, ph);
          e_expect(B_FR + 8 * s, 8192);
          e_tma3d_ef(GR + s * 8192, &mp.m_gu, bid * 32, n * 64, B_FR + 8 * s, EVICT_FIRST);
          STAMP2(64 + n);
          asm volatile("cp.async.wait_group 1;" ::: "memory");
          fence_async_smem();
          __syncwarp();
          if (n < 13) slices(n + 3, s + 3 * ph);
          else asm volatile("cp.async.commit_group;" ::: "memory");
          if (++s == 3) { s = 0; ph ^= 1; }
        }
      }
      e_expect(B_DR, 16384);
      if (bid < 112) mbar_wait(B_FE + 8, 0);
      e_tma2d_ef(FR, &mp.m_down, (bid & 15) * 64, (bid >> 4) * 448, B_DR, EVICT_FIRST);
      if (bid < 112) mbar_wait(B_FE + 16, 0);
      e_tma2d_ef(FR + 8192, &mp.m_down, (bid & 15) * 64, (bid >> 4) * 448 + 64, B_DR, EVICT_FIRST);
    }
  } else if (w >= 8) {
    asm volatile("setmaxnreg.dec.sync.aligned.u32 56;");
    const int t = tid - 256, ww = w - 8;
    const uint32_t ep = ld_relaxed(&g_epoch) + 1, par = ep & 1u;
    sts32(FONES + t * 4, 0x3f803f80u);
    {
      const int r0 = (lane >> 3) + (lane & 4);
      const uint32_t a = FR + (ww >> 1) * 8192 + r0 * 128 + ((((ww & 1) * 4 + (lane & 3)) ^ r0) << 4);
      float c[8];
      reg_zero(c);
      mbar_wait(B_WK, 0);
#pragma unroll 2
      for (int i = 0; i < 8; i++) {
        const uint4 v = lds128(a + i * 1024);
        c[0] += bf_lo(v.x); c[1] += bf_hi(v.x); c[2] += bf_lo(v.y); c[3] += bf_hi(v.y);
        c[4] += bf_lo(v.z); c[5] += bf_hi(v.z); c[6] += bf_lo(v.w); c[7] += bf_hi(v.w);
      }
      const bool u16 = lane & 16, u8 = lane & 8, u4 = lane & 4;
      const float d0 = xred(c[0], c[4], u16, 16), d1 = xred(c[1], c[5], u16, 16), d2 = xred(c[2], c[6], u16, 16), d3 = xred(c[3], c[7], u16, 16);
      fence_async_smem();
      e_arrive(B_CSDN);
      const float sum = xred(xred(d0, d2, u8, 8), xred(d1, d3, u8, 8), u4, 4);
      st_relaxed(g_csum + (2 + tm) * 1024 + tn * 128 + ww * 32 + (lane & 3) * 8 + (lane >> 2), tagf(sum, par));
      STAMP_IF(t == 0, 8);
      nb_sync(NB_WG2, 128);
      if (ww == 0) { e_signal(H_CS + tn, tm); await(H_CS + tn, 0xffffu, ep); }
      nb_sync(NB_WG2, 128);
      uint32_t p[16];
      poll16(p, g_csum + 2048 + tn * 128 + t, par, 1u);
      float tot = 0.f;
#pragma unroll
      for (int i = 0; i < 16; i += 4) tot += (__uint_as_float(p[i]) + __uint_as_float(p[i + 1])) + (__uint_as_float(p[i + 2]) + __uint_as_float(p[i + 3]));
      sts32(S_CSK + t * 4, __float_as_uint(tot));
      nb_arrive(NB_FDONE, 416);
      STAMP_IF(t == 0, 9);
    }
    const int ks = bid >> 4, nt = bid & 15;
    if (bid < 112) {
      float fg[8];
      reg_zero(fg);
      mbar_wait(B_SEL, 0);
      constexpr uint64_t DA0 = mkdesc(GR, 4096, 512, 2), DB0 = mkdesc(AUX, 16, FONES - AUX, 2), DBS = 32 - (32ull << 32);
      uint64_t da = DA0, db = DB0;
      uint32_t bar = B_FR, ph = 0;
#pragma unroll 1
      for (int n = 0; n < 16; n++) {
        mbar_wait(bar, ph);
        wg_fence();
#pragma unroll
        for (int q = 0; q < 4; q++) wgmma_n16_ss<1, 0>(fg, da + q * 64, db + (q >> 1) * DBS + (q & 1) * 2, 1);
        wg_commit();
        const uint32_t rel = bar + (B_FE - B_FR);
        const bool wrap = bar == B_FR + 16;
        da = wrap ? DA0 : da + 512;
        db = wrap && ph ? DB0 : db + 2 * DBS;
        bar = wrap ? B_FR : bar + 8;
        ph ^= wrap;
        wg_wait<0>();
        if (t == 0) mbar_arrive(rel);
      }
      if (t == 0) mbar_arrive(B_PFREE);
      const uint4 st = lds128(S_SEL + (lane & 3) * 16);
      const float r0 = rcp(bf_lo(st.y)), r1 = rcp(bf_lo(st.w));
      reg_fence(fg);
      const float fa[4] = {fmaf(-bf_hi(st.y), fg[4], fg[0]) * r0, fmaf(-bf_hi(st.w), fg[4], fg[1]) * r1,
                           fmaf(-bf_hi(st.y), fg[6], fg[2]) * r0, fmaf(-bf_hi(st.w), fg[6], fg[3]) * r1};
      STAMP_IF(t == 0, 12);
      const bool isup = (ww >> 1) != (mp.wu < mp.wg);
      nb_sync(NB_WG2, 128);
      if (isup) sts128f(HOP + (t & 63) * 16, fa[0], fa[1], fa[2], fa[3]);
      nb_sync(NB_WG2, 128);
      if (!isup) {
        const float4 u = lds128f(HOP + (t & 63) * 16);
        const float uu[4] = {u.x, u.y, u.z, u.w};
        uint32_t* hp = g_h + bid * 256 + (lane & 3) * 64 + (ww & 1) * 16 + (lane >> 2);
#pragma unroll
        for (int i = 0; i < 4; i++) {
          const float g = fa[i], hv = g * rcp(1.f + ex2(-g * LOG2E)) * uu[i];
          st_relaxed(hp + (i & 1) * 32 + (i >> 1) * 8, __byte_perm(pack(hv, hv), ep, 0x3254));
        }
      }
      nb_sync(NB_WG2, 128);
      if (ww == 0) e_signal(H_H + bid / 14, bid % 14);
    }
    {
      uint32_t v[28];
      if (ww == 0) await(H_H + ks, 0x3fffu, ep);
      nb_sync(NB_WG2, 128);
      poll7x4(v, g_h + ks * 3584 + t * 4, ep, 0xffffu);
      mbar_wait(B_WK, 1);
#pragma unroll
      for (int q = 0; q < 7; q++)
        asm volatile("st.shared.v2.u32 [%0], {%1,%2};" ::"r"((q < 6 ? HOP + q * 1024 : S_CSK) + (t >> 3) * 64 + ((((t >> 1) & 3) ^ ((t >> 4) & 3)) << 4) + (t & 1) * 8),
                     "r"(__byte_perm(v[4 * q], v[4 * q + 1], 0x7632)), "r"(__byte_perm(v[4 * q + 2], v[4 * q + 3], 0x7632)) : "memory");
      fence_async_smem();
      nb_sync(NB_WG2, 128);
    }
    STAMP_IF(t == 0, 13);
    float fa[4] = {0.f, 0.f, 0.f, 0.f};
    auto down = [&](uint32_t a, int k0, int nk) {
#pragma unroll
      for (int q = 0; q < nk; q++) wgmma_n8_ss<1, 0>(fa, mkdesc(a + q * 2048, 4096, 1024, 1), mkdesc((k0 < 24 ? HOP : S_CSK - 6144) + ((k0 + q) >> 1) * 512 + (q & 1) * 32, 16, 512, 2), 1);
    };
    mbar_wait(B_DR, 0);
    mbar_wait(B_DR + 16, 0);
    mbar_wait(B_DR + 8, 0);
    wg_fence();
    down(RING + 2 * SLOT + 16384, 24, 4);
    down(RING + 3 * SLOT + 16384, 8, 8);
    down(RING + 4 * SLOT + 16384, 16, 8);
    wg_commit();
    wg_fence();
    down(FR, 0, 8);
    wg_commit();
    wg_wait<1>();
    if (t == 0) mbar_arrive(B_DND);
    wg_wait<0>();
    reg_fence(fa);
    STAMP_IF(t == 0, 14);
    {
      uint32_t* yp = g_yp + (nt * 8 + ks) * 512 + (lane & 3) * 128 + ww * 16 + (lane >> 2);
#pragma unroll
      for (int i = 0; i < 4; i++) st_relaxed(yp + (i & 1) * 64 + (i >> 1) * 8, tagf(fa[i], par));
    }
    nb_sync(NB_WG2, 128);
    if (ww == 0) e_signal(H_Y + (nt >> 1), (nt & 1) * 8 + ks);
    mbar_wait(B_SEL, 0);
    const uint32_t mykey = lds32(S_SEL + (lane & 7) * 8);
    const uint32_t inmask = __ballot_sync(0xffffffffu, (key_token(mykey) >> 7) == tm) & 0xffu;
    sts128(FR + t * 16, 0u, 0u, 0u, 0u);
    if (inmask) {
      if (ww == 0) await(H_Y + tn, 0xffffu, ep);
      nb_sync(NB_WG2, 128);
      const float sg = rcp(1.f + ex2(-key_score(mykey) * LOG2E));
#pragma unroll 1
      for (uint32_t mine = __ballot_sync(0xffffffffu, ((inmask >> lane) & 1) && (__popc(inmask & ((1u << lane) - 1)) & 3) == ww); mine; mine &= mine - 1) {
        const int j = __ffs(mine) - 1;
        uint32_t p[32];
        poll8x4(p, g_yp + (tn * 2 + (lane >> 4)) * 4096 + j * 64 + (lane & 15) * 4, par, 1u);
        float y[4];
        const float sj = __shfl_sync(0xffffffffu, sg, j);
#pragma unroll
        for (int i = 0; i < 4; i++)
          y[i] = sj * (((__uint_as_float(p[i]) + __uint_as_float(p[4 + i])) + (__uint_as_float(p[8 + i]) + __uint_as_float(p[12 + i]))) +
                       ((__uint_as_float(p[16 + i]) + __uint_as_float(p[20 + i])) + (__uint_as_float(p[24 + i]) + __uint_as_float(p[28 + i]))));
        asm volatile("st.shared.v2.u32 [%0], {%1,%2};" ::"r"(FR + (lane >> 4) * 1024 + j * 128 + ((((lane >> 1) & 7) ^ j) << 4) + (lane & 1) * 8),
                     "r"(pack(y[0], y[1])), "r"(pack(y[2], y[3])) : "memory");
      }
    }
    fence_async_smem();
    nb_arrive(NB_ST, 288);
    STAMP_IF(t == 0, 15);
  } else if (w >= 4) {
    asm volatile("setmaxnreg.inc.sync.aligned.u32 208;");
    const int t = tid - 128, ww = w - 4, g = lane >> 2, t4 = lane & 3;
    const bool leader = t == 0;
    const uint32_t ep = ld_relaxed(&g_epoch) + 1, par = ep & 1u;
    {
      const uint4* wp = reinterpret_cast<const uint4*>(mp.w_r) + lane;
      uint4 w0 = __ldg(wp), w1 = __ldg(wp + 32), w2 = __ldg(wp + 64), w3 = __ldg(wp + 96);
      if (leader) sts32(S_EPOCH, ep);
      if (KV_SPEC && t4 == 0) {
        const int grp = (tm & 1) * 2 + ((lane >> 3) & 1), row = ww * 2 + ((lane >> 2) & 1);
        st_unit(g_kv + tn * 512 + ((tm >> 3) * 4 + grp) * 64 + row * 8 + (((tm & 2) * 2 + ((tm >> 1) & 2) + (lane >> 4)) ^ row), 0u, 0u, 0u, 0u, par ^ 1u);
      }
      float s[4] = {0.f, 0.f, 0.f, 0.f}, q[4] = {0.f, 0.f, 0.f, 0.f}, d[4] = {0.f, 0.f, 0.f, 0.f}, wsum = 0.f;
#pragma unroll 1
      for (int c = 0; c < 4; c++) {
        const float wr[8] = {bf_lo(w0.x), bf_hi(w0.x), bf_lo(w0.y), bf_hi(w0.y), bf_lo(w0.z), bf_hi(w0.z), bf_lo(w0.w), bf_hi(w0.w)};
        w0 = w1; w1 = w2; w2 = w3;
        wsum += ((wr[0] + wr[1]) + (wr[2] + wr[3])) + ((wr[4] + wr[5]) + (wr[6] + wr[7]));
        mbar_wait(B_XS + 8 * c, 0);
#pragma unroll
        for (int r = 0; r < 4; r++) {
          const uint4 v = lds128(STG + c * 8192 + (ww * 4 + r) * 512 + lane * 16);
          const uint32_t xw[4] = {v.x, v.y, v.z, v.w};
#pragma unroll
          for (int i = 0; i < 4; i++) {
            const uint32_t dep = __float_as_uint(q[i ? r : (r + 3) & 3]);
            const float lo = __uint_as_float(prmt(xw[i], dep, 0x10ff)), hi = __uint_as_float(prmt(xw[i], dep, 0x32ff));
            s[r] += lo; q[r] = fmaf(lo, lo, q[r]); d[r] = fmaf(lo, wr[2 * i], d[r]);
            s[r] += hi; q[r] = fmaf(hi, hi, q[r]); d[r] = fmaf(hi, wr[2 * i + 1], d[r]);
          }
        }
      }
      STAMP_IF(leader, 16);
      const bool u16 = lane & 16, u8 = lane & 8, u4 = lane & 4, u2 = lane & 2;
      const float s1 = xred(xred(s[0], s[2], u16, 16), xred(s[1], s[3], u16, 16), u8, 8);
      const float q1 = xred(xred(q[0], q[2], u16, 16), xred(q[1], q[3], u16, 16), u8, 8);
      const float d1 = xred(xred(d[0], d[2], u16, 16), xred(d[1], d[3], u16, 16), u8, 8);
      wsum += __shfl_xor_sync(0xffffffffu, wsum, 16);
      wsum += __shfl_xor_sync(0xffffffffu, wsum, 8);
      float tot = xred(xred(s1, d1, u4, 4), xred(q1, wsum, u4, 4), u2, 2);
      tot += __shfl_xor_sync(0xffffffffu, tot, 1);
      const float qq = __shfl_down_sync(0xffffffffu, tot, 2), dd = __shfl_down_sync(0xffffffffu, tot, 4), ws = __shfl_down_sync(0xffffffffu, tot, 6);
      if ((lane & 7) == 0) {
        const float mean = tot * (1.f / 1024.f);
        const float var = fmaxf(fmaf(-mean, mean, qq * (1.f / 1024.f)), 0.f);
        float sd;
        asm("sqrt.approx.ftz.f32 %0, %1;" : "=f"(sd) : "f"(bf_round(bf_round(var) + 1e-5f)));
        const uint32_t ms = pack(sd, mean);
        const int row = tm * 128 + tn * 16 + ww * 4 + (lane >> 3);
        const uint32_t rbits = pack(0.f, fmaf(-bf_hi(ms), ws, dd) * rcp(bf_lo(ms)));
        const uint32_t key = (rbits ^ (((int)rbits >> 31 & 0x7fff0000u) | 0x80000000u)) | ((2047 - row) << 5) | (ep & 31u);
        asm volatile("{\n.reg .b64 x;\nmov.b64 x, {%1,%2};\nst.relaxed.gpu.global.b64 [%0], x;\n}" ::"l"(g_keys + row), "r"(key), "r"(ms) : "memory");
      }
      STAMP_IF(leader, 17);
      __nanosleep(400);
      uint32_t st[2];
      poll_pair(st, g_keys + tm * 128 + t, ep, 31u);
      asm volatile("st.shared.v2.f32 [%0], {%1,%2};" ::"r"(S_KSTAT + t * 8), "f"(bf_hi(st[1])), "f"(rcp(bf_lo(st[1])) * LOG2E) : "memory");
      nb_arrive(NB_FDONE, 416);
      STAMP_IF(leader, 10);
    }
    float a0[64], a1[64];
    reg_zero(a0); reg_zero(a1); reg_fence(a0); reg_fence(a1);
    STAMP_IF(leader, 18);
    nb_sync(NB_KV, 256);
    mainloop<true, 14>(a0, a1, 1, 1, 0, 0, leader);
    {
      auto half = [&](float (&a)[64], int s, int m) {
#pragma unroll
        for (int j = 0; j < 4; j++)
          wgmma_n128_ss<1, 0>(a, mkdesc(RING + s * SLOT + m * 8192 + j * 2048, 8192, 1024, 1), mkdesc(RING + s * SLOT + 16384 + j * 32, 16, 1024, 1), 1);
      };
      auto kvmma = [&](float (&a)[64], float (&c)[32], int m) {
        reg_fence(a);
        uint32_t f[32];
#pragma unroll
        for (int i = 0; i < 32; i++) f[i] = pack(a[2 * i], a[2 * i + 1]);
        reg_zero(c);
        wg_fence();
#pragma unroll
        for (int k = 0; k < 8; k++) {
          wgmma_n64_rs<0>(c, f[4 * k], f[4 * k + 1], f[4 * k + 2], f[4 * k + 3], mkdesc(STG + (k >> 2) * 16384 + m * 8192 + (k & 3) * 32, 16, 1024, 1), k != 0);
          if (m && k == HAND_K) nb_arrive(NB_VQ, 256);
        }
        wg_commit();
      };
      float c0[32], c1[32];
      mbar_wait(B_FULL, 0);
      wg_fence();
      half(a0, 0, 0);
      wg_commit();
      mbar_wait(B_FULL + 8, 0);
      wg_fence();
      half(a0, 1, 0);
      wg_commit();
      wg_wait<2>();
      if (leader) mbar_arrive(B_EMPTY + 32);
      wg_fence();
      half(a1, 0, 1);
      half(a1, 1, 1);
      wg_commit();
      nb_sync(NB_PK, 256);
      wg_wait<1>();
      kvmma(a0, c0, 0);
      wg_wait<1>();
      if (leader) { mbar_arrive(B_EMPTY); mbar_arrive(B_EMPTY + 8); }
      STAMP_IF(leader, 19);
      kvmma(a1, c1, 1);
      const bool hp = ww >> 1;
      float c[4];
      float2 tt[8];
#pragma unroll
      for (int i = 0; i < 8; i++) tt[i] = lds64f(S_CSK + ((i >> 2) * 64 + hp * 32 + (i & 3) * 8 + 2 * t4) * 4);
      mbar_wait(B_CSV, 0);
#pragma unroll
      for (int i = 0; i < 4; i++) c[i] = -__uint_as_float(lds32(S_CSV + ((i >> 1) * 64 + ww * 16 + (i & 1) * 8 + g) * 4));
      wg_wait<0>();
      reg_fence(c0);
      reg_fence(c1);
      if (leader) mbar_arrive(B_SFREE);
      STAMP_IF(leader, 20);
      uint4* pp = g_kvp + (tn * 16 + tm) * 512 + t;
      auto put = [&](int q, const float* d) {
        const float ca = c[q & 2], cb = c[q | 1];
        const float2 ta = tt[2 * q], tb = tt[2 * q + 1];
        st_unit(pp + q * 128, pack(fmaf(ca, ta.x, d[0]), fmaf(ca, ta.y, d[1])), pack(fmaf(cb, ta.x, d[2]), fmaf(cb, ta.y, d[3])),
                pack(fmaf(ca, tb.x, d[4]), fmaf(ca, tb.y, d[5])), pack(fmaf(cb, tb.x, d[6]), fmaf(cb, tb.y, d[7])), par);
      };
      if (!hp) { put(0, c0); put(1, c0 + 8); put(2, c1); put(3, c1 + 8); }
      else { put(0, c0 + 16); put(1, c0 + 24); put(2, c1 + 16); put(3, c1 + 24); }
      STAMP_IF(leader, 47);
      {
        uint32_t p[16];
        nb_sync(NB_WG1, 128);
        if (ww == 0) { e_signal(H_KVP + tn, tm); await(H_KVP + tn, 0xffffu, ep); }
        nb_sync(NB_WG1, 128);
        STAMP_IF(leader, 1);
        poll_kvp(p, g_kvp + (tn * 16 + (lane >> 3) * 4) * 512 + tm * 32 + ww * 8 + (lane & 7), par, 1u);
        float r[8];
#pragma unroll
        for (int i = 0; i < 4; i++) {
          r[2 * i] = (bf_lo(p[i]) + bf_lo(p[4 + i])) + (bf_lo(p[8 + i]) + bf_lo(p[12 + i]));
          r[2 * i + 1] = (bf_hi(p[i]) + bf_hi(p[4 + i])) + (bf_hi(p[8 + i]) + bf_hi(p[12 + i]));
        }
        const bool u16 = lane & 16, u8 = lane & 8;
        const uint32_t wd = pack(xred(xred(r[0], r[4], u16, 16), xred(r[2], r[6], u16, 16), u8, 8), xred(xred(r[1], r[5], u16, 16), xred(r[3], r[7], u16, 16), u8, 8));
        const uint32_t w1 = __shfl_down_sync(0xffffffffu, wd, 1), w2 = __shfl_down_sync(0xffffffffu, wd, 2), w3 = __shfl_down_sync(0xffffffffu, wd, 3);
        const int grp = (tm & 1) * 2 + ((lane >> 3) & 1), row = ww * 2 + ((lane >> 2) & 1);
        if (t4 == 0) st_unit(g_kv + tn * 512 + ((tm >> 3) * 4 + grp) * 64 + row * 8 + (((tm & 2) * 2 + ((tm >> 1) & 2) + (lane >> 4)) ^ row), wd, w1, w2, w3, par);
        nb_sync(NB_WG1, 128);
        if (ww == 0) { if (!KV_SPEC) e_signal(H_KV + tn, tm); e_arrive(B_WK); }
      }
      STAMP_IF(leader, 21);
    }
    const uint32_t sx = lane & 7, sc = lane >> 4;
    const uint32_t sa = STG + (ww * 16 + (lane & 15)) * 128;
    const uint32_t sw[4] = {sa + ((sc ^ sx) << 4), sa + (((2 + sc) ^ sx) << 4), sa + (((4 + sc) ^ sx) << 4), sa + (((6 + sc) ^ sx) << 4)};
    auto residual = [&]() {
      float ka[4], kb[4];
#pragma unroll
      for (int i = 0; i < 4; i++) {
        const float2 st = lds64f(S_KSTAT + ((i >> 1) * 64 + ww * 16 + (i & 1) * 8 + g) * 8);
        const float r = st.y * LN2;
        ka[i] = 1.f + r; kb[i] = -st.x * r;
      }
#pragma unroll
      for (int j = 0; j < 8; j++) {
        if ((j & 3) == 0) mbar_wait(B_XRES + 8 * (j >> 2), 0);
        const uint4 v = ldsm4(sw[j & 3] + (j >> 2) * 16384), u = ldsm4(sw[j & 3] + (j >> 2) * 16384 + 8192);
        const uint32_t vv[4] = {v.x, v.y, v.z, v.w}, uu[4] = {u.x, u.y, u.z, u.w};
#pragma unroll
        for (int i = 0; i < 4; i++) {
          a0[8 * j + 2 * i] = fmaf(bf_lo(vv[i]), ka[i & 1], kb[i & 1]);
          a0[8 * j + 2 * i + 1] = fmaf(bf_hi(vv[i]), ka[i & 1], kb[i & 1]);
          a1[8 * j + 2 * i] = fmaf(bf_lo(uu[i]), ka[2 + (i & 1)], kb[2 + (i & 1)]);
          a1[8 * j + 2 * i + 1] = fmaf(bf_hi(uu[i]), ka[2 + (i & 1)], kb[2 + (i & 1)]);
        }
      }
      reg_fence(a0);
      reg_fence(a1);
      STAMP_IF(leader, 22);
    };
    residual();
    nb_arrive(NB_KVB, 320);
    uint32_t oh[4];
    {
      mbar_wait(B_SEL, 0);
      const int r0 = key_token(lds32(S_SEL + t4 * 16)) - tm * 128, r1 = key_token(lds32(S_SEL + t4 * 16 + 8)) - tm * 128;
#pragma unroll
      for (int i = 0; i < 4; i++) {
        const int row = (i >> 1) * 64 + ww * 16 + (i & 1) * 8 + g;
        oh[i] = (r0 == row ? 0x3f00u : 0u) | (r1 == row ? 0x3f000000u : 0u);
      }
    }
    uint32_t va = RING + 16384 + sc * 8192 + (ww * 16 + (lane & 8)) * 128 + sx * 16 + (lane >> 3) * 4;
    asm volatile("" : "+r"(va));
    {
      auto own = [&](int r) {
        nb_sync(NB_OWN0 + r, r ? 256 : 288);
        mbar_wait(B_FULL + 8 * (3 + r), 1);
        STAMP_IF(leader, 25 + r);
        const uint64_t dw = mkdesc(RING + (3 + r) * SLOT, 8192, 1024, 1), dx = mkdesc(STG + r * 16384, 16, 1024, 1);
        wg_fence();
#pragma unroll
        for (int j = 0; j < 4; j++) {
          wgmma_n128_ss<0, 1>(a0, dx + j * 2, dw + j * 128, 1);
          wgmma_n128_ss<0, 1>(a1, dx + j * 2 + 512, dw + j * 128, 1);
        }
        wg_commit();
      };
      own(0);
      wg_wait<0>();
      if (leader) mbar_arrive(B_EMPTY + 24);
      own(1);
      auto check = [&](int r, int s) {
          uint32_t bad;
          asm volatile("{\n.reg .u32 a, b, c, d, e, f, g, h;\n.reg .pred p;\n"
                       "ld.shared.u32 a, [%1];\nld.shared.u32 b, [%1+128];\nld.shared.u32 c, [%1+256];\nld.shared.u32 d, [%1+384];\n"
                       "ld.shared.u32 e, [%1+512];\nld.shared.u32 f, [%1+640];\nld.shared.u32 g, [%1+768];\nld.shared.u32 h, [%1+896];\n"
                       "lop3.b32 a, a, b, %2, 0x7e;\nlop3.b32 c, c, d, %2, 0x7e;\nlop3.b32 e, e, f, %2, 0x7e;\nlop3.b32 g, g, h, %2, 0x7e;\n"
                       "lop3.b32 a, a, c, e, 0xfe;\nlop3.b32 a, a, g, 1, 0xa8;\nsetp.ne.u32 p, a, 0;\nvote.sync.any.pred p, p, 0xffffffff;\nselp.u32 %0, 1, 0, p;\n}"
                       : "=r"(bad) : "r"(va + s * SLOT), "r"(par) : "memory");
          if (bad) {
            const uint4* src = reinterpret_cast<const uint4*>(g_o + (tm * 128 + sc * 64 + ww * 16 + (lane & 15)) * 1024 + out_kblock(r, tn) * 64);
#pragma unroll 1
            for (int i = 0; i < 8; i++) {
              uint32_t v[4];
              asm volatile("{\n.reg .b64 x, y;\n.reg .b128 z;\n.reg .pred p, q, h;\n.reg .u32 c, b;\nmov.u32 c, 0;\nsetp.ne.u32 h, %6, 0;\nLW:\n"
                           "ld.relaxed.gpu.global.b128 z, [%4];\nmov.b128 {x, y}, z;\nmov.b64 {%0,%1}, x;\nmov.b64 {%2,%3}, y;\n"
                           "selp.b64 x, y, x, h;\nshr.b64 x, x, %7;\ncvt.u32.u64 b, x;\nand.b32 b, b, 1;\nsetp.eq.u32 p, b, %5;\n"
                           "vote.sync.all.pred p, p, 0xffffffff;\n@p bra.uni LD;\nadd.u32 c, c, 1;\nsetp.lt.u32 q, c, 1000000;\n@q bra.uni LW;\ntrap;\nLD:\n}"
                           : "=&r"(v[0]), "=&r"(v[1]), "=&r"(v[2]), "=&r"(v[3]) : "l"(src + i), "r"(par), "r"(sc), "r"((lane & 8) * 4) : "memory");
              sts128(RING + 16384 + s * SLOT + sc * 8192 + (ww * 16 + (lane & 15)) * 128 + ((i ^ sx) << 4), v[0], v[1], v[2], v[3]);
            }
            fence_async_smem();
            __syncwarp();
          }
      };
      int s = 0, ph = 0;
      uint32_t prev = B_EMPTY + 32;
#pragma unroll 1
      for (int r = 2; r < 12; r++) {
        mbar_wait(B_FULL + 8 * s, ph);
        check(r, s);
        if (!LITE || ((LITE_MASK >> 27) & 1)) STAMP_IF(leader && r == 2, 27);
        const uint64_t dw = mkdesc(RING, 8192, 1024, 1) + s * (SLOT >> 4), dx = mkdesc(RING + 16384, 16, 1024, 1) + s * (SLOT >> 4);
        wg_fence();
#pragma unroll
        for (int j = 0; j < 4; j++) {
          wgmma_n128_ss<0, 1>(a0, dx + j * 2, dw + j * 128, 1);
          wgmma_n128_ss<0, 1>(a1, dx + j * 2 + 512, dw + j * 128, 1);
        }
        wg_commit();
        wg_wait<1>();
        if (leader) mbar_arrive(prev);
        prev = B_EMPTY + 8 * s;
        if (++s == NST) { s = 0; ph ^= 1; }
      }
      auto half = [&](float (&a)[64], int s, int m) {
        const uint64_t dw = mkdesc(RING, 8192, 1024, 1) + s * (SLOT >> 4), dx = mkdesc(RING + 16384 + m * 8192, 16, 1024, 1) + s * (SLOT >> 4);
#pragma unroll
        for (int j = 0; j < 4; j++) wgmma_n128_ss<0, 1>(a, dx + j * 2, dw + j * 128, 1);
      };
      auto store = [&](float (&a)[64], int m) {
        reg_fence(a);
#pragma unroll
        for (int j = 0; j < 8; j++) {
          stsm4(sw[j & 3] + (j >> 2) * 16384 + m * 8192, pack(a[8 * j], a[8 * j + 1]), pack(a[8 * j + 2], a[8 * j + 3]), pack(a[8 * j + 4], a[8 * j + 5]), pack(a[8 * j + 6], a[8 * j + 7]));
          if ((j & 3) == 3) {
            fence_async_smem();
            e_store2d(&mp.m_out, tn * 128 + (j >> 2) * 64, tm * 128 + m * 64 + ww * 16, STG + (j >> 2) * 16384 + m * 8192 + ww * 2048);
          }
        }
      };
#pragma unroll 1
      for (int q = 0; q < 4; q++) {
        mbar_wait(B_FULL + 8 * q, 0);
        check(12 + q, q);
        wg_fence();
        half(a0, q, 0);
        wg_commit();
      }
      nb_sync(NB_ST, 288);
      wg_fence();
      wgmma_n128_rs<1>(a0, oh[0], oh[1], oh[0], oh[1], mkdesc(FR, 1024, 0, 1), 1);
      wg_commit();
      wg_fence();
      half(a1, 0, 1);
      half(a1, 1, 1);
      wg_commit();
      wg_wait<1>();
      store(a0, 0);
      wg_fence();
      half(a1, 2, 1);
      half(a1, 3, 1);
      wgmma_n128_rs<1>(a1, oh[2], oh[3], oh[2], oh[3], mkdesc(FR, 1024, 0, 1), 1);
      wg_commit();
      wg_wait<0>();
      STAMP_IF(leader, 28);
      store(a1, 1);
    }
    bulk_wait_read();
    if (bid == 0 && leader) st_relaxed(&g_epoch, ep);
    STAMP_IF(leader, 29);
  } else {
    asm volatile("setmaxnreg.inc.sync.aligned.u32 216;");
    const int g = lane >> 2, t4 = lane & 3;
    const bool leader = tid == 0;
    const uint32_t sx = lane & 7, sc = lane >> 4;
    const uint32_t sa = STG + (w * 16 + (lane & 15)) * 128;
    const uint32_t sw[4] = {sa + ((sc ^ sx) << 4), sa + (((2 + sc) ^ sx) << 4), sa + (((4 + sc) ^ sx) << 4), sa + (((6 + sc) ^ sx) << 4)};
    float a0[64], a1[64];
    reg_zero(a0); reg_zero(a1); reg_fence(a0); reg_fence(a1);
    mainloop<true>(a0, a1, 0, 0, NB_KV, 0, leader);
    STAMP_IF(leader, 33);
    {
      nb_sync(NB_FDONE, 416);
      STAMP_IF(leader, 34);
      const uint32_t par = lds32(S_EPOCH) & 1u;
#pragma unroll 1
      for (int m = 0;; m++) {
        const uint32_t ca = S_CSK + (m * 64 + w * 16 + g) * 4;
        const float c[2] = {-lds32v(ca), -lds32v(ca + 32)};
        float z[2] = {0.f, 0.f}, tt[2] = {0.f, 0.f};
#pragma unroll
        for (int j = 0; j < 8; j++) {
          const float4 s0 = lds128v(S_KSTAT + (j * 16 + 2 * t4) * 8), s1 = lds128v(S_KSTAT + (j * 16 + 8 + 2 * t4) * 8);
          const float mu[4] = {s0.x, s0.z, s1.x, s1.z}, rl[4] = {s0.y, s0.w, s1.y, s1.w};
          float p[8];
#pragma unroll
          for (int i = 0; i < 8; i++) {
            const int r = (i >> 1) & 1, cc = (i >> 2) * 2 + (i & 1);
            p[i] = phi2(fmaf(c[r], mu[cc], a0[8 * j + i]) * rl[cc]);
            a0[8 * j + i] = a1[8 * j + i];
            z[r] += p[i];
            p[i] *= rl[cc];
            tt[r] = fmaf(p[i], mu[cc], tt[r]);
          }
          stsm4(sw[j & 3] + (j >> 2) * 16384 + m * 8192, pack(p[0], p[1]), pack(p[2], p[3]), pack(p[4], p[5]), pack(p[6], p[7]));
        }
        const bool u2 = lane & 2, u1 = lane & 1;
        const float v = xred(xred(z[0], tt[0], u2, 2), xred(z[1], tt[1], u2, 2), u1, 1);
        if (u2) sts32(ca + (t4 & 1) * 32, __float_as_uint(v));
        else st_relaxed(g_z + tm * 1024 + tn * 128 + m * 64 + w * 16 + t4 * 8 + g, tagf(v * LOG2E, par));
        if (m) break;
      }
      fence_async_smem();
      nb_arrive(NB_PK, 256);
      nb_arrive(NB_Z, 160);
    }
    STAMP_IF(leader, 35);
    float rl0[2];
    const uint32_t ep = lds32(S_EPOCH);
    {
      nb_sync(NB_CSQ, 160);
      float mu[4];
#pragma unroll
      for (int i = 0; i < 4; i++) {
        const float2 st = lds64f(S_KSTAT + ((i >> 1) * 64 + w * 16 + (i & 1) * 8 + g) * 8);
        mu[i] = -st.x;
        if (i < 2) rl0[i] = st.y;
      }
#pragma unroll
      for (int j = 0; j < 16; j++) {
        const float2 c = lds64f(S_CSQ + (j * 8 + 2 * t4) * 4);
        a0[4 * j] = mu[0] * c.x; a0[4 * j + 1] = mu[0] * c.y; a0[4 * j + 2] = mu[1] * c.x; a0[4 * j + 3] = mu[1] * c.y;
        a1[4 * j] = mu[2] * c.x; a1[4 * j + 1] = mu[2] * c.y; a1[4 * j + 2] = mu[3] * c.x; a1[4 * j + 3] = mu[3] * c.y;
      }
      reg_fence(a0); reg_fence(a1);
    }
    STAMP_IF(leader, 40);
    nb_sync(NB_VQ, 256);
    mainloop<false>(a0, a1, 2, 0, 0, 4 + (tn & 3), leader);
    STAMP_IF(leader, 36);
    {
      const uint32_t mk[4] = {t4 == 0, t4 == 1, t4 == 2, t4 == 3};
      uint64_t db = mkdesc(KVB, 16, 1024, 1);
      uint32_t so = 0;
#pragma unroll 1
      for (int j = 0;; j++) {
        uint32_t f[2][16];
        float oc[2][2][20];
        auto phi = [&](const float (&a)[64], float r0, float r1, uint32_t (&o)[16]) {
#pragma unroll
          for (int i = 0; i < 16; i++) o[i] = pack(phi2(a[2 * i] * (i & 1 ? r1 : r0)), phi2(a[2 * i + 1] * (i & 1 ? r1 : r0)));
        };
        auto mma = [&](const uint32_t (&a)[16], float (&o)[2][20]) {
          reg_zero(o[0]); reg_zero(o[1]);
          wg_fence();
          wgmma_n40_rs<0>(o[0], a[0], a[1], a[2], a[3], db, 0);
          wgmma_n40_rs<0>(o[1], a[8], a[9], a[10], a[11], db + 4, 0);
          wgmma_n40_rs<0>(o[0], a[4], a[5], a[6], a[7], db + 2, 1);
          wgmma_n40_rs<0>(o[1], a[12], a[13], a[14], a[15], db + 6, 1);
          wg_commit();
        };
        auto fin = [&](int m, float (&o)[2][20]) {
          const uint32_t m0 = mk[2 * m], m1 = mk[2 * m + 1];
#pragma unroll
          for (int h = 0; h < 2; h++) {
            const float r0 = rcp(o[h][0] + 1e-6f * LOG2E), r1 = rcp(o[h][2] + 1e-6f * LOG2E);
#pragma unroll
            for (int q = 0; q < 2; q++)
              stsm4(sw[h * 2 + q] + so + m * 8192,
                    bsel(pack(o[h][4 + 8 * q] * r0, o[h][5 + 8 * q] * r0), ep, m0), bsel(pack(o[h][6 + 8 * q] * r1, o[h][7 + 8 * q] * r1), ep, m1),
                    bsel(pack(o[h][8 + 8 * q] * r0, o[h][9 + 8 * q] * r0), ep, m0), bsel(pack(o[h][10 + 8 * q] * r1, o[h][11 + 8 * q] * r1), ep, m1));
          }
        };
        phi(a0, rl0[0], rl0[1], f[0]);
        if (j == 0) nb_sync(NB_KVB, 320);
        STAMP_IF(leader && j == 0, 37);
        const float r2 = lds32v(S_KSTAT + (64 + w * 16 + g) * 8 + 4), r3 = lds32v(S_KSTAT + (72 + w * 16 + g) * 8 + 4);
        mma(f[0], oc[0]);
        phi(a1, r2, r3, f[1]);
        wg_wait<0>();
        reg_fence(oc[0][0]); reg_fence(oc[0][1]);
        mma(f[1], oc[1]);
        fin(0, oc[0]);
        if (j == 0) { fence_async_smem(); nb_arrive(NB_Q0, 192); }
        wg_wait<0>();
        reg_fence(oc[1][0]); reg_fence(oc[1][1]);
        fin(1, oc[1]);
        fence_async_smem();
        if (j) break;
        nb_arrive(NB_OWN0, 288);
        STAMP_IF(leader, 38);
#pragma unroll
        for (int i = 0; i < 32; i++) { a0[i] = a0[32 + i]; a1[i] = a1[32 + i]; }
        db = mkdesc(KVB + 5120, 16, 1024, 1);
        so = 16384;
      }
      nb_arrive(NB_OWN1, 256);
      nb_arrive(NB_H1, 160);
      STAMP_IF(leader, 39);
    }
  }
}

#undef CK
typedef CUresult (*EncodeFn)(CUtensorMap*, CUtensorMapDataType, cuuint32_t, void*, const cuuint64_t*, const cuuint64_t*, const cuuint32_t*,
                             const cuuint32_t*, CUtensorMapInterleave, CUtensorMapSwizzle, CUtensorMapL2promotion, CUtensorMapFloatOOBfill);

void make_map(EncodeFn enc, CUtensorMap* m, const void* p, int rank, uint64_t d0, uint64_t d1, uint64_t d2, uint64_t s1, uint64_t s2,
              uint32_t b0, uint32_t b1, uint32_t b2, CUtensorMapSwizzle sw) {
  cuuint64_t gd[3] = {d0, d1, d2}, gs[2] = {s1, s2};
  cuuint32_t bd[3] = {b0, b1, b2}, es[3] = {1, 1, 1};
  enc(m, CU_TENSOR_MAP_DATA_TYPE_BFLOAT16, rank, const_cast<void*>(p), gd, gs, bd, es, CU_TENSOR_MAP_INTERLEAVE_NONE, sw,
      CU_TENSOR_MAP_L2_PROMOTION_L2_128B, CU_TENSOR_MAP_FLOAT_OOB_FILL_NONE);
}

}

extern "C" void kernel_launch(void* const* d_in, const int* in_sizes, int n_in, void* d_out, int out_size) {
  (void)in_sizes; (void)n_in; (void)out_size;
  void* fn = nullptr;
  cudaDriverEntryPointQueryResult qr;
  cudaGetDriverEntryPoint("cuTensorMapEncodeTiled", &fn, cudaEnableDefault, &qr);
  EncodeFn enc = (EncodeFn)fn;
  void* o;
  cudaGetSymbolAddress(&o, g_o);
  const CUtensorMapSwizzle S128 = CU_TENSOR_MAP_SWIZZLE_128B, S64 = CU_TENSOR_MAP_SWIZZLE_64B, S0 = CU_TENSOR_MAP_SWIZZLE_NONE;
  Params mp;
  mp.x = (const char*)d_in[0]; mp.wqkv = (const char*)d_in[1]; mp.w_r = (const char*)d_in[4];
  mp.wg = (const char*)d_in[5]; mp.wu = (const char*)d_in[6]; mp.wd = (const char*)d_in[7];
  make_map(enc, &mp.m_wqkv, d_in[1], 3, 64, 1024, 48, 6144, 128, 64, 64, 2, S128);
  make_map(enc, &mp.m_x, d_in[0], 2, 1024, 2048, 1, 2048, 0, 64, 128, 1, S128);
  make_map(enc, &mp.m_os, o, 2, 1024, 2048, 1, 2048, 0, 64, 64, 1, S128);
  make_map(enc, &mp.m_o, o, 2, 1024, 2048, 1, 2048, 0, 64, 128, 1, S128);
  make_map(enc, &mp.m_wo, d_in[2], 3, 64, 1024, 16, 2048, 128, 64, 64, 2, S128);
  make_map(enc, &mp.m_xs, d_in[0], 2, 1024, 2048, 1, 2048, 0, 256, 16, 1, S0);
  const char *wg = (const char*)d_in[5], *wu = (const char*)d_in[6];
  make_map(enc, &mp.m_gu, wu < wg ? wu : wg, 3, 3584, 1024, 2, 7168, (uint64_t)(wu < wg ? wg - wu : wu - wg), 32, 64, 2, S64);
  make_map(enc, &mp.m_down, d_in[7], 2, 1024, 3584, 1, 2048, 0, 64, 64, 1, S128);
  make_map(enc, &mp.m_out, d_out, 2, 1024, 2048, 1, 2048, 0, 64, 16, 1, S128);
  int dev = 0, sms = 0;
  cudaGetDevice(&dev);
  cudaDeviceGetAttribute(&sms, cudaDevAttrMultiProcessorCount, dev);
  auto kern = sms == 132 ? fused_kernel<true> : fused_kernel<false>;
  cudaFuncSetAttribute(kern, cudaFuncAttributeMaxDynamicSharedMemorySize, SMEM_BYTES);
  kern<<<132, 512, SMEM_BYTES>>>(mp);
}
```

```cpp
#include <cuda_runtime.h>
#include <cuda.h>
#include <cuda_bf16.h>
#include <stdint.h>

namespace {

template <int TA, int TB>
__device__ __forceinline__ void wgmma_n8_ss(float (&d)[4], uint64_t da, uint64_t db, int sc) {
  asm volatile("{\n.reg .pred p;\nsetp.ne.b32 p, %6, 0;\n"
    "wgmma.mma_async.sync.aligned.m64n8k16.f32.bf16.bf16 {%0, %1, %2, %3}, %4, %5, p, 1, 1, %7, %8;\n}\n"
    : "+f"(d[0]), "+f"(d[1]), "+f"(d[2]), "+f"(d[3])
    : "l"(da), "l"(db), "r"(sc), "n"(TA), "n"(TB));
}
template <int TA, int TB>
__device__ __forceinline__ void wgmma_n16_ss(float (&d)[8], uint64_t da, uint64_t db, int sc) {
  asm volatile("{\n.reg .pred p;\nsetp.ne.b32 p, %10, 0;\n"
    "wgmma.mma_async.sync.aligned.m64n16k16.f32.bf16.bf16 {%0, %1, %2, %3, %4, %5, %6, %7}, %8, %9, p, 1, 1, %11, %12;\n}\n"
    : "+f"(d[0]), "+f"(d[1]), "+f"(d[2]), "+f"(d[3]), "+f"(d[4]), "+f"(d[5]), "+f"(d[6]), "+f"(d[7])
    : "l"(da), "l"(db), "r"(sc), "n"(TA), "n"(TB));
}
template <int TB>
__device__ __forceinline__ void wgmma_n40_rs(float (&d)[20], uint32_t a0, uint32_t a1, uint32_t a2, uint32_t a3, uint64_t db, int sc) {
  asm volatile("{\n.reg .pred p;\nsetp.ne.b32 p, %25, 0;\n"
    "wgmma.mma_async.sync.aligned.m64n40k16.f32.bf16.bf16 {%0, %1, %2, %3, %4, %5, %6, %7, %8, %9, %10, %11, %12, %13, %14, %15, %16, %17, %18, %19}, {%20,%21,%22,%23}, %24, p, 1, 1, %26;\n}\n"
    : "+f"(d[0]), "+f"(d[1]), "+f"(d[2]), "+f"(d[3]), "+f"(d[4]), "+f"(d[5]), "+f"(d[6]), "+f"(d[7]),
      "+f"(d[8]), "+f"(d[9]), "+f"(d[10]), "+f"(d[11]), "+f"(d[12]), "+f"(d[13]), "+f"(d[14]), "+f"(d[15]),
      "+f"(d[16]), "+f"(d[17]), "+f"(d[18]), "+f"(d[19])
    : "r"(a0), "r"(a1), "r"(a2), "r"(a3), "l"(db), "r"(sc), "n"(TB));
}
template <int TB>
__device__ __forceinline__ void wgmma_n64_rs(float (&d)[32], uint32_t a0, uint32_t a1, uint32_t a2, uint32_t a3, uint64_t db, int sc) {
  asm volatile("{\n.reg .pred p;\nsetp.ne.b32 p, %37, 0;\n"
    "wgmma.mma_async.sync.aligned.m64n64k16.f32.bf16.bf16 {%0, %1, %2, %3, %4, %5, %6, %7, %8, %9, %10, %11, %12, %13, %14, %15, %16, %17, %18, %19, %20, %21, %22, %23, %24, %25, %26, %27, %28, %29, %30, %31}, {%32,%33,%34,%35}, %36, p, 1, 1, %38;\n}\n"
    : "+f"(d[0]), "+f"(d[1]), "+f"(d[2]), "+f"(d[3]), "+f"(d[4]), "+f"(d[5]), "+f"(d[6]), "+f"(d[7]),
      "+f"(d[8]), "+f"(d[9]), "+f"(d[10]), "+f"(d[11]), "+f"(d[12]), "+f"(d[13]), "+f"(d[14]), "+f"(d[15]),
      "+f"(d[16]), "+f"(d[17]), "+f"(d[18]), "+f"(d[19]), "+f"(d[20]), "+f"(d[21]), "+f"(d[22]), "+f"(d[23]),
      "+f"(d[24]), "+f"(d[25]), "+f"(d[26]), "+f"(d[27]), "+f"(d[28]), "+f"(d[29]), "+f"(d[30]), "+f"(d[31])
    : "r"(a0), "r"(a1), "r"(a2), "r"(a3), "l"(db), "r"(sc), "n"(TB));
}
template <int TA, int TB>
__device__ __forceinline__ void wgmma_n128_ss(float (&d)[64], uint64_t da, uint64_t db, int sc) {
  asm volatile("{\n.reg .pred p;\nsetp.ne.b32 p, %66, 0;\n"
    "wgmma.mma_async.sync.aligned.m64n128k16.f32.bf16.bf16 {%0, %1, %2, %3, %4, %5, %6, %7, %8, %9, %10, %11, %12, %13, %14, %15, %16, %17, %18, %19, %20, %21, %22, %23, %24, %25, %26, %27, %28, %29, %30, %31, %32, %33, %34, %35, %36, %37, %38, %39, %40, %41, %42, %43, %44, %45, %46, %47, %48, %49, %50, %51, %52, %53, %54, %55, %56, %57, %58, %59, %60, %61, %62, %63}, %64, %65, p, 1, 1, %67, %68;\n}\n"
    : "+f"(d[0]), "+f"(d[1]), "+f"(d[2]), "+f"(d[3]), "+f"(d[4]), "+f"(d[5]), "+f"(d[6]), "+f"(d[7]),
      "+f"(d[8]), "+f"(d[9]), "+f"(d[10]), "+f"(d[11]), "+f"(d[12]), "+f"(d[13]), "+f"(d[14]), "+f"(d[15]),
      "+f"(d[16]), "+f"(d[17]), "+f"(d[18]), "+f"(d[19]), "+f"(d[20]), "+f"(d[21]), "+f"(d[22]), "+f"(d[23]),
      "+f"(d[24]), "+f"(d[25]), "+f"(d[26]), "+f"(d[27]), "+f"(d[28]), "+f"(d[29]), "+f"(d[30]), "+f"(d[31]),
      "+f"(d[32]), "+f"(d[33]), "+f"(d[34]), "+f"(d[35]), "+f"(d[36]), "+f"(d[37]), "+f"(d[38]), "+f"(d[39]),
      "+f"(d[40]), "+f"(d[41]), "+f"(d[42]), "+f"(d[43]), "+f"(d[44]), "+f"(d[45]), "+f"(d[46]), "+f"(d[47]),
      "+f"(d[48]), "+f"(d[49]), "+f"(d[50]), "+f"(d[51]), "+f"(d[52]), "+f"(d[53]), "+f"(d[54]), "+f"(d[55]),
      "+f"(d[56]), "+f"(d[57]), "+f"(d[58]), "+f"(d[59]), "+f"(d[60]), "+f"(d[61]), "+f"(d[62]), "+f"(d[63])
    : "l"(da), "l"(db), "r"(sc), "n"(TA), "n"(TB));
}
template <int TB>
__device__ __forceinline__ void wgmma_n128_rs(float (&d)[64], uint32_t a0, uint32_t a1, uint32_t a2, uint32_t a3, uint64_t db, int sc) {
  asm volatile("{\n.reg .pred p;\nsetp.ne.b32 p, %69, 0;\n"
    "wgmma.mma_async.sync.aligned.m64n128k16.f32.bf16.bf16 {%0, %1, %2, %3, %4, %5, %6, %7, %8, %9, %10, %11, %12, %13, %14, %15, %16, %17, %18, %19, %20, %21, %22, %23, %24, %25, %26, %27, %28, %29, %30, %31, %32, %33, %34, %35, %36, %37, %38, %39, %40, %41, %42, %43, %44, %45, %46, %47, %48, %49, %50, %51, %52, %53, %54, %55, %56, %57, %58, %59, %60, %61, %62, %63}, {%64,%65,%66,%67}, %68, p, 1, 1, %70;\n}\n"
    : "+f"(d[0]), "+f"(d[1]), "+f"(d[2]), "+f"(d[3]), "+f"(d[4]), "+f"(d[5]), "+f"(d[6]), "+f"(d[7]),
      "+f"(d[8]), "+f"(d[9]), "+f"(d[10]), "+f"(d[11]), "+f"(d[12]), "+f"(d[13]), "+f"(d[14]), "+f"(d[15]),
      "+f"(d[16]), "+f"(d[17]), "+f"(d[18]), "+f"(d[19]), "+f"(d[20]), "+f"(d[21]), "+f"(d[22]), "+f"(d[23]),
      "+f"(d[24]), "+f"(d[25]), "+f"(d[26]), "+f"(d[27]), "+f"(d[28]), "+f"(d[29]), "+f"(d[30]), "+f"(d[31]),
      "+f"(d[32]), "+f"(d[33]), "+f"(d[34]), "+f"(d[35]), "+f"(d[36]), "+f"(d[37]), "+f"(d[38]), "+f"(d[39]),
      "+f"(d[40]), "+f"(d[41]), "+f"(d[42]), "+f"(d[43]), "+f"(d[44]), "+f"(d[45]), "+f"(d[46]), "+f"(d[47]),
      "+f"(d[48]), "+f"(d[49]), "+f"(d[50]), "+f"(d[51]), "+f"(d[52]), "+f"(d[53]), "+f"(d[54]), "+f"(d[55]),
      "+f"(d[56]), "+f"(d[57]), "+f"(d[58]), "+f"(d[59]), "+f"(d[60]), "+f"(d[61]), "+f"(d[62]), "+f"(d[63])
    : "r"(a0), "r"(a1), "r"(a2), "r"(a3), "l"(db), "r"(sc), "n"(TB));
}

__device__ __forceinline__ void poll1f(uint32_t (&v)[1], const void* p, uint32_t tag, uint32_t mask) {
  asm volatile("{\n.reg .pred p, q;\n.reg .u32 c, b;\n.reg .b64 x, y;\n.reg .b128 z;\nmov.u32 c, 0;\nLW:\n"
               "ld.relaxed.gpu.global.u32 %0, [%1+0];\n"
               "xor.b32 b, %0, %2;\n"
               "and.b32 b, b, %3;\nsetp.eq.u32 p, b, 0;\nvote.sync.all.pred p, p, 0xffffffff;\n@p bra.uni LD;\n"
               "nanosleep.u32 50;\nadd.u32 c, c, 1;\nsetp.lt.u32 q, c, 1000000;\n@q bra.uni LW;\ntrap;\nLD:\n}"
               : "=&r"(v[0])
               : "l"(p), "r"(tag), "r"(mask) : "memory");
}
__device__ __forceinline__ void poll0(uint32_t (&v)[1], const void* p, uint32_t tag, uint32_t mask) {
  asm volatile("{\n.reg .pred p, q;\n.reg .u32 c, b;\n.reg .b64 x, y;\n.reg .b128 z;\nmov.u32 c, 0;\nLW:\n"
               "ld.relaxed.gpu.global.u32 %0, [%1+0];\n"
               "xor.b32 b, %0, %2;\n"
               "and.b32 b, b, %3;\nsetp.eq.u32 p, b, 0;\nvote.sync.all.pred p, p, 0xffffffff;\n@p bra.uni LD;\n"
               "add.u32 c, c, 1;\nsetp.lt.u32 q, c, 1000000;\n@q bra.uni LW;\ntrap;\nLD:\n}"
               : "=&r"(v[0])
               : "l"(p), "r"(tag), "r"(mask) : "memory");
}
__device__ __forceinline__ void poll_pair(uint32_t (&v)[2], const void* p, uint32_t tag, uint32_t mask) {
  asm volatile("{\n.reg .pred p, q;\n.reg .u32 c, b;\n.reg .b64 x, y;\n.reg .b128 z;\nmov.u32 c, 0;\nLW:\n"
               "ld.relaxed.gpu.global.b64 x, [%2+0];\nmov.b64 {%0,%1}, x;\n"
               "xor.b32 b, %0, %3;\n"
               "and.b32 b, b, %4;\nsetp.eq.u32 p, b, 0;\nvote.sync.all.pred p, p, 0xffffffff;\n@p bra.uni LD;\n"
               "nanosleep.u32 100;\nadd.u32 c, c, 1;\nsetp.lt.u32 q, c, 1000000;\n@q bra.uni LW;\ntrap;\nLD:\n}"
               : "=&r"(v[0]), "=&r"(v[1])
               : "l"(p), "r"(tag), "r"(mask) : "memory");
}
__device__ __forceinline__ void poll_quad(uint32_t (&v)[4], const void* p, uint32_t tag, uint32_t mask) {
  asm volatile("{\n.reg .pred p, q;\n.reg .u32 c, b;\n.reg .b64 x, y;\n.reg .b128 z;\nmov.u32 c, 0;\nLW:\n"
               "ld.relaxed.gpu.global.v4.u32 {%0,%1,%2,%3}, [%4+0];\n"
               "xor.b32 b, %0, %5;\n"
               "lop3.b32 b, b, %1, %5, 0xf6;\nlop3.b32 b, b, %2, %5, 0xf6;\nlop3.b32 b, b, %3, %5, 0xf6;\n"
               "and.b32 b, b, %6;\nsetp.eq.u32 p, b, 0;\nvote.sync.all.pred p, p, 0xffffffff;\n@p bra.uni LD;\n"
               "nanosleep.u32 200;\nadd.u32 c, c, 1;\nsetp.lt.u32 q, c, 1000000;\n@q bra.uni LW;\ntrap;\nLD:\n}"
               : "=&r"(v[0]), "=&r"(v[1]), "=&r"(v[2]), "=&r"(v[3])
               : "l"(p), "r"(tag), "r"(mask) : "memory");
}
__device__ __forceinline__ void poll8x4(uint32_t (&v)[32], const void* p, uint32_t tag, uint32_t mask) {
  asm volatile("{\n.reg .pred p, q;\n.reg .u32 c, b;\n.reg .b64 x, y;\n.reg .b128 z;\nmov.u32 c, 0;\nLW:\n"
               "ld.relaxed.gpu.global.v4.u32 {%0,%1,%2,%3}, [%32+0];\n"
               "ld.relaxed.gpu.global.v4.u32 {%4,%5,%6,%7}, [%32+2048];\n"
               "ld.relaxed.gpu.global.v4.u32 {%8,%9,%10,%11}, [%32+4096];\n"
               "ld.relaxed.gpu.global.v4.u32 {%12,%13,%14,%15}, [%32+6144];\n"
               "ld.relaxed.gpu.global.v4.u32 {%16,%17,%18,%19}, [%32+8192];\n"
               "ld.relaxed.gpu.global.v4.u32 {%20,%21,%22,%23}, [%32+10240];\n"
               "ld.relaxed.gpu.global.v4.u32 {%24,%25,%26,%27}, [%32+12288];\n"
               "ld.relaxed.gpu.global.v4.u32 {%28,%29,%30,%31}, [%32+14336];\n"
               "xor.b32 b, %0, %33;\n"
               "lop3.b32 b, b, %1, %33, 0xf6;\nlop3.b32 b, b, %2, %33, 0xf6;\nlop3.b32 b, b, %3, %33, 0xf6;\nlop3.b32 b, b, %4, %33, 0xf6;\n"
               "lop3.b32 b, b, %5, %33, 0xf6;\nlop3.b32 b, b, %6, %33, 0xf6;\nlop3.b32 b, b, %7, %33, 0xf6;\nlop3.b32 b, b, %8, %33, 0xf6;\n"
               "lop3.b32 b, b, %9, %33, 0xf6;\nlop3.b32 b, b, %10, %33, 0xf6;\nlop3.b32 b, b, %11, %33, 0xf6;\nlop3.b32 b, b, %12, %33, 0xf6;\n"
               "lop3.b32 b, b, %13, %33, 0xf6;\nlop3.b32 b, b, %14, %33, 0xf6;\nlop3.b32 b, b, %15, %33, 0xf6;\nlop3.b32 b, b, %16, %33, 0xf6;\n"
               "lop3.b32 b, b, %17, %33, 0xf6;\nlop3.b32 b, b, %18, %33, 0xf6;\nlop3.b32 b, b, %19, %33, 0xf6;\nlop3.b32 b, b, %20, %33, 0xf6;\n"
               "lop3.b32 b, b, %21, %33, 0xf6;\nlop3.b32 b, b, %22, %33, 0xf6;\nlop3.b32 b, b, %23, %33, 0xf6;\nlop3.b32 b, b, %24, %33, 0xf6;\n"
               "lop3.b32 b, b, %25, %33, 0xf6;\nlop3.b32 b, b, %26, %33, 0xf6;\nlop3.b32 b, b, %27, %33, 0xf6;\nlop3.b32 b, b, %28, %33, 0xf6;\n"
               "lop3.b32 b, b, %29, %33, 0xf6;\nlop3.b32 b, b, %30, %33, 0xf6;\nlop3.b32 b, b, %31, %33, 0xf6;\n"
               "and.b32 b, b, %34;\nsetp.eq.u32 p, b, 0;\nvote.sync.all.pred p, p, 0xffffffff;\n@p bra.uni LD;\n"
               "nanosleep.u32 50;\nadd.u32 c, c, 1;\nsetp.lt.u32 q, c, 1000000;\n@q bra.uni LW;\ntrap;\nLD:\n}"
               : "=&r"(v[0]), "=&r"(v[1]), "=&r"(v[2]), "=&r"(v[3]), "=&r"(v[4]), "=&r"(v[5]), "=&r"(v[6]), "=&r"(v[7]), "=&r"(v[8]), "=&r"(v[9]), "=&r"(v[10]), "=&r"(v[11]), "=&r"(v[12]), "=&r"(v[13]), "=&r"(v[14]), "=&r"(v[15]), "=&r"(v[16]), "=&r"(v[17]), "=&r"(v[18]), "=&r"(v[19]), "=&r"(v[20]), "=&r"(v[21]), "=&r"(v[22]), "=&r"(v[23]), "=&r"(v[24]), "=&r"(v[25]), "=&r"(v[26]), "=&r"(v[27]), "=&r"(v[28]), "=&r"(v[29]), "=&r"(v[30]), "=&r"(v[31])
               : "l"(p), "r"(tag), "r"(mask) : "memory");
}
__device__ __forceinline__ void poll16(uint32_t (&v)[16], const void* p, uint32_t tag, uint32_t mask) {
  asm volatile("{\n.reg .pred p, q;\n.reg .u32 c, b;\n.reg .b64 x, y;\n.reg .b128 z;\nmov.u32 c, 0;\nLW:\n"
               "ld.relaxed.gpu.global.u32 %0, [%16+0];\n"
               "ld.relaxed.gpu.global.u32 %1, [%16+4096];\n"
               "ld.relaxed.gpu.global.u32 %2, [%16+8192];\n"
               "ld.relaxed.gpu.global.u32 %3, [%16+12288];\n"
               "ld.relaxed.gpu.global.u32 %4, [%16+16384];\n"
               "ld.relaxed.gpu.global.u32 %5, [%16+20480];\n"
               "ld.relaxed.gpu.global.u32 %6, [%16+24576];\n"
               "ld.relaxed.gpu.global.u32 %7, [%16+28672];\n"
               "ld.relaxed.gpu.global.u32 %8, [%16+32768];\n"
               "ld.relaxed.gpu.global.u32 %9, [%16+36864];\n"
               "ld.relaxed.gpu.global.u32 %10, [%16+40960];\n"
               "ld.relaxed.gpu.global.u32 %11, [%16+45056];\n"
               "ld.relaxed.gpu.global.u32 %12, [%16+49152];\n"
               "ld.relaxed.gpu.global.u32 %13, [%16+53248];\n"
               "ld.relaxed.gpu.global.u32 %14, [%16+57344];\n"
               "ld.relaxed.gpu.global.u32 %15, [%16+61440];\n"
               "xor.b32 b, %0, %17;\n"
               "lop3.b32 b, b, %1, %17, 0xf6;\nlop3.b32 b, b, %2, %17, 0xf6;\nlop3.b32 b, b, %3, %17, 0xf6;\nlop3.b32 b, b, %4, %17, 0xf6;\n"
               "lop3.b32 b, b, %5, %17, 0xf6;\nlop3.b32 b, b, %6, %17, 0xf6;\nlop3.b32 b, b, %7, %17, 0xf6;\nlop3.b32 b, b, %8, %17, 0xf6;\n"
               "lop3.b32 b, b, %9, %17, 0xf6;\nlop3.b32 b, b, %10, %17, 0xf6;\nlop3.b32 b, b, %11, %17, 0xf6;\nlop3.b32 b, b, %12, %17, 0xf6;\n"
               "lop3.b32 b, b, %13, %17, 0xf6;\nlop3.b32 b, b, %14, %17, 0xf6;\nlop3.b32 b, b, %15, %17, 0xf6;\n"
               "and.b32 b, b, %18;\nsetp.eq.u32 p, b, 0;\nvote.sync.all.pred p, p, 0xffffffff;\n@p bra.uni LD;\n"
               "nanosleep.u32 200;\nadd.u32 c, c, 1;\nsetp.lt.u32 q, c, 1000000;\n@q bra.uni LW;\ntrap;\nLD:\n}"
               : "=&r"(v[0]), "=&r"(v[1]), "=&r"(v[2]), "=&r"(v[3]), "=&r"(v[4]), "=&r"(v[5]), "=&r"(v[6]), "=&r"(v[7]), "=&r"(v[8]), "=&r"(v[9]), "=&r"(v[10]), "=&r"(v[11]), "=&r"(v[12]), "=&r"(v[13]), "=&r"(v[14]), "=&r"(v[15])
               : "l"(p), "r"(tag), "r"(mask) : "memory");
}
__device__ __forceinline__ void poll_keys(uint32_t (&v)[16], const void* p, uint32_t tag, uint32_t mask) {
  asm volatile("{\n.reg .pred p, q;\n.reg .u32 c, b;\n.reg .b64 x, y;\n.reg .b128 z;\nmov.u32 c, 0;\nLW:\n"
               "ld.relaxed.gpu.global.v2.b64 {x, y}, [%16+0];\nmov.b64 {%0,%1}, x;\nmov.b64 {%2,%3}, y;\n"
               "ld.relaxed.gpu.global.v2.b64 {x, y}, [%16+4096];\nmov.b64 {%4,%5}, x;\nmov.b64 {%6,%7}, y;\n"
               "ld.relaxed.gpu.global.v2.b64 {x, y}, [%16+8192];\nmov.b64 {%8,%9}, x;\nmov.b64 {%10,%11}, y;\n"
               "ld.relaxed.gpu.global.v2.b64 {x, y}, [%16+12288];\nmov.b64 {%12,%13}, x;\nmov.b64 {%14,%15}, y;\n"
               "xor.b32 b, %0, %17;\n"
               "lop3.b32 b, b, %2, %17, 0xf6;\nlop3.b32 b, b, %4, %17, 0xf6;\nlop3.b32 b, b, %6, %17, 0xf6;\nlop3.b32 b, b, %8, %17, 0xf6;\n"
               "lop3.b32 b, b, %10, %17, 0xf6;\nlop3.b32 b, b, %12, %17, 0xf6;\nlop3.b32 b, b, %14, %17, 0xf6;\n"
               "and.b32 b, b, %18;\nsetp.eq.u32 p, b, 0;\nvote.sync.all.pred p, p, 0xffffffff;\n@p bra.uni LD;\n"
               "nanosleep.u32 20;\nadd.u32 c, c, 1;\nsetp.lt.u32 q, c, 1000000;\n@q bra.uni LW;\ntrap;\nLD:\n}"
               : "=&r"(v[0]), "=&r"(v[1]), "=&r"(v[2]), "=&r"(v[3]), "=&r"(v[4]), "=&r"(v[5]), "=&r"(v[6]), "=&r"(v[7]), "=&r"(v[8]), "=&r"(v[9]), "=&r"(v[10]), "=&r"(v[11]), "=&r"(v[12]), "=&r"(v[13]), "=&r"(v[14]), "=&r"(v[15])
               : "l"(p), "r"(tag), "r"(mask) : "memory");
}
__device__ __forceinline__ void poll_z(uint32_t (&v)[16], const void* p, uint32_t tag, uint32_t mask) {
  asm volatile("{\n.reg .pred p, q;\n.reg .u32 c, b;\n.reg .b64 x, y;\n.reg .b128 z;\nmov.u32 c, 0;\nLW:\n"
               "ld.relaxed.gpu.global.v4.u32 {%0,%1,%2,%3}, [%16+0];\n"
               "ld.relaxed.gpu.global.v4.u32 {%4,%5,%6,%7}, [%16+4096];\n"
               "ld.relaxed.gpu.global.v4.u32 {%8,%9,%10,%11}, [%16+8192];\n"
               "ld.relaxed.gpu.global.v4.u32 {%12,%13,%14,%15}, [%16+12288];\n"
               "xor.b32 b, %0, %17;\n"
               "lop3.b32 b, b, %1, %17, 0xf6;\nlop3.b32 b, b, %2, %17, 0xf6;\nlop3.b32 b, b, %3, %17, 0xf6;\nlop3.b32 b, b, %4, %17, 0xf6;\n"
               "lop3.b32 b, b, %5, %17, 0xf6;\nlop3.b32 b, b, %6, %17, 0xf6;\nlop3.b32 b, b, %7, %17, 0xf6;\nlop3.b32 b, b, %8, %17, 0xf6;\n"
               "lop3.b32 b, b, %9, %17, 0xf6;\nlop3.b32 b, b, %10, %17, 0xf6;\nlop3.b32 b, b, %11, %17, 0xf6;\nlop3.b32 b, b, %12, %17, 0xf6;\n"
               "lop3.b32 b, b, %13, %17, 0xf6;\nlop3.b32 b, b, %14, %17, 0xf6;\nlop3.b32 b, b, %15, %17, 0xf6;\n"
               "and.b32 b, b, %18;\nsetp.eq.u32 p, b, 0;\nvote.sync.all.pred p, p, 0xffffffff;\n@p bra.uni LD;\n"
               "nanosleep.u32 300;\nadd.u32 c, c, 1;\nsetp.lt.u32 q, c, 1000000;\n@q bra.uni LW;\ntrap;\nLD:\n}"
               : "=&r"(v[0]), "=&r"(v[1]), "=&r"(v[2]), "=&r"(v[3]), "=&r"(v[4]), "=&r"(v[5]), "=&r"(v[6]), "=&r"(v[7]), "=&r"(v[8]), "=&r"(v[9]), "=&r"(v[10]), "=&r"(v[11]), "=&r"(v[12]), "=&r"(v[13]), "=&r"(v[14]), "=&r"(v[15])
               : "l"(p), "r"(tag), "r"(mask) : "memory");
}
__device__ __forceinline__ void poll7x4(uint32_t (&v)[28], const void* p, uint32_t tag, uint32_t mask) {
  asm volatile("{\n.reg .pred p, q;\n.reg .u32 c, b;\n.reg .b64 x, y;\n.reg .b128 z;\nmov.u32 c, 0;\nLW:\n"
               "ld.relaxed.gpu.global.v4.u32 {%0,%1,%2,%3}, [%28+0];\n"
               "ld.relaxed.gpu.global.v4.u32 {%4,%5,%6,%7}, [%28+2048];\n"
               "ld.relaxed.gpu.global.v4.u32 {%8,%9,%10,%11}, [%28+4096];\n"
               "ld.relaxed.gpu.global.v4.u32 {%12,%13,%14,%15}, [%28+6144];\n"
               "ld.relaxed.gpu.global.v4.u32 {%16,%17,%18,%19}, [%28+8192];\n"
               "ld.relaxed.gpu.global.v4.u32 {%20,%21,%22,%23}, [%28+10240];\n"
               "ld.relaxed.gpu.global.v4.u32 {%24,%25,%26,%27}, [%28+12288];\n"
               "xor.b32 b, %0, %29;\n"
               "lop3.b32 b, b, %1, %29, 0xf6;\nlop3.b32 b, b, %2, %29, 0xf6;\nlop3.b32 b, b, %3, %29, 0xf6;\nlop3.b32 b, b, %4, %29, 0xf6;\n"
               "lop3.b32 b, b, %5, %29, 0xf6;\nlop3.b32 b, b, %6, %29, 0xf6;\nlop3.b32 b, b, %7, %29, 0xf6;\nlop3.b32 b, b, %8, %29, 0xf6;\n"
               "lop3.b32 b, b, %9, %29, 0xf6;\nlop3.b32 b, b, %10, %29, 0xf6;\nlop3.b32 b, b, %11, %29, 0xf6;\nlop3.b32 b, b, %12, %29, 0xf6;\n"
               "lop3.b32 b, b, %13, %29, 0xf6;\nlop3.b32 b, b, %14, %29, 0xf6;\nlop3.b32 b, b, %15, %29, 0xf6;\nlop3.b32 b, b, %16, %29, 0xf6;\n"
               "lop3.b32 b, b, %17, %29, 0xf6;\nlop3.b32 b, b, %18, %29, 0xf6;\nlop3.b32 b, b, %19, %29, 0xf6;\nlop3.b32 b, b, %20, %29, 0xf6;\n"
               "lop3.b32 b, b, %21, %29, 0xf6;\nlop3.b32 b, b, %22, %29, 0xf6;\nlop3.b32 b, b, %23, %29, 0xf6;\nlop3.b32 b, b, %24, %29, 0xf6;\n"
               "lop3.b32 b, b, %25, %29, 0xf6;\nlop3.b32 b, b, %26, %29, 0xf6;\nlop3.b32 b, b, %27, %29, 0xf6;\n"
               "and.b32 b, b, %30;\nsetp.eq.u32 p, b, 0;\nvote.sync.all.pred p, p, 0xffffffff;\n@p bra.uni LD;\n"
               "nanosleep.u32 50;\nadd.u32 c, c, 1;\nsetp.lt.u32 q, c, 1000000;\n@q bra.uni LW;\ntrap;\nLD:\n}"
               : "=&r"(v[0]), "=&r"(v[1]), "=&r"(v[2]), "=&r"(v[3]), "=&r"(v[4]), "=&r"(v[5]), "=&r"(v[6]), "=&r"(v[7]), "=&r"(v[8]), "=&r"(v[9]), "=&r"(v[10]), "=&r"(v[11]), "=&r"(v[12]), "=&r"(v[13]), "=&r"(v[14]), "=&r"(v[15]), "=&r"(v[16]), "=&r"(v[17]), "=&r"(v[18]), "=&r"(v[19]), "=&r"(v[20]), "=&r"(v[21]), "=&r"(v[22]), "=&r"(v[23]), "=&r"(v[24]), "=&r"(v[25]), "=&r"(v[26]), "=&r"(v[27])
               : "l"(p), "r"(tag), "r"(mask) : "memory");
}
__device__ __forceinline__ void poll_kvp(uint32_t (&v)[16], const void* p, uint32_t tag, uint32_t mask) {
  asm volatile("{\n.reg .pred p, q;\n.reg .u32 c, b;\n.reg .b64 x, y;\n.reg .b128 z;\nmov.u32 c, 0;\nLW:\n"
               "ld.relaxed.gpu.global.b128 z, [%16+0];\nmov.b128 {x, y}, z;\nmov.b64 {%0,%1}, x;\nmov.b64 {%2,%3}, y;\n"
               "ld.relaxed.gpu.global.b128 z, [%16+8192];\nmov.b128 {x, y}, z;\nmov.b64 {%4,%5}, x;\nmov.b64 {%6,%7}, y;\n"
               "ld.relaxed.gpu.global.b128 z, [%16+16384];\nmov.b128 {x, y}, z;\nmov.b64 {%8,%9}, x;\nmov.b64 {%10,%11}, y;\n"
               "ld.relaxed.gpu.global.b128 z, [%16+24576];\nmov.b128 {x, y}, z;\nmov.b64 {%12,%13}, x;\nmov.b64 {%14,%15}, y;\n"
               "xor.b32 b, %0, %17;\n"
               "lop3.b32 b, b, %4, %17, 0xf6;\nlop3.b32 b, b, %8, %17, 0xf6;\nlop3.b32 b, b, %12, %17, 0xf6;\n"
               "and.b32 b, b, %18;\nsetp.eq.u32 p, b, 0;\nvote.sync.all.pred p, p, 0xffffffff;\n@p bra.uni LD;\n"
               "nanosleep.u32 50;\nadd.u32 c, c, 1;\nsetp.lt.u32 q, c, 1000000;\n@q bra.uni LW;\ntrap;\nLD:\n}"
               : "=&r"(v[0]), "=&r"(v[1]), "=&r"(v[2]), "=&r"(v[3]), "=&r"(v[4]), "=&r"(v[5]), "=&r"(v[6]), "=&r"(v[7]), "=&r"(v[8]), "=&r"(v[9]), "=&r"(v[10]), "=&r"(v[11]), "=&r"(v[12]), "=&r"(v[13]), "=&r"(v[14]), "=&r"(v[15])
               : "l"(p), "r"(tag), "r"(mask) : "memory");
}

__device__ __align__(1024) __nv_bfloat16 g_o[2048 * 1024];
__device__ __align__(128) uint2 g_keys[2048];
__device__ __align__(128) uint32_t g_csum[18 * 1024];
__device__ __align__(128) uint32_t g_z[16 * 1024];
__device__ __align__(128) uint4 g_kvp[128 * 512];
__device__ __align__(128) uint4 g_kv[8 * 512];
__device__ __align__(128) uint32_t g_h[112 * 256];
__device__ __align__(128) uint32_t g_yp[128 * 512];
__device__ __align__(128) uint2 g_sel[8 * 16];
enum { H_CS = 0, H_KVP = 8, H_KV = 16, H_H = 24, H_Y = 32, H_O = 40, H_Z = 56 };
__device__ __align__(128) uint32_t g_sig[64 * 32];
__device__ uint32_t g_epoch;

constexpr uint32_t RING = 1024, SLOT = 32768, SMEM_BYTES = 232448;
constexpr int NST = 5, HST = 7;
constexpr uint32_t STG = RING + 163840, AUX = RING + 196608, FR = RING + 212992, MISC = RING + 229376;
constexpr uint32_t B_FULL = MISC, B_EMPTY = MISC + 56, B_XS = MISC + 112, B_SEL = MISC + 144, B_WK = MISC + 160, B_CSDN = MISC + 168,
                   B_FR = MISC + 176, B_FE = MISC + 200, B_DR = MISC + 224, B_CSV = MISC + 248,
                   B_DND = MISC + 256, B_XRES = MISC + 264, B_PFREE = MISC + 280, B_SFREE = MISC + 288, B_KVL = MISC + 296, NBAR = 38;
constexpr uint32_t S_EPOCH = MISC + 352, S_NCAND = MISC + 356, S_SEL = MISC + 368, S_WMAX = MISC + 432,
                   S_KSTAT = MISC + 512, S_CSK = MISC + 1536, S_CSV = MISC + 2048, S_CSQ = MISC + 2560, S_ONES = MISC + 512;
constexpr uint32_t KVB = AUX, HOP = AUX + 10240, FONES = AUX + 6144, GR = FR - 8192;
enum { NB_Z = 0, NB_KV = 1, NB_VQ = 2, NB_WG0 = 3, NB_FDONE = 4, NB_PK = 5, NB_KVB = 6, NB_WG1 = 7, NB_WG2 = 8, NB_CSQ = 9,
       NB_Y = 10, NB_ST = 11, NB_OWN0 = 12, NB_OWN1 = 13, NB_Q0 = 14, NB_H1 = 15 };

#define XS_FLY 2
#define FFN_GAP 400
#define PF_GAP 200
#define PF_WAIT 1000
#define GPCMAP 0x75143620u
#define KV_SPEC 200
#define HAND_K 5
#define PF_V 0
#define PF_O 0
#define PHI_CUT 11
#define SIG_EARLY 50
constexpr uint64_t EVICT_FIRST = 0x12f0000000000000ull;
constexpr float LOG2E = 1.4426950408889634f, LN2 = 0.6931471805599453f;

#define ELECT "{\n.reg .pred p;\nelect.sync _|p, 0xffffffff;\n"
#define TMA2D "cp.async.bulk.tensor.2d.shared::cluster.global.mbarrier::complete_tx::bytes"
#define TMA3D "cp.async.bulk.tensor.3d.shared::cluster.global.mbarrier::complete_tx::bytes"
__device__ __forceinline__ void e_expect(uint32_t b, uint32_t n) {
  asm volatile(ELECT "@p mbarrier.arrive.expect_tx.shared::cta.b64 _, [%0], %1;\n}" ::"r"(b), "r"(n) : "memory");
}
__device__ __forceinline__ void e_arrive(uint32_t b) { asm volatile(ELECT "@p mbarrier.arrive.shared::cta.b64 _, [%0];\n}" ::"r"(b) : "memory"); }
__device__ __forceinline__ void e_tma2d(uint32_t dst, const CUtensorMap* m, int c0, int c1, uint32_t bar) {
  asm volatile(ELECT "@p " TMA2D " [%0], [%1, {%3, %4}], [%2];\n}" ::"r"(dst), "l"(m), "r"(bar), "r"(c0), "r"(c1) : "memory");
}
__device__ __forceinline__ void e_tma2d_ef(uint32_t dst, const CUtensorMap* m, int c0, int c1, uint32_t bar, uint64_t pol) {
  asm volatile(ELECT "@p " TMA2D ".L2::cache_hint [%0], [%1, {%3, %4}], [%2], %5;\n}" ::"r"(dst), "l"(m), "r"(bar), "r"(c0), "r"(c1), "l"(pol) : "memory");
}
__device__ __forceinline__ void e_tma3d(uint32_t dst, const CUtensorMap* m, int c1, int c2, uint32_t bar) {
  asm volatile(ELECT "@p " TMA3D " [%0], [%1, {0, %3, %4}], [%2];\n}" ::"r"(dst), "l"(m), "r"(bar), "r"(c1), "r"(c2) : "memory");
}
__device__ __forceinline__ void e_store2d(const CUtensorMap* m, int c0, int c1, uint32_t src) {
  asm volatile(ELECT "@p cp.async.bulk.tensor.2d.global.shared::cta.bulk_group [%0, {%2, %3}], [%1];\n}" ::"l"(m), "r"(src), "r"(c0), "r"(c1) : "memory");
}
__device__ __forceinline__ void e_tma3d_ef(uint32_t dst, const CUtensorMap* m, int c0, int c1, uint32_t bar, uint64_t pol) {
  asm volatile(ELECT "@p " TMA3D ".L2::cache_hint [%0], [%1, {%3, %4, 0}], [%2], %5;\n}" ::"r"(dst), "l"(m), "r"(bar), "r"(c0), "r"(c1), "l"(pol) : "memory");
}
__device__ __forceinline__ void e_load(uint32_t dst, const void* src, uint32_t n, uint32_t bar) {
  asm volatile(ELECT "@p cp.async.bulk.shared::cluster.global.mbarrier::complete_tx::bytes [%0], [%1], %2, [%3];\n}" ::"r"(dst), "l"(src), "r"(n), "r"(bar) : "memory");
}
__device__ __forceinline__ void e_pfmap(const CUtensorMap* m) { asm volatile(ELECT "@p prefetch.tensormap [%0];\n}" ::"l"(m) : "memory"); }
__device__ __forceinline__ void bulk_wait_read() { asm volatile("cp.async.bulk.commit_group;\ncp.async.bulk.wait_group.read 0;" ::: "memory"); }
__device__ __forceinline__ void e_signal(int word, int bit) {
  asm volatile(ELECT "@p red.relaxed.gpu.global.xor.b32 [%0], %1;\n}" ::"l"(g_sig + word * 32), "r"(1u << bit) : "memory");
}
__device__ __forceinline__ void await(int word, uint32_t mask, uint32_t ep) {
  uint32_t f[1];
  poll1f(f, g_sig + word * 32, 0u - (ep & 1u), mask);
}

__device__ __forceinline__ void mbar_arrive(uint32_t b) { asm volatile("mbarrier.arrive.shared::cta.b64 _, [%0];" ::"r"(b) : "memory"); }
__device__ __forceinline__ void mbar_wait(uint32_t b, uint32_t ph) {
  asm volatile("{\n.reg .pred p, q;\n.reg .u32 c;\nmov.u32 c, 0;\nLW:\nmbarrier.try_wait.parity.shared::cta.b64 p, [%0], %1;\n@p bra LD;\n"
               "add.u32 c, c, 1;\nsetp.lt.u32 q, c, 100000;\n@q bra LW;\ntrap;\nLD:\n}" ::"r"(b), "r"(ph) : "memory");
}
__device__ __forceinline__ void nb_sync(int id, int n) { asm volatile("bar.sync %0, %1;" ::"r"(id), "r"(n) : "memory"); }
__device__ __forceinline__ void nb_arrive(int id, int n) { asm volatile("bar.arrive %0, %1;" ::"r"(id), "r"(n) : "memory"); }
__device__ __forceinline__ void wg_fence() { asm volatile("wgmma.fence.sync.aligned;" ::: "memory"); }
__device__ __forceinline__ void wg_commit() { asm volatile("wgmma.commit_group.sync.aligned;" ::: "memory"); }
template <int N> __device__ __forceinline__ void wg_wait() { asm volatile("wgmma.wait_group.sync.aligned %0;" ::"n"(N) : "memory"); }
template <int N> __device__ __forceinline__ void reg_fence(float (&a)[N]) {
#pragma unroll
  for (int i = 0; i < N; i++) asm volatile("" : "+f"(a[i])::"memory");
}
template <int N> __device__ __forceinline__ void reg_zero(float (&a)[N]) {
#pragma unroll
  for (int i = 0; i < N; i++) a[i] = 0.f;
}
__device__ __forceinline__ constexpr uint64_t mkdesc(uint32_t addr, uint32_t lbo, uint32_t sbo, uint32_t swz) {
  return (uint64_t)(addr >> 4) | ((uint64_t)(lbo >> 4) << 16) | ((uint64_t)(sbo >> 4) << 32) | ((uint64_t)swz << 62);
}
__device__ __forceinline__ void fence_async_smem() { asm volatile("fence.proxy.async.shared::cta;" ::: "memory"); }
__device__ __forceinline__ void st_relaxed(uint32_t* p, uint32_t v) { asm volatile("st.relaxed.gpu.global.u32 [%0], %1;" ::"l"(p), "r"(v) : "memory"); }
__device__ __forceinline__ uint32_t ld_relaxed(const uint32_t* p) { uint32_t v; asm volatile("ld.relaxed.gpu.global.u32 %0, [%1];" : "=r"(v) : "l"(p) : "memory"); return v; }
__device__ __forceinline__ void st_unit(uint4* p, uint32_t a, uint32_t b, uint32_t c, uint32_t d, uint32_t par) {
  asm volatile("{\n.reg .b64 x, y;\n.reg .b128 z;\nmov.b64 x, {%1,%2};\nmov.b64 y, {%3,%4};\nmov.b128 z, {x, y};\nst.relaxed.gpu.global.b128 [%0], z;\n}"
               ::"l"(p), "r"((a & ~1u) | par), "r"(b), "r"(c), "r"(d) : "memory");
}
__device__ __forceinline__ uint4 lds128(uint32_t a) { uint4 v; asm volatile("ld.shared.v4.u32 {%0,%1,%2,%3}, [%4];" : "=r"(v.x), "=r"(v.y), "=r"(v.z), "=r"(v.w) : "r"(a)); return v; }
__device__ __forceinline__ float4 lds128f(uint32_t a) { float4 v; asm volatile("ld.shared.v4.f32 {%0,%1,%2,%3}, [%4];" : "=f"(v.x), "=f"(v.y), "=f"(v.z), "=f"(v.w) : "r"(a)); return v; }
__device__ __forceinline__ float4 lds128v(uint32_t a) { float4 v; asm volatile("ld.volatile.shared.v4.f32 {%0,%1,%2,%3}, [%4];" : "=f"(v.x), "=f"(v.y), "=f"(v.z), "=f"(v.w) : "r"(a) : "memory"); return v; }
__device__ __forceinline__ float lds32v(uint32_t a) { float v; asm volatile("ld.volatile.shared.f32 %0, [%1];" : "=f"(v) : "r"(a) : "memory"); return v; }
__device__ __forceinline__ float2 lds64f(uint32_t a) { float2 v; asm volatile("ld.shared.v2.f32 {%0,%1}, [%2];" : "=f"(v.x), "=f"(v.y) : "r"(a)); return v; }
__device__ __forceinline__ uint32_t lds32(uint32_t a) { uint32_t v; asm volatile("ld.shared.u32 %0, [%1];" : "=r"(v) : "r"(a)); return v; }
__device__ __forceinline__ void sts128(uint32_t a, uint32_t x, uint32_t y, uint32_t z, uint32_t w) { asm volatile("st.shared.v4.u32 [%0], {%1,%2,%3,%4};" ::"r"(a), "r"(x), "r"(y), "r"(z), "r"(w) : "memory"); }
__device__ __forceinline__ void sts128f(uint32_t a, float x, float y, float z, float w) { asm volatile("st.shared.v4.f32 [%0], {%1,%2,%3,%4};" ::"r"(a), "f"(x), "f"(y), "f"(z), "f"(w) : "memory"); }
__device__ __forceinline__ void sts64(uint32_t a, uint32_t x, uint32_t y) { asm volatile("st.shared.v2.u32 [%0], {%1,%2};" ::"r"(a), "r"(x), "r"(y) : "memory"); }
__device__ __forceinline__ void sts32(uint32_t a, uint32_t x) { asm volatile("st.shared.u32 [%0], %1;" ::"r"(a), "r"(x) : "memory"); }
__device__ __forceinline__ void stsm4(uint32_t a, uint32_t r0, uint32_t r1, uint32_t r2, uint32_t r3) {
  asm volatile("stmatrix.sync.aligned.m8n8.x4.shared.b16 [%0], {%1,%2,%3,%4};" ::"r"(a), "r"(r0), "r"(r1), "r"(r2), "r"(r3) : "memory");
}
__device__ __forceinline__ uint4 ldsm4(uint32_t a) {
  uint4 v; asm volatile("ldmatrix.sync.aligned.m8n8.x4.shared.b16 {%0,%1,%2,%3}, [%4];" : "=r"(v.x), "=r"(v.y), "=r"(v.z), "=r"(v.w) : "r"(a) : "memory"); return v;
}
__device__ __forceinline__ uint32_t pack(float lo, float hi) { uint32_t r; asm("cvt.rn.bf16x2.f32 %0, %1, %2;" : "=r"(r) : "f"(hi), "f"(lo)); return r; }
__device__ __forceinline__ float bf_lo(uint32_t w) { return __uint_as_float(w << 16); }
__device__ __forceinline__ float bf_hi(uint32_t w) { return __uint_as_float(w & 0xffff0000u); }
__device__ __forceinline__ float bf_round(float x) { return bf_lo(pack(x, x)); }
__device__ __forceinline__ float ex2(float x) { float v; asm("ex2.approx.ftz.f32 %0, %1;" : "=f"(v) : "f"(x)); return v; }
__device__ __forceinline__ float rcp(float x) { float v; asm("rcp.approx.ftz.f32 %0, %1;" : "=f"(v) : "f"(x)); return v; }
__device__ __forceinline__ float addsat(float a, float b) { float v; asm("add.sat.f32 %0, %1, %2;" : "=f"(v) : "f"(a), "f"(b)); return v; }
__device__ __forceinline__ float phi2(float a) { return fmaf(fmaxf(a, 0.f), LN2, addsat(ex2(a), 1e-6f)); }
__device__ __forceinline__ float key_score(uint32_t key) { uint32_t u = key >> 16; u = (u & 0x8000u) ? (u & 0x7fffu) : (~u & 0xffffu); return __uint_as_float(u << 16); }
__device__ __forceinline__ int key_token(uint32_t key) { return 2047 - (int)((key >> 5) & 2047u); }
__device__ __forceinline__ uint32_t bsel(uint32_t a, uint32_t b, uint32_t m) { uint32_t r; asm("lop3.b32 %0, %1, %2, %3, 0xd8;" : "=r"(r) : "r"(a), "r"(b), "r"(m)); return r; }
__device__ __forceinline__ uint32_t prmt(uint32_t a, uint32_t b, uint32_t c) { uint32_t r; asm("prmt.b32 %0, %1, %2, %3;" : "=r"(r) : "r"(a), "r"(b), "r"(c)); return r; }
__device__ __forceinline__ uint32_t tagf(float v, uint32_t par) { return (__float_as_uint(v) & ~1u) | par; }
__device__ __forceinline__ float xred(float a, float b, bool up, int o) { return (up ? b : a) + __shfl_xor_sync(0xffffffffu, up ? a : b, o); }

#define STAMP(id)
#define STAMP_IF(c, id)
#define STAMP2(i)
#define LITE 1
#define LITE_MASK 0ull

template <bool TRANS, int NK = 16>
__device__ __forceinline__ void mainloop(float (&a0)[64], float (&a1)[64], int s, int ph, int handoff, int xpair, bool leader) {
  uint32_t prev = 0;
#pragma unroll 1
  for (int kt = 0; kt < NK; kt++) {
    const bool xr = !TRANS && (kt >> 1) == xpair;
    mbar_wait(B_FULL + 8 * s, ph);
    const uint64_t dw = mkdesc(RING, 8192, 1024, 1) + s * (SLOT >> 4), dx = mkdesc(0, 16, 1024, 1) + (xr ? (STG >> 4) + (kt & 1) * 1024 : ((RING + 16384) >> 4) + s * (SLOT >> 4));
    if (xr) mbar_wait(B_XRES + 8 * (kt & 1), 0);
    wg_fence();
#pragma unroll
    for (int j = 0; j < 4; j++) {
      if (TRANS) {
        wgmma_n128_ss<1, 0>(a0, dw + j * 128, dx + j * 2, 1);
        wgmma_n128_ss<1, 0>(a1, dw + j * 128 + 512, dx + j * 2, 1);
      } else {
        wgmma_n128_ss<0, 1>(a0, dx + j * 2, dw + j * 128, 1);
        wgmma_n128_ss<0, 1>(a1, dx + j * 2 + 512, dw + j * 128, 1);
      }
    }
    wg_commit();
    if (handoff && kt == 15) nb_arrive(handoff, 256);
    wg_wait<1>();
    if (prev && leader) mbar_arrive(prev);
    prev = B_EMPTY + 8 * s;
    if (++s == NST) { s = 0; ph ^= 1; }
  }
  if (NK < 16) return;
  wg_wait<0>();
  if (leader) mbar_arrive(prev);
  reg_fence(a0);
  reg_fence(a1);
}

__device__ __forceinline__ int out_kblock(int r, int tn) {
  const int q = r - 2, half = q >= 7, pi = q - 7 * half;
  return r < 2 ? 2 * tn + r : 2 * ((pi + (pi >= (tn & 3))) ^ (tn & 4)) + half;
}

struct Params {
  const char *x, *wqkv, *w_r, *wg, *wu, *wd, *wo;
  CUtensorMap m_wqkv, m_x, m_xs, m_o, m_os, m_wo, m_gu, m_down, m_out;
};

template <bool BY_SMID>
__global__ void __launch_bounds__(512, 1) fused_kernel(const __grid_constant__ Params mp) {
  extern __shared__ __align__(1024) uint8_t smem_raw[];
#define CK(i)
  CK(0);
  const int tid = threadIdx.x, lane = tid & 31;
  const int w = __shfl_sync(0xffffffffu, tid >> 5, 0);
  int bid = blockIdx.x;
  if (BY_SMID) {
    uint32_t sm;
    asm volatile("mov.u32 %0, %%smid;" : "=r"(sm));
    const uint32_t p = sm >> 1, q = ((p - 32) * 37) >> 8;
    const uint32_t gpc = p < 32 ? p & 7 : p < 60 ? p - 31 - 7 * q : 0, tpc = p < 32 ? p >> 3 : p < 60 ? 4 + q : p - 58;
    bid = (p >> 1) == 30 ? 128 + ((0x9cu >> (2 * (sm & 3))) & 3) : ((GPCMAP >> (4 * gpc)) & 7) * 16 + tpc * 2 + (sm & 1);
  }
  const int tn = (bid & 3) + 4 * (bid >> 6), tm = (bid >> 2) & 15;

  CK(1);
  if (w == 0) {
#pragma unroll 1
    for (int s = 0; s < NST; s++) {
      asm volatile(ELECT "@p mbarrier.init.shared::cta.b64 [%0], 1;\n}" ::"r"(B_FULL + 8 * s) : "memory");
      if (bid < 128) {
        e_expect(B_FULL + 8 * s, 32768);
        e_tma2d(RING + s * SLOT + 16384, &mp.m_x, s * 64, tm * 128, B_FULL + 8 * s);
        e_tma3d(RING + s * SLOT, &mp.m_wqkv, s * 64, 16 + 2 * tn, B_FULL + 8 * s);
      }
      if (s == 0) CK(2);
    }
  }
  if (w == 1) e_pfmap(&mp.m_wqkv);
  if (w == 2) e_pfmap(&mp.m_xs);
  if (w >= 4) {
#pragma unroll 1
    for (uint32_t b = MISC + 8 * (w + 1); b < MISC + 8 * NBAR; b += 96)
      asm volatile(ELECT "@p mbarrier.init.shared::cta.b64 [%0], %1;\n}" ::"r"(b), "r"(b == B_CSDN ? 4 : 1) : "memory");
    if (w == 15) sts32(S_NCAND, 0);
  }
  CK(3);
  asm volatile("fence.mbarrier_init.release.cluster;" ::: "memory");
  __syncthreads();

  if (bid >= 128) {
    const int h0 = bid == 128 ? 14 : bid - 129, hs = bid == 128 ? 1 : 3, h1 = bid == 128 ? 16 : 14;
    if (w == 12) {
      int s = 0, ph = 1;
#pragma unroll 1
      for (int h = h0; h < h1; h += hs) {
        const int c = 2 * h + (h & 8) * 2;
        if (h == 14) mbar_wait(B_SEL, 0);
#pragma unroll 1
        for (int kt = 0; kt < 16; kt += 2) {
          mbar_wait(B_EMPTY + 8 * s, ph);
          e_expect(B_FULL + 8 * s, 32768);
          e_tma3d(RING + s * SLOT, &mp.m_wqkv, kt * 64, c, B_FULL + 8 * s);
          e_tma3d(RING + s * SLOT + 16384, &mp.m_wqkv, kt * 64 + 64, c, B_FULL + 8 * s);
          if (++s == HST) { s = 0; ph ^= 1; }
        }
      }
    } else if (w < 4) {
      const uint32_t par = (ld_relaxed(&g_epoch) + 1) & 1u;
      sts32(S_ONES + tid * 4, 0x3f803f80u);
      fence_async_smem();
      nb_sync(NB_WG0, 128);
      int s = 0, ph = 0;
#pragma unroll 1
      for (int h = h0; h < h1; h += hs) {
        float c[4][4];
#pragma unroll
        for (int q = 0; q < 4; q++) reg_zero(c[q]);
        uint32_t prev = 0;
#pragma unroll 1
        for (int kt = 0; kt < 8; kt++) {
          mbar_wait(B_FULL + 8 * s, ph);
          const uint64_t dw = mkdesc(RING, 8192, 1024, 1) + s * (SLOT >> 4);
          wg_fence();
#pragma unroll
          for (int j = 0; j < 16; j++) wgmma_n8_ss<1, 0>(c[j & 3], dw + (j & 3) * 512 + (j >> 2) * 128, mkdesc(S_ONES, 128, 128, 0), 1);
          wg_commit();
          wg_wait<1>();
          if (prev && tid == 0) mbar_arrive(prev);
          prev = B_EMPTY + 8 * s;
          if (++s == HST) { s = 0; ph ^= 1; }
        }
        wg_wait<0>();
        if (tid == 0) mbar_arrive(prev);
#pragma unroll
        for (int q = 0; q < 4; q++) reg_fence(c[q]);
        const bool u2 = lane & 2, u1 = lane & 1;
        const float lo = u2 ? c[1][0] + c[3][0] : c[0][0] + c[2][0], hi = u2 ? c[1][2] + c[3][2] : c[0][2] + c[2][2];
        st_relaxed(g_csum + h * 128 + (lane & 2) * 32 + w * 16 + (lane & 1) * 8 + (lane >> 2), tagf(u1 ? hi : lo, par));
        STAMP_IF(tid == 0, h >= 8 ? 6 : 30);
      }
    } else if (w < 12 && bid == 128) {
      const int t = tid - 128, j = w - 4;
      const uint32_t ep = ld_relaxed(&g_epoch) + 1;
      uint32_t kk[16];
      poll_keys(kk, g_keys + t * 2, ep, 31u);
      STAMP_IF(t == 0, 42);
      const uint32_t m = __reduce_max_sync(0xffffffffu, max(max(max(kk[0], kk[2]), max(kk[4], kk[6])), max(max(kk[8], kk[10]), max(kk[12], kk[14]))));
      if (lane == 0) sts32(S_WMAX + j * 4, m);
      nb_sync(NB_WG1, 256);
      const uint32_t T = __reduce_min_sync(0xffffffffu, lds32(S_WMAX + (lane & 7) * 4));
      uint32_t cnt = 0;
#pragma unroll
      for (int i = 0; i < 8; i++) cnt += kk[2 * i] >= T;
      if (cnt) {
        uint32_t pos;
        asm volatile("atom.shared.add.u32 %0, [%1], %2;" : "=r"(pos) : "r"(S_NCAND), "r"(cnt * 8) : "memory");
#pragma unroll
        for (int i = 0; i < 8; i++)
          if (kk[2 * i] >= T) { sts64(AUX + pos, kk[2 * i], kk[2 * i + 1]); pos += 8; }
      }
      nb_sync(NB_WG1, 256);
      const uint32_t n8 = lds32(S_NCAND);
#pragma unroll 1
      for (uint32_t i = j * 8; i < n8; i += 64) {
        const float2 c = lds64f(AUX + i);
        uint32_t rank = 0;
#pragma unroll 1
        for (uint32_t q = lane * 8; q < n8 + lane * 8; q += 256) rank += __popc(__ballot_sync(0xffffffffu, q < n8 && lds32(AUX + q) > __float_as_uint(c.x)));
        if (rank < 8) sts64(S_SEL + rank * 8, __float_as_uint(c.x), __float_as_uint(c.y));
      }
      fence_async_smem();
      nb_sync(NB_WG1, 256);
      if (j == 0) {
        const uint4 v = lds128(S_SEL + (lane & 3) * 16);
        asm volatile("{\n.reg .b64 x, y;\nmov.b64 x, {%1,%2};\nmov.b64 y, {%3,%4};\nst.relaxed.gpu.global.v2.b64 [%0], {x, y};\n}"
                     ::"l"(g_sel + (lane >> 2) * 16 + (lane & 3) * 2), "r"(v.x), "r"(v.y), "r"(v.z), "r"(v.w) : "memory");
        e_arrive(B_SEL);
      }
      STAMP_IF(t == 0, 45);
    }
  } else if (w >= 12) {
    asm volatile("setmaxnreg.dec.sync.aligned.u32 32;");
    if (w == 12) {
      int s = 0, ph = 0;
#pragma unroll 1
      for (int it = NST; it < 48; it++) {
        const int c = (it < 32 ? (it & 16) + 16 : 0) + 2 * tn;
        const int k0 = ((it + (it >= 32 && tn < 4 ? 8 : 0)) & 15) * 64;
        const bool xr = (it >> 1) == 20 + (tn & 3);
        if (xr) { mbar_wait(B_SFREE, 0); e_expect(B_XRES + 8 * (it & 1), 16384); }
        mbar_wait(B_EMPTY + 8 * s, ph);
        e_expect(B_FULL + 8 * s, xr ? 16384 : 32768);
        e_tma3d(RING + s * SLOT, &mp.m_wqkv, k0, c, B_FULL + 8 * s);
        e_tma2d(xr ? STG + (it & 1) * 16384 : RING + s * SLOT + 16384, &mp.m_x, k0, tm * 128, xr ? B_XRES + 8 * (it & 1) : B_FULL + 8 * s);
        if (it >= NST) STAMP2(it - NST);
        if (++s == NST) { s = 0; ph ^= 1; }
      }
#pragma unroll 1
      for (int r = 0; r < 16; r++) {
        const int kb = out_kblock(r, tn);
        mbar_wait(B_EMPTY + 8 * s, ph);
        e_expect(B_FULL + 8 * s, r < 2 ? 16384 : 32768);
        e_tma3d(RING + s * SLOT, &mp.m_wo, kb * 64, 2 * tn, B_FULL + 8 * s);
        if (r < 2 || r == 4) {
          const uint32_t bar = B_DR + (r < 2 ? 16 : 8);
          const int k0 = (bid >> 4) * 448 + 128 + min(r, 2) * 128;
          if (r != 1) e_expect(bar, r ? 8192 : 32768);
          e_tma2d_ef(RING + s * SLOT + 16384, &mp.m_down, (bid & 15) * 64, k0, bar, EVICT_FIRST);
          if (r < 2) e_tma2d_ef(RING + s * SLOT + 24576, &mp.m_down, (bid & 15) * 64, k0 + 64, bar, EVICT_FIRST);
        }
        STAMP2(r + 48 - NST);
        if (++s == NST) { s = 0; ph ^= 1; }
      }
    } else if (w == 13) {
      mbar_wait(B_FULL, 0);
#pragma unroll 1
      for (int c = 0; c < 4; c++) {
        if (c >= XS_FLY) mbar_wait(B_XS + 8 * (c - XS_FLY), 0);
        if (c == (tm >> 2)) {
          e_expect(B_WK, 16384);
          e_tma3d(FR, &mp.m_wqkv, tm * 64, 16 + 2 * tn, B_WK);
        }
        e_expect(B_XS + 8 * c, 8192);
        e_tma2d(STG + c * 8192, &mp.m_xs, c * 256, tm * 128 + tn * 16, B_XS + 8 * c);
      }
      {
        const char* pv = mp.wqkv + (tm * 16 + (lane >> 1)) * 6144 + 4096 + tn * 256 + (lane & 1) * 128;
        const char* pd = mp.wd + (bid & 15) * 128 + ((bid >> 4) * 448 + lane) * 2048;
        const char* po = mp.wo + bid * 16384 + lane * 128;
        mbar_wait(B_XS + 24, 0);
        __nanosleep(PF_WAIT);
#pragma unroll 1
        for (int i = PF_V ? 0 : 4; i < (PF_O ? 22 : 18); i++) {
          asm volatile("prefetch.global.L2 [%0];" ::"l"(i < 4 ? pv + i * (256 * 6144) : i < 18 ? pd + (i - 4) * 65536 : po + (i - 18) * 4096));
          __nanosleep(PF_GAP);
        }
      }
      nb_sync(NB_Z, 160);
      const uint32_t ep = lds32(S_EPOCH);
      {
        float z[4] = {0.f, 0.f, 0.f, 0.f};
        e_signal(H_Z + tn, tm);
        await(H_Z + tn, 0xffffu, ep);
#pragma unroll 1
        for (int i = 0; i < 4; i++) {
          uint32_t p[16];
          poll_z(p, g_z + i * 4096 + tn * 128 + lane * 4, ep, 1u);
#pragma unroll
          for (int q = 0; q < 4; q++) z[q] += (__uint_as_float(p[q]) + __uint_as_float(p[4 + q])) + (__uint_as_float(p[8 + q]) + __uint_as_float(p[12 + q]));
        }
        const uint32_t z01 = pack(z[0], z[1]), z23 = pack(z[2], z[3]);
        if (bid < 112) mbar_wait(B_PFREE, 0);
#pragma unroll
        for (int n = 0; n < 8; n++) sts64(KVB + (lane >> 4) * 5120 + n * 128 + ((((lane >> 1) & 7) ^ n) << 4) + (lane & 1) * 8, z01, z23);
        fence_async_smem();
        nb_arrive(NB_KVB, 320);
        STAMP_IF(lane == 0, 46);
      }
      nb_sync(NB_Q0, 192);
      e_store2d(&mp.m_os, tn * 128, tm * 128, STG);
      nb_sync(NB_OWN0, 288);
      e_store2d(&mp.m_os, tn * 128, tm * 128 + 64, STG + 8192);
      if (!SIG_EARLY) bulk_wait_read(); else if (SIG_EARLY > 1) __nanosleep(SIG_EARLY);
      e_signal(H_O + tm, 2 * tn);
      STAMP_IF(lane == 0, 4);
      nb_sync(NB_H1, 160);
      e_store2d(&mp.m_os, tn * 128 + 64, tm * 128, STG + 16384);
      e_store2d(&mp.m_os, tn * 128 + 64, tm * 128 + 64, STG + 24576);
      bulk_wait_read();
      e_signal(H_O + tm, 2 * tn + 1);
      STAMP_IF(lane == 0, 5);
      nb_arrive(NB_ST, 288);
    } else if (w == 14) {
      e_pfmap(&mp.m_gu); e_pfmap(&mp.m_o); e_pfmap(&mp.m_os); e_pfmap(&mp.m_wo); e_pfmap(&mp.m_down); e_pfmap(&mp.m_out);
      const uint32_t ep = ld_relaxed(&g_epoch) + 1;
      nb_sync(NB_FDONE, 416);
      {
        uint32_t c[4];
        poll_quad(c, g_csum + tn * 128 + lane * 4, ep, 1u);
        sts128(S_CSQ + lane * 16, c[0], c[1], c[2], c[3]);
        nb_arrive(NB_CSQ, 160);
        poll_quad(c, g_csum + 1024 + tn * 128 + lane * 4, ep, 1u);
        sts128(S_CSV + lane * 16, c[0], c[1], c[2], c[3]);
        __syncwarp();
        e_arrive(B_CSV);
      }
      {
        mbar_wait(B_WK, 1);
        if (KV_SPEC) __nanosleep(KV_SPEC); else await(H_KV + tn, 0xffffu, ep);
        STAMP_IF(lane == 0, 7);
        if (bid < 112) mbar_wait(B_PFREE, 0);
        STAMP_IF(lane == 0, 23);
        uint32_t bad, ph = 0;
        do {
          e_expect(B_KVL, 8192);
          e_load(KVB + 1024, g_kv + tn * 512, 4096, B_KVL);
          e_load(KVB + 6144, g_kv + tn * 512 + 256, 4096, B_KVL);
          mbar_wait(B_KVL, ph & 1);
          bad = 0;
#pragma unroll
          for (int i = 0; i < 16; i++) bad |= __float_as_uint(lds32v(KVB + 1024 + (i & 8) * 128 + i * 512 + lane * 16)) ^ ep;
          bad = __any_sync(0xffffffffu, bad & 1u);
          if (bad) fence_async_smem();
        } while (bad && ++ph < 100000);
        nb_arrive(NB_KVB, 320);
        STAMP_IF(lane == 0, 24);
      }
      nb_sync(NB_Q0, 192);
      uint32_t ready = 0;
      int s = 0, ph = 1;
#pragma unroll 1
      for (int r = 2; r < 16; r++) {
        const int kb = out_kblock(r, tn);
        if (!((ready >> kb) & 1)) {
          uint32_t f[1];
          poll0(f, g_sig + (H_O + tm) * 32, 0u - (ep & 1u), 1u << kb);
          ready = f[0] ^ ((ep & 1u) - 1u);
        }
        if (r == 4) mbar_wait(B_DND, 0);
        mbar_wait(B_EMPTY + 8 * s, ph);
        e_tma2d(RING + s * SLOT + 16384, &mp.m_o, kb * 64, tm * 128, B_FULL + 8 * s);
        STAMP_IF(lane == 0 && r == 2, 2);
        STAMP_IF(lane == 0 && r == 9, 3);
        if (++s == NST) { s = 0; ph ^= 1; }
      }
    } else {
      uint32_t nsm = 132;
      if (BY_SMID) asm volatile("mov.u32 %0, %%nsmid;" : "=r"(nsm));
      asm volatile("{\n.reg .pred q;\nsetp.eq.u32 q, %0, 1156;\n@q bra LOK;\ntrap;\nLOK:\n}" ::"r"((uint32_t)__cvta_generic_to_shared(smem_raw) + nsm));
      const uint32_t ep = ld_relaxed(&g_epoch) + 1;
      mbar_wait(B_CSDN, 0);
#pragma unroll 1
      for (int n = 0; n < 3 && bid < 112; n++) {
        __nanosleep(FFN_GAP);
        e_expect(B_FR + 8 * n, 8192);
        e_tma3d_ef(GR + n * 8192, &mp.m_gu, bid * 32, n * 64, B_FR + 8 * n, EVICT_FIRST);
      }
      uint32_t sel[2];
      poll_pair(sel, g_sel + (bid >> 4) * 16 + (lane >> 2), ep, 31u);
      const char* xs = mp.x + key_token(sel[0]) * 2048 + (lane & 3) * 16;
      const uint32_t xd = AUX + (lane >> 2) * 64 + (((lane & 3) ^ (lane >> 3)) << 4);
      auto slices = [&](int n, int p) {
        asm volatile("cp.async.cg.shared.global [%0], [%1], 16;\ncp.async.cg.shared.global [%0+512], [%1+64], 16;\ncp.async.commit_group;"
                     ::"r"(xd + p * 1024), "l"(xs + n * 128) : "memory");
      };
      if ((lane & 3) == 0) sts64(S_SEL + lane * 2, sel[0], sel[1]);
      if (bid < 112) {
#pragma unroll
        for (int i = 0; i < 6; i++) slices(i, i);
      }
      asm volatile("cp.async.wait_group 2;" ::: "memory");
      fence_async_smem();
      __syncwarp();
      e_arrive(B_SEL);
      if (bid < 112) {
        int s = 0, ph = 0;
#pragma unroll 1
        for (int n = 3; n < 16; n++) {
          mbar_wait(B_FE + 8 * s, ph);
          e_expect(B_FR + 8 * s, 8192);
          e_tma3d_ef(GR + s * 8192, &mp.m_gu, bid * 32, n * 64, B_FR + 8 * s, EVICT_FIRST);
          STAMP2(64 + n);
          asm volatile("cp.async.wait_group 1;" ::: "memory");
          fence_async_smem();
          __syncwarp();
          if (n < 13) slices(n + 3, s + 3 * ph);
          else asm volatile("cp.async.commit_group;" ::: "memory");
          if (++s == 3) { s = 0; ph ^= 1; }
        }
      }
      e_expect(B_DR, 16384);
      if (bid < 112) mbar_wait(B_FE + 8, 0);
      e_tma2d_ef(FR, &mp.m_down, (bid & 15) * 64, (bid >> 4) * 448, B_DR, EVICT_FIRST);
      if (bid < 112) mbar_wait(B_FE + 16, 0);
      e_tma2d_ef(FR + 8192, &mp.m_down, (bid & 15) * 64, (bid >> 4) * 448 + 64, B_DR, EVICT_FIRST);
    }
  } else if (w >= 8) {
    asm volatile("setmaxnreg.dec.sync.aligned.u32 56;");
    const int t = tid - 256, ww = w - 8;
    const uint32_t ep = ld_relaxed(&g_epoch) + 1, par = ep & 1u;
    sts32(FONES + t * 4, 0x3f803f80u);
    {
      const int r0 = (lane >> 3) + (lane & 4);
      const uint32_t a = FR + (ww >> 1) * 8192 + r0 * 128 + ((((ww & 1) * 4 + (lane & 3)) ^ r0) << 4);
      float c[8];
      reg_zero(c);
      mbar_wait(B_WK, 0);
#pragma unroll 2
      for (int i = 0; i < 8; i++) {
        const uint4 v = lds128(a + i * 1024);
        c[0] += bf_lo(v.x); c[1] += bf_hi(v.x); c[2] += bf_lo(v.y); c[3] += bf_hi(v.y);
        c[4] += bf_lo(v.z); c[5] += bf_hi(v.z); c[6] += bf_lo(v.w); c[7] += bf_hi(v.w);
      }
      const bool u16 = lane & 16, u8 = lane & 8, u4 = lane & 4;
      const float d0 = xred(c[0], c[4], u16, 16), d1 = xred(c[1], c[5], u16, 16), d2 = xred(c[2], c[6], u16, 16), d3 = xred(c[3], c[7], u16, 16);
      fence_async_smem();
      e_arrive(B_CSDN);
      const float sum = xred(xred(d0, d2, u8, 8), xred(d1, d3, u8, 8), u4, 4);
      st_relaxed(g_csum + (2 + tm) * 1024 + tn * 128 + ww * 32 + (lane & 3) * 8 + (lane >> 2), tagf(sum, par));
      STAMP_IF(t == 0, 8);
      nb_sync(NB_WG2, 128);
      if (ww == 0) { e_signal(H_CS + tn, tm); await(H_CS + tn, 0xffffu, ep); }
      nb_sync(NB_WG2, 128);
      uint32_t p[16];
      poll16(p, g_csum + 2048 + tn * 128 + t, par, 1u);
      float tot = 0.f;
#pragma unroll
      for (int i = 0; i < 16; i += 4) tot += (__uint_as_float(p[i]) + __uint_as_float(p[i + 1])) + (__uint_as_float(p[i + 2]) + __uint_as_float(p[i + 3]));
      sts32(S_CSK + t * 4, __float_as_uint(tot));
      nb_arrive(NB_FDONE, 416);
      STAMP_IF(t == 0, 9);
    }
    const int ks = bid >> 4, nt = bid & 15;
    if (bid < 112) {
      float fg[8];
      reg_zero(fg);
      mbar_wait(B_SEL, 0);
      constexpr uint64_t DA0 = mkdesc(GR, 4096, 512, 2), DB0 = mkdesc(AUX, 16, FONES - AUX, 2), DBS = 32 - (32ull << 32);
      uint64_t da = DA0, db = DB0;
      uint32_t bar = B_FR, ph = 0;
#pragma unroll 1
      for (int n = 0; n < 16; n++) {
        mbar_wait(bar, ph);
        wg_fence();
#pragma unroll
        for (int q = 0; q < 4; q++) wgmma_n16_ss<1, 0>(fg, da + q * 64, db + (q >> 1) * DBS + (q & 1) * 2, 1);
        wg_commit();
        const uint32_t rel = bar + (B_FE - B_FR);
        const bool wrap = bar == B_FR + 16;
        da = wrap ? DA0 : da + 512;
        db = wrap && ph ? DB0 : db + 2 * DBS;
        bar = wrap ? B_FR : bar + 8;
        ph ^= wrap;
        wg_wait<0>();
        if (t == 0) mbar_arrive(rel);
      }
      if (t == 0) mbar_arrive(B_PFREE);
      const uint4 st = lds128(S_SEL + (lane & 3) * 16);
      const float r0 = rcp(bf_lo(st.y)), r1 = rcp(bf_lo(st.w));
      reg_fence(fg);
      const float fa[4] = {fmaf(-bf_hi(st.y), fg[4], fg[0]) * r0, fmaf(-bf_hi(st.w), fg[4], fg[1]) * r1,
                           fmaf(-bf_hi(st.y), fg[6], fg[2]) * r0, fmaf(-bf_hi(st.w), fg[6], fg[3]) * r1};
      STAMP_IF(t == 0, 12);
      const bool isup = (ww >> 1) != (mp.wu < mp.wg);
      nb_sync(NB_WG2, 128);
      if (isup) sts128f(HOP + (t & 63) * 16, fa[0], fa[1], fa[2], fa[3]);
      nb_sync(NB_WG2, 128);
      if (!isup) {
        const float4 u = lds128f(HOP + (t & 63) * 16);
        const float uu[4] = {u.x, u.y, u.z, u.w};
        uint32_t* hp = g_h + bid * 256 + (lane & 3) * 64 + (ww & 1) * 16 + (lane >> 2);
#pragma unroll
        for (int i = 0; i < 4; i++) {
          const float g = fa[i], hv = g * rcp(1.f + ex2(-g * LOG2E)) * uu[i];
          st_relaxed(hp + (i & 1) * 32 + (i >> 1) * 8, __byte_perm(pack(hv, hv), ep, 0x3254));
        }
      }
      nb_sync(NB_WG2, 128);
      if (ww == 0) e_signal(H_H + bid / 14, bid % 14);
    }
    {
      uint32_t v[28];
      if (ww == 0) await(H_H + ks, 0x3fffu, ep);
      nb_sync(NB_WG2, 128);
      poll7x4(v, g_h + ks * 3584 + t * 4, ep, 0xffffu);
      mbar_wait(B_WK, 1);
#pragma unroll
      for (int q = 0; q < 7; q++)
        asm volatile("st.shared.v2.u32 [%0], {%1,%2};" ::"r"((q < 6 ? HOP + q * 1024 : S_CSK) + (t >> 3) * 64 + ((((t >> 1) & 3) ^ ((t >> 4) & 3)) << 4) + (t & 1) * 8),
                     "r"(__byte_perm(v[4 * q], v[4 * q + 1], 0x7632)), "r"(__byte_perm(v[4 * q + 2], v[4 * q + 3], 0x7632)) : "memory");
      fence_async_smem();
      nb_sync(NB_WG2, 128);
    }
    STAMP_IF(t == 0, 13);
    float fa[4] = {0.f, 0.f, 0.f, 0.f};
    auto down = [&](uint32_t a, int k0, int nk) {
#pragma unroll
      for (int q = 0; q < nk; q++) wgmma_n8_ss<1, 0>(fa, mkdesc(a + q * 2048, 4096, 1024, 1), mkdesc((k0 < 24 ? HOP : S_CSK - 6144) + ((k0 + q) >> 1) * 512 + (q & 1) * 32, 16, 512, 2), 1);
    };
    mbar_wait(B_DR, 0);
    mbar_wait(B_DR + 16, 0);
    mbar_wait(B_DR + 8, 0);
    wg_fence();
    down(RING + 2 * SLOT + 16384, 24, 4);
    down(RING + 3 * SLOT + 16384, 8, 8);
    down(RING + 4 * SLOT + 16384, 16, 8);
    wg_commit();
    wg_fence();
    down(FR, 0, 8);
    wg_commit();
    wg_wait<1>();
    if (t == 0) mbar_arrive(B_DND);
    wg_wait<0>();
    reg_fence(fa);
    STAMP_IF(t == 0, 14);
    {
      uint32_t* yp = g_yp + (nt * 8 + ks) * 512 + (lane & 3) * 128 + ww * 16 + (lane >> 2);
#pragma unroll
      for (int i = 0; i < 4; i++) st_relaxed(yp + (i & 1) * 64 + (i >> 1) * 8, tagf(fa[i], par));
    }
    nb_sync(NB_WG2, 128);
    if (ww == 0) e_signal(H_Y + (nt >> 1), (nt & 1) * 8 + ks);
    mbar_wait(B_SEL, 0);
    const uint32_t mykey = lds32(S_SEL + (lane & 7) * 8);
    const uint32_t inmask = __ballot_sync(0xffffffffu, (key_token(mykey) >> 7) == tm) & 0xffu;
    sts128(FR + t * 16, 0u, 0u, 0u, 0u);
    if (inmask) {
      if (ww == 0) await(H_Y + tn, 0xffffu, ep);
      nb_sync(NB_WG2, 128);
      const float sg = rcp(1.f + ex2(-key_score(mykey) * LOG2E));
#pragma unroll 1
      for (uint32_t mine = __ballot_sync(0xffffffffu, ((inmask >> lane) & 1) && (__popc(inmask & ((1u << lane) - 1)) & 3) == ww); mine; mine &= mine - 1) {
        const int j = __ffs(mine) - 1;
        uint32_t p[32];
        poll8x4(p, g_yp + (tn * 2 + (lane >> 4)) * 4096 + j * 64 + (lane & 15) * 4, par, 1u);
        float y[4];
        const float sj = __shfl_sync(0xffffffffu, sg, j);
#pragma unroll
        for (int i = 0; i < 4; i++)
          y[i] = sj * (((__uint_as_float(p[i]) + __uint_as_float(p[4 + i])) + (__uint_as_float(p[8 + i]) + __uint_as_float(p[12 + i]))) +
                       ((__uint_as_float(p[16 + i]) + __uint_as_float(p[20 + i])) + (__uint_as_float(p[24 + i]) + __uint_as_float(p[28 + i]))));
        asm volatile("st.shared.v2.u32 [%0], {%1,%2};" ::"r"(FR + (lane >> 4) * 1024 + j * 128 + ((((lane >> 1) & 7) ^ j) << 4) + (lane & 1) * 8),
                     "r"(pack(y[0], y[1])), "r"(pack(y[2], y[3])) : "memory");
      }
    }
    fence_async_smem();
    nb_arrive(NB_ST, 288);
    STAMP_IF(t == 0, 15);
  } else if (w >= 4) {
    asm volatile("setmaxnreg.inc.sync.aligned.u32 208;");
    const int t = tid - 128, ww = w - 4, g = lane >> 2, t4 = lane & 3;
    const bool leader = t == 0;
    const uint32_t ep = ld_relaxed(&g_epoch) + 1, par = ep & 1u;
    {
      const uint4* wp = reinterpret_cast<const uint4*>(mp.w_r) + lane;
      uint4 w0 = __ldg(wp), w1 = __ldg(wp + 32), w2 = __ldg(wp + 64), w3 = __ldg(wp + 96);
      if (leader) sts32(S_EPOCH, ep);
      if (KV_SPEC && t4 == 0) {
        const int grp = (tm & 1) * 2 + ((lane >> 3) & 1), row = ww * 2 + ((lane >> 2) & 1);
        st_unit(g_kv + tn * 512 + ((tm >> 3) * 4 + grp) * 64 + row * 8 + (((tm & 2) * 2 + ((tm >> 1) & 2) + (lane >> 4)) ^ row), 0u, 0u, 0u, 0u, par ^ 1u);
      }
      float s[4] = {0.f, 0.f, 0.f, 0.f}, q[4] = {0.f, 0.f, 0.f, 0.f}, d[4] = {0.f, 0.f, 0.f, 0.f}, wsum = 0.f;
#pragma unroll 1
      for (int c = 0; c < 4; c++) {
        const float wr[8] = {bf_lo(w0.x), bf_hi(w0.x), bf_lo(w0.y), bf_hi(w0.y), bf_lo(w0.z), bf_hi(w0.z), bf_lo(w0.w), bf_hi(w0.w)};
        w0 = w1; w1 = w2; w2 = w3;
        wsum += ((wr[0] + wr[1]) + (wr[2] + wr[3])) + ((wr[4] + wr[5]) + (wr[6] + wr[7]));
        mbar_wait(B_XS + 8 * c, 0);
#pragma unroll
        for (int r = 0; r < 4; r++) {
          const uint4 v = lds128(STG + c * 8192 + (ww * 4 + r) * 512 + lane * 16);
          const uint32_t xw[4] = {v.x, v.y, v.z, v.w};
#pragma unroll
          for (int i = 0; i < 4; i++) {
            const uint32_t dep = __float_as_uint(q[i ? r : (r + 3) & 3]);
            const float lo = __uint_as_float(prmt(xw[i], dep, 0x10ff)), hi = __uint_as_float(prmt(xw[i], dep, 0x32ff));
            s[r] += lo; q[r] = fmaf(lo, lo, q[r]); d[r] = fmaf(lo, wr[2 * i], d[r]);
            s[r] += hi; q[r] = fmaf(hi, hi, q[r]); d[r] = fmaf(hi, wr[2 * i + 1], d[r]);
          }
        }
      }
      STAMP_IF(leader, 16);
      const bool u16 = lane & 16, u8 = lane & 8, u4 = lane & 4, u2 = lane & 2;
      const float s1 = xred(xred(s[0], s[2], u16, 16), xred(s[1], s[3], u16, 16), u8, 8);
      const float q1 = xred(xred(q[0], q[2], u16, 16), xred(q[1], q[3], u16, 16), u8, 8);
      const float d1 = xred(xred(d[0], d[2], u16, 16), xred(d[1], d[3], u16, 16), u8, 8);
      wsum += __shfl_xor_sync(0xffffffffu, wsum, 16);
      wsum += __shfl_xor_sync(0xffffffffu, wsum, 8);
      float tot = xred(xred(s1, d1, u4, 4), xred(q1, wsum, u4, 4), u2, 2);
      tot += __shfl_xor_sync(0xffffffffu, tot, 1);
      const float qq = __shfl_down_sync(0xffffffffu, tot, 2), dd = __shfl_down_sync(0xffffffffu, tot, 4), ws = __shfl_down_sync(0xffffffffu, tot, 6);
      if ((lane & 7) == 0) {
        const float mean = tot * (1.f / 1024.f);
        const float var = fmaxf(fmaf(-mean, mean, qq * (1.f / 1024.f)), 0.f);
        float sd;
        asm("sqrt.approx.ftz.f32 %0, %1;" : "=f"(sd) : "f"(bf_round(bf_round(var) + 1e-5f)));
        const uint32_t ms = pack(sd, mean);
        const int row = tm * 128 + tn * 16 + ww * 4 + (lane >> 3);
        const uint32_t rbits = pack(0.f, fmaf(-bf_hi(ms), ws, dd) * rcp(bf_lo(ms)));
        const uint32_t key = (rbits ^ (((int)rbits >> 31 & 0x7fff0000u) | 0x80000000u)) | ((2047 - row) << 5) | (ep & 31u);
        asm volatile("{\n.reg .b64 x;\nmov.b64 x, {%1,%2};\nst.relaxed.gpu.global.b64 [%0], x;\n}" ::"l"(g_keys + row), "r"(key), "r"(ms) : "memory");
      }
      STAMP_IF(leader, 17);
      __nanosleep(400);
      uint32_t st[2];
      poll_pair(st, g_keys + tm * 128 + t, ep, 31u);
      asm volatile("st.shared.v2.f32 [%0], {%1,%2};" ::"r"(S_KSTAT + t * 8), "f"(bf_hi(st[1])), "f"(rcp(bf_lo(st[1])) * LOG2E) : "memory");
      nb_arrive(NB_FDONE, 416);
      STAMP_IF(leader, 10);
    }
    float a0[64], a1[64];
    reg_zero(a0); reg_zero(a1); reg_fence(a0); reg_fence(a1);
    STAMP_IF(leader, 18);
    nb_sync(NB_KV, 256);
    mainloop<true, 14>(a0, a1, 1, 1, 0, 0, leader);
    {
      auto half = [&](float (&a)[64], int s, int m) {
#pragma unroll
        for (int j = 0; j < 4; j++)
          wgmma_n128_ss<1, 0>(a, mkdesc(RING + s * SLOT + m * 8192 + j * 2048, 8192, 1024, 1), mkdesc(RING + s * SLOT + 16384 + j * 32, 16, 1024, 1), 1);
      };
      auto kvmma = [&](float (&a)[64], float (&c)[32], int m) {
        reg_fence(a);
        uint32_t f[32];
#pragma unroll
        for (int i = 0; i < 32; i++) f[i] = pack(a[2 * i], a[2 * i + 1]);
        reg_zero(c);
        wg_fence();
#pragma unroll
        for (int k = 0; k < 8; k++) {
          wgmma_n64_rs<0>(c, f[4 * k], f[4 * k + 1], f[4 * k + 2], f[4 * k + 3], mkdesc(STG + (k >> 2) * 16384 + m * 8192 + (k & 3) * 32, 16, 1024, 1), k != 0);
          if (m && k == HAND_K) nb_arrive(NB_VQ, 256);
        }
        wg_commit();
      };
      float c0[32], c1[32];
      mbar_wait(B_FULL, 0);
      wg_fence();
      half(a0, 0, 0);
      wg_commit();
      mbar_wait(B_FULL + 8, 0);
      wg_fence();
      half(a0, 1, 0);
      wg_commit();
      wg_wait<2>();
      if (leader) mbar_arrive(B_EMPTY + 32);
      wg_fence();
      half(a1, 0, 1);
      half(a1, 1, 1);
      wg_commit();
      nb_sync(NB_PK, 256);
      wg_wait<1>();
      kvmma(a0, c0, 0);
      wg_wait<1>();
      if (leader) { mbar_arrive(B_EMPTY); mbar_arrive(B_EMPTY + 8); }
      STAMP_IF(leader, 19);
      kvmma(a1, c1, 1);
      const bool hp = ww >> 1;
      float c[4];
      float2 tt[8];
#pragma unroll
      for (int i = 0; i < 8; i++) tt[i] = lds64f(S_CSK + ((i >> 2) * 64 + hp * 32 + (i & 3) * 8 + 2 * t4) * 4);
      mbar_wait(B_CSV, 0);
#pragma unroll
      for (int i = 0; i < 4; i++) c[i] = -__uint_as_float(lds32(S_CSV + ((i >> 1) * 64 + ww * 16 + (i & 1) * 8 + g) * 4));
      wg_wait<0>();
      reg_fence(c0);
      reg_fence(c1);
      if (leader) mbar_arrive(B_SFREE);
      STAMP_IF(leader, 20);
      uint4* pp = g_kvp + (tn * 16 + tm) * 512 + t;
      auto put = [&](int q, const float* d) {
        const float ca = c[q & 2], cb = c[q | 1];
        const float2 ta = tt[2 * q], tb = tt[2 * q + 1];
        st_unit(pp + q * 128, pack(fmaf(ca, ta.x, d[0]), fmaf(ca, ta.y, d[1])), pack(fmaf(cb, ta.x, d[2]), fmaf(cb, ta.y, d[3])),
                pack(fmaf(ca, tb.x, d[4]), fmaf(ca, tb.y, d[5])), pack(fmaf(cb, tb.x, d[6]), fmaf(cb, tb.y, d[7])), par);
      };
      if (!hp) { put(0, c0); put(1, c0 + 8); put(2, c1); put(3, c1 + 8); }
      else { put(0, c0 + 16); put(1, c0 + 24); put(2, c1 + 16); put(3, c1 + 24); }
      STAMP_IF(leader, 47);
      {
        uint32_t p[16];
        nb_sync(NB_WG1, 128);
        if (ww == 0) { e_signal(H_KVP + tn, tm); await(H_KVP + tn, 0xffffu, ep); }
        nb_sync(NB_WG1, 128);
        STAMP_IF(leader, 1);
        poll_kvp(p, g_kvp + (tn * 16 + (lane >> 3) * 4) * 512 + tm * 32 + ww * 8 + (lane & 7), par, 1u);
        float r[8];
#pragma unroll
        for (int i = 0; i < 4; i++) {
          r[2 * i] = (bf_lo(p[i]) + bf_lo(p[4 + i])) + (bf_lo(p[8 + i]) + bf_lo(p[12 + i]));
          r[2 * i + 1] = (bf_hi(p[i]) + bf_hi(p[4 + i])) + (bf_hi(p[8 + i]) + bf_hi(p[12 + i]));
        }
        const bool u16 = lane & 16, u8 = lane & 8;
        const uint32_t wd = pack(xred(xred(r[0], r[4], u16, 16), xred(r[2], r[6], u16, 16), u8, 8), xred(xred(r[1], r[5], u16, 16), xred(r[3], r[7], u16, 16), u8, 8));
        const uint32_t w1 = __shfl_down_sync(0xffffffffu, wd, 1), w2 = __shfl_down_sync(0xffffffffu, wd, 2), w3 = __shfl_down_sync(0xffffffffu, wd, 3);
        const int grp = (tm & 1) * 2 + ((lane >> 3) & 1), row = ww * 2 + ((lane >> 2) & 1);
        if (t4 == 0) st_unit(g_kv + tn * 512 + ((tm >> 3) * 4 + grp) * 64 + row * 8 + (((tm & 2) * 2 + ((tm >> 1) & 2) + (lane >> 4)) ^ row), wd, w1, w2, w3, par);
        nb_sync(NB_WG1, 128);
        if (ww == 0) { if (!KV_SPEC) e_signal(H_KV + tn, tm); e_arrive(B_WK); }
      }
      STAMP_IF(leader, 21);
    }
    const uint32_t sx = lane & 7, sc = lane >> 4;
    const uint32_t sa = STG + (ww * 16 + (lane & 15)) * 128;
    const uint32_t sw[4] = {sa + ((sc ^ sx) << 4), sa + (((2 + sc) ^ sx) << 4), sa + (((4 + sc) ^ sx) << 4), sa + (((6 + sc) ^ sx) << 4)};
    auto residual = [&]() {
      float ka[4], kb[4];
#pragma unroll
      for (int i = 0; i < 4; i++) {
        const float2 st = lds64f(S_KSTAT + ((i >> 1) * 64 + ww * 16 + (i & 1) * 8 + g) * 8);
        const float r = st.y * LN2;
        ka[i] = 1.f + r; kb[i] = -st.x * r;
      }
#pragma unroll
      for (int j = 0; j < 8; j++) {
        if ((j & 3) == 0) mbar_wait(B_XRES + 8 * (j >> 2), 0);
        const uint4 v = ldsm4(sw[j & 3] + (j >> 2) * 16384), u = ldsm4(sw[j & 3] + (j >> 2) * 16384 + 8192);
        const uint32_t vv[4] = {v.x, v.y, v.z, v.w}, uu[4] = {u.x, u.y, u.z, u.w};
#pragma unroll
        for (int i = 0; i < 4; i++) {
          a0[8 * j + 2 * i] = fmaf(bf_lo(vv[i]), ka[i & 1], kb[i & 1]);
          a0[8 * j + 2 * i + 1] = fmaf(bf_hi(vv[i]), ka[i & 1], kb[i & 1]);
          a1[8 * j + 2 * i] = fmaf(bf_lo(uu[i]), ka[2 + (i & 1)], kb[2 + (i & 1)]);
          a1[8 * j + 2 * i + 1] = fmaf(bf_hi(uu[i]), ka[2 + (i & 1)], kb[2 + (i & 1)]);
        }
      }
      reg_fence(a0);
      reg_fence(a1);
      STAMP_IF(leader, 22);
    };
    residual();
    nb_arrive(NB_KVB, 320);
    uint32_t oh[4];
    {
      mbar_wait(B_SEL, 0);
      const int r0 = key_token(lds32(S_SEL + t4 * 16)) - tm * 128, r1 = key_token(lds32(S_SEL + t4 * 16 + 8)) - tm * 128;
#pragma unroll
      for (int i = 0; i < 4; i++) {
        const int row = (i >> 1) * 64 + ww * 16 + (i & 1) * 8 + g;
        oh[i] = (r0 == row ? 0x3f00u : 0u) | (r1 == row ? 0x3f000000u : 0u);
      }
    }
    uint32_t va = RING + 16384 + sc * 8192 + (ww * 16 + (lane & 8)) * 128 + sx * 16 + (lane >> 3) * 4;
    asm volatile("" : "+r"(va));
    {
      auto own = [&](int r) {
        nb_sync(NB_OWN0 + r, r ? 256 : 288);
        mbar_wait(B_FULL + 8 * (3 + r), 1);
        STAMP_IF(leader, 25 + r);
        const uint64_t dw = mkdesc(RING + (3 + r) * SLOT, 8192, 1024, 1), dx = mkdesc(STG + r * 16384, 16, 1024, 1);
        wg_fence();
#pragma unroll
        for (int j = 0; j < 4; j++) {
          wgmma_n128_ss<0, 1>(a0, dx + j * 2, dw + j * 128, 1);
          wgmma_n128_ss<0, 1>(a1, dx + j * 2 + 512, dw + j * 128, 1);
        }
        wg_commit();
      };
      own(0);
      wg_wait<0>();
      if (leader) mbar_arrive(B_EMPTY + 24);
      own(1);
      auto check = [&](int r, int s) {
          uint32_t bad;
          asm volatile("{\n.reg .u32 a, b, c, d, e, f, g, h;\n.reg .pred p;\n"
                       "ld.shared.u32 a, [%1];\nld.shared.u32 b, [%1+128];\nld.shared.u32 c, [%1+256];\nld.shared.u32 d, [%1+384];\n"
                       "ld.shared.u32 e, [%1+512];\nld.shared.u32 f, [%1+640];\nld.shared.u32 g, [%1+768];\nld.shared.u32 h, [%1+896];\n"
                       "lop3.b32 a, a, b, %2, 0x7e;\nlop3.b32 c, c, d, %2, 0x7e;\nlop3.b32 e, e, f, %2, 0x7e;\nlop3.b32 g, g, h, %2, 0x7e;\n"
                       "lop3.b32 a, a, c, e, 0xfe;\nlop3.b32 a, a, g, 1, 0xa8;\nsetp.ne.u32 p, a, 0;\nvote.sync.any.pred p, p, 0xffffffff;\nselp.u32 %0, 1, 0, p;\n}"
                       : "=r"(bad) : "r"(va + s * SLOT), "r"(par) : "memory");
          if (bad) {
            const uint4* src = reinterpret_cast<const uint4*>(g_o + (tm * 128 + sc * 64 + ww * 16 + (lane & 15)) * 1024 + out_kblock(r, tn) * 64);
#pragma unroll 1
            for (int i = 0; i < 8; i++) {
              uint32_t v[4];
              asm volatile("{\n.reg .b64 x, y;\n.reg .b128 z;\n.reg .pred p, q, h;\n.reg .u32 c, b;\nmov.u32 c, 0;\nsetp.ne.u32 h, %6, 0;\nLW:\n"
                           "ld.relaxed.gpu.global.b128 z, [%4];\nmov.b128 {x, y}, z;\nmov.b64 {%0,%1}, x;\nmov.b64 {%2,%3}, y;\n"
                           "selp.b64 x, y, x, h;\nshr.b64 x, x, %7;\ncvt.u32.u64 b, x;\nand.b32 b, b, 1;\nsetp.eq.u32 p, b, %5;\n"
                           "vote.sync.all.pred p, p, 0xffffffff;\n@p bra.uni LD;\nadd.u32 c, c, 1;\nsetp.lt.u32 q, c, 1000000;\n@q bra.uni LW;\ntrap;\nLD:\n}"
                           : "=&r"(v[0]), "=&r"(v[1]), "=&r"(v[2]), "=&r"(v[3]) : "l"(src + i), "r"(par), "r"(sc), "r"((lane & 8) * 4) : "memory");
              sts128(RING + 16384 + s * SLOT + sc * 8192 + (ww * 16 + (lane & 15)) * 128 + ((i ^ sx) << 4), v[0], v[1], v[2], v[3]);
            }
            fence_async_smem();
            __syncwarp();
          }
      };
      int s = 0, ph = 0;
      uint32_t prev = B_EMPTY + 32;
#pragma unroll 1
      for (int r = 2; r < 12; r++) {
        mbar_wait(B_FULL + 8 * s, ph);
        check(r, s);
        if (!LITE || ((LITE_MASK >> 27) & 1)) STAMP_IF(leader && r == 2, 27);
        const uint64_t dw = mkdesc(RING, 8192, 1024, 1) + s * (SLOT >> 4), dx = mkdesc(RING + 16384, 16, 1024, 1) + s * (SLOT >> 4);
        wg_fence();
#pragma unroll
        for (int j = 0; j < 4; j++) {
          wgmma_n128_ss<0, 1>(a0, dx + j * 2, dw + j * 128, 1);
          wgmma_n128_ss<0, 1>(a1, dx + j * 2 + 512, dw + j * 128, 1);
        }
        wg_commit();
        wg_wait<1>();
        if (leader) mbar_arrive(prev);
        prev = B_EMPTY + 8 * s;
        if (++s == NST) { s = 0; ph ^= 1; }
      }
      auto half = [&](float (&a)[64], int s, int m) {
        const uint64_t dw = mkdesc(RING, 8192, 1024, 1) + s * (SLOT >> 4), dx = mkdesc(RING + 16384 + m * 8192, 16, 1024, 1) + s * (SLOT >> 4);
#pragma unroll
        for (int j = 0; j < 4; j++) wgmma_n128_ss<0, 1>(a, dx + j * 2, dw + j * 128, 1);
      };
      auto store = [&](float (&a)[64], int m) {
        reg_fence(a);
#pragma unroll
        for (int j = 0; j < 8; j++) {
          stsm4(sw[j & 3] + (j >> 2) * 16384 + m * 8192, pack(a[8 * j], a[8 * j + 1]), pack(a[8 * j + 2], a[8 * j + 3]), pack(a[8 * j + 4], a[8 * j + 5]), pack(a[8 * j + 6], a[8 * j + 7]));
          if ((j & 3) == 3) {
            fence_async_smem();
            e_store2d(&mp.m_out, tn * 128 + (j >> 2) * 64, tm * 128 + m * 64 + ww * 16, STG + (j >> 2) * 16384 + m * 8192 + ww * 2048);
          }
        }
      };
#pragma unroll 1
      for (int q = 0; q < 4; q++) {
        mbar_wait(B_FULL + 8 * q, 0);
        check(12 + q, q);
        wg_fence();
        half(a0, q, 0);
        wg_commit();
      }
      nb_sync(NB_ST, 288);
      wg_fence();
      wgmma_n128_rs<1>(a0, oh[0], oh[1], oh[0], oh[1], mkdesc(FR, 1024, 0, 1), 1);
      wg_commit();
      wg_fence();
      half(a1, 0, 1);
      half(a1, 1, 1);
      wg_commit();
      wg_wait<1>();
      store(a0, 0);
      wg_fence();
      half(a1, 2, 1);
      half(a1, 3, 1);
      wgmma_n128_rs<1>(a1, oh[2], oh[3], oh[2], oh[3], mkdesc(FR, 1024, 0, 1), 1);
      wg_commit();
      wg_wait<0>();
      STAMP_IF(leader, 28);
      store(a1, 1);
    }
    bulk_wait_read();
    if (bid == 0 && leader) st_relaxed(&g_epoch, ep);
    STAMP_IF(leader, 29);
  } else {
    asm volatile("setmaxnreg.inc.sync.aligned.u32 216;");
    const int g = lane >> 2, t4 = lane & 3;
    const bool leader = tid == 0;
    const uint32_t sx = lane & 7, sc = lane >> 4;
    const uint32_t sa = STG + (w * 16 + (lane & 15)) * 128;
    const uint32_t sw[4] = {sa + ((sc ^ sx) << 4), sa + (((2 + sc) ^ sx) << 4), sa + (((4 + sc) ^ sx) << 4), sa + (((6 + sc) ^ sx) << 4)};
    float a0[64], a1[64];
    reg_zero(a0); reg_zero(a1); reg_fence(a0); reg_fence(a1);
    mainloop<true>(a0, a1, 0, 0, NB_KV, 0, leader);
    STAMP_IF(leader, 33);
    {
      nb_sync(NB_FDONE, 416);
      STAMP_IF(leader, 34);
      const uint32_t par = lds32(S_EPOCH) & 1u;
#pragma unroll 1
      for (int m = 0;; m++) {
        const uint32_t ca = S_CSK + (m * 64 + w * 16 + g) * 4;
        const float c[2] = {-lds32v(ca), -lds32v(ca + 32)};
        float z[2] = {0.f, 0.f}, tt[2] = {0.f, 0.f};
#pragma unroll
        for (int j = 0; j < 8; j++) {
          const float4 s0 = lds128v(S_KSTAT + (j * 16 + 2 * t4) * 8), s1 = lds128v(S_KSTAT + (j * 16 + 8 + 2 * t4) * 8);
          const float mu[4] = {s0.x, s0.z, s1.x, s1.z}, rl[4] = {s0.y, s0.w, s1.y, s1.w};
          float p[8];
#pragma unroll
          for (int i = 0; i < 8; i++) {
            const int r = (i >> 1) & 1, cc = (i >> 2) * 2 + (i & 1);
            p[i] = phi2(fmaf(c[r], mu[cc], a0[8 * j + i]) * rl[cc]);
            a0[8 * j + i] = a1[8 * j + i];
            z[r] += p[i];
            p[i] *= rl[cc];
            tt[r] = fmaf(p[i], mu[cc], tt[r]);
          }
          stsm4(sw[j & 3] + (j >> 2) * 16384 + m * 8192, pack(p[0], p[1]), pack(p[2], p[3]), pack(p[4], p[5]), pack(p[6], p[7]));
        }
        const bool u2 = lane & 2, u1 = lane & 1;
        const float v = xred(xred(z[0], tt[0], u2, 2), xred(z[1], tt[1], u2, 2), u1, 1);
        if (u2) sts32(ca + (t4 & 1) * 32, __float_as_uint(v));
        else st_relaxed(g_z + tm * 1024 + tn * 128 + m * 64 + w * 16 + t4 * 8 + g, tagf(v * LOG2E, par));
        if (m) break;
      }
      fence_async_smem();
      nb_arrive(NB_PK, 256);
      nb_arrive(NB_Z, 160);
    }
    STAMP_IF(leader, 35);
    const uint32_t ep = lds32(S_EPOCH);
    {
      nb_sync(NB_CSQ, 160);
      float mu[4];
#pragma unroll
      for (int i = 0; i < 4; i++) {
        const float2 st = lds64f(S_KSTAT + ((i >> 1) * 64 + w * 16 + (i & 1) * 8 + g) * 8);
        mu[i] = -st.x;
      }
#pragma unroll
      for (int j = 0; j < 16; j++) {
        const float2 c = lds64f(S_CSQ + (j * 8 + 2 * t4) * 4);
        a0[4 * j] = mu[0] * c.x; a0[4 * j + 1] = mu[0] * c.y; a0[4 * j + 2] = mu[1] * c.x; a0[4 * j + 3] = mu[1] * c.y;
        a1[4 * j] = mu[2] * c.x; a1[4 * j + 1] = mu[2] * c.y; a1[4 * j + 2] = mu[3] * c.x; a1[4 * j + 3] = mu[3] * c.y;
      }
      reg_fence(a0); reg_fence(a1);
    }
    STAMP_IF(leader, 40);
    nb_sync(NB_VQ, 256);
    mainloop<false, 13>(a0, a1, 2, 0, 0, 4 + (tn & 3), leader);
    {
      uint32_t f[2][16];
      const uint32_t ra = S_KSTAT + (w * 16 + g) * 8 + 4;
      auto phi = [&](const float (&a)[64], int off, int m, int i0, int i1, uint32_t (&o)[16]) {
        const float r0 = lds32v(ra + m * 512), r1 = lds32v(ra + m * 512 + 64);
#pragma unroll
        for (int i = i0; i < i1; i++) o[i] = pack(phi2(a[off + 2 * i] * (i & 1 ? r1 : r0)), phi2(a[off + 2 * i + 1] * (i & 1 ? r1 : r0)));
      };
      auto half = [&](float (&a)[64], int s, int m) {
        const bool xr = ((13 + s) >> 1) == 4 + (tn & 3);
        if (!m) {
          mbar_wait(B_FULL + 8 * s, 1);
          if (xr) mbar_wait(B_XRES + 8 * (~s & 1), 0);
          wg_fence();
        }
        const uint64_t dx = mkdesc(m * 8192, 16, 1024, 1) + ((xr ? STG + (~s & 1) * 16384 : RING + s * SLOT + 16384) >> 4);
#pragma unroll
        for (int j = 0; j < 4; j++) wgmma_n128_ss<0, 1>(a, dx + j * 2, mkdesc(RING + s * SLOT + j * 2048, 8192, 1024, 1), 1);
      };
      half(a0, 0, 0);
      wg_commit();
      half(a0, 1, 0);
      wg_commit();
      wg_wait<2>();
      if (leader) mbar_arrive(B_EMPTY + 32);
      half(a0, 2, 0);
      wg_commit();
      wg_fence();
      half(a1, 0, 1);
      half(a1, 1, 1);
      wg_commit();
      wg_wait<1>();
      reg_fence(a0);
      phi(a0, 0, 0, 0, PHI_CUT, f[0]);
      wg_fence();
      half(a1, 2, 1);
      wg_commit();
      phi(a0, 0, 0, PHI_CUT, 16, f[0]);
      nb_sync(NB_KVB, 320);
      wg_wait<0>();
      if (leader) { mbar_arrive(B_EMPTY); mbar_arrive(B_EMPTY + 8); mbar_arrive(B_EMPTY + 16); }
      reg_fence(a1);
      STAMP_IF(leader, 36);
      const uint32_t mk[4] = {t4 == 0, t4 == 1, t4 == 2, t4 == 3};
      uint64_t db = mkdesc(KVB, 16, 1024, 1);
      uint32_t so = 0;
#pragma unroll 1
      for (int j = 0;; j++) {
        float oc[2][2][20];
        auto mma = [&](const uint32_t (&a)[16], float (&o)[2][20]) {
          reg_zero(o[0]); reg_zero(o[1]);
          wg_fence();
          wgmma_n40_rs<0>(o[0], a[0], a[1], a[2], a[3], db, 0);
          wgmma_n40_rs<0>(o[1], a[8], a[9], a[10], a[11], db + 4, 0);
          wgmma_n40_rs<0>(o[0], a[4], a[5], a[6], a[7], db + 2, 1);
          wgmma_n40_rs<0>(o[1], a[12], a[13], a[14], a[15], db + 6, 1);
          wg_commit();
        };
        auto fin = [&](int m, float (&o)[2][20]) {
          const uint32_t m0 = mk[2 * m], m1 = mk[2 * m + 1];
#pragma unroll
          for (int h = 0; h < 2; h++) {
            const float r0 = rcp(o[h][0] + 1e-6f * LOG2E), r1 = rcp(o[h][2] + 1e-6f * LOG2E);
#pragma unroll
            for (int q = 0; q < 2; q++)
              stsm4(sw[h * 2 + q] + so + m * 8192,
                    bsel(pack(o[h][4 + 8 * q] * r0, o[h][5 + 8 * q] * r0), ep, m0), bsel(pack(o[h][6 + 8 * q] * r1, o[h][7 + 8 * q] * r1), ep, m1),
                    bsel(pack(o[h][8 + 8 * q] * r0, o[h][9 + 8 * q] * r0), ep, m0), bsel(pack(o[h][10 + 8 * q] * r1, o[h][11 + 8 * q] * r1), ep, m1));
          }
        };
        mma(f[0], oc[0]);
        phi(a1, 0, 1, 0, 16, f[1]);
        wg_wait<0>();
        reg_fence(oc[0][0]); reg_fence(oc[0][1]);
        mma(f[1], oc[1]);
        fin(0, oc[0]);
        if (j == 0) { fence_async_smem(); nb_arrive(NB_Q0, 192); }
        wg_wait<0>();
        reg_fence(oc[1][0]); reg_fence(oc[1][1]);
        fin(1, oc[1]);
        fence_async_smem();
        if (j) break;
        nb_arrive(NB_OWN0, 288);
        STAMP_IF(leader, 38);
#pragma unroll
        for (int i = 0; i < 32; i++) a1[i] = a1[32 + i];
        phi(a0, 32, 0, 0, 16, f[0]);
        db = mkdesc(KVB + 5120, 16, 1024, 1);
        so = 16384;
      }
      nb_arrive(NB_OWN1, 256);
      nb_arrive(NB_H1, 160);
      STAMP_IF(leader, 39);
    }
  }
}

#undef CK
typedef CUresult (*EncodeFn)(CUtensorMap*, CUtensorMapDataType, cuuint32_t, void*, const cuuint64_t*, const cuuint64_t*, const cuuint32_t*,
                             const cuuint32_t*, CUtensorMapInterleave, CUtensorMapSwizzle, CUtensorMapL2promotion, CUtensorMapFloatOOBfill);

void make_map(EncodeFn enc, CUtensorMap* m, const void* p, int rank, uint64_t d0, uint64_t d1, uint64_t d2, uint64_t s1, uint64_t s2,
              uint32_t b0, uint32_t b1, uint32_t b2, CUtensorMapSwizzle sw) {
  cuuint64_t gd[3] = {d0, d1, d2}, gs[2] = {s1, s2};
  cuuint32_t bd[3] = {b0, b1, b2}, es[3] = {1, 1, 1};
  enc(m, CU_TENSOR_MAP_DATA_TYPE_BFLOAT16, rank, const_cast<void*>(p), gd, gs, bd, es, CU_TENSOR_MAP_INTERLEAVE_NONE, sw,
      CU_TENSOR_MAP_L2_PROMOTION_L2_128B, CU_TENSOR_MAP_FLOAT_OOB_FILL_NONE);
}

}

extern "C" void kernel_launch(void* const* d_in, const int* in_sizes, int n_in, void* d_out, int out_size) {
  (void)in_sizes; (void)n_in; (void)out_size;
  void* fn = nullptr;
  cudaDriverEntryPointQueryResult qr;
  cudaGetDriverEntryPoint("cuTensorMapEncodeTiled", &fn, cudaEnableDefault, &qr);
  EncodeFn enc = (EncodeFn)fn;
  void* o;
  cudaGetSymbolAddress(&o, g_o);
  const CUtensorMapSwizzle S128 = CU_TENSOR_MAP_SWIZZLE_128B, S64 = CU_TENSOR_MAP_SWIZZLE_64B, S0 = CU_TENSOR_MAP_SWIZZLE_NONE;
  Params mp;
  mp.x = (const char*)d_in[0]; mp.wqkv = (const char*)d_in[1]; mp.w_r = (const char*)d_in[4];
  mp.wg = (const char*)d_in[5]; mp.wu = (const char*)d_in[6]; mp.wd = (const char*)d_in[7]; mp.wo = (const char*)d_in[2];
  make_map(enc, &mp.m_wqkv, d_in[1], 3, 64, 1024, 48, 6144, 128, 64, 64, 2, S128);
  make_map(enc, &mp.m_x, d_in[0], 2, 1024, 2048, 1, 2048, 0, 64, 128, 1, S128);
  make_map(enc, &mp.m_os, o, 2, 1024, 2048, 1, 2048, 0, 64, 64, 1, S128);
  make_map(enc, &mp.m_o, o, 2, 1024, 2048, 1, 2048, 0, 64, 128, 1, S128);
  make_map(enc, &mp.m_wo, d_in[2], 3, 64, 1024, 16, 2048, 128, 64, 64, 2, S128);
  make_map(enc, &mp.m_xs, d_in[0], 2, 1024, 2048, 1, 2048, 0, 256, 16, 1, S0);
  const char *wg = (const char*)d_in[5], *wu = (const char*)d_in[6];
  make_map(enc, &mp.m_gu, wu < wg ? wu : wg, 3, 3584, 1024, 2, 7168, (uint64_t)(wu < wg ? wg - wu : wu - wg), 32, 64, 2, S64);
  make_map(enc, &mp.m_down, d_in[7], 2, 1024, 3584, 1, 2048, 0, 64, 64, 1, S128);
  make_map(enc, &mp.m_out, d_out, 2, 1024, 2048, 1, 2048, 0, 64, 16, 1, S128);
  int dev = 0, sms = 0;
  cudaGetDevice(&dev);
  cudaDeviceGetAttribute(&sms, cudaDevAttrMultiProcessorCount, dev);
  auto kern = sms == 132 ? fused_kernel<true> : fused_kernel<false>;
  cudaFuncSetAttribute(kern, cudaFuncAttributeMaxDynamicSharedMemorySize, SMEM_BYTES);
  kern<<<132, 512, SMEM_BYTES>>>(mp);
}
```

```cpp
#include <cuda_runtime.h>
#include <cuda.h>
#include <cuda_bf16.h>
#include <stdint.h>

namespace {

template <int TA, int TB>
__device__ __forceinline__ void wgmma_n8_ss(float (&d)[4], uint64_t da, uint64_t db, int sc) {
  asm volatile("{\n.reg .pred p;\nsetp.ne.b32 p, %6, 0;\n"
    "wgmma.mma_async.sync.aligned.m64n8k16.f32.bf16.bf16 {%0, %1, %2, %3}, %4, %5, p, 1, 1, %7, %8;\n}\n"
    : "+f"(d[0]), "+f"(d[1]), "+f"(d[2]), "+f"(d[3])
    : "l"(da), "l"(db), "r"(sc), "n"(TA), "n"(TB));
}
template <int TA, int TB>
__device__ __forceinline__ void wgmma_n16_ss(float (&d)[8], uint64_t da, uint64_t db, int sc) {
  asm volatile("{\n.reg .pred p;\nsetp.ne.b32 p, %10, 0;\n"
    "wgmma.mma_async.sync.aligned.m64n16k16.f32.bf16.bf16 {%0, %1, %2, %3, %4, %5, %6, %7}, %8, %9, p, 1, 1, %11, %12;\n}\n"
    : "+f"(d[0]), "+f"(d[1]), "+f"(d[2]), "+f"(d[3]), "+f"(d[4]), "+f"(d[5]), "+f"(d[6]), "+f"(d[7])
    : "l"(da), "l"(db), "r"(sc), "n"(TA), "n"(TB));
}
template <int TB>
__device__ __forceinline__ void wgmma_n40_rs(float (&d)[20], uint32_t a0, uint32_t a1, uint32_t a2, uint32_t a3, uint64_t db, int sc) {
  asm volatile("{\n.reg .pred p;\nsetp.ne.b32 p, %25, 0;\n"
    "wgmma.mma_async.sync.aligned.m64n40k16.f32.bf16.bf16 {%0, %1, %2, %3, %4, %5, %6, %7, %8, %9, %10, %11, %12, %13, %14, %15, %16, %17, %18, %19}, {%20,%21,%22,%23}, %24, p, 1, 1, %26;\n}\n"
    : "+f"(d[0]), "+f"(d[1]), "+f"(d[2]), "+f"(d[3]), "+f"(d[4]), "+f"(d[5]), "+f"(d[6]), "+f"(d[7]),
      "+f"(d[8]), "+f"(d[9]), "+f"(d[10]), "+f"(d[11]), "+f"(d[12]), "+f"(d[13]), "+f"(d[14]), "+f"(d[15]),
      "+f"(d[16]), "+f"(d[17]), "+f"(d[18]), "+f"(d[19])
    : "r"(a0), "r"(a1), "r"(a2), "r"(a3), "l"(db), "r"(sc), "n"(TB));
}
template <int TB>
__device__ __forceinline__ void wgmma_n64_rs(float (&d)[32], uint32_t a0, uint32_t a1, uint32_t a2, uint32_t a3, uint64_t db, int sc) {
  asm volatile("{\n.reg .pred p;\nsetp.ne.b32 p, %37, 0;\n"
    "wgmma.mma_async.sync.aligned.m64n64k16.f32.bf16.bf16 {%0, %1, %2, %3, %4, %5, %6, %7, %8, %9, %10, %11, %12, %13, %14, %15, %16, %17, %18, %19, %20, %21, %22, %23, %24, %25, %26, %27, %28, %29, %30, %31}, {%32,%33,%34,%35}, %36, p, 1, 1, %38;\n}\n"
    : "+f"(d[0]), "+f"(d[1]), "+f"(d[2]), "+f"(d[3]), "+f"(d[4]), "+f"(d[5]), "+f"(d[6]), "+f"(d[7]),
      "+f"(d[8]), "+f"(d[9]), "+f"(d[10]), "+f"(d[11]), "+f"(d[12]), "+f"(d[13]), "+f"(d[14]), "+f"(d[15]),
      "+f"(d[16]), "+f"(d[17]), "+f"(d[18]), "+f"(d[19]), "+f"(d[20]), "+f"(d[21]), "+f"(d[22]), "+f"(d[23]),
      "+f"(d[24]), "+f"(d[25]), "+f"(d[26]), "+f"(d[27]), "+f"(d[28]), "+f"(d[29]), "+f"(d[30]), "+f"(d[31])
    : "r"(a0), "r"(a1), "r"(a2), "r"(a3), "l"(db), "r"(sc), "n"(TB));
}
template <int TA, int TB>
__device__ __forceinline__ void wgmma_n128_ss(float (&d)[64], uint64_t da, uint64_t db, int sc) {
  asm volatile("{\n.reg .pred p;\nsetp.ne.b32 p, %66, 0;\n"
    "wgmma.mma_async.sync.aligned.m64n128k16.f32.bf16.bf16 {%0, %1, %2, %3, %4, %5, %6, %7, %8, %9, %10, %11, %12, %13, %14, %15, %16, %17, %18, %19, %20, %21, %22, %23, %24, %25, %26, %27, %28, %29, %30, %31, %32, %33, %34, %35, %36, %37, %38, %39, %40, %41, %42, %43, %44, %45, %46, %47, %48, %49, %50, %51, %52, %53, %54, %55, %56, %57, %58, %59, %60, %61, %62, %63}, %64, %65, p, 1, 1, %67, %68;\n}\n"
    : "+f"(d[0]), "+f"(d[1]), "+f"(d[2]), "+f"(d[3]), "+f"(d[4]), "+f"(d[5]), "+f"(d[6]), "+f"(d[7]),
      "+f"(d[8]), "+f"(d[9]), "+f"(d[10]), "+f"(d[11]), "+f"(d[12]), "+f"(d[13]), "+f"(d[14]), "+f"(d[15]),
      "+f"(d[16]), "+f"(d[17]), "+f"(d[18]), "+f"(d[19]), "+f"(d[20]), "+f"(d[21]), "+f"(d[22]), "+f"(d[23]),
      "+f"(d[24]), "+f"(d[25]), "+f"(d[26]), "+f"(d[27]), "+f"(d[28]), "+f"(d[29]), "+f"(d[30]), "+f"(d[31]),
      "+f"(d[32]), "+f"(d[33]), "+f"(d[34]), "+f"(d[35]), "+f"(d[36]), "+f"(d[37]), "+f"(d[38]), "+f"(d[39]),
      "+f"(d[40]), "+f"(d[41]), "+f"(d[42]), "+f"(d[43]), "+f"(d[44]), "+f"(d[45]), "+f"(d[46]), "+f"(d[47]),
      "+f"(d[48]), "+f"(d[49]), "+f"(d[50]), "+f"(d[51]), "+f"(d[52]), "+f"(d[53]), "+f"(d[54]), "+f"(d[55]),
      "+f"(d[56]), "+f"(d[57]), "+f"(d[58]), "+f"(d[59]), "+f"(d[60]), "+f"(d[61]), "+f"(d[62]), "+f"(d[63])
    : "l"(da), "l"(db), "r"(sc), "n"(TA), "n"(TB));
}
template <int TB>
__device__ __forceinline__ void wgmma_n128_rs(float (&d)[64], uint32_t a0, uint32_t a1, uint32_t a2, uint32_t a3, uint64_t db, int sc) {
  asm volatile("{\n.reg .pred p;\nsetp.ne.b32 p, %69, 0;\n"
    "wgmma.mma_async.sync.aligned.m64n128k16.f32.bf16.bf16 {%0, %1, %2, %3, %4, %5, %6, %7, %8, %9, %10, %11, %12, %13, %14, %15, %16, %17, %18, %19, %20, %21, %22, %23, %24, %25, %26, %27, %28, %29, %30, %31, %32, %33, %34, %35, %36, %37, %38, %39, %40, %41, %42, %43, %44, %45, %46, %47, %48, %49, %50, %51, %52, %53, %54, %55, %56, %57, %58, %59, %60, %61, %62, %63}, {%64,%65,%66,%67}, %68, p, 1, 1, %70;\n}\n"
    : "+f"(d[0]), "+f"(d[1]), "+f"(d[2]), "+f"(d[3]), "+f"(d[4]), "+f"(d[5]), "+f"(d[6]), "+f"(d[7]),
      "+f"(d[8]), "+f"(d[9]), "+f"(d[10]), "+f"(d[11]), "+f"(d[12]), "+f"(d[13]), "+f"(d[14]), "+f"(d[15]),
      "+f"(d[16]), "+f"(d[17]), "+f"(d[18]), "+f"(d[19]), "+f"(d[20]), "+f"(d[21]), "+f"(d[22]), "+f"(d[23]),
      "+f"(d[24]), "+f"(d[25]), "+f"(d[26]), "+f"(d[27]), "+f"(d[28]), "+f"(d[29]), "+f"(d[30]), "+f"(d[31]),
      "+f"(d[32]), "+f"(d[33]), "+f"(d[34]), "+f"(d[35]), "+f"(d[36]), "+f"(d[37]), "+f"(d[38]), "+f"(d[39]),
      "+f"(d[40]), "+f"(d[41]), "+f"(d[42]), "+f"(d[43]), "+f"(d[44]), "+f"(d[45]), "+f"(d[46]), "+f"(d[47]),
      "+f"(d[48]), "+f"(d[49]), "+f"(d[50]), "+f"(d[51]), "+f"(d[52]), "+f"(d[53]), "+f"(d[54]), "+f"(d[55]),
      "+f"(d[56]), "+f"(d[57]), "+f"(d[58]), "+f"(d[59]), "+f"(d[60]), "+f"(d[61]), "+f"(d[62]), "+f"(d[63])
    : "r"(a0), "r"(a1), "r"(a2), "r"(a3), "l"(db), "r"(sc), "n"(TB));
}

__device__ __forceinline__ void poll1f(uint32_t (&v)[1], const void* p, uint32_t tag, uint32_t mask) {
  asm volatile("{\n.reg .pred p, q;\n.reg .u32 c, b;\n.reg .b64 x, y;\n.reg .b128 z;\nmov.u32 c, 0;\nLW:\n"
               "ld.relaxed.gpu.global.u32 %0, [%1+0];\n"
               "xor.b32 b, %0, %2;\n"
               "and.b32 b, b, %3;\nsetp.eq.u32 p, b, 0;\nvote.sync.all.pred p, p, 0xffffffff;\n@p bra.uni LD;\n"
               "nanosleep.u32 50;\nadd.u32 c, c, 1;\nsetp.lt.u32 q, c, 1000000;\n@q bra.uni LW;\ntrap;\nLD:\n}"
               : "=&r"(v[0])
               : "l"(p), "r"(tag), "r"(mask) : "memory");
}
__device__ __forceinline__ void poll0(uint32_t (&v)[1], const void* p, uint32_t tag, uint32_t mask) {
  asm volatile("{\n.reg .pred p, q;\n.reg .u32 c, b;\n.reg .b64 x, y;\n.reg .b128 z;\nmov.u32 c, 0;\nLW:\n"
               "ld.relaxed.gpu.global.u32 %0, [%1+0];\n"
               "xor.b32 b, %0, %2;\n"
               "and.b32 b, b, %3;\nsetp.eq.u32 p, b, 0;\nvote.sync.all.pred p, p, 0xffffffff;\n@p bra.uni LD;\n"
               "add.u32 c, c, 1;\nsetp.lt.u32 q, c, 1000000;\n@q bra.uni LW;\ntrap;\nLD:\n}"
               : "=&r"(v[0])
               : "l"(p), "r"(tag), "r"(mask) : "memory");
}
__device__ __forceinline__ void poll_pair(uint32_t (&v)[2], const void* p, uint32_t tag, uint32_t mask) {
  asm volatile("{\n.reg .pred p, q;\n.reg .u32 c, b;\n.reg .b64 x, y;\n.reg .b128 z;\nmov.u32 c, 0;\nLW:\n"
               "ld.relaxed.gpu.global.b64 x, [%2+0];\nmov.b64 {%0,%1}, x;\n"
               "xor.b32 b, %0, %3;\n"
               "and.b32 b, b, %4;\nsetp.eq.u32 p, b, 0;\nvote.sync.all.pred p, p, 0xffffffff;\n@p bra.uni LD;\n"
               "nanosleep.u32 100;\nadd.u32 c, c, 1;\nsetp.lt.u32 q, c, 1000000;\n@q bra.uni LW;\ntrap;\nLD:\n}"
               : "=&r"(v[0]), "=&r"(v[1])
               : "l"(p), "r"(tag), "r"(mask) : "memory");
}
__device__ __forceinline__ void poll_quad(uint32_t (&v)[4], const void* p, uint32_t tag, uint32_t mask) {
  asm volatile("{\n.reg .pred p, q;\n.reg .u32 c, b;\n.reg .b64 x, y;\n.reg .b128 z;\nmov.u32 c, 0;\nLW:\n"
               "ld.relaxed.gpu.global.v4.u32 {%0,%1,%2,%3}, [%4+0];\n"
               "xor.b32 b, %0, %5;\n"
               "lop3.b32 b, b, %1, %5, 0xf6;\nlop3.b32 b, b, %2, %5, 0xf6;\nlop3.b32 b, b, %3, %5, 0xf6;\n"
               "and.b32 b, b, %6;\nsetp.eq.u32 p, b, 0;\nvote.sync.all.pred p, p, 0xffffffff;\n@p bra.uni LD;\n"
               "nanosleep.u32 200;\nadd.u32 c, c, 1;\nsetp.lt.u32 q, c, 1000000;\n@q bra.uni LW;\ntrap;\nLD:\n}"
               : "=&r"(v[0]), "=&r"(v[1]), "=&r"(v[2]), "=&r"(v[3])
               : "l"(p), "r"(tag), "r"(mask) : "memory");
}
__device__ __forceinline__ void poll8x4(uint32_t (&v)[32], const void* p, uint32_t tag, uint32_t mask) {
  asm volatile("{\n.reg .pred p, q;\n.reg .u32 c, b;\n.reg .b64 x, y;\n.reg .b128 z;\nmov.u32 c, 0;\nLW:\n"
               "ld.relaxed.gpu.global.v4.u32 {%0,%1,%2,%3}, [%32+0];\n"
               "ld.relaxed.gpu.global.v4.u32 {%4,%5,%6,%7}, [%32+2048];\n"
               "ld.relaxed.gpu.global.v4.u32 {%8,%9,%10,%11}, [%32+4096];\n"
               "ld.relaxed.gpu.global.v4.u32 {%12,%13,%14,%15}, [%32+6144];\n"
               "ld.relaxed.gpu.global.v4.u32 {%16,%17,%18,%19}, [%32+8192];\n"
               "ld.relaxed.gpu.global.v4.u32 {%20,%21,%22,%23}, [%32+10240];\n"
               "ld.relaxed.gpu.global.v4.u32 {%24,%25,%26,%27}, [%32+12288];\n"
               "ld.relaxed.gpu.global.v4.u32 {%28,%29,%30,%31}, [%32+14336];\n"
               "xor.b32 b, %0, %33;\n"
               "lop3.b32 b, b, %1, %33, 0xf6;\nlop3.b32 b, b, %2, %33, 0xf6;\nlop3.b32 b, b, %3, %33, 0xf6;\nlop3.b32 b, b, %4, %33, 0xf6;\n"
               "lop3.b32 b, b, %5, %33, 0xf6;\nlop3.b32 b, b, %6, %33, 0xf6;\nlop3.b32 b, b, %7, %33, 0xf6;\nlop3.b32 b, b, %8, %33, 0xf6;\n"
               "lop3.b32 b, b, %9, %33, 0xf6;\nlop3.b32 b, b, %10, %33, 0xf6;\nlop3.b32 b, b, %11, %33, 0xf6;\nlop3.b32 b, b, %12, %33, 0xf6;\n"
               "lop3.b32 b, b, %13, %33, 0xf6;\nlop3.b32 b, b, %14, %33, 0xf6;\nlop3.b32 b, b, %15, %33, 0xf6;\nlop3.b32 b, b, %16, %33, 0xf6;\n"
               "lop3.b32 b, b, %17, %33, 0xf6;\nlop3.b32 b, b, %18, %33, 0xf6;\nlop3.b32 b, b, %19, %33, 0xf6;\nlop3.b32 b, b, %20, %33, 0xf6;\n"
               "lop3.b32 b, b, %21, %33, 0xf6;\nlop3.b32 b, b, %22, %33, 0xf6;\nlop3.b32 b, b, %23, %33, 0xf6;\nlop3.b32 b, b, %24, %33, 0xf6;\n"
               "lop3.b32 b, b, %25, %33, 0xf6;\nlop3.b32 b, b, %26, %33, 0xf6;\nlop3.b32 b, b, %27, %33, 0xf6;\nlop3.b32 b, b, %28, %33, 0xf6;\n"
               "lop3.b32 b, b, %29, %33, 0xf6;\nlop3.b32 b, b, %30, %33, 0xf6;\nlop3.b32 b, b, %31, %33, 0xf6;\n"
               "and.b32 b, b, %34;\nsetp.eq.u32 p, b, 0;\nvote.sync.all.pred p, p, 0xffffffff;\n@p bra.uni LD;\n"
               "nanosleep.u32 50;\nadd.u32 c, c, 1;\nsetp.lt.u32 q, c, 1000000;\n@q bra.uni LW;\ntrap;\nLD:\n}"
               : "=&r"(v[0]), "=&r"(v[1]), "=&r"(v[2]), "=&r"(v[3]), "=&r"(v[4]), "=&r"(v[5]), "=&r"(v[6]), "=&r"(v[7]), "=&r"(v[8]), "=&r"(v[9]), "=&r"(v[10]), "=&r"(v[11]), "=&r"(v[12]), "=&r"(v[13]), "=&r"(v[14]), "=&r"(v[15]), "=&r"(v[16]), "=&r"(v[17]), "=&r"(v[18]), "=&r"(v[19]), "=&r"(v[20]), "=&r"(v[21]), "=&r"(v[22]), "=&r"(v[23]), "=&r"(v[24]), "=&r"(v[25]), "=&r"(v[26]), "=&r"(v[27]), "=&r"(v[28]), "=&r"(v[29]), "=&r"(v[30]), "=&r"(v[31])
               : "l"(p), "r"(tag), "r"(mask) : "memory");
}
__device__ __forceinline__ void poll16(uint32_t (&v)[16], const void* p, uint32_t tag, uint32_t mask) {
  asm volatile("{\n.reg .pred p, q;\n.reg .u32 c, b;\n.reg .b64 x, y;\n.reg .b128 z;\nmov.u32 c, 0;\nLW:\n"
               "ld.relaxed.gpu.global.u32 %0, [%16+0];\n"
               "ld.relaxed.gpu.global.u32 %1, [%16+4096];\n"
               "ld.relaxed.gpu.global.u32 %2, [%16+8192];\n"
               "ld.relaxed.gpu.global.u32 %3, [%16+12288];\n"
               "ld.relaxed.gpu.global.u32 %4, [%16+16384];\n"
               "ld.relaxed.gpu.global.u32 %5, [%16+20480];\n"
               "ld.relaxed.gpu.global.u32 %6, [%16+24576];\n"
               "ld.relaxed.gpu.global.u32 %7, [%16+28672];\n"
               "ld.relaxed.gpu.global.u32 %8, [%16+32768];\n"
               "ld.relaxed.gpu.global.u32 %9, [%16+36864];\n"
               "ld.relaxed.gpu.global.u32 %10, [%16+40960];\n"
               "ld.relaxed.gpu.global.u32 %11, [%16+45056];\n"
               "ld.relaxed.gpu.global.u32 %12, [%16+49152];\n"
               "ld.relaxed.gpu.global.u32 %13, [%16+53248];\n"
               "ld.relaxed.gpu.global.u32 %14, [%16+57344];\n"
               "ld.relaxed.gpu.global.u32 %15, [%16+61440];\n"
               "xor.b32 b, %0, %17;\n"
               "lop3.b32 b, b, %1, %17, 0xf6;\nlop3.b32 b, b, %2, %17, 0xf6;\nlop3.b32 b, b, %3, %17, 0xf6;\nlop3.b32 b, b, %4, %17, 0xf6;\n"
               "lop3.b32 b, b, %5, %17, 0xf6;\nlop3.b32 b, b, %6, %17, 0xf6;\nlop3.b32 b, b, %7, %17, 0xf6;\nlop3.b32 b, b, %8, %17, 0xf6;\n"
               "lop3.b32 b, b, %9, %17, 0xf6;\nlop3.b32 b, b, %10, %17, 0xf6;\nlop3.b32 b, b, %11, %17, 0xf6;\nlop3.b32 b, b, %12, %17, 0xf6;\n"
               "lop3.b32 b, b, %13, %17, 0xf6;\nlop3.b32 b, b, %14, %17, 0xf6;\nlop3.b32 b, b, %15, %17, 0xf6;\n"
               "and.b32 b, b, %18;\nsetp.eq.u32 p, b, 0;\nvote.sync.all.pred p, p, 0xffffffff;\n@p bra.uni LD;\n"
               "nanosleep.u32 200;\nadd.u32 c, c, 1;\nsetp.lt.u32 q, c, 1000000;\n@q bra.uni LW;\ntrap;\nLD:\n}"
               : "=&r"(v[0]), "=&r"(v[1]), "=&r"(v[2]), "=&r"(v[3]), "=&r"(v[4]), "=&r"(v[5]), "=&r"(v[6]), "=&r"(v[7]), "=&r"(v[8]), "=&r"(v[9]), "=&r"(v[10]), "=&r"(v[11]), "=&r"(v[12]), "=&r"(v[13]), "=&r"(v[14]), "=&r"(v[15])
               : "l"(p), "r"(tag), "r"(mask) : "memory");
}
__device__ __forceinline__ void poll_keys(uint32_t (&v)[16], const void* p, uint32_t tag, uint32_t mask) {
  asm volatile("{\n.reg .pred p, q;\n.reg .u32 c, b;\n.reg .b64 x, y;\n.reg .b128 z;\nmov.u32 c, 0;\nLW:\n"
               "ld.relaxed.gpu.global.v2.b64 {x, y}, [%16+0];\nmov.b64 {%0,%1}, x;\nmov.b64 {%2,%3}, y;\n"
               "ld.relaxed.gpu.global.v2.b64 {x, y}, [%16+4096];\nmov.b64 {%4,%5}, x;\nmov.b64 {%6,%7}, y;\n"
               "ld.relaxed.gpu.global.v2.b64 {x, y}, [%16+8192];\nmov.b64 {%8,%9}, x;\nmov.b64 {%10,%11}, y;\n"
               "ld.relaxed.gpu.global.v2.b64 {x, y}, [%16+12288];\nmov.b64 {%12,%13}, x;\nmov.b64 {%14,%15}, y;\n"
               "xor.b32 b, %0, %17;\n"
               "lop3.b32 b, b, %2, %17, 0xf6;\nlop3.b32 b, b, %4, %17, 0xf6;\nlop3.b32 b, b, %6, %17, 0xf6;\nlop3.b32 b, b, %8, %17, 0xf6;\n"
               "lop3.b32 b, b, %10, %17, 0xf6;\nlop3.b32 b, b, %12, %17, 0xf6;\nlop3.b32 b, b, %14, %17, 0xf6;\n"
               "and.b32 b, b, %18;\nsetp.eq.u32 p, b, 0;\nvote.sync.all.pred p, p, 0xffffffff;\n@p bra.uni LD;\n"
               "nanosleep.u32 20;\nadd.u32 c, c, 1;\nsetp.lt.u32 q, c, 1000000;\n@q bra.uni LW;\ntrap;\nLD:\n}"
               : "=&r"(v[0]), "=&r"(v[1]), "=&r"(v[2]), "=&r"(v[3]), "=&r"(v[4]), "=&r"(v[5]), "=&r"(v[6]), "=&r"(v[7]), "=&r"(v[8]), "=&r"(v[9]), "=&r"(v[10]), "=&r"(v[11]), "=&r"(v[12]), "=&r"(v[13]), "=&r"(v[14]), "=&r"(v[15])
               : "l"(p), "r"(tag), "r"(mask) : "memory");
}
__device__ __forceinline__ void poll_z(uint32_t (&v)[16], const void* p, uint32_t tag, uint32_t mask) {
  asm volatile("{\n.reg .pred p, q;\n.reg .u32 c, b;\n.reg .b64 x, y;\n.reg .b128 z;\nmov.u32 c, 0;\nLW:\n"
               "ld.relaxed.gpu.global.v4.u32 {%0,%1,%2,%3}, [%16+0];\n"
               "ld.relaxed.gpu.global.v4.u32 {%4,%5,%6,%7}, [%16+4096];\n"
               "ld.relaxed.gpu.global.v4.u32 {%8,%9,%10,%11}, [%16+8192];\n"
               "ld.relaxed.gpu.global.v4.u32 {%12,%13,%14,%15}, [%16+12288];\n"
               "xor.b32 b, %0, %17;\n"
               "lop3.b32 b, b, %1, %17, 0xf6;\nlop3.b32 b, b, %2, %17, 0xf6;\nlop3.b32 b, b, %3, %17, 0xf6;\nlop3.b32 b, b, %4, %17, 0xf6;\n"
               "lop3.b32 b, b, %5, %17, 0xf6;\nlop3.b32 b, b, %6, %17, 0xf6;\nlop3.b32 b, b, %7, %17, 0xf6;\nlop3.b32 b, b, %8, %17, 0xf6;\n"
               "lop3.b32 b, b, %9, %17, 0xf6;\nlop3.b32 b, b, %10, %17, 0xf6;\nlop3.b32 b, b, %11, %17, 0xf6;\nlop3.b32 b, b, %12, %17, 0xf6;\n"
               "lop3.b32 b, b, %13, %17, 0xf6;\nlop3.b32 b, b, %14, %17, 0xf6;\nlop3.b32 b, b, %15, %17, 0xf6;\n"
               "and.b32 b, b, %18;\nsetp.eq.u32 p, b, 0;\nvote.sync.all.pred p, p, 0xffffffff;\n@p bra.uni LD;\n"
               "nanosleep.u32 300;\nadd.u32 c, c, 1;\nsetp.lt.u32 q, c, 1000000;\n@q bra.uni LW;\ntrap;\nLD:\n}"
               : "=&r"(v[0]), "=&r"(v[1]), "=&r"(v[2]), "=&r"(v[3]), "=&r"(v[4]), "=&r"(v[5]), "=&r"(v[6]), "=&r"(v[7]), "=&r"(v[8]), "=&r"(v[9]), "=&r"(v[10]), "=&r"(v[11]), "=&r"(v[12]), "=&r"(v[13]), "=&r"(v[14]), "=&r"(v[15])
               : "l"(p), "r"(tag), "r"(mask) : "memory");
}
__device__ __forceinline__ void poll7x4(uint32_t (&v)[28], const void* p, uint32_t tag, uint32_t mask) {
  asm volatile("{\n.reg .pred p, q;\n.reg .u32 c, b;\n.reg .b64 x, y;\n.reg .b128 z;\nmov.u32 c, 0;\nLW:\n"
               "ld.relaxed.gpu.global.v4.u32 {%0,%1,%2,%3}, [%28+0];\n"
               "ld.relaxed.gpu.global.v4.u32 {%4,%5,%6,%7}, [%28+2048];\n"
               "ld.relaxed.gpu.global.v4.u32 {%8,%9,%10,%11}, [%28+4096];\n"
               "ld.relaxed.gpu.global.v4.u32 {%12,%13,%14,%15}, [%28+6144];\n"
               "ld.relaxed.gpu.global.v4.u32 {%16,%17,%18,%19}, [%28+8192];\n"
               "ld.relaxed.gpu.global.v4.u32 {%20,%21,%22,%23}, [%28+10240];\n"
               "ld.relaxed.gpu.global.v4.u32 {%24,%25,%26,%27}, [%28+12288];\n"
               "xor.b32 b, %0, %29;\n"
               "lop3.b32 b, b, %1, %29, 0xf6;\nlop3.b32 b, b, %2, %29, 0xf6;\nlop3.b32 b, b, %3, %29, 0xf6;\nlop3.b32 b, b, %4, %29, 0xf6;\n"
               "lop3.b32 b, b, %5, %29, 0xf6;\nlop3.b32 b, b, %6, %29, 0xf6;\nlop3.b32 b, b, %7, %29, 0xf6;\nlop3.b32 b, b, %8, %29, 0xf6;\n"
               "lop3.b32 b, b, %9, %29, 0xf6;\nlop3.b32 b, b, %10, %29, 0xf6;\nlop3.b32 b, b, %11, %29, 0xf6;\nlop3.b32 b, b, %12, %29, 0xf6;\n"
               "lop3.b32 b, b, %13, %29, 0xf6;\nlop3.b32 b, b, %14, %29, 0xf6;\nlop3.b32 b, b, %15, %29, 0xf6;\nlop3.b32 b, b, %16, %29, 0xf6;\n"
               "lop3.b32 b, b, %17, %29, 0xf6;\nlop3.b32 b, b, %18, %29, 0xf6;\nlop3.b32 b, b, %19, %29, 0xf6;\nlop3.b32 b, b, %20, %29, 0xf6;\n"
               "lop3.b32 b, b, %21, %29, 0xf6;\nlop3.b32 b, b, %22, %29, 0xf6;\nlop3.b32 b, b, %23, %29, 0xf6;\nlop3.b32 b, b, %24, %29, 0xf6;\n"
               "lop3.b32 b, b, %25, %29, 0xf6;\nlop3.b32 b, b, %26, %29, 0xf6;\nlop3.b32 b, b, %27, %29, 0xf6;\n"
               "and.b32 b, b, %30;\nsetp.eq.u32 p, b, 0;\nvote.sync.all.pred p, p, 0xffffffff;\n@p bra.uni LD;\n"
               "nanosleep.u32 50;\nadd.u32 c, c, 1;\nsetp.lt.u32 q, c, 1000000;\n@q bra.uni LW;\ntrap;\nLD:\n}"
               : "=&r"(v[0]), "=&r"(v[1]), "=&r"(v[2]), "=&r"(v[3]), "=&r"(v[4]), "=&r"(v[5]), "=&r"(v[6]), "=&r"(v[7]), "=&r"(v[8]), "=&r"(v[9]), "=&r"(v[10]), "=&r"(v[11]), "=&r"(v[12]), "=&r"(v[13]), "=&r"(v[14]), "=&r"(v[15]), "=&r"(v[16]), "=&r"(v[17]), "=&r"(v[18]), "=&r"(v[19]), "=&r"(v[20]), "=&r"(v[21]), "=&r"(v[22]), "=&r"(v[23]), "=&r"(v[24]), "=&r"(v[25]), "=&r"(v[26]), "=&r"(v[27])
               : "l"(p), "r"(tag), "r"(mask) : "memory");
}
__device__ __forceinline__ void poll_kvp(uint32_t (&v)[16], const void* p, uint32_t tag, uint32_t mask) {
  asm volatile("{\n.reg .pred p, q;\n.reg .u32 c, b;\n.reg .b64 x, y;\n.reg .b128 z;\nmov.u32 c, 0;\nLW:\n"
               "ld.relaxed.gpu.global.b128 z, [%16+0];\nmov.b128 {x, y}, z;\nmov.b64 {%0,%1}, x;\nmov.b64 {%2,%3}, y;\n"
               "ld.relaxed.gpu.global.b128 z, [%16+8192];\nmov.b128 {x, y}, z;\nmov.b64 {%4,%5}, x;\nmov.b64 {%6,%7}, y;\n"
               "ld.relaxed.gpu.global.b128 z, [%16+16384];\nmov.b128 {x, y}, z;\nmov.b64 {%8,%9}, x;\nmov.b64 {%10,%11}, y;\n"
               "ld.relaxed.gpu.global.b128 z, [%16+24576];\nmov.b128 {x, y}, z;\nmov.b64 {%12,%13}, x;\nmov.b64 {%14,%15}, y;\n"
               "xor.b32 b, %0, %17;\n"
               "lop3.b32 b, b, %4, %17, 0xf6;\nlop3.b32 b, b, %8, %17, 0xf6;\nlop3.b32 b, b, %12, %17, 0xf6;\n"
               "and.b32 b, b, %18;\nsetp.eq.u32 p, b, 0;\nvote.sync.all.pred p, p, 0xffffffff;\n@p bra.uni LD;\n"
               "nanosleep.u32 50;\nadd.u32 c, c, 1;\nsetp.lt.u32 q, c, 1000000;\n@q bra.uni LW;\ntrap;\nLD:\n}"
               : "=&r"(v[0]), "=&r"(v[1]), "=&r"(v[2]), "=&r"(v[3]), "=&r"(v[4]), "=&r"(v[5]), "=&r"(v[6]), "=&r"(v[7]), "=&r"(v[8]), "=&r"(v[9]), "=&r"(v[10]), "=&r"(v[11]), "=&r"(v[12]), "=&r"(v[13]), "=&r"(v[14]), "=&r"(v[15])
               : "l"(p), "r"(tag), "r"(mask) : "memory");
}

__device__ __align__(1024) __nv_bfloat16 g_o[2048 * 1024];
__device__ __align__(128) uint2 g_keys[2048];
__device__ __align__(128) uint32_t g_csum[18 * 1024];
__device__ __align__(128) uint32_t g_z[16 * 1024];
__device__ __align__(128) uint4 g_kvp[128 * 512];
__device__ __align__(128) uint4 g_kv[8 * 512];
__device__ __align__(128) uint32_t g_h[112 * 256];
__device__ __align__(128) uint32_t g_yp[128 * 512];
__device__ __align__(128) uint2 g_sel[8 * 16];
enum { H_CS = 0, H_KVP = 8, H_KV = 16, H_H = 24, H_Y = 32, H_O = 40, H_Z = 56 };
__device__ __align__(128) uint32_t g_sig[64 * 32];
__device__ uint32_t g_epoch;

constexpr uint32_t RING = 1024, SLOT = 32768, SMEM_BYTES = 232448;
constexpr int NST = 5, HST = 7;
constexpr uint32_t STG = RING + 163840, AUX = RING + 196608, FR = RING + 212992, MISC = RING + 229376;
constexpr uint32_t B_FULL = MISC, B_EMPTY = MISC + 56, B_XS = MISC + 112, B_SEL = MISC + 144, B_WK = MISC + 160, B_CSDN = MISC + 168,
                   B_FR = MISC + 176, B_FE = MISC + 200, B_DR = MISC + 224, B_CSV = MISC + 248,
                   B_DND = MISC + 256, B_XRES = MISC + 264, B_PFREE = MISC + 280, B_SFREE = MISC + 288, B_KVL = MISC + 296, NBAR = 38;
constexpr uint32_t S_EPOCH = MISC + 352, S_NCAND = MISC + 356, S_SEL = MISC + 368, S_WMAX = MISC + 432,
                   S_KSTAT = MISC + 512, S_CSK = MISC + 1536, S_CSV = MISC + 2048, S_CSQ = MISC + 2560, S_ONES = MISC + 512;
constexpr uint32_t KVB = AUX, HOP = AUX + 10240, FONES = AUX + 6144, GR = FR - 8192;
enum { NB_Z = 0, NB_KV = 1, NB_VQ = 2, NB_WG0 = 3, NB_FDONE = 4, NB_PK = 5, NB_KVB = 6, NB_WG1 = 7, NB_WG2 = 8, NB_CSQ = 9,
       NB_Y = 10, NB_ST = 11, NB_OWN0 = 12, NB_OWN1 = 13, NB_Q0 = 14, NB_H1 = 15 };

#define XS_FLY 2
#define FFN_GAP 400
#define PF_GAP 200
#define PF_WAIT 1000
#define GPCMAP 0x75143620u
#define KV_SPEC 200
#define HAND_K 5
#define PF_V 0
#define PF_O 0
#define PHI_CUT 11
#define SIG_EARLY 50
constexpr uint64_t EVICT_FIRST = 0x12f0000000000000ull;
constexpr float LOG2E = 1.4426950408889634f, LN2 = 0.6931471805599453f;

#define ELECT "{\n.reg .pred p;\nelect.sync _|p, 0xffffffff;\n"
#define TMA2D "cp.async.bulk.tensor.2d.shared::cluster.global.mbarrier::complete_tx::bytes"
#define TMA3D "cp.async.bulk.tensor.3d.shared::cluster.global.mbarrier::complete_tx::bytes"
__device__ __forceinline__ void e_expect(uint32_t b, uint32_t n) {
  asm volatile(ELECT "@p mbarrier.arrive.expect_tx.shared::cta.b64 _, [%0], %1;\n}" ::"r"(b), "r"(n) : "memory");
}
__device__ __forceinline__ void e_arrive(uint32_t b) { asm volatile(ELECT "@p mbarrier.arrive.shared::cta.b64 _, [%0];\n}" ::"r"(b) : "memory"); }
__device__ __forceinline__ void e_tma2d(uint32_t dst, const CUtensorMap* m, int c0, int c1, uint32_t bar) {
  asm volatile(ELECT "@p " TMA2D " [%0], [%1, {%3, %4}], [%2];\n}" ::"r"(dst), "l"(m), "r"(bar), "r"(c0), "r"(c1) : "memory");
}
__device__ __forceinline__ void e_tma2d_ef(uint32_t dst, const CUtensorMap* m, int c0, int c1, uint32_t bar, uint64_t pol) {
  asm volatile(ELECT "@p " TMA2D ".L2::cache_hint [%0], [%1, {%3, %4}], [%2], %5;\n}" ::"r"(dst), "l"(m), "r"(bar), "r"(c0), "r"(c1), "l"(pol) : "memory");
}
__device__ __forceinline__ void e_tma3d(uint32_t dst, const CUtensorMap* m, int c1, int c2, uint32_t bar) {
  asm volatile(ELECT "@p " TMA3D " [%0], [%1, {0, %3, %4}], [%2];\n}" ::"r"(dst), "l"(m), "r"(bar), "r"(c1), "r"(c2) : "memory");
}
__device__ __forceinline__ void e_store2d(const CUtensorMap* m, int c0, int c1, uint32_t src) {
  asm volatile(ELECT "@p cp.async.bulk.tensor.2d.global.shared::cta.bulk_group [%0, {%2, %3}], [%1];\n}" ::"l"(m), "r"(src), "r"(c0), "r"(c1) : "memory");
}
__device__ __forceinline__ void e_tma3d_ef(uint32_t dst, const CUtensorMap* m, int c0, int c1, uint32_t bar, uint64_t pol) {
  asm volatile(ELECT "@p " TMA3D ".L2::cache_hint [%0], [%1, {%3, %4, 0}], [%2], %5;\n}" ::"r"(dst), "l"(m), "r"(bar), "r"(c0), "r"(c1), "l"(pol) : "memory");
}
__device__ __forceinline__ void e_load(uint32_t dst, const void* src, uint32_t n, uint32_t bar) {
  asm volatile(ELECT "@p cp.async.bulk.shared::cluster.global.mbarrier::complete_tx::bytes [%0], [%1], %2, [%3];\n}" ::"r"(dst), "l"(src), "r"(n), "r"(bar) : "memory");
}
__device__ __forceinline__ void e_pfmap(const CUtensorMap* m) { asm volatile(ELECT "@p prefetch.tensormap [%0];\n}" ::"l"(m) : "memory"); }
__device__ __forceinline__ void bulk_wait_read() { asm volatile("cp.async.bulk.commit_group;\ncp.async.bulk.wait_group.read 0;" ::: "memory"); }
__device__ __forceinline__ void e_signal(int word, int bit) {
  asm volatile(ELECT "@p red.relaxed.gpu.global.xor.b32 [%0], %1;\n}" ::"l"(g_sig + word * 32), "r"(1u << bit) : "memory");
}
__device__ __forceinline__ void await(int word, uint32_t mask, uint32_t ep) {
  uint32_t f[1];
  poll1f(f, g_sig + word * 32, 0u - (ep & 1u), mask);
}

__device__ __forceinline__ void mbar_arrive(uint32_t b) { asm volatile("mbarrier.arrive.shared::cta.b64 _, [%0];" ::"r"(b) : "memory"); }
__device__ __forceinline__ void mbar_wait(uint32_t b, uint32_t ph) {
  asm volatile("{\n.reg .pred p, q;\n.reg .u32 c;\nmov.u32 c, 0;\nLW:\nmbarrier.try_wait.parity.shared::cta.b64 p, [%0], %1;\n@p bra LD;\n"
               "add.u32 c, c, 1;\nsetp.lt.u32 q, c, 100000;\n@q bra LW;\ntrap;\nLD:\n}" ::"r"(b), "r"(ph) : "memory");
}
#define WAIT01 "{\n.reg .pred p, q;\n.reg .u32 c;\nmov.u32 c, 0;\nLW:\nmbarrier.try_wait.parity.shared::cta.b64 p, [%0], %1;\n@p bra LD;\n" \
               "add.u32 c, c, 1;\nsetp.lt.u32 q, c, 100000;\n@q bra LW;\ntrap;\nLD:\nelect.sync _|p, 0xffffffff;\n"
__device__ __forceinline__ void refill_wx(uint32_t eb, uint32_t ph, uint32_t fb, uint32_t bytes, uint32_t dw, const CUtensorMap* mw, int k0, int c,
                                          uint32_t dx, const CUtensorMap* mx, int row, uint32_t xb) {
  asm volatile(WAIT01 "@p " TMA3D " [%4], [%5, {0, %6, %7}], [%2];\n@p " TMA2D " [%8], [%9, {%6, %10}], [%11];\n"
               "@p mbarrier.arrive.expect_tx.shared::cta.b64 _, [%2], %3;\n}"
               ::"r"(eb), "r"(ph), "r"(fb), "r"(bytes), "r"(dw), "l"(mw), "r"(k0), "r"(c), "r"(dx), "l"(mx), "r"(row), "r"(xb) : "memory");
}
__device__ __forceinline__ void refill_w(uint32_t eb, uint32_t ph, uint32_t fb, uint32_t bytes, uint32_t dw, const CUtensorMap* mw, int k0, int c) {
  asm volatile(WAIT01 "@p " TMA3D " [%4], [%5, {0, %6, %7}], [%2];\n@p mbarrier.arrive.expect_tx.shared::cta.b64 _, [%2], %3;\n}"
               ::"r"(eb), "r"(ph), "r"(fb), "r"(bytes), "r"(dw), "l"(mw), "r"(k0), "r"(c) : "memory");
}
__device__ __forceinline__ void refill_x(uint32_t eb, uint32_t ph, uint32_t fb, uint32_t dx, const CUtensorMap* mx, int k0, int row) {
  asm volatile(WAIT01 "@p " TMA2D " [%3], [%4, {%5, %6}], [%2];\n}" ::"r"(eb), "r"(ph), "r"(fb), "r"(dx), "l"(mx), "r"(k0), "r"(row) : "memory");
}
__device__ __forceinline__ void refill_g(uint32_t eb, uint32_t ph, uint32_t fb, uint32_t dw, const CUtensorMap* mw, int c0, int k0) {
  asm volatile(WAIT01 "@p " TMA3D ".L2::cache_hint [%3], [%4, {%5, %6, 0}], [%2], %7;\n@p mbarrier.arrive.expect_tx.shared::cta.b64 _, [%2], 8192;\n}"
               ::"r"(eb), "r"(ph), "r"(fb), "r"(dw), "l"(mw), "r"(c0), "r"(k0), "l"(EVICT_FIRST) : "memory");
}
__device__ __forceinline__ void nb_sync(int id, int n) { asm volatile("bar.sync %0, %1;" ::"r"(id), "r"(n) : "memory"); }
__device__ __forceinline__ void nb_arrive(int id, int n) { asm volatile("bar.arrive %0, %1;" ::"r"(id), "r"(n) : "memory"); }
__device__ __forceinline__ void wg_fence() { asm volatile("wgmma.fence.sync.aligned;" ::: "memory"); }
__device__ __forceinline__ void wg_commit() { asm volatile("wgmma.commit_group.sync.aligned;" ::: "memory"); }
template <int N> __device__ __forceinline__ void wg_wait() { asm volatile("wgmma.wait_group.sync.aligned %0;" ::"n"(N) : "memory"); }
template <int N> __device__ __forceinline__ void reg_fence(float (&a)[N]) {
#pragma unroll
  for (int i = 0; i < N; i++) asm volatile("" : "+f"(a[i])::"memory");
}
template <int N> __device__ __forceinline__ void reg_zero(float (&a)[N]) {
#pragma unroll
  for (int i = 0; i < N; i++) a[i] = 0.f;
}
__device__ __forceinline__ constexpr uint64_t mkdesc(uint32_t addr, uint32_t lbo, uint32_t sbo, uint32_t swz) {
  return (uint64_t)(addr >> 4) | ((uint64_t)(lbo >> 4) << 16) | ((uint64_t)(sbo >> 4) << 32) | ((uint64_t)swz << 62);
}
__device__ __forceinline__ void fence_async_smem() { asm volatile("fence.proxy.async.shared::cta;" ::: "memory"); }
__device__ __forceinline__ void st_relaxed(uint32_t* p, uint32_t v) { asm volatile("st.relaxed.gpu.global.u32 [%0], %1;" ::"l"(p), "r"(v) : "memory"); }
__device__ __forceinline__ uint32_t ld_relaxed(const uint32_t* p) { uint32_t v; asm volatile("ld.relaxed.gpu.global.u32 %0, [%1];" : "=r"(v) : "l"(p) : "memory"); return v; }
__device__ __forceinline__ void st_unit(uint4* p, uint32_t a, uint32_t b, uint32_t c, uint32_t d, uint32_t par) {
  asm volatile("{\n.reg .b64 x, y;\n.reg .b128 z;\nmov.b64 x, {%1,%2};\nmov.b64 y, {%3,%4};\nmov.b128 z, {x, y};\nst.relaxed.gpu.global.b128 [%0], z;\n}"
               ::"l"(p), "r"((a & ~1u) | par), "r"(b), "r"(c), "r"(d) : "memory");
}
__device__ __forceinline__ uint4 lds128(uint32_t a) { uint4 v; asm volatile("ld.shared.v4.u32 {%0,%1,%2,%3}, [%4];" : "=r"(v.x), "=r"(v.y), "=r"(v.z), "=r"(v.w) : "r"(a)); return v; }
__device__ __forceinline__ float4 lds128f(uint32_t a) { float4 v; asm volatile("ld.shared.v4.f32 {%0,%1,%2,%3}, [%4];" : "=f"(v.x), "=f"(v.y), "=f"(v.z), "=f"(v.w) : "r"(a)); return v; }
__device__ __forceinline__ float4 lds128v(uint32_t a) { float4 v; asm volatile("ld.volatile.shared.v4.f32 {%0,%1,%2,%3}, [%4];" : "=f"(v.x), "=f"(v.y), "=f"(v.z), "=f"(v.w) : "r"(a) : "memory"); return v; }
__device__ __forceinline__ float lds32v(uint32_t a) { float v; asm volatile("ld.volatile.shared.f32 %0, [%1];" : "=f"(v) : "r"(a) : "memory"); return v; }
__device__ __forceinline__ float2 lds64f(uint32_t a) { float2 v; asm volatile("ld.shared.v2.f32 {%0,%1}, [%2];" : "=f"(v.x), "=f"(v.y) : "r"(a)); return v; }
__device__ __forceinline__ uint32_t lds32(uint32_t a) { uint32_t v; asm volatile("ld.shared.u32 %0, [%1];" : "=r"(v) : "r"(a)); return v; }
__device__ __forceinline__ void sts128(uint32_t a, uint32_t x, uint32_t y, uint32_t z, uint32_t w) { asm volatile("st.shared.v4.u32 [%0], {%1,%2,%3,%4};" ::"r"(a), "r"(x), "r"(y), "r"(z), "r"(w) : "memory"); }
__device__ __forceinline__ void sts128f(uint32_t a, float x, float y, float z, float w) { asm volatile("st.shared.v4.f32 [%0], {%1,%2,%3,%4};" ::"r"(a), "f"(x), "f"(y), "f"(z), "f"(w) : "memory"); }
__device__ __forceinline__ void sts64(uint32_t a, uint32_t x, uint32_t y) { asm volatile("st.shared.v2.u32 [%0], {%1,%2};" ::"r"(a), "r"(x), "r"(y) : "memory"); }
__device__ __forceinline__ void sts32(uint32_t a, uint32_t x) { asm volatile("st.shared.u32 [%0], %1;" ::"r"(a), "r"(x) : "memory"); }
__device__ __forceinline__ void stsm4(uint32_t a, uint32_t r0, uint32_t r1, uint32_t r2, uint32_t r3) {
  asm volatile("stmatrix.sync.aligned.m8n8.x4.shared.b16 [%0], {%1,%2,%3,%4};" ::"r"(a), "r"(r0), "r"(r1), "r"(r2), "r"(r3) : "memory");
}
__device__ __forceinline__ uint4 ldsm4(uint32_t a) {
  uint4 v; asm volatile("ldmatrix.sync.aligned.m8n8.x4.shared.b16 {%0,%1,%2,%3}, [%4];" : "=r"(v.x), "=r"(v.y), "=r"(v.z), "=r"(v.w) : "r"(a) : "memory"); return v;
}
__device__ __forceinline__ uint32_t pack(float lo, float hi) { uint32_t r; asm("cvt.rn.bf16x2.f32 %0, %1, %2;" : "=r"(r) : "f"(hi), "f"(lo)); return r; }
__device__ __forceinline__ float bf_lo(uint32_t w) { return __uint_as_float(w << 16); }
__device__ __forceinline__ float bf_hi(uint32_t w) { return __uint_as_float(w & 0xffff0000u); }
__device__ __forceinline__ float bf_round(float x) { return bf_lo(pack(x, x)); }
__device__ __forceinline__ float ex2(float x) { float v; asm("ex2.approx.ftz.f32 %0, %1;" : "=f"(v) : "f"(x)); return v; }
__device__ __forceinline__ float rcp(float x) { float v; asm("rcp.approx.ftz.f32 %0, %1;" : "=f"(v) : "f"(x)); return v; }
__device__ __forceinline__ float addsat(float a, float b) { float v; asm("add.sat.f32 %0, %1, %2;" : "=f"(v) : "f"(a), "f"(b)); return v; }
__device__ __forceinline__ float phi2(float a) { return fmaf(fmaxf(a, 0.f), LN2, addsat(ex2(a), 1e-6f)); }
__device__ __forceinline__ float key_score(uint32_t key) { uint32_t u = key >> 16; u = (u & 0x8000u) ? (u & 0x7fffu) : (~u & 0xffffu); return __uint_as_float(u << 16); }
__device__ __forceinline__ int key_token(uint32_t key) { return 2047 - (int)((key >> 5) & 2047u); }
__device__ __forceinline__ uint32_t bsel(uint32_t a, uint32_t b, uint32_t m) { uint32_t r; asm("lop3.b32 %0, %1, %2, %3, 0xd8;" : "=r"(r) : "r"(a), "r"(b), "r"(m)); return r; }
__device__ __forceinline__ uint32_t prmt(uint32_t a, uint32_t b, uint32_t c) { uint32_t r; asm("prmt.b32 %0, %1, %2, %3;" : "=r"(r) : "r"(a), "r"(b), "r"(c)); return r; }
__device__ __forceinline__ uint32_t tagf(float v, uint32_t par) { return (__float_as_uint(v) & ~1u) | par; }
__device__ __forceinline__ float xred(float a, float b, bool up, int o) { return (up ? b : a) + __shfl_xor_sync(0xffffffffu, up ? a : b, o); }

#define STAMP(id)
#define STAMP_IF(c, id)
#define STAMP2(i)
#define LITE 1
#define LITE_MASK 0ull

template <bool TRANS, int NK = 16>
__device__ __forceinline__ void mainloop(float (&a0)[64], float (&a1)[64], int s, int ph, int handoff, int xpair, bool leader) {
  uint32_t prev = 0;
#pragma unroll 1
  for (int kt = 0; kt < NK; kt++) {
    const bool xr = !TRANS && (kt >> 1) == xpair;
    mbar_wait(B_FULL + 8 * s, ph);
    const uint64_t dw = mkdesc(RING, 8192, 1024, 1) + s * (SLOT >> 4), dx = mkdesc(0, 16, 1024, 1) + (xr ? (STG >> 4) + (kt & 1) * 1024 : ((RING + 16384) >> 4) + s * (SLOT >> 4));
    if (xr) mbar_wait(B_XRES + 8 * (kt & 1), 0);
    wg_fence();
#pragma unroll
    for (int j = 0; j < 4; j++) {
      if (TRANS) {
        wgmma_n128_ss<1, 0>(a0, dw + j * 128, dx + j * 2, 1);
        wgmma_n128_ss<1, 0>(a1, dw + j * 128 + 512, dx + j * 2, 1);
      } else {
        wgmma_n128_ss<0, 1>(a0, dx + j * 2, dw + j * 128, 1);
        wgmma_n128_ss<0, 1>(a1, dx + j * 2 + 512, dw + j * 128, 1);
      }
    }
    wg_commit();
    if (handoff && kt == 15) nb_arrive(handoff, 256);
    wg_wait<1>();
    if (prev && leader) mbar_arrive(prev);
    prev = B_EMPTY + 8 * s;
    if (++s == NST) { s = 0; ph ^= 1; }
  }
  if (NK < 16) return;
  wg_wait<0>();
  if (leader) mbar_arrive(prev);
  reg_fence(a0);
  reg_fence(a1);
}

__device__ __forceinline__ int out_kblock(int r, int tn) {
  const int q = r - 2, half = q >= 7, pi = q - 7 * half;
  return r < 2 ? 2 * tn + r : 2 * ((pi + (pi >= (tn & 3))) ^ (tn & 4)) + half;
}

struct Params {
  const char *x, *wqkv, *w_r, *wg, *wu, *wd, *wo;
  CUtensorMap m_wqkv, m_x, m_xs, m_o, m_os, m_wo, m_gu, m_down, m_out;
};

template <bool BY_SMID>
__global__ void __launch_bounds__(512, 1) fused_kernel(const __grid_constant__ Params mp) {
  extern __shared__ __align__(1024) uint8_t smem_raw[];
#define CK(i)
  CK(0);
  const int tid = threadIdx.x, lane = tid & 31;
  const int w = __shfl_sync(0xffffffffu, tid >> 5, 0);
  int bid = blockIdx.x;
  if (BY_SMID) {
    uint32_t sm;
    asm volatile("mov.u32 %0, %%smid;" : "=r"(sm));
    const uint32_t p = sm >> 1, q = ((p - 32) * 37) >> 8;
    const uint32_t gpc = p < 32 ? p & 7 : p < 60 ? p - 31 - 7 * q : 0, tpc = p < 32 ? p >> 3 : p < 60 ? 4 + q : p - 58;
    bid = (p >> 1) == 30 ? 128 + ((0x9cu >> (2 * (sm & 3))) & 3) : ((GPCMAP >> (4 * gpc)) & 7) * 16 + tpc * 2 + (sm & 1);
  }
  const int tn = (bid & 3) + 4 * (bid >> 6), tm = (bid >> 2) & 15;

  CK(1);
  if (w == 0) {
#pragma unroll 1
    for (int s = 0; s < NST; s++) {
      asm volatile(ELECT "@p mbarrier.init.shared::cta.b64 [%0], 1;\n}" ::"r"(B_FULL + 8 * s) : "memory");
      if (bid < 128) {
        e_expect(B_FULL + 8 * s, 32768);
        e_tma2d(RING + s * SLOT + 16384, &mp.m_x, s * 64, tm * 128, B_FULL + 8 * s);
        e_tma3d(RING + s * SLOT, &mp.m_wqkv, s * 64, 16 + 2 * tn, B_FULL + 8 * s);
      }
      if (s == 0) CK(2);
    }
  }
  if (w == 1) e_pfmap(&mp.m_wqkv);
  if (w == 2) e_pfmap(&mp.m_xs);
  if (w >= 4) {
#pragma unroll 1
    for (uint32_t b = MISC + 8 * (w + 1); b < MISC + 8 * NBAR; b += 96)
      asm volatile(ELECT "@p mbarrier.init.shared::cta.b64 [%0], %1;\n}" ::"r"(b), "r"(b == B_CSDN ? 4 : 1) : "memory");
    if (w == 15) sts32(S_NCAND, 0);
  }
  CK(3);
  asm volatile("fence.mbarrier_init.release.cluster;" ::: "memory");
  __syncthreads();

  if (bid >= 128) {
    const int h0 = bid == 128 ? 14 : bid - 129, hs = bid == 128 ? 1 : 3, h1 = bid == 128 ? 16 : 14;
    if (w == 12) {
      int s = 0, ph = 1;
#pragma unroll 1
      for (int h = h0; h < h1; h += hs) {
        const int c = 2 * h + (h & 8) * 2;
        if (h == 14) mbar_wait(B_SEL, 0);
#pragma unroll 1
        for (int kt = 0; kt < 16; kt += 2) {
          mbar_wait(B_EMPTY + 8 * s, ph);
          e_expect(B_FULL + 8 * s, 32768);
          e_tma3d(RING + s * SLOT, &mp.m_wqkv, kt * 64, c, B_FULL + 8 * s);
          e_tma3d(RING + s * SLOT + 16384, &mp.m_wqkv, kt * 64 + 64, c, B_FULL + 8 * s);
          if (++s == HST) { s = 0; ph ^= 1; }
        }
      }
    } else if (w < 4) {
      const uint32_t par = (ld_relaxed(&g_epoch) + 1) & 1u;
      sts32(S_ONES + tid * 4, 0x3f803f80u);
      fence_async_smem();
      nb_sync(NB_WG0, 128);
      int s = 0, ph = 0;
#pragma unroll 1
      for (int h = h0; h < h1; h += hs) {
        float c[4][4];
#pragma unroll
        for (int q = 0; q < 4; q++) reg_zero(c[q]);
        uint32_t prev = 0;
#pragma unroll 1
        for (int kt = 0; kt < 8; kt++) {
          mbar_wait(B_FULL + 8 * s, ph);
          const uint64_t dw = mkdesc(RING, 8192, 1024, 1) + s * (SLOT >> 4);
          wg_fence();
#pragma unroll
          for (int j = 0; j < 16; j++) wgmma_n8_ss<1, 0>(c[j & 3], dw + (j & 3) * 512 + (j >> 2) * 128, mkdesc(S_ONES, 128, 128, 0), 1);
          wg_commit();
          wg_wait<1>();
          if (prev && tid == 0) mbar_arrive(prev);
          prev = B_EMPTY + 8 * s;
          if (++s == HST) { s = 0; ph ^= 1; }
        }
        wg_wait<0>();
        if (tid == 0) mbar_arrive(prev);
#pragma unroll
        for (int q = 0; q < 4; q++) reg_fence(c[q]);
        const bool u2 = lane & 2, u1 = lane & 1;
        const float lo = u2 ? c[1][0] + c[3][0] : c[0][0] + c[2][0], hi = u2 ? c[1][2] + c[3][2] : c[0][2] + c[2][2];
        st_relaxed(g_csum + h * 128 + (lane & 2) * 32 + w * 16 + (lane & 1) * 8 + (lane >> 2), tagf(u1 ? hi : lo, par));
        STAMP_IF(tid == 0, h >= 8 ? 6 : 30);
      }
    } else if (w < 12 && bid == 128) {
      const int t = tid - 128, j = w - 4;
      const uint32_t ep = ld_relaxed(&g_epoch) + 1;
      uint32_t kk[16];
      poll_keys(kk, g_keys + t * 2, ep, 31u);
      STAMP_IF(t == 0, 42);
      const uint32_t m = __reduce_max_sync(0xffffffffu, max(max(max(kk[0], kk[2]), max(kk[4], kk[6])), max(max(kk[8], kk[10]), max(kk[12], kk[14]))));
      if (lane == 0) sts32(S_WMAX + j * 4, m);
      nb_sync(NB_WG1, 256);
      const uint32_t T = __reduce_min_sync(0xffffffffu, lds32(S_WMAX + (lane & 7) * 4));
      uint32_t cnt = 0;
#pragma unroll
      for (int i = 0; i < 8; i++) cnt += kk[2 * i] >= T;
      if (cnt) {
        uint32_t pos;
        asm volatile("atom.shared.add.u32 %0, [%1], %2;" : "=r"(pos) : "r"(S_NCAND), "r"(cnt * 8) : "memory");
#pragma unroll
        for (int i = 0; i < 8; i++)
          if (kk[2 * i] >= T) { sts64(AUX + pos, kk[2 * i], kk[2 * i + 1]); pos += 8; }
      }
      nb_sync(NB_WG1, 256);
      const uint32_t n8 = lds32(S_NCAND);
#pragma unroll 1
      for (uint32_t i = j * 8; i < n8; i += 64) {
        const float2 c = lds64f(AUX + i);
        uint32_t rank = 0;
#pragma unroll 1
        for (uint32_t q = lane * 8; q < n8 + lane * 8; q += 256) rank += __popc(__ballot_sync(0xffffffffu, q < n8 && lds32(AUX + q) > __float_as_uint(c.x)));
        if (rank < 8) sts64(S_SEL + rank * 8, __float_as_uint(c.x), __float_as_uint(c.y));
      }
      fence_async_smem();
      nb_sync(NB_WG1, 256);
      if (j == 0) {
        const uint4 v = lds128(S_SEL + (lane & 3) * 16);
        asm volatile("{\n.reg .b64 x, y;\nmov.b64 x, {%1,%2};\nmov.b64 y, {%3,%4};\nst.relaxed.gpu.global.v2.b64 [%0], {x, y};\n}"
                     ::"l"(g_sel + (lane >> 2) * 16 + (lane & 3) * 2), "r"(v.x), "r"(v.y), "r"(v.z), "r"(v.w) : "memory");
        e_arrive(B_SEL);
      }
      STAMP_IF(t == 0, 45);
    }
  } else if (w >= 12) {
    asm volatile("setmaxnreg.dec.sync.aligned.u32 32;");
    if (w == 12) {
      int s = 0, ph = 0;
#pragma unroll 1
      for (int it = NST; it < 48; it++) {
        const int c = (it < 32 ? (it & 16) + 16 : 0) + 2 * tn;
        const int k0 = ((it + (it >= 32 && tn < 4 ? 8 : 0)) & 15) * 64;
        const bool xr = (it >> 1) == 20 + (tn & 3);
        if (xr) { mbar_wait(B_SFREE, 0); e_expect(B_XRES + 8 * (it & 1), 16384); }
        refill_wx(B_EMPTY + 8 * s, ph, B_FULL + 8 * s, xr ? 16384 : 32768, RING + s * SLOT, &mp.m_wqkv, k0, c,
                  xr ? STG + (it & 1) * 16384 : RING + s * SLOT + 16384, &mp.m_x, tm * 128, xr ? B_XRES + 8 * (it & 1) : B_FULL + 8 * s);
        if (it >= NST) STAMP2(it - NST);
        if (++s == NST) { s = 0; ph ^= 1; }
      }
#pragma unroll 1
      for (int r = 0; r < 16; r++) {
        const int kb = out_kblock(r, tn);
        refill_w(B_EMPTY + 8 * s, ph, B_FULL + 8 * s, r < 2 ? 16384 : 32768, RING + s * SLOT, &mp.m_wo, kb * 64, 2 * tn);
        if (r < 2 || r == 4) {
          const uint32_t bar = B_DR + (r < 2 ? 16 : 8);
          const int k0 = (bid >> 4) * 448 + 128 + min(r, 2) * 128;
          if (r != 1) e_expect(bar, r ? 8192 : 32768);
          e_tma2d_ef(RING + s * SLOT + 16384, &mp.m_down, (bid & 15) * 64, k0, bar, EVICT_FIRST);
          if (r < 2) e_tma2d_ef(RING + s * SLOT + 24576, &mp.m_down, (bid & 15) * 64, k0 + 64, bar, EVICT_FIRST);
        }
        STAMP2(r + 48 - NST);
        if (++s == NST) { s = 0; ph ^= 1; }
      }
    } else if (w == 13) {
      mbar_wait(B_FULL, 0);
#pragma unroll 1
      for (int c = 0; c < 4; c++) {
        if (c >= XS_FLY) mbar_wait(B_XS + 8 * (c - XS_FLY), 0);
        if (c == (tm >> 2)) {
          e_expect(B_WK, 16384);
          e_tma3d(FR, &mp.m_wqkv, tm * 64, 16 + 2 * tn, B_WK);
        }
        e_expect(B_XS + 8 * c, 8192);
        e_tma2d(STG + c * 8192, &mp.m_xs, c * 256, tm * 128 + tn * 16, B_XS + 8 * c);
      }
      {
        const char* pv = mp.wqkv + (tm * 16 + (lane >> 1)) * 6144 + 4096 + tn * 256 + (lane & 1) * 128;
        const char* pd = mp.wd + (bid & 15) * 128 + ((bid >> 4) * 448 + lane) * 2048;
        const char* po = mp.wo + bid * 16384 + lane * 128;
        mbar_wait(B_XS + 24, 0);
        __nanosleep(PF_WAIT);
#pragma unroll 1
        for (int i = PF_V ? 0 : 4; i < (PF_O ? 22 : 18); i++) {
          asm volatile("prefetch.global.L2 [%0];" ::"l"(i < 4 ? pv + i * (256 * 6144) : i < 18 ? pd + (i - 4) * 65536 : po + (i - 18) * 4096));
          __nanosleep(PF_GAP);
        }
      }
      nb_sync(NB_Z, 160);
      const uint32_t ep = lds32(S_EPOCH);
      {
        float z[4] = {0.f, 0.f, 0.f, 0.f};
        e_signal(H_Z + tn, tm);
        await(H_Z + tn, 0xffffu, ep);
#pragma unroll 1
        for (int i = 0; i < 4; i++) {
          uint32_t p[16];
          poll_z(p, g_z + i * 4096 + tn * 128 + lane * 4, ep, 1u);
#pragma unroll
          for (int q = 0; q < 4; q++) z[q] += (__uint_as_float(p[q]) + __uint_as_float(p[4 + q])) + (__uint_as_float(p[8 + q]) + __uint_as_float(p[12 + q]));
        }
        const uint32_t z01 = pack(z[0], z[1]), z23 = pack(z[2], z[3]);
        if (bid < 112) mbar_wait(B_PFREE, 0);
#pragma unroll
        for (int n = 0; n < 8; n++) sts64(KVB + (lane >> 4) * 5120 + n * 128 + ((((lane >> 1) & 7) ^ n) << 4) + (lane & 1) * 8, z01, z23);
        fence_async_smem();
        nb_arrive(NB_KVB, 320);
        STAMP_IF(lane == 0, 46);
      }
      nb_sync(NB_Q0, 192);
      e_store2d(&mp.m_os, tn * 128, tm * 128, STG);
      nb_sync(NB_OWN0, 288);
      e_store2d(&mp.m_os, tn * 128, tm * 128 + 64, STG + 8192);
      if (!SIG_EARLY) bulk_wait_read(); else if (SIG_EARLY > 1) __nanosleep(SIG_EARLY);
      e_signal(H_O + tm, 2 * tn);
      STAMP_IF(lane == 0, 4);
      nb_sync(NB_H1, 160);
      e_store2d(&mp.m_os, tn * 128 + 64, tm * 128, STG + 16384);
      e_store2d(&mp.m_os, tn * 128 + 64, tm * 128 + 64, STG + 24576);
      bulk_wait_read();
      e_signal(H_O + tm, 2 * tn + 1);
      STAMP_IF(lane == 0, 5);
      nb_arrive(NB_ST, 288);
    } else if (w == 14) {
      e_pfmap(&mp.m_gu); e_pfmap(&mp.m_o); e_pfmap(&mp.m_os); e_pfmap(&mp.m_wo); e_pfmap(&mp.m_down); e_pfmap(&mp.m_out);
      const uint32_t ep = ld_relaxed(&g_epoch) + 1;
      nb_sync(NB_FDONE, 416);
      {
        uint32_t c[4];
        poll_quad(c, g_csum + tn * 128 + lane * 4, ep, 1u);
        sts128(S_CSQ + lane * 16, c[0], c[1], c[2], c[3]);
        nb_arrive(NB_CSQ, 160);
        poll_quad(c, g_csum + 1024 + tn * 128 + lane * 4, ep, 1u);
        sts128(S_CSV + lane * 16, c[0], c[1], c[2], c[3]);
        __syncwarp();
        e_arrive(B_CSV);
      }
      {
        mbar_wait(B_WK, 1);
        if (KV_SPEC) __nanosleep(KV_SPEC); else await(H_KV + tn, 0xffffu, ep);
        STAMP_IF(lane == 0, 7);
        if (bid < 112) mbar_wait(B_PFREE, 0);
        STAMP_IF(lane == 0, 23);
        uint32_t bad, ph = 0;
        do {
          e_expect(B_KVL, 8192);
          e_load(KVB + 1024, g_kv + tn * 512, 4096, B_KVL);
          e_load(KVB + 6144, g_kv + tn * 512 + 256, 4096, B_KVL);
          mbar_wait(B_KVL, ph & 1);
          bad = 0;
#pragma unroll
          for (int i = 0; i < 16; i++) bad |= __float_as_uint(lds32v(KVB + 1024 + (i & 8) * 128 + i * 512 + lane * 16)) ^ ep;
          bad = __any_sync(0xffffffffu, bad & 1u);
          if (bad) fence_async_smem();
        } while (bad && ++ph < 100000);
        nb_arrive(NB_KVB, 320);
        STAMP_IF(lane == 0, 24);
      }
      nb_sync(NB_Q0, 192);
      uint32_t ready = 0;
      int s = 0, ph = 1;
#pragma unroll 1
      for (int r = 2; r < 16; r++) {
        const int kb = out_kblock(r, tn);
        if (!((ready >> kb) & 1)) {
          uint32_t f[1];
          poll0(f, g_sig + (H_O + tm) * 32, 0u - (ep & 1u), 1u << kb);
          ready = f[0] ^ ((ep & 1u) - 1u);
        }
        if (r == 4) mbar_wait(B_DND, 0);
        refill_x(B_EMPTY + 8 * s, ph, B_FULL + 8 * s, RING + s * SLOT + 16384, &mp.m_o, kb * 64, tm * 128);
        STAMP_IF(lane == 0 && r == 2, 2);
        STAMP_IF(lane == 0 && r == 9, 3);
        if (++s == NST) { s = 0; ph ^= 1; }
      }
    } else {
      uint32_t nsm = 132;
      if (BY_SMID) asm volatile("mov.u32 %0, %%nsmid;" : "=r"(nsm));
      asm volatile("{\n.reg .pred q;\nsetp.eq.u32 q, %0, 1156;\n@q bra LOK;\ntrap;\nLOK:\n}" ::"r"((uint32_t)__cvta_generic_to_shared(smem_raw) + nsm));
      const uint32_t ep = ld_relaxed(&g_epoch) + 1;
      mbar_wait(B_CSDN, 0);
#pragma unroll 1
      for (int n = 0; n < 3 && bid < 112; n++) {
        __nanosleep(FFN_GAP);
        e_expect(B_FR + 8 * n, 8192);
        e_tma3d_ef(GR + n * 8192, &mp.m_gu, bid * 32, n * 64, B_FR + 8 * n, EVICT_FIRST);
      }
      uint32_t sel[2];
      poll_pair(sel, g_sel + (bid >> 4) * 16 + (lane >> 2), ep, 31u);
      const char* xs = mp.x + key_token(sel[0]) * 2048 + (lane & 3) * 16;
      const uint32_t xd = AUX + (lane >> 2) * 64 + (((lane & 3) ^ (lane >> 3)) << 4);
      auto slices = [&](int n, int p) {
        asm volatile("cp.async.cg.shared.global [%0], [%1], 16;\ncp.async.cg.shared.global [%0+512], [%1+64], 16;\ncp.async.commit_group;"
                     ::"r"(xd + p * 1024), "l"(xs + n * 128) : "memory");
      };
      if ((lane & 3) == 0) sts64(S_SEL + lane * 2, sel[0], sel[1]);
      if (bid < 112) {
#pragma unroll
        for (int i = 0; i < 6; i++) slices(i, i);
      }
      asm volatile("cp.async.wait_group 2;" ::: "memory");
      fence_async_smem();
      __syncwarp();
      e_arrive(B_SEL);
      if (bid < 112) {
        int s = 0, ph = 0;
#pragma unroll 1
        for (int n = 3; n < 16; n++) {
          refill_g(B_FE + 8 * s, ph, B_FR + 8 * s, GR + s * 8192, &mp.m_gu, bid * 32, n * 64);
          STAMP2(64 + n);
          asm volatile("cp.async.wait_group 1;" ::: "memory");
          fence_async_smem();
          __syncwarp();
          if (n < 13) slices(n + 3, s + 3 * ph);
          else asm volatile("cp.async.commit_group;" ::: "memory");
          if (++s == 3) { s = 0; ph ^= 1; }
        }
      }
      e_expect(B_DR, 16384);
      if (bid < 112) mbar_wait(B_FE + 8, 0);
      e_tma2d_ef(FR, &mp.m_down, (bid & 15) * 64, (bid >> 4) * 448, B_DR, EVICT_FIRST);
      if (bid < 112) mbar_wait(B_FE + 16, 0);
      e_tma2d_ef(FR + 8192, &mp.m_down, (bid & 15) * 64, (bid >> 4) * 448 + 64, B_DR, EVICT_FIRST);
    }
  } else if (w >= 8) {
    asm volatile("setmaxnreg.dec.sync.aligned.u32 56;");
    const int t = tid - 256, ww = w - 8;
    const uint32_t ep = ld_relaxed(&g_epoch) + 1, par = ep & 1u;
    sts32(FONES + t * 4, 0x3f803f80u);
    {
      const int r0 = (lane >> 3) + (lane & 4);
      const uint32_t a = FR + (ww >> 1) * 8192 + r0 * 128 + ((((ww & 1) * 4 + (lane & 3)) ^ r0) << 4);
      float c[8];
      reg_zero(c);
      mbar_wait(B_WK, 0);
#pragma unroll 2
      for (int i = 0; i < 8; i++) {
        const uint4 v = lds128(a + i * 1024);
        c[0] += bf_lo(v.x); c[1] += bf_hi(v.x); c[2] += bf_lo(v.y); c[3] += bf_hi(v.y);
        c[4] += bf_lo(v.z); c[5] += bf_hi(v.z); c[6] += bf_lo(v.w); c[7] += bf_hi(v.w);
      }
      const bool u16 = lane & 16, u8 = lane & 8, u4 = lane & 4;
      const float d0 = xred(c[0], c[4], u16, 16), d1 = xred(c[1], c[5], u16, 16), d2 = xred(c[2], c[6], u16, 16), d3 = xred(c[3], c[7], u16, 16);
      fence_async_smem();
      e_arrive(B_CSDN);
      const float sum = xred(xred(d0, d2, u8, 8), xred(d1, d3, u8, 8), u4, 4);
      st_relaxed(g_csum + (2 + tm) * 1024 + tn * 128 + ww * 32 + (lane & 3) * 8 + (lane >> 2), tagf(sum, par));
      STAMP_IF(t == 0, 8);
      nb_sync(NB_WG2, 128);
      if (ww == 0) { e_signal(H_CS + tn, tm); await(H_CS + tn, 0xffffu, ep); }
      nb_sync(NB_WG2, 128);
      uint32_t p[16];
      poll16(p, g_csum + 2048 + tn * 128 + t, par, 1u);
      float tot = 0.f;
#pragma unroll
      for (int i = 0; i < 16; i += 4) tot += (__uint_as_float(p[i]) + __uint_as_float(p[i + 1])) + (__uint_as_float(p[i + 2]) + __uint_as_float(p[i + 3]));
      sts32(S_CSK + t * 4, __float_as_uint(tot));
      nb_arrive(NB_FDONE, 416);
      STAMP_IF(t == 0, 9);
    }
    const int ks = bid >> 4, nt = bid & 15;
    if (bid < 112) {
      float fg[8];
      reg_zero(fg);
      mbar_wait(B_SEL, 0);
      constexpr uint64_t DA0 = mkdesc(GR, 4096, 512, 2), DB0 = mkdesc(AUX, 16, FONES - AUX, 2), DBS = 32 - (32ull << 32);
      uint64_t da = DA0, db = DB0;
      uint32_t bar = B_FR, ph = 0;
#pragma unroll 1
      for (int n = 0; n < 16; n++) {
        mbar_wait(bar, ph);
        wg_fence();
#pragma unroll
        for (int q = 0; q < 4; q++) wgmma_n16_ss<1, 0>(fg, da + q * 64, db + (q >> 1) * DBS + (q & 1) * 2, 1);
        wg_commit();
        const uint32_t rel = bar + (B_FE - B_FR);
        const bool wrap = bar == B_FR + 16;
        da = wrap ? DA0 : da + 512;
        db = wrap && ph ? DB0 : db + 2 * DBS;
        bar = wrap ? B_FR : bar + 8;
        ph ^= wrap;
        wg_wait<0>();
        if (t == 0) mbar_arrive(rel);
      }
      if (t == 0) mbar_arrive(B_PFREE);
      const uint4 st = lds128(S_SEL + (lane & 3) * 16);
      const float r0 = rcp(bf_lo(st.y)), r1 = rcp(bf_lo(st.w));
      reg_fence(fg);
      const float fa[4] = {fmaf(-bf_hi(st.y), fg[4], fg[0]) * r0, fmaf(-bf_hi(st.w), fg[4], fg[1]) * r1,
                           fmaf(-bf_hi(st.y), fg[6], fg[2]) * r0, fmaf(-bf_hi(st.w), fg[6], fg[3]) * r1};
      STAMP_IF(t == 0, 12);
      const bool isup = (ww >> 1) != (mp.wu < mp.wg);
      nb_sync(NB_WG2, 128);
      if (isup) sts128f(HOP + (t & 63) * 16, fa[0], fa[1], fa[2], fa[3]);
      nb_sync(NB_WG2, 128);
      if (!isup) {
        const float4 u = lds128f(HOP + (t & 63) * 16);
        const float uu[4] = {u.x, u.y, u.z, u.w};
        uint32_t* hp = g_h + bid * 256 + (lane & 3) * 64 + (ww & 1) * 16 + (lane >> 2);
#pragma unroll
        for (int i = 0; i < 4; i++) {
          const float g = fa[i], hv = g * rcp(1.f + ex2(-g * LOG2E)) * uu[i];
          st_relaxed(hp + (i & 1) * 32 + (i >> 1) * 8, __byte_perm(pack(hv, hv), ep, 0x3254));
        }
      }
      nb_sync(NB_WG2, 128);
      if (ww == 0) e_signal(H_H + bid / 14, bid % 14);
    }
    {
      uint32_t v[28];
      if (ww == 0) await(H_H + ks, 0x3fffu, ep);
      nb_sync(NB_WG2, 128);
      poll7x4(v, g_h + ks * 3584 + t * 4, ep, 0xffffu);
      mbar_wait(B_WK, 1);
#pragma unroll
      for (int q = 0; q < 7; q++)
        asm volatile("st.shared.v2.u32 [%0], {%1,%2};" ::"r"((q < 6 ? HOP + q * 1024 : S_CSK) + (t >> 3) * 64 + ((((t >> 1) & 3) ^ ((t >> 4) & 3)) << 4) + (t & 1) * 8),
                     "r"(__byte_perm(v[4 * q], v[4 * q + 1], 0x7632)), "r"(__byte_perm(v[4 * q + 2], v[4 * q + 3], 0x7632)) : "memory");
      fence_async_smem();
      nb_sync(NB_WG2, 128);
    }
    STAMP_IF(t == 0, 13);
    float fa[4] = {0.f, 0.f, 0.f, 0.f};
    auto down = [&](uint32_t a, int k0, int nk) {
#pragma unroll
      for (int q = 0; q < nk; q++) wgmma_n8_ss<1, 0>(fa, mkdesc(a + q * 2048, 4096, 1024, 1), mkdesc((k0 < 24 ? HOP : S_CSK - 6144) + ((k0 + q) >> 1) * 512 + (q & 1) * 32, 16, 512, 2), 1);
    };
    mbar_wait(B_DR, 0);
    mbar_wait(B_DR + 16, 0);
    mbar_wait(B_DR + 8, 0);
    wg_fence();
    down(RING + 2 * SLOT + 16384, 24, 4);
    down(RING + 3 * SLOT + 16384, 8, 8);
    down(RING + 4 * SLOT + 16384, 16, 8);
    wg_commit();
    wg_fence();
    down(FR, 0, 8);
    wg_commit();
    wg_wait<1>();
    if (t == 0) mbar_arrive(B_DND);
    wg_wait<0>();
    reg_fence(fa);
    STAMP_IF(t == 0, 14);
    {
      uint32_t* yp = g_yp + (nt * 8 + ks) * 512 + (lane & 3) * 128 + ww * 16 + (lane >> 2);
#pragma unroll
      for (int i = 0; i < 4; i++) st_relaxed(yp + (i & 1) * 64 + (i >> 1) * 8, tagf(fa[i], par));
    }
    nb_sync(NB_WG2, 128);
    if (ww == 0) e_signal(H_Y + (nt >> 1), (nt & 1) * 8 + ks);
    mbar_wait(B_SEL, 0);
    const uint32_t mykey = lds32(S_SEL + (lane & 7) * 8);
    const uint32_t inmask = __ballot_sync(0xffffffffu, (key_token(mykey) >> 7) == tm) & 0xffu;
    sts128(FR + t * 16, 0u, 0u, 0u, 0u);
    if (inmask) {
      if (ww == 0) await(H_Y + tn, 0xffffu, ep);
      nb_sync(NB_WG2, 128);
      const float sg = rcp(1.f + ex2(-key_score(mykey) * LOG2E));
#pragma unroll 1
      for (uint32_t mine = __ballot_sync(0xffffffffu, ((inmask >> lane) & 1) && (__popc(inmask & ((1u << lane) - 1)) & 3) == ww); mine; mine &= mine - 1) {
        const int j = __ffs(mine) - 1;
        uint32_t p[32];
        poll8x4(p, g_yp + (tn * 2 + (lane >> 4)) * 4096 + j * 64 + (lane & 15) * 4, par, 1u);
        float y[4];
        const float sj = __shfl_sync(0xffffffffu, sg, j);
#pragma unroll
        for (int i = 0; i < 4; i++)
          y[i] = sj * (((__uint_as_float(p[i]) + __uint_as_float(p[4 + i])) + (__uint_as_float(p[8 + i]) + __uint_as_float(p[12 + i]))) +
                       ((__uint_as_float(p[16 + i]) + __uint_as_float(p[20 + i])) + (__uint_as_float(p[24 + i]) + __uint_as_float(p[28 + i]))));
        asm volatile("st.shared.v2.u32 [%0], {%1,%2};" ::"r"(FR + (lane >> 4) * 1024 + j * 128 + ((((lane >> 1) & 7) ^ j) << 4) + (lane & 1) * 8),
                     "r"(pack(y[0], y[1])), "r"(pack(y[2], y[3])) : "memory");
      }
    }
    fence_async_smem();
    nb_arrive(NB_ST, 288);
    STAMP_IF(t == 0, 15);
  } else if (w >= 4) {
    asm volatile("setmaxnreg.inc.sync.aligned.u32 208;");
    const int t = tid - 128, ww = w - 4, g = lane >> 2, t4 = lane & 3;
    const bool leader = t == 0;
    const uint32_t ep = ld_relaxed(&g_epoch) + 1, par = ep & 1u;
    {
      const uint4* wp = reinterpret_cast<const uint4*>(mp.w_r) + lane;
      uint4 w0 = __ldg(wp), w1 = __ldg(wp + 32), w2 = __ldg(wp + 64), w3 = __ldg(wp + 96);
      if (leader) sts32(S_EPOCH, ep);
      if (KV_SPEC && t4 == 0) {
        const int grp = (tm & 1) * 2 + ((lane >> 3) & 1), row = ww * 2 + ((lane >> 2) & 1);
        st_unit(g_kv + tn * 512 + ((tm >> 3) * 4 + grp) * 64 + row * 8 + (((tm & 2) * 2 + ((tm >> 1) & 2) + (lane >> 4)) ^ row), 0u, 0u, 0u, 0u, par ^ 1u);
      }
      float s[4] = {0.f, 0.f, 0.f, 0.f}, q[4] = {0.f, 0.f, 0.f, 0.f}, d[4] = {0.f, 0.f, 0.f, 0.f}, wsum = 0.f;
#pragma unroll 1
      for (int c = 0; c < 4; c++) {
        const float wr[8] = {bf_lo(w0.x), bf_hi(w0.x), bf_lo(w0.y), bf_hi(w0.y), bf_lo(w0.z), bf_hi(w0.z), bf_lo(w0.w), bf_hi(w0.w)};
        w0 = w1; w1 = w2; w2 = w3;
        wsum += ((wr[0] + wr[1]) + (wr[2] + wr[3])) + ((wr[4] + wr[5]) + (wr[6] + wr[7]));
        mbar_wait(B_XS + 8 * c, 0);
#pragma unroll
        for (int r = 0; r < 4; r++) {
          const uint4 v = lds128(STG + c * 8192 + (ww * 4 + r) * 512 + lane * 16);
          const uint32_t xw[4] = {v.x, v.y, v.z, v.w};
#pragma unroll
          for (int i = 0; i < 4; i++) {
            const uint32_t dep = __float_as_uint(q[i ? r : (r + 3) & 3]);
            const float lo = __uint_as_float(prmt(xw[i], dep, 0x10ff)), hi = __uint_as_float(prmt(xw[i], dep, 0x32ff));
            s[r] += lo; q[r] = fmaf(lo, lo, q[r]); d[r] = fmaf(lo, wr[2 * i], d[r]);
            s[r] += hi; q[r] = fmaf(hi, hi, q[r]); d[r] = fmaf(hi, wr[2 * i + 1], d[r]);
          }
        }
      }
      STAMP_IF(leader, 16);
      const bool u16 = lane & 16, u8 = lane & 8, u4 = lane & 4, u2 = lane & 2;
      const float s1 = xred(xred(s[0], s[2], u16, 16), xred(s[1], s[3], u16, 16), u8, 8);
      const float q1 = xred(xred(q[0], q[2], u16, 16), xred(q[1], q[3], u16, 16), u8, 8);
      const float d1 = xred(xred(d[0], d[2], u16, 16), xred(d[1], d[3], u16, 16), u8, 8);
      wsum += __shfl_xor_sync(0xffffffffu, wsum, 16);
      wsum += __shfl_xor_sync(0xffffffffu, wsum, 8);
      float tot = xred(xred(s1, d1, u4, 4), xred(q1, wsum, u4, 4), u2, 2);
      tot += __shfl_xor_sync(0xffffffffu, tot, 1);
      const float qq = __shfl_down_sync(0xffffffffu, tot, 2), dd = __shfl_down_sync(0xffffffffu, tot, 4), ws = __shfl_down_sync(0xffffffffu, tot, 6);
      if ((lane & 7) == 0) {
        const float mean = tot * (1.f / 1024.f);
        const float var = fmaxf(fmaf(-mean, mean, qq * (1.f / 1024.f)), 0.f);
        float sd;
        asm("sqrt.approx.ftz.f32 %0, %1;" : "=f"(sd) : "f"(bf_round(bf_round(var) + 1e-5f)));
        const uint32_t ms = pack(sd, mean);
        const int row = tm * 128 + tn * 16 + ww * 4 + (lane >> 3);
        const uint32_t rbits = pack(0.f, fmaf(-bf_hi(ms), ws, dd) * rcp(bf_lo(ms)));
        const uint32_t key = (rbits ^ (((int)rbits >> 31 & 0x7fff0000u) | 0x80000000u)) | ((2047 - row) << 5) | (ep & 31u);
        asm volatile("{\n.reg .b64 x;\nmov.b64 x, {%1,%2};\nst.relaxed.gpu.global.b64 [%0], x;\n}" ::"l"(g_keys + row), "r"(key), "r"(ms) : "memory");
      }
      STAMP_IF(leader, 17);
      __nanosleep(400);
      uint32_t st[2];
      poll_pair(st, g_keys + tm * 128 + t, ep, 31u);
      asm volatile("st.shared.v2.f32 [%0], {%1,%2};" ::"r"(S_KSTAT + t * 8), "f"(bf_hi(st[1])), "f"(rcp(bf_lo(st[1])) * LOG2E) : "memory");
      nb_arrive(NB_FDONE, 416);
      STAMP_IF(leader, 10);
    }
    float a0[64], a1[64];
    reg_zero(a0); reg_zero(a1); reg_fence(a0); reg_fence(a1);
    STAMP_IF(leader, 18);
    nb_sync(NB_KV, 256);
    mainloop<true, 14>(a0, a1, 1, 1, 0, 0, leader);
    {
      auto half = [&](float (&a)[64], int s, int m) {
#pragma unroll
        for (int j = 0; j < 4; j++)
          wgmma_n128_ss<1, 0>(a, mkdesc(RING + s * SLOT + m * 8192 + j * 2048, 8192, 1024, 1), mkdesc(RING + s * SLOT + 16384 + j * 32, 16, 1024, 1), 1);
      };
      auto kvmma = [&](float (&a)[64], float (&c)[32], int m) {
        reg_fence(a);
        uint32_t f[32];
#pragma unroll
        for (int i = 0; i < 32; i++) f[i] = pack(a[2 * i], a[2 * i + 1]);
        reg_zero(c);
        wg_fence();
#pragma unroll
        for (int k = 0; k < 8; k++) {
          wgmma_n64_rs<0>(c, f[4 * k], f[4 * k + 1], f[4 * k + 2], f[4 * k + 3], mkdesc(STG + (k >> 2) * 16384 + m * 8192 + (k & 3) * 32, 16, 1024, 1), k != 0);
          if (m && k == HAND_K) nb_arrive(NB_VQ, 256);
        }
        wg_commit();
      };
      float c0[32], c1[32];
      mbar_wait(B_FULL, 0);
      wg_fence();
      half(a0, 0, 0);
      wg_commit();
      mbar_wait(B_FULL + 8, 0);
      wg_fence();
      half(a0, 1, 0);
      wg_commit();
      wg_wait<2>();
      if (leader) mbar_arrive(B_EMPTY + 32);
      wg_fence();
      half(a1, 0, 1);
      half(a1, 1, 1);
      wg_commit();
      nb_sync(NB_PK, 256);
      wg_wait<1>();
      kvmma(a0, c0, 0);
      wg_wait<1>();
      if (leader) { mbar_arrive(B_EMPTY); mbar_arrive(B_EMPTY + 8); }
      STAMP_IF(leader, 19);
      kvmma(a1, c1, 1);
      const bool hp = ww >> 1;
      float c[4];
      float2 tt[8];
#pragma unroll
      for (int i = 0; i < 8; i++) tt[i] = lds64f(S_CSK + ((i >> 2) * 64 + hp * 32 + (i & 3) * 8 + 2 * t4) * 4);
      mbar_wait(B_CSV, 0);
#pragma unroll
      for (int i = 0; i < 4; i++) c[i] = -__uint_as_float(lds32(S_CSV + ((i >> 1) * 64 + ww * 16 + (i & 1) * 8 + g) * 4));
      wg_wait<0>();
      reg_fence(c0);
      reg_fence(c1);
      if (leader) mbar_arrive(B_SFREE);
      STAMP_IF(leader, 20);
      uint4* pp = g_kvp + (tn * 16 + tm) * 512 + t;
      auto put = [&](int q, const float* d) {
        const float ca = c[q & 2], cb = c[q | 1];
        const float2 ta = tt[2 * q], tb = tt[2 * q + 1];
        st_unit(pp + q * 128, pack(fmaf(ca, ta.x, d[0]), fmaf(ca, ta.y, d[1])), pack(fmaf(cb, ta.x, d[2]), fmaf(cb, ta.y, d[3])),
                pack(fmaf(ca, tb.x, d[4]), fmaf(ca, tb.y, d[5])), pack(fmaf(cb, tb.x, d[6]), fmaf(cb, tb.y, d[7])), par);
      };
      if (!hp) { put(0, c0); put(1, c0 + 8); put(2, c1); put(3, c1 + 8); }
      else { put(0, c0 + 16); put(1, c0 + 24); put(2, c1 + 16); put(3, c1 + 24); }
      STAMP_IF(leader, 47);
      {
        uint32_t p[16];
        nb_sync(NB_WG1, 128);
        if (ww == 0) { e_signal(H_KVP + tn, tm); await(H_KVP + tn, 0xffffu, ep); }
        nb_sync(NB_WG1, 128);
        STAMP_IF(leader, 1);
        poll_kvp(p, g_kvp + (tn * 16 + (lane >> 3) * 4) * 512 + tm * 32 + ww * 8 + (lane & 7), par, 1u);
        float r[8];
#pragma unroll
        for (int i = 0; i < 4; i++) {
          r[2 * i] = (bf_lo(p[i]) + bf_lo(p[4 + i])) + (bf_lo(p[8 + i]) + bf_lo(p[12 + i]));
          r[2 * i + 1] = (bf_hi(p[i]) + bf_hi(p[4 + i])) + (bf_hi(p[8 + i]) + bf_hi(p[12 + i]));
        }
        const bool u16 = lane & 16, u8 = lane & 8;
        const uint32_t wd = pack(xred(xred(r[0], r[4], u16, 16), xred(r[2], r[6], u16, 16), u8, 8), xred(xred(r[1], r[5], u16, 16), xred(r[3], r[7], u16, 16), u8, 8));
        const uint32_t w1 = __shfl_down_sync(0xffffffffu, wd, 1), w2 = __shfl_down_sync(0xffffffffu, wd, 2), w3 = __shfl_down_sync(0xffffffffu, wd, 3);
        const int grp = (tm & 1) * 2 + ((lane >> 3) & 1), row = ww * 2 + ((lane >> 2) & 1);
        if (t4 == 0) st_unit(g_kv + tn * 512 + ((tm >> 3) * 4 + grp) * 64 + row * 8 + (((tm & 2) * 2 + ((tm >> 1) & 2) + (lane >> 4)) ^ row), wd, w1, w2, w3, par);
        nb_sync(NB_WG1, 128);
        if (ww == 0) { if (!KV_SPEC) e_signal(H_KV + tn, tm); e_arrive(B_WK); }
      }
      STAMP_IF(leader, 21);
    }
    const uint32_t sx = lane & 7, sc = lane >> 4;
    const uint32_t sa = STG + (ww * 16 + (lane & 15)) * 128;
    const uint32_t sw[4] = {sa + ((sc ^ sx) << 4), sa + (((2 + sc) ^ sx) << 4), sa + (((4 + sc) ^ sx) << 4), sa + (((6 + sc) ^ sx) << 4)};
    auto residual = [&]() {
      float ka[4], kb[4];
#pragma unroll
      for (int i = 0; i < 4; i++) {
        const float2 st = lds64f(S_KSTAT + ((i >> 1) * 64 + ww * 16 + (i & 1) * 8 + g) * 8);
        const float r = st.y * LN2;
        ka[i] = 1.f + r; kb[i] = -st.x * r;
      }
#pragma unroll
      for (int j = 0; j < 8; j++) {
        if ((j & 3) == 0) mbar_wait(B_XRES + 8 * (j >> 2), 0);
        const uint4 v = ldsm4(sw[j & 3] + (j >> 2) * 16384), u = ldsm4(sw[j & 3] + (j >> 2) * 16384 + 8192);
        const uint32_t vv[4] = {v.x, v.y, v.z, v.w}, uu[4] = {u.x, u.y, u.z, u.w};
#pragma unroll
        for (int i = 0; i < 4; i++) {
          a0[8 * j + 2 * i] = fmaf(bf_lo(vv[i]), ka[i & 1], kb[i & 1]);
          a0[8 * j + 2 * i + 1] = fmaf(bf_hi(vv[i]), ka[i & 1], kb[i & 1]);
          a1[8 * j + 2 * i] = fmaf(bf_lo(uu[i]), ka[2 + (i & 1)], kb[2 + (i & 1)]);
          a1[8 * j + 2 * i + 1] = fmaf(bf_hi(uu[i]), ka[2 + (i & 1)], kb[2 + (i & 1)]);
        }
      }
      reg_fence(a0);
      reg_fence(a1);
      STAMP_IF(leader, 22);
    };
    residual();
    nb_arrive(NB_KVB, 320);
    uint32_t oh[4];
    {
      mbar_wait(B_SEL, 0);
      const int r0 = key_token(lds32(S_SEL + t4 * 16)) - tm * 128, r1 = key_token(lds32(S_SEL + t4 * 16 + 8)) - tm * 128;
#pragma unroll
      for (int i = 0; i < 4; i++) {
        const int row = (i >> 1) * 64 + ww * 16 + (i & 1) * 8 + g;
        oh[i] = (r0 == row ? 0x3f00u : 0u) | (r1 == row ? 0x3f000000u : 0u);
      }
    }
    uint32_t va = RING + 16384 + sc * 8192 + (ww * 16 + (lane & 8)) * 128 + sx * 16 + (lane >> 3) * 4;
    asm volatile("" : "+r"(va));
    {
      auto own = [&](int r) {
        nb_sync(NB_OWN0 + r, r ? 256 : 288);
        mbar_wait(B_FULL + 8 * (3 + r), 1);
        STAMP_IF(leader, 25 + r);
        const uint64_t dw = mkdesc(RING + (3 + r) * SLOT, 8192, 1024, 1), dx = mkdesc(STG + r * 16384, 16, 1024, 1);
        wg_fence();
#pragma unroll
        for (int j = 0; j < 4; j++) {
          wgmma_n128_ss<0, 1>(a0, dx + j * 2, dw + j * 128, 1);
          wgmma_n128_ss<0, 1>(a1, dx + j * 2 + 512, dw + j * 128, 1);
        }
        wg_commit();
      };
      own(0);
      wg_wait<0>();
      if (leader) mbar_arrive(B_EMPTY + 24);
      own(1);
      auto check = [&](int r, int s) {
          uint32_t bad;
          asm volatile("{\n.reg .u32 a, b, c, d, e, f, g, h;\n.reg .pred p;\n"
                       "ld.shared.u32 a, [%1];\nld.shared.u32 b, [%1+128];\nld.shared.u32 c, [%1+256];\nld.shared.u32 d, [%1+384];\n"
                       "ld.shared.u32 e, [%1+512];\nld.shared.u32 f, [%1+640];\nld.shared.u32 g, [%1+768];\nld.shared.u32 h, [%1+896];\n"
                       "lop3.b32 a, a, b, %2, 0x7e;\nlop3.b32 c, c, d, %2, 0x7e;\nlop3.b32 e, e, f, %2, 0x7e;\nlop3.b32 g, g, h, %2, 0x7e;\n"
                       "lop3.b32 a, a, c, e, 0xfe;\nlop3.b32 a, a, g, 1, 0xa8;\nsetp.ne.u32 p, a, 0;\nvote.sync.any.pred p, p, 0xffffffff;\nselp.u32 %0, 1, 0, p;\n}"
                       : "=r"(bad) : "r"(va + s * SLOT), "r"(par) : "memory");
          if (bad) {
            const uint4* src = reinterpret_cast<const uint4*>(g_o + (tm * 128 + sc * 64 + ww * 16 + (lane & 15)) * 1024 + out_kblock(r, tn) * 64);
#pragma unroll 1
            for (int i = 0; i < 8; i++) {
              uint32_t v[4];
              asm volatile("{\n.reg .b64 x, y;\n.reg .b128 z;\n.reg .pred p, q, h;\n.reg .u32 c, b;\nmov.u32 c, 0;\nsetp.ne.u32 h, %6, 0;\nLW:\n"
                           "ld.relaxed.gpu.global.b128 z, [%4];\nmov.b128 {x, y}, z;\nmov.b64 {%0,%1}, x;\nmov.b64 {%2,%3}, y;\n"
                           "selp.b64 x, y, x, h;\nshr.b64 x, x, %7;\ncvt.u32.u64 b, x;\nand.b32 b, b, 1;\nsetp.eq.u32 p, b, %5;\n"
                           "vote.sync.all.pred p, p, 0xffffffff;\n@p bra.uni LD;\nadd.u32 c, c, 1;\nsetp.lt.u32 q, c, 1000000;\n@q bra.uni LW;\ntrap;\nLD:\n}"
                           : "=&r"(v[0]), "=&r"(v[1]), "=&r"(v[2]), "=&r"(v[3]) : "l"(src + i), "r"(par), "r"(sc), "r"((lane & 8) * 4) : "memory");
              sts128(RING + 16384 + s * SLOT + sc * 8192 + (ww * 16 + (lane & 15)) * 128 + ((i ^ sx) << 4), v[0], v[1], v[2], v[3]);
            }
            fence_async_smem();
            __syncwarp();
          }
      };
      int s = 0, ph = 0;
      uint32_t prev = B_EMPTY + 32;
#pragma unroll 1
      for (int r = 2; r < 12; r++) {
        mbar_wait(B_FULL + 8 * s, ph);
        check(r, s);
        if (!LITE || ((LITE_MASK >> 27) & 1)) STAMP_IF(leader && r == 2, 27);
        const uint64_t dw = mkdesc(RING, 8192, 1024, 1) + s * (SLOT >> 4), dx = mkdesc(RING + 16384, 16, 1024, 1) + s * (SLOT >> 4);
        wg_fence();
#pragma unroll
        for (int j = 0; j < 4; j++) {
          wgmma_n128_ss<0, 1>(a0, dx + j * 2, dw + j * 128, 1);
          wgmma_n128_ss<0, 1>(a1, dx + j * 2 + 512, dw + j * 128, 1);
        }
        wg_commit();
        wg_wait<1>();
        if (leader) mbar_arrive(prev);
        prev = B_EMPTY + 8 * s;
        if (++s == NST) { s = 0; ph ^= 1; }
      }
      auto half = [&](float (&a)[64], int s, int m) {
        const uint64_t dw = mkdesc(RING, 8192, 1024, 1) + s * (SLOT >> 4), dx = mkdesc(RING + 16384 + m * 8192, 16, 1024, 1) + s * (SLOT >> 4);
#pragma unroll
        for (int j = 0; j < 4; j++) wgmma_n128_ss<0, 1>(a, dx + j * 2, dw + j * 128, 1);
      };
      auto store = [&](float (&a)[64], int m) {
        reg_fence(a);
#pragma unroll
        for (int j = 0; j < 8; j++) {
          stsm4(sw[j & 3] + (j >> 2) * 16384 + m * 8192, pack(a[8 * j], a[8 * j + 1]), pack(a[8 * j + 2], a[8 * j + 3]), pack(a[8 * j + 4], a[8 * j + 5]), pack(a[8 * j + 6], a[8 * j + 7]));
          if ((j & 3) == 3) {
            fence_async_smem();
            e_store2d(&mp.m_out, tn * 128 + (j >> 2) * 64, tm * 128 + m * 64 + ww * 16, STG + (j >> 2) * 16384 + m * 8192 + ww * 2048);
          }
        }
      };
#pragma unroll 1
      for (int q = 0; q < 4; q++) {
        mbar_wait(B_FULL + 8 * q, 0);
        check(12 + q, q);
        wg_fence();
        half(a0, q, 0);
        wg_commit();
      }
      nb_sync(NB_ST, 288);
      wg_fence();
      wgmma_n128_rs<1>(a0, oh[0], oh[1], oh[0], oh[1], mkdesc(FR, 1024, 0, 1), 1);
      wg_commit();
      wg_fence();
      half(a1, 0, 1);
      half(a1, 1, 1);
      wg_commit();
      wg_wait<1>();
      store(a0, 0);
      wg_fence();
      half(a1, 2, 1);
      half(a1, 3, 1);
      wgmma_n128_rs<1>(a1, oh[2], oh[3], oh[2], oh[3], mkdesc(FR, 1024, 0, 1), 1);
      wg_commit();
      wg_wait<0>();
      STAMP_IF(leader, 28);
      store(a1, 1);
    }
    bulk_wait_read();
    if (bid == 0 && leader) st_relaxed(&g_epoch, ep);
    STAMP_IF(leader, 29);
  } else {
    asm volatile("setmaxnreg.inc.sync.aligned.u32 216;");
    const int g = lane >> 2, t4 = lane & 3;
    const bool leader = tid == 0;
    const uint32_t sx = lane & 7, sc = lane >> 4;
    const uint32_t sa = STG + (w * 16 + (lane & 15)) * 128;
    const uint32_t sw[4] = {sa + ((sc ^ sx) << 4), sa + (((2 + sc) ^ sx) << 4), sa + (((4 + sc) ^ sx) << 4), sa + (((6 + sc) ^ sx) << 4)};
    float a0[64], a1[64];
    reg_zero(a0); reg_zero(a1); reg_fence(a0); reg_fence(a1);
    mainloop<true>(a0, a1, 0, 0, NB_KV, 0, leader);
    STAMP_IF(leader, 33);
    {
      nb_sync(NB_FDONE, 416);
      STAMP_IF(leader, 34);
      const uint32_t par = lds32(S_EPOCH) & 1u;
#pragma unroll 1
      for (int m = 0;; m++) {
        const uint32_t ca = S_CSK + (m * 64 + w * 16 + g) * 4;
        const float c[2] = {-lds32v(ca), -lds32v(ca + 32)};
        float z[2] = {0.f, 0.f}, tt[2] = {0.f, 0.f};
#pragma unroll
        for (int j = 0; j < 8; j++) {
          const float4 s0 = lds128v(S_KSTAT + (j * 16 + 2 * t4) * 8), s1 = lds128v(S_KSTAT + (j * 16 + 8 + 2 * t4) * 8);
          const float mu[4] = {s0.x, s0.z, s1.x, s1.z}, rl[4] = {s0.y, s0.w, s1.y, s1.w};
          float p[8];
#pragma unroll
          for (int i = 0; i < 8; i++) {
            const int r = (i >> 1) & 1, cc = (i >> 2) * 2 + (i & 1);
            p[i] = phi2(fmaf(c[r], mu[cc], a0[8 * j + i]) * rl[cc]);
            a0[8 * j + i] = a1[8 * j + i];
            z[r] += p[i];
            p[i] *= rl[cc];
            tt[r] = fmaf(p[i], mu[cc], tt[r]);
          }
          stsm4(sw[j & 3] + (j >> 2) * 16384 + m * 8192, pack(p[0], p[1]), pack(p[2], p[3]), pack(p[4], p[5]), pack(p[6], p[7]));
        }
        const bool u2 = lane & 2, u1 = lane & 1;
        const float v = xred(xred(z[0], tt[0], u2, 2), xred(z[1], tt[1], u2, 2), u1, 1);
        if (u2) sts32(ca + (t4 & 1) * 32, __float_as_uint(v));
        else st_relaxed(g_z + tm * 1024 + tn * 128 + m * 64 + w * 16 + t4 * 8 + g, tagf(v * LOG2E, par));
        if (m) break;
      }
      fence_async_smem();
      nb_arrive(NB_PK, 256);
      nb_arrive(NB_Z, 160);
    }
    STAMP_IF(leader, 35);
    const uint32_t ep = lds32(S_EPOCH);
    {
      nb_sync(NB_CSQ, 160);
      float mu[4];
#pragma unroll
      for (int i = 0; i < 4; i++) {
        const float2 st = lds64f(S_KSTAT + ((i >> 1) * 64 + w * 16 + (i & 1) * 8 + g) * 8);
        mu[i] = -st.x;
      }
#pragma unroll
      for (int j = 0; j < 16; j++) {
        const float2 c = lds64f(S_CSQ + (j * 8 + 2 * t4) * 4);
        a0[4 * j] = mu[0] * c.x; a0[4 * j + 1] = mu[0] * c.y; a0[4 * j + 2] = mu[1] * c.x; a0[4 * j + 3] = mu[1] * c.y;
        a1[4 * j] = mu[2] * c.x; a1[4 * j + 1] = mu[2] * c.y; a1[4 * j + 2] = mu[3] * c.x; a1[4 * j + 3] = mu[3] * c.y;
      }
      reg_fence(a0); reg_fence(a1);
    }
    STAMP_IF(leader, 40);
    nb_sync(NB_VQ, 256);
    mainloop<false, 13>(a0, a1, 2, 0, 0, 4 + (tn & 3), leader);
    {
      uint32_t f[2][16];
      const uint32_t ra = S_KSTAT + (w * 16 + g) * 8 + 4;
      auto phi = [&](const float (&a)[64], int off, int m, int i0, int i1, uint32_t (&o)[16]) {
        const float r0 = lds32v(ra + m * 512), r1 = lds32v(ra + m * 512 + 64);
#pragma unroll
        for (int i = i0; i < i1; i++) o[i] = pack(phi2(a[off + 2 * i] * (i & 1 ? r1 : r0)), phi2(a[off + 2 * i + 1] * (i & 1 ? r1 : r0)));
      };
      auto half = [&](float (&a)[64], int s, int m) {
        const bool xr = ((13 + s) >> 1) == 4 + (tn & 3);
        if (!m) {
          mbar_wait(B_FULL + 8 * s, 1);
          if (xr) mbar_wait(B_XRES + 8 * (~s & 1), 0);
          wg_fence();
        }
        const uint64_t dx = mkdesc(m * 8192, 16, 1024, 1) + ((xr ? STG + (~s & 1) * 16384 : RING + s * SLOT + 16384) >> 4);
#pragma unroll
        for (int j = 0; j < 4; j++) wgmma_n128_ss<0, 1>(a, dx + j * 2, mkdesc(RING + s * SLOT + j * 2048, 8192, 1024, 1), 1);
      };
      half(a0, 0, 0);
      wg_commit();
      half(a0, 1, 0);
      wg_commit();
      wg_wait<2>();
      if (leader) mbar_arrive(B_EMPTY + 32);
      half(a0, 2, 0);
      wg_commit();
      wg_fence();
      half(a1, 0, 1);
      half(a1, 1, 1);
      wg_commit();
      wg_wait<1>();
      reg_fence(a0);
      phi(a0, 0, 0, 0, PHI_CUT, f[0]);
      wg_fence();
      half(a1, 2, 1);
      wg_commit();
      phi(a0, 0, 0, PHI_CUT, 16, f[0]);
      nb_sync(NB_KVB, 320);
      wg_wait<0>();
      if (leader) { mbar_arrive(B_EMPTY); mbar_arrive(B_EMPTY + 8); mbar_arrive(B_EMPTY + 16); }
      reg_fence(a1);
      STAMP_IF(leader, 36);
      const uint32_t mk[4] = {t4 == 0, t4 == 1, t4 == 2, t4 == 3};
      uint64_t db = mkdesc(KVB, 16, 1024, 1);
      uint32_t so = 0;
#pragma unroll 1
      for (int j = 0;; j++) {
        float oc[2][2][20];
        auto mma = [&](const uint32_t (&a)[16], float (&o)[2][20]) {
          reg_zero(o[0]); reg_zero(o[1]);
          wg_fence();
          wgmma_n40_rs<0>(o[0], a[0], a[1], a[2], a[3], db, 0);
          wgmma_n40_rs<0>(o[1], a[8], a[9], a[10], a[11], db + 4, 0);
          wgmma_n40_rs<0>(o[0], a[4], a[5], a[6], a[7], db + 2, 1);
          wgmma_n40_rs<0>(o[1], a[12], a[13], a[14], a[15], db + 6, 1);
          wg_commit();
        };
        auto fin = [&](int m, float (&o)[2][20]) {
          const uint32_t m0 = mk[2 * m], m1 = mk[2 * m + 1];
#pragma unroll
          for (int h = 0; h < 2; h++) {
            const float r0 = rcp(o[h][0] + 1e-6f * LOG2E), r1 = rcp(o[h][2] + 1e-6f * LOG2E);
#pragma unroll
            for (int q = 0; q < 2; q++)
              stsm4(sw[h * 2 + q] + so + m * 8192,
                    bsel(pack(o[h][4 + 8 * q] * r0, o[h][5 + 8 * q] * r0), ep, m0), bsel(pack(o[h][6 + 8 * q] * r1, o[h][7 + 8 * q] * r1), ep, m1),
                    bsel(pack(o[h][8 + 8 * q] * r0, o[h][9 + 8 * q] * r0), ep, m0), bsel(pack(o[h][10 + 8 * q] * r1, o[h][11 + 8 * q] * r1), ep, m1));
          }
        };
        mma(f[0], oc[0]);
        phi(a1, 0, 1, 0, 16, f[1]);
        wg_wait<0>();
        reg_fence(oc[0][0]); reg_fence(oc[0][1]);
        mma(f[1], oc[1]);
        fin(0, oc[0]);
        if (j == 0) { fence_async_smem(); nb_arrive(NB_Q0, 192); }
        wg_wait<0>();
        reg_fence(oc[1][0]); reg_fence(oc[1][1]);
        fin(1, oc[1]);
        fence_async_smem();
        if (j) break;
        nb_arrive(NB_OWN0, 288);
        STAMP_IF(leader, 38);
#pragma unroll
        for (int i = 0; i < 32; i++) a1[i] = a1[32 + i];
        phi(a0, 32, 0, 0, 16, f[0]);
        db = mkdesc(KVB + 5120, 16, 1024, 1);
        so = 16384;
      }
      nb_arrive(NB_OWN1, 256);
      nb_arrive(NB_H1, 160);
      STAMP_IF(leader, 39);
    }
  }
}

#undef CK
typedef CUresult (*EncodeFn)(CUtensorMap*, CUtensorMapDataType, cuuint32_t, void*, const cuuint64_t*, const cuuint64_t*, const cuuint32_t*,
                             const cuuint32_t*, CUtensorMapInterleave, CUtensorMapSwizzle, CUtensorMapL2promotion, CUtensorMapFloatOOBfill);

void make_map(EncodeFn enc, CUtensorMap* m, const void* p, int rank, uint64_t d0, uint64_t d1, uint64_t d2, uint64_t s1, uint64_t s2,
              uint32_t b0, uint32_t b1, uint32_t b2, CUtensorMapSwizzle sw) {
  cuuint64_t gd[3] = {d0, d1, d2}, gs[2] = {s1, s2};
  cuuint32_t bd[3] = {b0, b1, b2}, es[3] = {1, 1, 1};
  enc(m, CU_TENSOR_MAP_DATA_TYPE_BFLOAT16, rank, const_cast<void*>(p), gd, gs, bd, es, CU_TENSOR_MAP_INTERLEAVE_NONE, sw,
      CU_TENSOR_MAP_L2_PROMOTION_L2_128B, CU_TENSOR_MAP_FLOAT_OOB_FILL_NONE);
}

}

extern "C" void kernel_launch(void* const* d_in, const int* in_sizes, int n_in, void* d_out, int out_size) {
  (void)in_sizes; (void)n_in; (void)out_size;
  void* fn = nullptr;
  cudaDriverEntryPointQueryResult qr;
  cudaGetDriverEntryPoint("cuTensorMapEncodeTiled", &fn, cudaEnableDefault, &qr);
  EncodeFn enc = (EncodeFn)fn;
  void* o;
  cudaGetSymbolAddress(&o, g_o);
  const CUtensorMapSwizzle S128 = CU_TENSOR_MAP_SWIZZLE_128B, S64 = CU_TENSOR_MAP_SWIZZLE_64B, S0 = CU_TENSOR_MAP_SWIZZLE_NONE;
  Params mp;
  mp.x = (const char*)d_in[0]; mp.wqkv = (const char*)d_in[1]; mp.w_r = (const char*)d_in[4];
  mp.wg = (const char*)d_in[5]; mp.wu = (const char*)d_in[6]; mp.wd = (const char*)d_in[7]; mp.wo = (const char*)d_in[2];
  make_map(enc, &mp.m_wqkv, d_in[1], 3, 64, 1024, 48, 6144, 128, 64, 64, 2, S128);
  make_map(enc, &mp.m_x, d_in[0], 2, 1024, 2048, 1, 2048, 0, 64, 128, 1, S128);
  make_map(enc, &mp.m_os, o, 2, 1024, 2048, 1, 2048, 0, 64, 64, 1, S128);
  make_map(enc, &mp.m_o, o, 2, 1024, 2048, 1, 2048, 0, 64, 128, 1, S128);
  make_map(enc, &mp.m_wo, d_in[2], 3, 64, 1024, 16, 2048, 128, 64, 64, 2, S128);
  make_map(enc, &mp.m_xs, d_in[0], 2, 1024, 2048, 1, 2048, 0, 256, 16, 1, S0);
  const char *wg = (const char*)d_in[5], *wu = (const char*)d_in[6];
  make_map(enc, &mp.m_gu, wu < wg ? wu : wg, 3, 3584, 1024, 2, 7168, (uint64_t)(wu < wg ? wg - wu : wu - wg), 32, 64, 2, S64);
  make_map(enc, &mp.m_down, d_in[7], 2, 1024, 3584, 1, 2048, 0, 64, 64, 1, S128);
  make_map(enc, &mp.m_out, d_out, 2, 1024, 2048, 1, 2048, 0, 64, 16, 1, S128);
  int dev = 0, sms = 0;
  cudaGetDevice(&dev);
  cudaDeviceGetAttribute(&sms, cudaDevAttrMultiProcessorCount, dev);
  auto kern = sms == 132 ? fused_kernel<true> : fused_kernel<false>;
  cudaFuncSetAttribute(kern, cudaFuncAttributeMaxDynamicSharedMemorySize, SMEM_BYTES);
  kern<<<132, 512, SMEM_BYTES>>>(mp);
}
```

```cpp
#include <cuda_runtime.h>
#include <cuda.h>
#include <cuda_bf16.h>
#include <stdint.h>

namespace {

template <int TA, int TB>
__device__ __forceinline__ void wgmma_n8_ss(float (&d)[4], uint64_t da, uint64_t db, int sc) {
  asm volatile("{\n.reg .pred p;\nsetp.ne.b32 p, %6, 0;\n"
    "wgmma.mma_async.sync.aligned.m64n8k16.f32.bf16.bf16 {%0, %1, %2, %3}, %4, %5, p, 1, 1, %7, %8;\n}\n"
    : "+f"(d[0]), "+f"(d[1]), "+f"(d[2]), "+f"(d[3])
    : "l"(da), "l"(db), "r"(sc), "n"(TA), "n"(TB));
}
template <int TA, int TB>
__device__ __forceinline__ void wgmma_n16_ss(float (&d)[8], uint64_t da, uint64_t db, int sc) {
  asm volatile("{\n.reg .pred p;\nsetp.ne.b32 p, %10, 0;\n"
    "wgmma.mma_async.sync.aligned.m64n16k16.f32.bf16.bf16 {%0, %1, %2, %3, %4, %5, %6, %7}, %8, %9, p, 1, 1, %11, %12;\n}\n"
    : "+f"(d[0]), "+f"(d[1]), "+f"(d[2]), "+f"(d[3]), "+f"(d[4]), "+f"(d[5]), "+f"(d[6]), "+f"(d[7])
    : "l"(da), "l"(db), "r"(sc), "n"(TA), "n"(TB));
}
template <int TB>
__device__ __forceinline__ void wgmma_n40_rs(float (&d)[20], uint32_t a0, uint32_t a1, uint32_t a2, uint32_t a3, uint64_t db, int sc) {
  asm volatile("{\n.reg .pred p;\nsetp.ne.b32 p, %25, 0;\n"
    "wgmma.mma_async.sync.aligned.m64n40k16.f32.bf16.bf16 {%0, %1, %2, %3, %4, %5, %6, %7, %8, %9, %10, %11, %12, %13, %14, %15, %16, %17, %18, %19}, {%20,%21,%22,%23}, %24, p, 1, 1, %26;\n}\n"
    : "+f"(d[0]), "+f"(d[1]), "+f"(d[2]), "+f"(d[3]), "+f"(d[4]), "+f"(d[5]), "+f"(d[6]), "+f"(d[7]),
      "+f"(d[8]), "+f"(d[9]), "+f"(d[10]), "+f"(d[11]), "+f"(d[12]), "+f"(d[13]), "+f"(d[14]), "+f"(d[15]),
      "+f"(d[16]), "+f"(d[17]), "+f"(d[18]), "+f"(d[19])
    : "r"(a0), "r"(a1), "r"(a2), "r"(a3), "l"(db), "r"(sc), "n"(TB));
}
template <int TB>
__device__ __forceinline__ void wgmma_n64_rs(float (&d)[32], uint32_t a0, uint32_t a1, uint32_t a2, uint32_t a3, uint64_t db, int sc) {
  asm volatile("{\n.reg .pred p;\nsetp.ne.b32 p, %37, 0;\n"
    "wgmma.mma_async.sync.aligned.m64n64k16.f32.bf16.bf16 {%0, %1, %2, %3, %4, %5, %6, %7, %8, %9, %10, %11, %12, %13, %14, %15, %16, %17, %18, %19, %20, %21, %22, %23, %24, %25, %26, %27, %28, %29, %30, %31}, {%32,%33,%34,%35}, %36, p, 1, 1, %38;\n}\n"
    : "+f"(d[0]), "+f"(d[1]), "+f"(d[2]), "+f"(d[3]), "+f"(d[4]), "+f"(d[5]), "+f"(d[6]), "+f"(d[7]),
      "+f"(d[8]), "+f"(d[9]), "+f"(d[10]), "+f"(d[11]), "+f"(d[12]), "+f"(d[13]), "+f"(d[14]), "+f"(d[15]),
      "+f"(d[16]), "+f"(d[17]), "+f"(d[18]), "+f"(d[19]), "+f"(d[20]), "+f"(d[21]), "+f"(d[22]), "+f"(d[23]),
      "+f"(d[24]), "+f"(d[25]), "+f"(d[26]), "+f"(d[27]), "+f"(d[28]), "+f"(d[29]), "+f"(d[30]), "+f"(d[31])
    : "r"(a0), "r"(a1), "r"(a2), "r"(a3), "l"(db), "r"(sc), "n"(TB));
}
template <int TA, int TB>
__device__ __forceinline__ void wgmma_n128_ss(float (&d)[64], uint64_t da, uint64_t db, int sc) {
  asm volatile("{\n.reg .pred p;\nsetp.ne.b32 p, %66, 0;\n"
    "wgmma.mma_async.sync.aligned.m64n128k16.f32.bf16.bf16 {%0, %1, %2, %3, %4, %5, %6, %7, %8, %9, %10, %11, %12, %13, %14, %15, %16, %17, %18, %19, %20, %21, %22, %23, %24, %25, %26, %27, %28, %29, %30, %31, %32, %33, %34, %35, %36, %37, %38, %39, %40, %41, %42, %43, %44, %45, %46, %47, %48, %49, %50, %51, %52, %53, %54, %55, %56, %57, %58, %59, %60, %61, %62, %63}, %64, %65, p, 1, 1, %67, %68;\n}\n"
    : "+f"(d[0]), "+f"(d[1]), "+f"(d[2]), "+f"(d[3]), "+f"(d[4]), "+f"(d[5]), "+f"(d[6]), "+f"(d[7]),
      "+f"(d[8]), "+f"(d[9]), "+f"(d[10]), "+f"(d[11]), "+f"(d[12]), "+f"(d[13]), "+f"(d[14]), "+f"(d[15]),
      "+f"(d[16]), "+f"(d[17]), "+f"(d[18]), "+f"(d[19]), "+f"(d[20]), "+f"(d[21]), "+f"(d[22]), "+f"(d[23]),
      "+f"(d[24]), "+f"(d[25]), "+f"(d[26]), "+f"(d[27]), "+f"(d[28]), "+f"(d[29]), "+f"(d[30]), "+f"(d[31]),
      "+f"(d[32]), "+f"(d[33]), "+f"(d[34]), "+f"(d[35]), "+f"(d[36]), "+f"(d[37]), "+f"(d[38]), "+f"(d[39]),
      "+f"(d[40]), "+f"(d[41]), "+f"(d[42]), "+f"(d[43]), "+f"(d[44]), "+f"(d[45]), "+f"(d[46]), "+f"(d[47]),
      "+f"(d[48]), "+f"(d[49]), "+f"(d[50]), "+f"(d[51]), "+f"(d[52]), "+f"(d[53]), "+f"(d[54]), "+f"(d[55]),
      "+f"(d[56]), "+f"(d[57]), "+f"(d[58]), "+f"(d[59]), "+f"(d[60]), "+f"(d[61]), "+f"(d[62]), "+f"(d[63])
    : "l"(da), "l"(db), "r"(sc), "n"(TA), "n"(TB));
}
template <int TB>
__device__ __forceinline__ void wgmma_n128_rs(float (&d)[64], uint32_t a0, uint32_t a1, uint32_t a2, uint32_t a3, uint64_t db, int sc) {
  asm volatile("{\n.reg .pred p;\nsetp.ne.b32 p, %69, 0;\n"
    "wgmma.mma_async.sync.aligned.m64n128k16.f32.bf16.bf16 {%0, %1, %2, %3, %4, %5, %6, %7, %8, %9, %10, %11, %12, %13, %14, %15, %16, %17, %18, %19, %20, %21, %22, %23, %24, %25, %26, %27, %28, %29, %30, %31, %32, %33, %34, %35, %36, %37, %38, %39, %40, %41, %42, %43, %44, %45, %46, %47, %48, %49, %50, %51, %52, %53, %54, %55, %56, %57, %58, %59, %60, %61, %62, %63}, {%64,%65,%66,%67}, %68, p, 1, 1, %70;\n}\n"
    : "+f"(d[0]), "+f"(d[1]), "+f"(d[2]), "+f"(d[3]), "+f"(d[4]), "+f"(d[5]), "+f"(d[6]), "+f"(d[7]),
      "+f"(d[8]), "+f"(d[9]), "+f"(d[10]), "+f"(d[11]), "+f"(d[12]), "+f"(d[13]), "+f"(d[14]), "+f"(d[15]),
      "+f"(d[16]), "+f"(d[17]), "+f"(d[18]), "+f"(d[19]), "+f"(d[20]), "+f"(d[21]), "+f"(d[22]), "+f"(d[23]),
      "+f"(d[24]), "+f"(d[25]), "+f"(d[26]), "+f"(d[27]), "+f"(d[28]), "+f"(d[29]), "+f"(d[30]), "+f"(d[31]),
      "+f"(d[32]), "+f"(d[33]), "+f"(d[34]), "+f"(d[35]), "+f"(d[36]), "+f"(d[37]), "+f"(d[38]), "+f"(d[39]),
      "+f"(d[40]), "+f"(d[41]), "+f"(d[42]), "+f"(d[43]), "+f"(d[44]), "+f"(d[45]), "+f"(d[46]), "+f"(d[47]),
      "+f"(d[48]), "+f"(d[49]), "+f"(d[50]), "+f"(d[51]), "+f"(d[52]), "+f"(d[53]), "+f"(d[54]), "+f"(d[55]),
      "+f"(d[56]), "+f"(d[57]), "+f"(d[58]), "+f"(d[59]), "+f"(d[60]), "+f"(d[61]), "+f"(d[62]), "+f"(d[63])
    : "r"(a0), "r"(a1), "r"(a2), "r"(a3), "l"(db), "r"(sc), "n"(TB));
}

__device__ __forceinline__ void poll1f(uint32_t (&v)[1], const void* p, uint32_t tag, uint32_t mask) {
  asm volatile("{\n.reg .pred p, q;\n.reg .u32 c, b;\n.reg .b64 x, y;\n.reg .b128 z;\nmov.u32 c, 0;\nLW:\n"
               "ld.relaxed.gpu.global.u32 %0, [%1+0];\n"
               "xor.b32 b, %0, %2;\n"
               "and.b32 b, b, %3;\nsetp.eq.u32 p, b, 0;\nvote.sync.all.pred p, p, 0xffffffff;\n@p bra.uni LD;\n"
               "nanosleep.u32 50;\nadd.u32 c, c, 1;\nsetp.lt.u32 q, c, 1000000;\n@q bra.uni LW;\ntrap;\nLD:\n}"
               : "=&r"(v[0])
               : "l"(p), "r"(tag), "r"(mask) : "memory");
}
__device__ __forceinline__ void poll0(uint32_t (&v)[1], const void* p, uint32_t tag, uint32_t mask) {
  asm volatile("{\n.reg .pred p, q;\n.reg .u32 c, b;\n.reg .b64 x, y;\n.reg .b128 z;\nmov.u32 c, 0;\nLW:\n"
               "ld.relaxed.gpu.global.u32 %0, [%1+0];\n"
               "xor.b32 b, %0, %2;\n"
               "and.b32 b, b, %3;\nsetp.eq.u32 p, b, 0;\nvote.sync.all.pred p, p, 0xffffffff;\n@p bra.uni LD;\n"
               "add.u32 c, c, 1;\nsetp.lt.u32 q, c, 1000000;\n@q bra.uni LW;\ntrap;\nLD:\n}"
               : "=&r"(v[0])
               : "l"(p), "r"(tag), "r"(mask) : "memory");
}
__device__ __forceinline__ void poll_pair(uint32_t (&v)[2], const void* p, uint32_t tag, uint32_t mask) {
  asm volatile("{\n.reg .pred p, q;\n.reg .u32 c, b;\n.reg .b64 x, y;\n.reg .b128 z;\nmov.u32 c, 0;\nLW:\n"
               "ld.relaxed.gpu.global.b64 x, [%2+0];\nmov.b64 {%0,%1}, x;\n"
               "xor.b32 b, %0, %3;\n"
               "and.b32 b, b, %4;\nsetp.eq.u32 p, b, 0;\nvote.sync.all.pred p, p, 0xffffffff;\n@p bra.uni LD;\n"
               "nanosleep.u32 100;\nadd.u32 c, c, 1;\nsetp.lt.u32 q, c, 1000000;\n@q bra.uni LW;\ntrap;\nLD:\n}"
               : "=&r"(v[0]), "=&r"(v[1])
               : "l"(p), "r"(tag), "r"(mask) : "memory");
}
__device__ __forceinline__ void poll_quad(uint32_t (&v)[4], const void* p, uint32_t tag, uint32_t mask) {
  asm volatile("{\n.reg .pred p, q;\n.reg .u32 c, b;\n.reg .b64 x, y;\n.reg .b128 z;\nmov.u32 c, 0;\nLW:\n"
               "ld.relaxed.gpu.global.v4.u32 {%0,%1,%2,%3}, [%4+0];\n"
               "xor.b32 b, %0, %5;\n"
               "lop3.b32 b, b, %1, %5, 0xf6;\nlop3.b32 b, b, %2, %5, 0xf6;\nlop3.b32 b, b, %3, %5, 0xf6;\n"
               "and.b32 b, b, %6;\nsetp.eq.u32 p, b, 0;\nvote.sync.all.pred p, p, 0xffffffff;\n@p bra.uni LD;\n"
               "nanosleep.u32 200;\nadd.u32 c, c, 1;\nsetp.lt.u32 q, c, 1000000;\n@q bra.uni LW;\ntrap;\nLD:\n}"
               : "=&r"(v[0]), "=&r"(v[1]), "=&r"(v[2]), "=&r"(v[3])
               : "l"(p), "r"(tag), "r"(mask) : "memory");
}
__device__ __forceinline__ void poll8x4(uint32_t (&v)[32], const void* p, uint32_t tag, uint32_t mask) {
  asm volatile("{\n.reg .pred p, q;\n.reg .u32 c, b;\n.reg .b64 x, y;\n.reg .b128 z;\nmov.u32 c, 0;\nLW:\n"
               "ld.relaxed.gpu.global.v4.u32 {%0,%1,%2,%3}, [%32+0];\n"
               "ld.relaxed.gpu.global.v4.u32 {%4,%5,%6,%7}, [%32+2048];\n"
               "ld.relaxed.gpu.global.v4.u32 {%8,%9,%10,%11}, [%32+4096];\n"
               "ld.relaxed.gpu.global.v4.u32 {%12,%13,%14,%15}, [%32+6144];\n"
               "ld.relaxed.gpu.global.v4.u32 {%16,%17,%18,%19}, [%32+8192];\n"
               "ld.relaxed.gpu.global.v4.u32 {%20,%21,%22,%23}, [%32+10240];\n"
               "ld.relaxed.gpu.global.v4.u32 {%24,%25,%26,%27}, [%32+12288];\n"
               "ld.relaxed.gpu.global.v4.u32 {%28,%29,%30,%31}, [%32+14336];\n"
               "xor.b32 b, %0, %33;\n"
               "lop3.b32 b, b, %1, %33, 0xf6;\nlop3.b32 b, b, %2, %33, 0xf6;\nlop3.b32 b, b, %3, %33, 0xf6;\nlop3.b32 b, b, %4, %33, 0xf6;\n"
               "lop3.b32 b, b, %5, %33, 0xf6;\nlop3.b32 b, b, %6, %33, 0xf6;\nlop3.b32 b, b, %7, %33, 0xf6;\nlop3.b32 b, b, %8, %33, 0xf6;\n"
               "lop3.b32 b, b, %9, %33, 0xf6;\nlop3.b32 b, b, %10, %33, 0xf6;\nlop3.b32 b, b, %11, %33, 0xf6;\nlop3.b32 b, b, %12, %33, 0xf6;\n"
               "lop3.b32 b, b, %13, %33, 0xf6;\nlop3.b32 b, b, %14, %33, 0xf6;\nlop3.b32 b, b, %15, %33, 0xf6;\nlop3.b32 b, b, %16, %33, 0xf6;\n"
               "lop3.b32 b, b, %17, %33, 0xf6;\nlop3.b32 b, b, %18, %33, 0xf6;\nlop3.b32 b, b, %19, %33, 0xf6;\nlop3.b32 b, b, %20, %33, 0xf6;\n"
               "lop3.b32 b, b, %21, %33, 0xf6;\nlop3.b32 b, b, %22, %33, 0xf6;\nlop3.b32 b, b, %23, %33, 0xf6;\nlop3.b32 b, b, %24, %33, 0xf6;\n"
               "lop3.b32 b, b, %25, %33, 0xf6;\nlop3.b32 b, b, %26, %33, 0xf6;\nlop3.b32 b, b, %27, %33, 0xf6;\nlop3.b32 b, b, %28, %33, 0xf6;\n"
               "lop3.b32 b, b, %29, %33, 0xf6;\nlop3.b32 b, b, %30, %33, 0xf6;\nlop3.b32 b, b, %31, %33, 0xf6;\n"
               "and.b32 b, b, %34;\nsetp.eq.u32 p, b, 0;\nvote.sync.all.pred p, p, 0xffffffff;\n@p bra.uni LD;\n"
               "nanosleep.u32 50;\nadd.u32 c, c, 1;\nsetp.lt.u32 q, c, 1000000;\n@q bra.uni LW;\ntrap;\nLD:\n}"
               : "=&r"(v[0]), "=&r"(v[1]), "=&r"(v[2]), "=&r"(v[3]), "=&r"(v[4]), "=&r"(v[5]), "=&r"(v[6]), "=&r"(v[7]), "=&r"(v[8]), "=&r"(v[9]), "=&r"(v[10]), "=&r"(v[11]), "=&r"(v[12]), "=&r"(v[13]), "=&r"(v[14]), "=&r"(v[15]), "=&r"(v[16]), "=&r"(v[17]), "=&r"(v[18]), "=&r"(v[19]), "=&r"(v[20]), "=&r"(v[21]), "=&r"(v[22]), "=&r"(v[23]), "=&r"(v[24]), "=&r"(v[25]), "=&r"(v[26]), "=&r"(v[27]), "=&r"(v[28]), "=&r"(v[29]), "=&r"(v[30]), "=&r"(v[31])
               : "l"(p), "r"(tag), "r"(mask) : "memory");
}
__device__ __forceinline__ void poll16(uint32_t (&v)[16], const void* p, uint32_t tag, uint32_t mask) {
  asm volatile("{\n.reg .pred p, q;\n.reg .u32 c, b;\n.reg .b64 x, y;\n.reg .b128 z;\nmov.u32 c, 0;\nLW:\n"
               "ld.relaxed.gpu.global.u32 %0, [%16+0];\n"
               "ld.relaxed.gpu.global.u32 %1, [%16+4096];\n"
               "ld.relaxed.gpu.global.u32 %2, [%16+8192];\n"
               "ld.relaxed.gpu.global.u32 %3, [%16+12288];\n"
               "ld.relaxed.gpu.global.u32 %4, [%16+16384];\n"
               "ld.relaxed.gpu.global.u32 %5, [%16+20480];\n"
               "ld.relaxed.gpu.global.u32 %6, [%16+24576];\n"
               "ld.relaxed.gpu.global.u32 %7, [%16+28672];\n"
               "ld.relaxed.gpu.global.u32 %8, [%16+32768];\n"
               "ld.relaxed.gpu.global.u32 %9, [%16+36864];\n"
               "ld.relaxed.gpu.global.u32 %10, [%16+40960];\n"
               "ld.relaxed.gpu.global.u32 %11, [%16+45056];\n"
               "ld.relaxed.gpu.global.u32 %12, [%16+49152];\n"
               "ld.relaxed.gpu.global.u32 %13, [%16+53248];\n"
               "ld.relaxed.gpu.global.u32 %14, [%16+57344];\n"
               "ld.relaxed.gpu.global.u32 %15, [%16+61440];\n"
               "xor.b32 b, %0, %17;\n"
               "lop3.b32 b, b, %1, %17, 0xf6;\nlop3.b32 b, b, %2, %17, 0xf6;\nlop3.b32 b, b, %3, %17, 0xf6;\nlop3.b32 b, b, %4, %17, 0xf6;\n"
               "lop3.b32 b, b, %5, %17, 0xf6;\nlop3.b32 b, b, %6, %17, 0xf6;\nlop3.b32 b, b, %7, %17, 0xf6;\nlop3.b32 b, b, %8, %17, 0xf6;\n"
               "lop3.b32 b, b, %9, %17, 0xf6;\nlop3.b32 b, b, %10, %17, 0xf6;\nlop3.b32 b, b, %11, %17, 0xf6;\nlop3.b32 b, b, %12, %17, 0xf6;\n"
               "lop3.b32 b, b, %13, %17, 0xf6;\nlop3.b32 b, b, %14, %17, 0xf6;\nlop3.b32 b, b, %15, %17, 0xf6;\n"
               "and.b32 b, b, %18;\nsetp.eq.u32 p, b, 0;\nvote.sync.all.pred p, p, 0xffffffff;\n@p bra.uni LD;\n"
               "nanosleep.u32 200;\nadd.u32 c, c, 1;\nsetp.lt.u32 q, c, 1000000;\n@q bra.uni LW;\ntrap;\nLD:\n}"
               : "=&r"(v[0]), "=&r"(v[1]), "=&r"(v[2]), "=&r"(v[3]), "=&r"(v[4]), "=&r"(v[5]), "=&r"(v[6]), "=&r"(v[7]), "=&r"(v[8]), "=&r"(v[9]), "=&r"(v[10]), "=&r"(v[11]), "=&r"(v[12]), "=&r"(v[13]), "=&r"(v[14]), "=&r"(v[15])
               : "l"(p), "r"(tag), "r"(mask) : "memory");
}
__device__ __forceinline__ void poll_keys(uint32_t (&v)[16], const void* p, uint32_t tag, uint32_t mask) {
  asm volatile("{\n.reg .pred p, q;\n.reg .u32 c, b;\n.reg .b64 x, y;\n.reg .b128 z;\nmov.u32 c, 0;\nLW:\n"
               "ld.relaxed.gpu.global.v2.b64 {x, y}, [%16+0];\nmov.b64 {%0,%1}, x;\nmov.b64 {%2,%3}, y;\n"
               "ld.relaxed.gpu.global.v2.b64 {x, y}, [%16+4096];\nmov.b64 {%4,%5}, x;\nmov.b64 {%6,%7}, y;\n"
               "ld.relaxed.gpu.global.v2.b64 {x, y}, [%16+8192];\nmov.b64 {%8,%9}, x;\nmov.b64 {%10,%11}, y;\n"
               "ld.relaxed.gpu.global.v2.b64 {x, y}, [%16+12288];\nmov.b64 {%12,%13}, x;\nmov.b64 {%14,%15}, y;\n"
               "xor.b32 b, %0, %17;\n"
               "lop3.b32 b, b, %2, %17, 0xf6;\nlop3.b32 b, b, %4, %17, 0xf6;\nlop3.b32 b, b, %6, %17, 0xf6;\nlop3.b32 b, b, %8, %17, 0xf6;\n"
               "lop3.b32 b, b, %10, %17, 0xf6;\nlop3.b32 b, b, %12, %17, 0xf6;\nlop3.b32 b, b, %14, %17, 0xf6;\n"
               "and.b32 b, b, %18;\nsetp.eq.u32 p, b, 0;\nvote.sync.all.pred p, p, 0xffffffff;\n@p bra.uni LD;\n"
               "nanosleep.u32 20;\nadd.u32 c, c, 1;\nsetp.lt.u32 q, c, 1000000;\n@q bra.uni LW;\ntrap;\nLD:\n}"
               : "=&r"(v[0]), "=&r"(v[1]), "=&r"(v[2]), "=&r"(v[3]), "=&r"(v[4]), "=&r"(v[5]), "=&r"(v[6]), "=&r"(v[7]), "=&r"(v[8]), "=&r"(v[9]), "=&r"(v[10]), "=&r"(v[11]), "=&r"(v[12]), "=&r"(v[13]), "=&r"(v[14]), "=&r"(v[15])
               : "l"(p), "r"(tag), "r"(mask) : "memory");
}
__device__ __forceinline__ void poll_z(uint32_t (&v)[16], const void* p, uint32_t tag, uint32_t mask) {
  asm volatile("{\n.reg .pred p, q;\n.reg .u32 c, b;\n.reg .b64 x, y;\n.reg .b128 z;\nmov.u32 c, 0;\nLW:\n"
               "ld.relaxed.gpu.global.v4.u32 {%0,%1,%2,%3}, [%16+0];\n"
               "ld.relaxed.gpu.global.v4.u32 {%4,%5,%6,%7}, [%16+4096];\n"
               "ld.relaxed.gpu.global.v4.u32 {%8,%9,%10,%11}, [%16+8192];\n"
               "ld.relaxed.gpu.global.v4.u32 {%12,%13,%14,%15}, [%16+12288];\n"
               "xor.b32 b, %0, %17;\n"
               "lop3.b32 b, b, %1, %17, 0xf6;\nlop3.b32 b, b, %2, %17, 0xf6;\nlop3.b32 b, b, %3, %17, 0xf6;\nlop3.b32 b, b, %4, %17, 0xf6;\n"
               "lop3.b32 b, b, %5, %17, 0xf6;\nlop3.b32 b, b, %6, %17, 0xf6;\nlop3.b32 b, b, %7, %17, 0xf6;\nlop3.b32 b, b, %8, %17, 0xf6;\n"
               "lop3.b32 b, b, %9, %17, 0xf6;\nlop3.b32 b, b, %10, %17, 0xf6;\nlop3.b32 b, b, %11, %17, 0xf6;\nlop3.b32 b, b, %12, %17, 0xf6;\n"
               "lop3.b32 b, b, %13, %17, 0xf6;\nlop3.b32 b, b, %14, %17, 0xf6;\nlop3.b32 b, b, %15, %17, 0xf6;\n"
               "and.b32 b, b, %18;\nsetp.eq.u32 p, b, 0;\nvote.sync.all.pred p, p, 0xffffffff;\n@p bra.uni LD;\n"
               "nanosleep.u32 300;\nadd.u32 c, c, 1;\nsetp.lt.u32 q, c, 1000000;\n@q bra.uni LW;\ntrap;\nLD:\n}"
               : "=&r"(v[0]), "=&r"(v[1]), "=&r"(v[2]), "=&r"(v[3]), "=&r"(v[4]), "=&r"(v[5]), "=&r"(v[6]), "=&r"(v[7]), "=&r"(v[8]), "=&r"(v[9]), "=&r"(v[10]), "=&r"(v[11]), "=&r"(v[12]), "=&r"(v[13]), "=&r"(v[14]), "=&r"(v[15])
               : "l"(p), "r"(tag), "r"(mask) : "memory");
}
__device__ __forceinline__ void poll7x4(uint32_t (&v)[28], const void* p, uint32_t tag, uint32_t mask) {
  asm volatile("{\n.reg .pred p, q;\n.reg .u32 c, b;\n.reg .b64 x, y;\n.reg .b128 z;\nmov.u32 c, 0;\nLW:\n"
               "ld.relaxed.gpu.global.v4.u32 {%0,%1,%2,%3}, [%28+0];\n"
               "ld.relaxed.gpu.global.v4.u32 {%4,%5,%6,%7}, [%28+2048];\n"
               "ld.relaxed.gpu.global.v4.u32 {%8,%9,%10,%11}, [%28+4096];\n"
               "ld.relaxed.gpu.global.v4.u32 {%12,%13,%14,%15}, [%28+6144];\n"
               "ld.relaxed.gpu.global.v4.u32 {%16,%17,%18,%19}, [%28+8192];\n"
               "ld.relaxed.gpu.global.v4.u32 {%20,%21,%22,%23}, [%28+10240];\n"
               "ld.relaxed.gpu.global.v4.u32 {%24,%25,%26,%27}, [%28+12288];\n"
               "xor.b32 b, %0, %29;\n"
               "lop3.b32 b, b, %1, %29, 0xf6;\nlop3.b32 b, b, %2, %29, 0xf6;\nlop3.b32 b, b, %3, %29, 0xf6;\nlop3.b32 b, b, %4, %29, 0xf6;\n"
               "lop3.b32 b, b, %5, %29, 0xf6;\nlop3.b32 b, b, %6, %29, 0xf6;\nlop3.b32 b, b, %7, %29, 0xf6;\nlop3.b32 b, b, %8, %29, 0xf6;\n"
               "lop3.b32 b, b, %9, %29, 0xf6;\nlop3.b32 b, b, %10, %29, 0xf6;\nlop3.b32 b, b, %11, %29, 0xf6;\nlop3.b32 b, b, %12, %29, 0xf6;\n"
               "lop3.b32 b, b, %13, %29, 0xf6;\nlop3.b32 b, b, %14, %29, 0xf6;\nlop3.b32 b, b, %15, %29, 0xf6;\nlop3.b32 b, b, %16, %29, 0xf6;\n"
               "lop3.b32 b, b, %17, %29, 0xf6;\nlop3.b32 b, b, %18, %29, 0xf6;\nlop3.b32 b, b, %19, %29, 0xf6;\nlop3.b32 b, b, %20, %29, 0xf6;\n"
               "lop3.b32 b, b, %21, %29, 0xf6;\nlop3.b32 b, b, %22, %29, 0xf6;\nlop3.b32 b, b, %23, %29, 0xf6;\nlop3.b32 b, b, %24, %29, 0xf6;\n"
               "lop3.b32 b, b, %25, %29, 0xf6;\nlop3.b32 b, b, %26, %29, 0xf6;\nlop3.b32 b, b, %27, %29, 0xf6;\n"
               "and.b32 b, b, %30;\nsetp.eq.u32 p, b, 0;\nvote.sync.all.pred p, p, 0xffffffff;\n@p bra.uni LD;\n"
               "nanosleep.u32 50;\nadd.u32 c, c, 1;\nsetp.lt.u32 q, c, 1000000;\n@q bra.uni LW;\ntrap;\nLD:\n}"
               : "=&r"(v[0]), "=&r"(v[1]), "=&r"(v[2]), "=&r"(v[3]), "=&r"(v[4]), "=&r"(v[5]), "=&r"(v[6]), "=&r"(v[7]), "=&r"(v[8]), "=&r"(v[9]), "=&r"(v[10]), "=&r"(v[11]), "=&r"(v[12]), "=&r"(v[13]), "=&r"(v[14]), "=&r"(v[15]), "=&r"(v[16]), "=&r"(v[17]), "=&r"(v[18]), "=&r"(v[19]), "=&r"(v[20]), "=&r"(v[21]), "=&r"(v[22]), "=&r"(v[23]), "=&r"(v[24]), "=&r"(v[25]), "=&r"(v[26]), "=&r"(v[27])
               : "l"(p), "r"(tag), "r"(mask) : "memory");
}
__device__ __forceinline__ void poll_kvp(uint32_t (&v)[16], const void* p, uint32_t tag, uint32_t mask) {
  asm volatile("{\n.reg .pred p, q;\n.reg .u32 c, b;\n.reg .b64 x, y;\n.reg .b128 z;\nmov.u32 c, 0;\nLW:\n"
               "ld.relaxed.gpu.global.b128 z, [%16+0];\nmov.b128 {x, y}, z;\nmov.b64 {%0,%1}, x;\nmov.b64 {%2,%3}, y;\n"
               "ld.relaxed.gpu.global.b128 z, [%16+8192];\nmov.b128 {x, y}, z;\nmov.b64 {%4,%5}, x;\nmov.b64 {%6,%7}, y;\n"
               "ld.relaxed.gpu.global.b128 z, [%16+16384];\nmov.b128 {x, y}, z;\nmov.b64 {%8,%9}, x;\nmov.b64 {%10,%11}, y;\n"
               "ld.relaxed.gpu.global.b128 z, [%16+24576];\nmov.b128 {x, y}, z;\nmov.b64 {%12,%13}, x;\nmov.b64 {%14,%15}, y;\n"
               "xor.b32 b, %0, %17;\n"
               "lop3.b32 b, b, %4, %17, 0xf6;\nlop3.b32 b, b, %8, %17, 0xf6;\nlop3.b32 b, b, %12, %17, 0xf6;\n"
               "and.b32 b, b, %18;\nsetp.eq.u32 p, b, 0;\nvote.sync.all.pred p, p, 0xffffffff;\n@p bra.uni LD;\n"
               "nanosleep.u32 50;\nadd.u32 c, c, 1;\nsetp.lt.u32 q, c, 1000000;\n@q bra.uni LW;\ntrap;\nLD:\n}"
               : "=&r"(v[0]), "=&r"(v[1]), "=&r"(v[2]), "=&r"(v[3]), "=&r"(v[4]), "=&r"(v[5]), "=&r"(v[6]), "=&r"(v[7]), "=&r"(v[8]), "=&r"(v[9]), "=&r"(v[10]), "=&r"(v[11]), "=&r"(v[12]), "=&r"(v[13]), "=&r"(v[14]), "=&r"(v[15])
               : "l"(p), "r"(tag), "r"(mask) : "memory");
}

__device__ __align__(1024) __nv_bfloat16 g_o[2048 * 1024];
__device__ __align__(128) uint2 g_keys[2048];
__device__ __align__(128) uint32_t g_csum[18 * 1024];
__device__ __align__(128) uint32_t g_z[16 * 1024];
__device__ __align__(128) uint4 g_kvp[128 * 512];
__device__ __align__(128) uint4 g_kv[8 * 512];
__device__ __align__(128) uint32_t g_h[112 * 256];
__device__ __align__(128) uint32_t g_yp[128 * 512];
__device__ __align__(128) uint2 g_sel[8 * 16];
enum { H_CS = 0, H_KVP = 8, H_KV = 16, H_H = 24, H_Y = 32, H_O = 40, H_Z = 56 };
__device__ __align__(128) uint32_t g_sig[64 * 32];
__device__ uint32_t g_epoch;

constexpr uint32_t RING = 1024, SLOT = 32768, SMEM_BYTES = 232448;
constexpr int NST = 5, HST = 7;
constexpr uint32_t STG = RING + 163840, AUX = RING + 196608, FR = RING + 212992, MISC = RING + 229376;
constexpr uint32_t B_FULL = MISC, B_EMPTY = MISC + 56, B_XS = MISC + 112, B_SEL = MISC + 144, B_WK = MISC + 160, B_CSDN = MISC + 168,
                   B_FR = MISC + 176, B_FE = MISC + 200, B_DR = MISC + 224, B_CSV = MISC + 248,
                   B_DND = MISC + 256, B_XRES = MISC + 264, B_PFREE = MISC + 280, B_SFREE = MISC + 288, B_KVL = MISC + 296, NBAR = 38;
constexpr uint32_t S_EPOCH = MISC + 352, S_NCAND = MISC + 356, S_SEL = MISC + 368, S_WMAX = MISC + 432,
                   S_KSTAT = MISC + 512, S_CSK = MISC + 1536, S_CSV = MISC + 2048, S_CSQ = MISC + 2560, S_ONES = MISC + 512;
constexpr uint32_t KVB = AUX, HOP = AUX + 10240, FONES = AUX + 6144, GR = FR - 8192;
enum { NB_Z = 0, NB_KV = 1, NB_VQ = 2, NB_WG0 = 3, NB_FDONE = 4, NB_PK = 5, NB_KVB = 6, NB_WG1 = 7, NB_WG2 = 8, NB_CSQ = 9,
       NB_Y = 10, NB_ST = 11, NB_OWN0 = 12, NB_OWN1 = 13, NB_Q0 = 14, NB_H1 = 15 };

#define XS_FLY 2
#define FFN_GAP 400
#define PF_GAP 200
#define PF_WAIT 1000
#define GPCMAP 0x75143620u
#define KV_SPEC 200
#define HAND_K 5
#define PF_V 0
#define PF_O 0
#define PHI_CUT 11
#define SIG_EARLY 50
#define OWN_LATE 3
#define EXP_ND 0
constexpr uint64_t EVICT_FIRST = 0x12f0000000000000ull;
constexpr float LOG2E = 1.4426950408889634f, LN2 = 0.6931471805599453f;

#define ELECT "{\n.reg .pred p;\nelect.sync _|p, 0xffffffff;\n"
#define TMA2D "cp.async.bulk.tensor.2d.shared::cluster.global.mbarrier::complete_tx::bytes"
#define TMA3D "cp.async.bulk.tensor.3d.shared::cluster.global.mbarrier::complete_tx::bytes"
__device__ __forceinline__ void e_expect(uint32_t b, uint32_t n) {
  asm volatile(ELECT "@p mbarrier.arrive.expect_tx.shared::cta.b64 _, [%0], %1;\n}" ::"r"(b), "r"(n) : "memory");
}
__device__ __forceinline__ void e_arrive(uint32_t b) { asm volatile(ELECT "@p mbarrier.arrive.shared::cta.b64 _, [%0];\n}" ::"r"(b) : "memory"); }
__device__ __forceinline__ void e_tma2d(uint32_t dst, const CUtensorMap* m, int c0, int c1, uint32_t bar) {
  asm volatile(ELECT "@p " TMA2D " [%0], [%1, {%3, %4}], [%2];\n}" ::"r"(dst), "l"(m), "r"(bar), "r"(c0), "r"(c1) : "memory");
}
__device__ __forceinline__ void e_tma2d_ef(uint32_t dst, const CUtensorMap* m, int c0, int c1, uint32_t bar, uint64_t pol) {
  asm volatile(ELECT "@p " TMA2D ".L2::cache_hint [%0], [%1, {%3, %4}], [%2], %5;\n}" ::"r"(dst), "l"(m), "r"(bar), "r"(c0), "r"(c1), "l"(pol) : "memory");
}
__device__ __forceinline__ void e_tma3d(uint32_t dst, const CUtensorMap* m, int c1, int c2, uint32_t bar) {
  asm volatile(ELECT "@p " TMA3D " [%0], [%1, {0, %3, %4}], [%2];\n}" ::"r"(dst), "l"(m), "r"(bar), "r"(c1), "r"(c2) : "memory");
}
__device__ __forceinline__ void e_store2d(const CUtensorMap* m, int c0, int c1, uint32_t src) {
  asm volatile(ELECT "@p cp.async.bulk.tensor.2d.global.shared::cta.bulk_group [%0, {%2, %3}], [%1];\n}" ::"l"(m), "r"(src), "r"(c0), "r"(c1) : "memory");
}
__device__ __forceinline__ void e_tma3d_ef(uint32_t dst, const CUtensorMap* m, int c0, int c1, uint32_t bar, uint64_t pol) {
  asm volatile(ELECT "@p " TMA3D ".L2::cache_hint [%0], [%1, {%3, %4, 0}], [%2], %5;\n}" ::"r"(dst), "l"(m), "r"(bar), "r"(c0), "r"(c1), "l"(pol) : "memory");
}
__device__ __forceinline__ void e_load(uint32_t dst, const void* src, uint32_t n, uint32_t bar) {
  asm volatile(ELECT "@p cp.async.bulk.shared::cluster.global.mbarrier::complete_tx::bytes [%0], [%1], %2, [%3];\n}" ::"r"(dst), "l"(src), "r"(n), "r"(bar) : "memory");
}
__device__ __forceinline__ void e_pfmap(const CUtensorMap* m) { asm volatile(ELECT "@p prefetch.tensormap [%0];\n}" ::"l"(m) : "memory"); }
__device__ __forceinline__ void bulk_wait_read() { asm volatile("cp.async.bulk.commit_group;\ncp.async.bulk.wait_group.read 0;" ::: "memory"); }
__device__ __forceinline__ void e_signal(int word, int bit) {
  asm volatile(ELECT "@p red.relaxed.gpu.global.xor.b32 [%0], %1;\n}" ::"l"(g_sig + word * 32), "r"(1u << bit) : "memory");
}
__device__ __forceinline__ void await(int word, uint32_t mask, uint32_t ep) {
  uint32_t f[1];
  poll1f(f, g_sig + word * 32, 0u - (ep & 1u), mask);
}

__device__ __forceinline__ void mbar_arrive(uint32_t b) { asm volatile("mbarrier.arrive.shared::cta.b64 _, [%0];" ::"r"(b) : "memory"); }
__device__ __forceinline__ void mbar_wait(uint32_t b, uint32_t ph) {
  asm volatile("{\n.reg .pred p, q;\n.reg .u32 c;\nmov.u32 c, 0;\nLW:\nmbarrier.try_wait.parity.shared::cta.b64 p, [%0], %1;\n@p bra LD;\n"
               "add.u32 c, c, 1;\nsetp.lt.u32 q, c, 100000;\n@q bra LW;\ntrap;\nLD:\n}" ::"r"(b), "r"(ph) : "memory");
}
#define WAIT01 "{\n.reg .pred p, q;\n.reg .u32 c;\nmov.u32 c, 0;\nLW:\nmbarrier.try_wait.parity.shared::cta.b64 p, [%0], %1;\n@p bra LD;\n" \
               "add.u32 c, c, 1;\nsetp.lt.u32 q, c, 100000;\n@q bra LW;\ntrap;\nLD:\nelect.sync _|p, 0xffffffff;\n"
__device__ __forceinline__ void refill_wx(uint32_t eb, uint32_t ph, uint32_t fb, uint32_t bytes, uint32_t dw, const CUtensorMap* mw, int k0, int c,
                                          uint32_t dx, const CUtensorMap* mx, int row, uint32_t xb) {
  asm volatile(WAIT01 "@p " TMA3D " [%4], [%5, {0, %6, %7}], [%2];\n@p " TMA2D " [%8], [%9, {%6, %10}], [%11];\n"
               "@p mbarrier.arrive.expect_tx.shared::cta.b64 _, [%2], %3;\n}"
               ::"r"(eb), "r"(ph), "r"(fb), "r"(bytes), "r"(dw), "l"(mw), "r"(k0), "r"(c), "r"(dx), "l"(mx), "r"(row), "r"(xb) : "memory");
}
__device__ __forceinline__ void refill_w(uint32_t eb, uint32_t ph, uint32_t fb, uint32_t bytes, uint32_t dw, const CUtensorMap* mw, int k0, int c) {
  asm volatile(WAIT01 "@p " TMA3D " [%4], [%5, {0, %6, %7}], [%2];\n@p mbarrier.arrive.expect_tx.shared::cta.b64 _, [%2], %3;\n}"
               ::"r"(eb), "r"(ph), "r"(fb), "r"(bytes), "r"(dw), "l"(mw), "r"(k0), "r"(c) : "memory");
}
__device__ __forceinline__ void refill_x(uint32_t eb, uint32_t ph, uint32_t fb, uint32_t dx, const CUtensorMap* mx, int k0, int row) {
  asm volatile(WAIT01 "@p " TMA2D " [%3], [%4, {%5, %6}], [%2];\n}" ::"r"(eb), "r"(ph), "r"(fb), "r"(dx), "l"(mx), "r"(k0), "r"(row) : "memory");
}
__device__ __forceinline__ void refill_g(uint32_t eb, uint32_t ph, uint32_t fb, uint32_t dw, const CUtensorMap* mw, int c0, int k0) {
  asm volatile(WAIT01 "@p " TMA3D ".L2::cache_hint [%3], [%4, {%5, %6, 0}], [%2], %7;\n@p mbarrier.arrive.expect_tx.shared::cta.b64 _, [%2], 8192;\n}"
               ::"r"(eb), "r"(ph), "r"(fb), "r"(dw), "l"(mw), "r"(c0), "r"(k0), "l"(EVICT_FIRST) : "memory");
}
__device__ __forceinline__ void nb_sync(int id, int n) { asm volatile("bar.sync %0, %1;" ::"r"(id), "r"(n) : "memory"); }
__device__ __forceinline__ void nb_arrive(int id, int n) { asm volatile("bar.arrive %0, %1;" ::"r"(id), "r"(n) : "memory"); }
__device__ __forceinline__ void wg_fence() { asm volatile("wgmma.fence.sync.aligned;" ::: "memory"); }
__device__ __forceinline__ void wg_commit() { asm volatile("wgmma.commit_group.sync.aligned;" ::: "memory"); }
template <int N> __device__ __forceinline__ void wg_wait() { asm volatile("wgmma.wait_group.sync.aligned %0;" ::"n"(N) : "memory"); }
template <int N> __device__ __forceinline__ void reg_fence(float (&a)[N]) {
#pragma unroll
  for (int i = 0; i < N; i++) asm volatile("" : "+f"(a[i])::"memory");
}
template <int N> __device__ __forceinline__ void reg_zero(float (&a)[N]) {
#pragma unroll
  for (int i = 0; i < N; i++) a[i] = 0.f;
}
__device__ __forceinline__ constexpr uint64_t mkdesc(uint32_t addr, uint32_t lbo, uint32_t sbo, uint32_t swz) {
  return (uint64_t)(addr >> 4) | ((uint64_t)(lbo >> 4) << 16) | ((uint64_t)(sbo >> 4) << 32) | ((uint64_t)swz << 62);
}
__device__ __forceinline__ void fence_async_smem() { asm volatile("fence.proxy.async.shared::cta;" ::: "memory"); }
__device__ __forceinline__ void st_relaxed(uint32_t* p, uint32_t v) { asm volatile("st.relaxed.gpu.global.u32 [%0], %1;" ::"l"(p), "r"(v) : "memory"); }
__device__ __forceinline__ uint32_t ld_relaxed(const uint32_t* p) { uint32_t v; asm volatile("ld.relaxed.gpu.global.u32 %0, [%1];" : "=r"(v) : "l"(p) : "memory"); return v; }
__device__ __forceinline__ void st_unit(uint4* p, uint32_t a, uint32_t b, uint32_t c, uint32_t d, uint32_t par) {
  asm volatile("{\n.reg .b64 x, y;\n.reg .b128 z;\nmov.b64 x, {%1,%2};\nmov.b64 y, {%3,%4};\nmov.b128 z, {x, y};\nst.relaxed.gpu.global.b128 [%0], z;\n}"
               ::"l"(p), "r"((a & ~1u) | par), "r"(b), "r"(c), "r"(d) : "memory");
}
__device__ __forceinline__ uint4 lds128(uint32_t a) { uint4 v; asm volatile("ld.shared.v4.u32 {%0,%1,%2,%3}, [%4];" : "=r"(v.x), "=r"(v.y), "=r"(v.z), "=r"(v.w) : "r"(a)); return v; }
__device__ __forceinline__ float4 lds128f(uint32_t a) { float4 v; asm volatile("ld.shared.v4.f32 {%0,%1,%2,%3}, [%4];" : "=f"(v.x), "=f"(v.y), "=f"(v.z), "=f"(v.w) : "r"(a)); return v; }
__device__ __forceinline__ float4 lds128v(uint32_t a) { float4 v; asm volatile("ld.volatile.shared.v4.f32 {%0,%1,%2,%3}, [%4];" : "=f"(v.x), "=f"(v.y), "=f"(v.z), "=f"(v.w) : "r"(a) : "memory"); return v; }
__device__ __forceinline__ float lds32v(uint32_t a) { float v; asm volatile("ld.volatile.shared.f32 %0, [%1];" : "=f"(v) : "r"(a) : "memory"); return v; }
__device__ __forceinline__ float2 lds64f(uint32_t a) { float2 v; asm volatile("ld.shared.v2.f32 {%0,%1}, [%2];" : "=f"(v.x), "=f"(v.y) : "r"(a)); return v; }
__device__ __forceinline__ uint32_t lds32(uint32_t a) { uint32_t v; asm volatile("ld.shared.u32 %0, [%1];" : "=r"(v) : "r"(a)); return v; }
__device__ __forceinline__ void sts128(uint32_t a, uint32_t x, uint32_t y, uint32_t z, uint32_t w) { asm volatile("st.shared.v4.u32 [%0], {%1,%2,%3,%4};" ::"r"(a), "r"(x), "r"(y), "r"(z), "r"(w) : "memory"); }
__device__ __forceinline__ void sts128f(uint32_t a, float x, float y, float z, float w) { asm volatile("st.shared.v4.f32 [%0], {%1,%2,%3,%4};" ::"r"(a), "f"(x), "f"(y), "f"(z), "f"(w) : "memory"); }
__device__ __forceinline__ void sts64(uint32_t a, uint32_t x, uint32_t y) { asm volatile("st.shared.v2.u32 [%0], {%1,%2};" ::"r"(a), "r"(x), "r"(y) : "memory"); }
__device__ __forceinline__ void sts32(uint32_t a, uint32_t x) { asm volatile("st.shared.u32 [%0], %1;" ::"r"(a), "r"(x) : "memory"); }
__device__ __forceinline__ void stsm4(uint32_t a, uint32_t r0, uint32_t r1, uint32_t r2, uint32_t r3) {
  asm volatile("stmatrix.sync.aligned.m8n8.x4.shared.b16 [%0], {%1,%2,%3,%4};" ::"r"(a), "r"(r0), "r"(r1), "r"(r2), "r"(r3) : "memory");
}
__device__ __forceinline__ uint4 ldsm4(uint32_t a) {
  uint4 v; asm volatile("ldmatrix.sync.aligned.m8n8.x4.shared.b16 {%0,%1,%2,%3}, [%4];" : "=r"(v.x), "=r"(v.y), "=r"(v.z), "=r"(v.w) : "r"(a) : "memory"); return v;
}
__device__ __forceinline__ uint32_t pack(float lo, float hi) { uint32_t r; asm("cvt.rn.bf16x2.f32 %0, %1, %2;" : "=r"(r) : "f"(hi), "f"(lo)); return r; }
__device__ __forceinline__ float bf_lo(uint32_t w) { return __uint_as_float(w << 16); }
__device__ __forceinline__ float bf_hi(uint32_t w) { return __uint_as_float(w & 0xffff0000u); }
__device__ __forceinline__ float bf_round(float x) { return bf_lo(pack(x, x)); }
__device__ __forceinline__ float ex2(float x) { float v; asm("ex2.approx.ftz.f32 %0, %1;" : "=f"(v) : "f"(x)); return v; }
__device__ __forceinline__ float rcp(float x) { float v; asm("rcp.approx.ftz.f32 %0, %1;" : "=f"(v) : "f"(x)); return v; }
__device__ __forceinline__ float addsat(float a, float b) { float v; asm("add.sat.f32 %0, %1, %2;" : "=f"(v) : "f"(a), "f"(b)); return v; }
__device__ __forceinline__ float phi2(float a) { return fmaf(fmaxf(a, 0.f), LN2, addsat(ex2(a), 1e-6f)); }
__device__ __forceinline__ uint32_t phi_pack(float u0, float u1, float rl, uint32_t sd2) {
  uint32_t r;
  asm("{\n.reg .b32 m;\ncvt.rn.relu.bf16x2.f32 m, %2, %1;\nfma.rn.bf16x2 %0, %3, %4, m;\n}"
      : "=r"(r) : "f"(u0), "f"(u1), "r"(pack(addsat(ex2(u0 * rl), 1e-6f), addsat(ex2(u1 * rl), 1e-6f))), "r"(sd2));
  return r;
}
__device__ __forceinline__ float key_score(uint32_t key) { uint32_t u = key >> 16; u = (u & 0x8000u) ? (u & 0x7fffu) : (~u & 0xffffu); return __uint_as_float(u << 16); }
__device__ __forceinline__ int key_token(uint32_t key) { return 2047 - (int)((key >> 5) & 2047u); }
__device__ __forceinline__ uint32_t bsel(uint32_t a, uint32_t b, uint32_t m) { uint32_t r; asm("lop3.b32 %0, %1, %2, %3, 0xd8;" : "=r"(r) : "r"(a), "r"(b), "r"(m)); return r; }
__device__ __forceinline__ uint32_t prmt(uint32_t a, uint32_t b, uint32_t c) { uint32_t r; asm("prmt.b32 %0, %1, %2, %3;" : "=r"(r) : "r"(a), "r"(b), "r"(c)); return r; }
__device__ __forceinline__ uint32_t tagf(float v, uint32_t par) { return (__float_as_uint(v) & ~1u) | par; }
__device__ __forceinline__ float xred(float a, float b, bool up, int o) { return (up ? b : a) + __shfl_xor_sync(0xffffffffu, up ? a : b, o); }

#define STAMP(id)
#define STAMP_IF(c, id)
#define STAMP2(i)
#define LITE 1
#define LITE_MASK 0ull

template <bool TRANS, int NK = 16>
__device__ __forceinline__ void mainloop(float (&a0)[64], float (&a1)[64], int s, int ph, int handoff, int xpair, bool leader) {
  uint32_t prev = 0;
#pragma unroll 1
  for (int kt = 0; kt < NK; kt++) {
    const bool xr = !TRANS && (kt >> 1) == xpair;
    mbar_wait(B_FULL + 8 * s, ph);
    const uint64_t dw = mkdesc(RING, 8192, 1024, 1) + s * (SLOT >> 4), dx = mkdesc(0, 16, 1024, 1) + (xr ? (STG >> 4) + (kt & 1) * 1024 : ((RING + 16384) >> 4) + s * (SLOT >> 4));
    if (xr) mbar_wait(B_XRES + 8 * (kt & 1), 0);
    wg_fence();
#pragma unroll
    for (int j = 0; j < 4; j++) {
      if (TRANS) {
        wgmma_n128_ss<1, 0>(a0, dw + j * 128, dx + j * 2, 1);
        wgmma_n128_ss<1, 0>(a1, dw + j * 128 + 512, dx + j * 2, 1);
      } else {
        wgmma_n128_ss<0, 1>(a0, dx + j * 2, dw + j * 128, 1);
        wgmma_n128_ss<0, 1>(a1, dx + j * 2 + 512, dw + j * 128, 1);
      }
    }
    wg_commit();
    if (handoff && kt == 15) nb_arrive(handoff, 256);
    wg_wait<1>();
    if (prev && leader) mbar_arrive(prev);
    prev = B_EMPTY + 8 * s;
    if (++s == NST) { s = 0; ph ^= 1; }
  }
  if (NK < 16) return;
  wg_wait<0>();
  if (leader) mbar_arrive(prev);
  reg_fence(a0);
  reg_fence(a1);
}

__device__ __forceinline__ int out_kblock(int r, int tn) {
  const int q = r - 2, half = q >= 7, pi = q - 7 * half;
  return r < 2 ? 2 * tn + r : 2 * ((pi + (pi >= (tn & 3))) ^ (tn & 4)) + half;
}

struct Params {
  const char *x, *wqkv, *w_r, *wg, *wu, *wd, *wo;
  CUtensorMap m_wqkv, m_x, m_xs, m_o, m_os, m_wo, m_gu, m_down, m_out;
};

template <bool BY_SMID>
__global__ void __launch_bounds__(512, 1) fused_kernel(const __grid_constant__ Params mp) {
  extern __shared__ __align__(1024) uint8_t smem_raw[];
#define CK(i)
  CK(0);
  const int tid = threadIdx.x, lane = tid & 31;
  const int w = __shfl_sync(0xffffffffu, tid >> 5, 0);
  int bid = blockIdx.x;
  if (BY_SMID) {
    uint32_t sm;
    asm volatile("mov.u32 %0, %%smid;" : "=r"(sm));
    const uint32_t p = sm >> 1, q = ((p - 32) * 37) >> 8;
    const uint32_t gpc = p < 32 ? p & 7 : p < 60 ? p - 31 - 7 * q : 0, tpc = p < 32 ? p >> 3 : p < 60 ? 4 + q : p - 58;
    bid = (p >> 1) == 30 ? 128 + ((0x9cu >> (2 * (sm & 3))) & 3) : ((GPCMAP >> (4 * gpc)) & 7) * 16 + tpc * 2 + (sm & 1);
  }
  const int tn = (bid & 3) + 4 * (bid >> 6), tm = (bid >> 2) & 15;

  CK(1);
  if (w == 0) {
#pragma unroll 1
    for (int s = 0; s < NST; s++) {
      asm volatile(ELECT "@p mbarrier.init.shared::cta.b64 [%0], 1;\n}" ::"r"(B_FULL + 8 * s) : "memory");
      if (bid < 128) {
        e_expect(B_FULL + 8 * s, 32768);
        e_tma2d(RING + s * SLOT + 16384, &mp.m_x, s * 64, tm * 128, B_FULL + 8 * s);
        e_tma3d(RING + s * SLOT, &mp.m_wqkv, s * 64, 16 + 2 * tn, B_FULL + 8 * s);
      }
      if (s == 0) CK(2);
    }
  }
  if (w == 1) e_pfmap(&mp.m_wqkv);
  if (w == 2) e_pfmap(&mp.m_xs);
  if (w >= 4) {
#pragma unroll 1
    for (uint32_t b = MISC + 8 * (w + 1); b < MISC + 8 * NBAR; b += 96)
      asm volatile(ELECT "@p mbarrier.init.shared::cta.b64 [%0], %1;\n}" ::"r"(b), "r"(b == B_CSDN ? 4 : 1) : "memory");
    if (w == 15) sts32(S_NCAND, 0);
  }
  CK(3);
  asm volatile("fence.mbarrier_init.release.cluster;" ::: "memory");
  __syncthreads();

  if (bid >= 128) {
    const int h0 = bid == 128 ? 14 : bid - 129, hs = bid == 128 ? 1 : 3, h1 = bid == 128 ? 16 : 14;
    if (w == 12) {
      int s = 0, ph = 1;
#pragma unroll 1
      for (int h = h0; h < h1; h += hs) {
        const int c = 2 * h + (h & 8) * 2;
        if (h == 14) mbar_wait(B_SEL, 0);
#pragma unroll 1
        for (int kt = 0; kt < 16; kt += 2) {
          mbar_wait(B_EMPTY + 8 * s, ph);
          e_expect(B_FULL + 8 * s, 32768);
          e_tma3d(RING + s * SLOT, &mp.m_wqkv, kt * 64, c, B_FULL + 8 * s);
          e_tma3d(RING + s * SLOT + 16384, &mp.m_wqkv, kt * 64 + 64, c, B_FULL + 8 * s);
          if (++s == HST) { s = 0; ph ^= 1; }
        }
      }
    } else if (w < 4) {
      const uint32_t par = (ld_relaxed(&g_epoch) + 1) & 1u;
      sts32(S_ONES + tid * 4, 0x3f803f80u);
      fence_async_smem();
      nb_sync(NB_WG0, 128);
      int s = 0, ph = 0;
#pragma unroll 1
      for (int h = h0; h < h1; h += hs) {
        float c[4][4];
#pragma unroll
        for (int q = 0; q < 4; q++) reg_zero(c[q]);
        uint32_t prev = 0;
#pragma unroll 1
        for (int kt = 0; kt < 8; kt++) {
          mbar_wait(B_FULL + 8 * s, ph);
          const uint64_t dw = mkdesc(RING, 8192, 1024, 1) + s * (SLOT >> 4);
          wg_fence();
#pragma unroll
          for (int j = 0; j < 16; j++) wgmma_n8_ss<1, 0>(c[j & 3], dw + (j & 3) * 512 + (j >> 2) * 128, mkdesc(S_ONES, 128, 128, 0), 1);
          wg_commit();
          wg_wait<1>();
          if (prev && tid == 0) mbar_arrive(prev);
          prev = B_EMPTY + 8 * s;
          if (++s == HST) { s = 0; ph ^= 1; }
        }
        wg_wait<0>();
        if (tid == 0) mbar_arrive(prev);
#pragma unroll
        for (int q = 0; q < 4; q++) reg_fence(c[q]);
        const bool u2 = lane & 2, u1 = lane & 1;
        const float lo = u2 ? c[1][0] + c[3][0] : c[0][0] + c[2][0], hi = u2 ? c[1][2] + c[3][2] : c[0][2] + c[2][2];
        st_relaxed(g_csum + h * 128 + (lane & 2) * 32 + w * 16 + (lane & 1) * 8 + (lane >> 2), tagf(u1 ? hi : lo, par));
        STAMP_IF(tid == 0, h >= 8 ? 6 : 30);
      }
    } else if (w < 12 && bid == 128) {
      const int t = tid - 128, j = w - 4;
      const uint32_t ep = ld_relaxed(&g_epoch) + 1;
      uint32_t kk[16];
      poll_keys(kk, g_keys + t * 2, ep, 31u);
      STAMP_IF(t == 0, 42);
      const uint32_t m = __reduce_max_sync(0xffffffffu, max(max(max(kk[0], kk[2]), max(kk[4], kk[6])), max(max(kk[8], kk[10]), max(kk[12], kk[14]))));
      if (lane == 0) sts32(S_WMAX + j * 4, m);
      nb_sync(NB_WG1, 256);
      const uint32_t T = __reduce_min_sync(0xffffffffu, lds32(S_WMAX + (lane & 7) * 4));
      uint32_t cnt = 0;
#pragma unroll
      for (int i = 0; i < 8; i++) cnt += kk[2 * i] >= T;
      if (cnt) {
        uint32_t pos;
        asm volatile("atom.shared.add.u32 %0, [%1], %2;" : "=r"(pos) : "r"(S_NCAND), "r"(cnt * 8) : "memory");
#pragma unroll
        for (int i = 0; i < 8; i++)
          if (kk[2 * i] >= T) { sts64(AUX + pos, kk[2 * i], kk[2 * i + 1]); pos += 8; }
      }
      nb_sync(NB_WG1, 256);
      const uint32_t n8 = lds32(S_NCAND);
#pragma unroll 1
      for (uint32_t i = j * 8; i < n8; i += 64) {
        const float2 c = lds64f(AUX + i);
        uint32_t rank = 0;
#pragma unroll 1
        for (uint32_t q = lane * 8; q < n8 + lane * 8; q += 256) rank += __popc(__ballot_sync(0xffffffffu, q < n8 && lds32(AUX + q) > __float_as_uint(c.x)));
        if (rank < 8) sts64(S_SEL + rank * 8, __float_as_uint(c.x), __float_as_uint(c.y));
      }
      fence_async_smem();
      nb_sync(NB_WG1, 256);
      if (j == 0) {
        const uint4 v = lds128(S_SEL + (lane & 3) * 16);
        asm volatile("{\n.reg .b64 x, y;\nmov.b64 x, {%1,%2};\nmov.b64 y, {%3,%4};\nst.relaxed.gpu.global.v2.b64 [%0], {x, y};\n}"
                     ::"l"(g_sel + (lane >> 2) * 16 + (lane & 3) * 2), "r"(v.x), "r"(v.y), "r"(v.z), "r"(v.w) : "memory");
        e_arrive(B_SEL);
      }
      STAMP_IF(t == 0, 45);
    }
  } else if (w >= 12) {
    asm volatile("setmaxnreg.dec.sync.aligned.u32 32;");
    if (w == 12) {
      int s = 0, ph = 0;
#pragma unroll 1
      for (int it = NST; it < 48; it++) {
        const int c = (it < 32 ? (it & 16) + 16 : 0) + 2 * tn;
        const int k0 = ((it + (it >= 32 && tn < 4 ? 8 : 0)) & 15) * 64;
        const bool xr = (it >> 1) == 20 + (tn & 3);
        if (xr) { mbar_wait(B_SFREE, 0); e_expect(B_XRES + 8 * (it & 1), 16384); }
        refill_wx(B_EMPTY + 8 * s, ph, B_FULL + 8 * s, xr ? 16384 : 32768, RING + s * SLOT, &mp.m_wqkv, k0, c,
                  xr ? STG + (it & 1) * 16384 : RING + s * SLOT + 16384, &mp.m_x, tm * 128, xr ? B_XRES + 8 * (it & 1) : B_FULL + 8 * s);
        if (it >= NST) STAMP2(it - NST);
        if (++s == NST) { s = 0; ph ^= 1; }
      }
#pragma unroll 1
      for (int r = 0; r < 16; r++) {
        const int kb = out_kblock(r, tn);
        refill_w(B_EMPTY + 8 * s, ph, B_FULL + 8 * s, r < 2 ? 16384 : 32768, RING + s * SLOT, &mp.m_wo, kb * 64, 2 * tn);
        if (r < 2 || r == 4) {
          const uint32_t bar = B_DR + (r < 2 ? 16 : 8);
          const int k0 = (bid >> 4) * 448 + 128 + min(r, 2) * 128;
          if (r != 1) e_expect(bar, r ? 8192 : 32768);
          e_tma2d_ef(RING + s * SLOT + 16384, &mp.m_down, (bid & 15) * 64, k0, bar, EVICT_FIRST);
          if (r < 2) e_tma2d_ef(RING + s * SLOT + 24576, &mp.m_down, (bid & 15) * 64, k0 + 64, bar, EVICT_FIRST);
        }
        STAMP2(r + 48 - NST);
        if (++s == NST) { s = 0; ph ^= 1; }
      }
    } else if (w == 13) {
      mbar_wait(B_FULL, 0);
#pragma unroll 1
      for (int c = 0; c < 4; c++) {
        if (c >= XS_FLY) mbar_wait(B_XS + 8 * (c - XS_FLY), 0);
        if (c == (tm >> 2)) {
          e_expect(B_WK, 16384);
          e_tma3d(FR, &mp.m_wqkv, tm * 64, 16 + 2 * tn, B_WK);
        }
        e_expect(B_XS + 8 * c, 8192);
        e_tma2d(STG + c * 8192, &mp.m_xs, c * 256, tm * 128 + tn * 16, B_XS + 8 * c);
      }
      {
        const char* pv = mp.wqkv + (tm * 16 + (lane >> 1)) * 6144 + 4096 + tn * 256 + (lane & 1) * 128;
        const char* pd = mp.wd + (bid & 15) * 128 + ((bid >> 4) * 448 + lane) * 2048;
        const char* po = mp.wo + bid * 16384 + lane * 128;
        mbar_wait(B_XS + 24, 0);
        __nanosleep(PF_WAIT);
#pragma unroll 1
        for (int i = PF_V ? 0 : 4; i < (PF_O ? 22 : 18); i++) {
          asm volatile("prefetch.global.L2 [%0];" ::"l"(i < 4 ? pv + i * (256 * 6144) : i < 18 ? pd + (i - 4) * 65536 : po + (i - 18) * 4096));
          __nanosleep(PF_GAP);
        }
      }
      nb_sync(NB_Z, 160);
      const uint32_t ep = lds32(S_EPOCH);
      {
        float z[4] = {0.f, 0.f, 0.f, 0.f};
        e_signal(H_Z + tn, tm);
        await(H_Z + tn, 0xffffu, ep);
#pragma unroll 1
        for (int i = 0; i < 4; i++) {
          uint32_t p[16];
          poll_z(p, g_z + i * 4096 + tn * 128 + lane * 4, ep, 1u);
#pragma unroll
          for (int q = 0; q < 4; q++) z[q] += (__uint_as_float(p[q]) + __uint_as_float(p[4 + q])) + (__uint_as_float(p[8 + q]) + __uint_as_float(p[12 + q]));
        }
        const uint32_t z01 = pack(z[0], z[1]), z23 = pack(z[2], z[3]);
        if (bid < 112) mbar_wait(B_PFREE, 0);
#pragma unroll
        for (int n = 0; n < 8; n++) sts64(KVB + (lane >> 4) * 5120 + n * 128 + ((((lane >> 1) & 7) ^ n) << 4) + (lane & 1) * 8, z01, z23);
        fence_async_smem();
        nb_arrive(NB_KVB, 320);
        STAMP_IF(lane == 0, 46);
      }
      nb_sync(NB_Q0, 192);
      e_store2d(&mp.m_os, tn * 128, tm * 128, STG);
      nb_sync(NB_OWN0, 288);
      e_store2d(&mp.m_os, tn * 128, tm * 128 + 64, STG + 8192);
      if (!SIG_EARLY) bulk_wait_read(); else if (SIG_EARLY > 1) __nanosleep(SIG_EARLY);
      e_signal(H_O + tm, 2 * tn);
      STAMP_IF(lane == 0, 4);
      nb_sync(NB_H1, 160);
      e_store2d(&mp.m_os, tn * 128 + 64, tm * 128, STG + 16384);
      e_store2d(&mp.m_os, tn * 128 + 64, tm * 128 + 64, STG + 24576);
      bulk_wait_read();
      e_signal(H_O + tm, 2 * tn + 1);
      STAMP_IF(lane == 0, 5);
      nb_arrive(NB_ST, 288);
    } else if (w == 14) {
      e_pfmap(&mp.m_gu); e_pfmap(&mp.m_o); e_pfmap(&mp.m_os); e_pfmap(&mp.m_wo); e_pfmap(&mp.m_down); e_pfmap(&mp.m_out);
      const uint32_t ep = ld_relaxed(&g_epoch) + 1;
      nb_sync(NB_FDONE, 416);
      {
        uint32_t c[4];
        poll_quad(c, g_csum + tn * 128 + lane * 4, ep, 1u);
        sts128(S_CSQ + lane * 16, c[0], c[1], c[2], c[3]);
        nb_arrive(NB_CSQ, 160);
        poll_quad(c, g_csum + 1024 + tn * 128 + lane * 4, ep, 1u);
        sts128(S_CSV + lane * 16, c[0], c[1], c[2], c[3]);
        __syncwarp();
        e_arrive(B_CSV);
      }
      {
        mbar_wait(B_WK, 1);
        if (KV_SPEC) __nanosleep(KV_SPEC); else await(H_KV + tn, 0xffffu, ep);
        STAMP_IF(lane == 0, 7);
        if (bid < 112) mbar_wait(B_PFREE, 0);
        STAMP_IF(lane == 0, 23);
        uint32_t bad, ph = 0;
        do {
          e_expect(B_KVL, 8192);
          e_load(KVB + 1024, g_kv + tn * 512, 4096, B_KVL);
          e_load(KVB + 6144, g_kv + tn * 512 + 256, 4096, B_KVL);
          mbar_wait(B_KVL, ph & 1);
          bad = 0;
#pragma unroll
          for (int i = 0; i < 16; i++) bad |= __float_as_uint(lds32v(KVB + 1024 + (i & 8) * 128 + i * 512 + lane * 16)) ^ ep;
          bad = __any_sync(0xffffffffu, bad & 1u);
          if (bad) fence_async_smem();
        } while (bad && ++ph < 100000);
        nb_arrive(NB_KVB, 320);
        STAMP_IF(lane == 0, 24);
      }
      nb_sync(NB_Q0, 192);
      uint32_t ready = 0;
      int s = 0, ph = 1;
#pragma unroll 1
      for (int r = 2; r < 16; r++) {
        const int kb = out_kblock(r, tn);
        if (!((ready >> kb) & 1)) {
          uint32_t f[1];
          poll0(f, g_sig + (H_O + tm) * 32, 0u - (ep & 1u), 1u << kb);
          ready = f[0] ^ ((ep & 1u) - 1u);
        }
        if (r == 4) mbar_wait(B_DND, 0);
        refill_x(B_EMPTY + 8 * s, ph, B_FULL + 8 * s, RING + s * SLOT + 16384, &mp.m_o, kb * 64, tm * 128);
        STAMP_IF(lane == 0 && r == 2, 2);
        STAMP_IF(lane == 0 && r == 9, 3);
        if (++s == NST) { s = 0; ph ^= 1; }
      }
    } else {
      uint32_t nsm = 132;
      if (BY_SMID) asm volatile("mov.u32 %0, %%nsmid;" : "=r"(nsm));
      asm volatile("{\n.reg .pred q;\nsetp.eq.u32 q, %0, 1156;\n@q bra LOK;\ntrap;\nLOK:\n}" ::"r"((uint32_t)__cvta_generic_to_shared(smem_raw) + nsm));
      const uint32_t ep = ld_relaxed(&g_epoch) + 1;
      mbar_wait(B_CSDN, 0);
#pragma unroll 1
      for (int n = 0; n < 3 && bid < 112; n++) {
        __nanosleep(FFN_GAP);
        e_expect(B_FR + 8 * n, 8192);
        e_tma3d_ef(GR + n * 8192, &mp.m_gu, bid * 32, n * 64, B_FR + 8 * n, EVICT_FIRST);
      }
      uint32_t sel[2];
      poll_pair(sel, g_sel + (bid >> 4) * 16 + (lane >> 2), ep, 31u);
      const char* xs = mp.x + key_token(sel[0]) * 2048 + (lane & 3) * 16;
      const uint32_t xd = AUX + (lane >> 2) * 64 + (((lane & 3) ^ (lane >> 3)) << 4);
      auto slices = [&](int n, int p) {
        asm volatile("cp.async.cg.shared.global [%0], [%1], 16;\ncp.async.cg.shared.global [%0+512], [%1+64], 16;\ncp.async.commit_group;"
                     ::"r"(xd + p * 1024), "l"(xs + n * 128) : "memory");
      };
      if ((lane & 3) == 0) sts64(S_SEL + lane * 2, sel[0], sel[1]);
      if (bid < 112) {
#pragma unroll
        for (int i = 0; i < 6; i++) slices(i, i);
      }
      asm volatile("cp.async.wait_group 2;" ::: "memory");
      fence_async_smem();
      __syncwarp();
      e_arrive(B_SEL);
      if (bid < 112) {
        int s = 0, ph = 0;
#pragma unroll 1
        for (int n = 3; n < 16; n++) {
          refill_g(B_FE + 8 * s, ph, B_FR + 8 * s, GR + s * 8192, &mp.m_gu, bid * 32, n * 64);
          STAMP2(64 + n);
          asm volatile("cp.async.wait_group 1;" ::: "memory");
          fence_async_smem();
          __syncwarp();
          if (n < 13) slices(n + 3, s + 3 * ph);
          else asm volatile("cp.async.commit_group;" ::: "memory");
          if (++s == 3) { s = 0; ph ^= 1; }
        }
      }
      e_expect(B_DR, 16384);
      if (bid < 112) mbar_wait(B_FE + 8, 0);
      e_tma2d_ef(FR, &mp.m_down, (bid & 15) * 64, (bid >> 4) * 448, B_DR, EVICT_FIRST);
      if (bid < 112) mbar_wait(B_FE + 16, 0);
      e_tma2d_ef(FR + 8192, &mp.m_down, (bid & 15) * 64, (bid >> 4) * 448 + 64, B_DR, EVICT_FIRST);
    }
  } else if (w >= 8) {
    asm volatile("setmaxnreg.dec.sync.aligned.u32 56;");
    const int t = tid - 256, ww = w - 8;
    const uint32_t ep = ld_relaxed(&g_epoch) + 1, par = ep & 1u;
    sts32(FONES + t * 4, 0x3f803f80u);
    {
      const int r0 = (lane >> 3) + (lane & 4);
      const uint32_t a = FR + (ww >> 1) * 8192 + r0 * 128 + ((((ww & 1) * 4 + (lane & 3)) ^ r0) << 4);
      float c[8];
      reg_zero(c);
      mbar_wait(B_WK, 0);
#pragma unroll 2
      for (int i = 0; i < 8; i++) {
        const uint4 v = lds128(a + i * 1024);
        c[0] += bf_lo(v.x); c[1] += bf_hi(v.x); c[2] += bf_lo(v.y); c[3] += bf_hi(v.y);
        c[4] += bf_lo(v.z); c[5] += bf_hi(v.z); c[6] += bf_lo(v.w); c[7] += bf_hi(v.w);
      }
      const bool u16 = lane & 16, u8 = lane & 8, u4 = lane & 4;
      const float d0 = xred(c[0], c[4], u16, 16), d1 = xred(c[1], c[5], u16, 16), d2 = xred(c[2], c[6], u16, 16), d3 = xred(c[3], c[7], u16, 16);
      fence_async_smem();
      e_arrive(B_CSDN);
      const float sum = xred(xred(d0, d2, u8, 8), xred(d1, d3, u8, 8), u4, 4);
      st_relaxed(g_csum + (2 + tm) * 1024 + tn * 128 + ww * 32 + (lane & 3) * 8 + (lane >> 2), tagf(sum, par));
      STAMP_IF(t == 0, 8);
      nb_sync(NB_WG2, 128);
      if (ww == 0) { e_signal(H_CS + tn, tm); await(H_CS + tn, 0xffffu, ep); }
      nb_sync(NB_WG2, 128);
      uint32_t p[16];
      poll16(p, g_csum + 2048 + tn * 128 + t, par, 1u);
      float tot = 0.f;
#pragma unroll
      for (int i = 0; i < 16; i += 4) tot += (__uint_as_float(p[i]) + __uint_as_float(p[i + 1])) + (__uint_as_float(p[i + 2]) + __uint_as_float(p[i + 3]));
      sts32(S_CSK + t * 4, __float_as_uint(tot));
      nb_arrive(NB_FDONE, 416);
      STAMP_IF(t == 0, 9);
    }
    const int ks = bid >> 4, nt = bid & 15;
    if (bid < 112) {
      float fg[8];
      reg_zero(fg);
      mbar_wait(B_SEL, 0);
      constexpr uint64_t DA0 = mkdesc(GR, 4096, 512, 2), DB0 = mkdesc(AUX, 16, FONES - AUX, 2), DBS = 32 - (32ull << 32);
      uint64_t da = DA0, db = DB0;
      uint32_t bar = B_FR, ph = 0;
#pragma unroll 1
      for (int n = 0; n < 16; n++) {
        mbar_wait(bar, ph);
        wg_fence();
#pragma unroll
        for (int q = 0; q < 4; q++) wgmma_n16_ss<1, 0>(fg, da + q * 64, db + (q >> 1) * DBS + (q & 1) * 2, 1);
        wg_commit();
        const uint32_t rel = bar + (B_FE - B_FR);
        const bool wrap = bar == B_FR + 16;
        da = wrap ? DA0 : da + 512;
        db = wrap && ph ? DB0 : db + 2 * DBS;
        bar = wrap ? B_FR : bar + 8;
        ph ^= wrap;
        wg_wait<0>();
        if (t == 0) mbar_arrive(rel);
      }
      if (t == 0) mbar_arrive(B_PFREE);
      const uint4 st = lds128(S_SEL + (lane & 3) * 16);
      const float r0 = rcp(bf_lo(st.y)), r1 = rcp(bf_lo(st.w));
      reg_fence(fg);
      const float fa[4] = {fmaf(-bf_hi(st.y), fg[4], fg[0]) * r0, fmaf(-bf_hi(st.w), fg[4], fg[1]) * r1,
                           fmaf(-bf_hi(st.y), fg[6], fg[2]) * r0, fmaf(-bf_hi(st.w), fg[6], fg[3]) * r1};
      STAMP_IF(t == 0, 12);
      const bool isup = (ww >> 1) != (mp.wu < mp.wg);
      nb_sync(NB_WG2, 128);
      if (isup) sts128f(HOP + (t & 63) * 16, fa[0], fa[1], fa[2], fa[3]);
      nb_sync(NB_WG2, 128);
      if (!isup) {
        const float4 u = lds128f(HOP + (t & 63) * 16);
        const float uu[4] = {u.x, u.y, u.z, u.w};
        uint32_t* hp = g_h + bid * 256 + (lane & 3) * 64 + (ww & 1) * 16 + (lane >> 2);
#pragma unroll
        for (int i = 0; i < 4; i++) {
          const float g = fa[i], hv = g * rcp(1.f + ex2(-g * LOG2E)) * uu[i];
          st_relaxed(hp + (i & 1) * 32 + (i >> 1) * 8, __byte_perm(pack(hv, hv), ep, 0x3254));
        }
      }
      nb_sync(NB_WG2, 128);
      if (ww == 0) e_signal(H_H + bid / 14, bid % 14);
    }
    {
      uint32_t v[28];
      if (ww == 0) await(H_H + ks, 0x3fffu, ep);
      nb_sync(NB_WG2, 128);
      poll7x4(v, g_h + ks * 3584 + t * 4, ep, 0xffffu);
      mbar_wait(B_WK, 1);
#pragma unroll
      for (int q = 0; q < 7; q++)
        asm volatile("st.shared.v2.u32 [%0], {%1,%2};" ::"r"((q < 6 ? HOP + q * 1024 : S_CSK) + (t >> 3) * 64 + ((((t >> 1) & 3) ^ ((t >> 4) & 3)) << 4) + (t & 1) * 8),
                     "r"(__byte_perm(v[4 * q], v[4 * q + 1], 0x7632)), "r"(__byte_perm(v[4 * q + 2], v[4 * q + 3], 0x7632)) : "memory");
      fence_async_smem();
      nb_sync(NB_WG2, 128);
    }
    STAMP_IF(t == 0, 13);
    float fa[4] = {0.f, 0.f, 0.f, 0.f};
    auto down = [&](uint32_t a, int k0, int nk) {
#pragma unroll
      for (int q = 0; q < (EXP_ND ? 1 : nk); q++) wgmma_n8_ss<1, 0>(fa, mkdesc(a + q * 2048, 4096, 1024, 1), mkdesc((k0 < 24 ? HOP : S_CSK - 6144) + ((k0 + q) >> 1) * 512 + (q & 1) * 32, 16, 512, 2), 1);
    };
    mbar_wait(B_DR, 0);
    mbar_wait(B_DR + 16, 0);
    mbar_wait(B_DR + 8, 0);
    wg_fence();
    down(RING + 2 * SLOT + 16384, 24, 4);
    down(RING + 3 * SLOT + 16384, 8, 8);
    down(RING + 4 * SLOT + 16384, 16, 8);
    wg_commit();
    wg_fence();
    down(FR, 0, 8);
    wg_commit();
    wg_wait<1>();
    if (t == 0) mbar_arrive(B_DND);
    wg_wait<0>();
    reg_fence(fa);
    STAMP_IF(t == 0, 14);
    {
      uint32_t* yp = g_yp + (nt * 8 + ks) * 512 + (lane & 3) * 128 + ww * 16 + (lane >> 2);
#pragma unroll
      for (int i = 0; i < 4; i++) st_relaxed(yp + (i & 1) * 64 + (i >> 1) * 8, tagf(fa[i], par));
    }
    nb_sync(NB_WG2, 128);
    if (ww == 0) e_signal(H_Y + (nt >> 1), (nt & 1) * 8 + ks);
    mbar_wait(B_SEL, 0);
    const uint32_t mykey = lds32(S_SEL + (lane & 7) * 8);
    const uint32_t inmask = __ballot_sync(0xffffffffu, (key_token(mykey) >> 7) == tm) & 0xffu;
    sts128(FR + t * 16, 0u, 0u, 0u, 0u);
    if (inmask) {
      if (ww == 0) await(H_Y + tn, 0xffffu, ep);
      nb_sync(NB_WG2, 128);
      const float sg = rcp(1.f + ex2(-key_score(mykey) * LOG2E));
#pragma unroll 1
      for (uint32_t mine = __ballot_sync(0xffffffffu, ((inmask >> lane) & 1) && (__popc(inmask & ((1u << lane) - 1)) & 3) == ww); mine; mine &= mine - 1) {
        const int j = __ffs(mine) - 1;
        uint32_t p[32];
        poll8x4(p, g_yp + (tn * 2 + (lane >> 4)) * 4096 + j * 64 + (lane & 15) * 4, par, 1u);
        float y[4];
        const float sj = __shfl_sync(0xffffffffu, sg, j);
#pragma unroll
        for (int i = 0; i < 4; i++)
          y[i] = sj * (((__uint_as_float(p[i]) + __uint_as_float(p[4 + i])) + (__uint_as_float(p[8 + i]) + __uint_as_float(p[12 + i]))) +
                       ((__uint_as_float(p[16 + i]) + __uint_as_float(p[20 + i])) + (__uint_as_float(p[24 + i]) + __uint_as_float(p[28 + i]))));
        asm volatile("st.shared.v2.u32 [%0], {%1,%2};" ::"r"(FR + (lane >> 4) * 1024 + j * 128 + ((((lane >> 1) & 7) ^ j) << 4) + (lane & 1) * 8),
                     "r"(pack(y[0], y[1])), "r"(pack(y[2], y[3])) : "memory");
      }
    }
    fence_async_smem();
    nb_arrive(NB_ST, 288);
    STAMP_IF(t == 0, 15);
  } else if (w >= 4) {
    asm volatile("setmaxnreg.inc.sync.aligned.u32 208;");
    const int t = tid - 128, ww = w - 4, g = lane >> 2, t4 = lane & 3;
    const bool leader = t == 0;
    const uint32_t ep = ld_relaxed(&g_epoch) + 1, par = ep & 1u;
    {
      const uint4* wp = reinterpret_cast<const uint4*>(mp.w_r) + lane;
      uint4 w0 = __ldg(wp), w1 = __ldg(wp + 32), w2 = __ldg(wp + 64), w3 = __ldg(wp + 96);
      if (leader) sts32(S_EPOCH, ep);
      if (KV_SPEC && t4 == 0) {
        const int grp = (tm & 1) * 2 + ((lane >> 3) & 1), row = ww * 2 + ((lane >> 2) & 1);
        st_unit(g_kv + tn * 512 + ((tm >> 3) * 4 + grp) * 64 + row * 8 + (((tm & 2) * 2 + ((tm >> 1) & 2) + (lane >> 4)) ^ row), 0u, 0u, 0u, 0u, par ^ 1u);
      }
      float s[4] = {0.f, 0.f, 0.f, 0.f}, q[4] = {0.f, 0.f, 0.f, 0.f}, d[4] = {0.f, 0.f, 0.f, 0.f}, wsum = 0.f;
#pragma unroll 1
      for (int c = 0; c < 4; c++) {
        const float wr[8] = {bf_lo(w0.x), bf_hi(w0.x), bf_lo(w0.y), bf_hi(w0.y), bf_lo(w0.z), bf_hi(w0.z), bf_lo(w0.w), bf_hi(w0.w)};
        w0 = w1; w1 = w2; w2 = w3;
        wsum += ((wr[0] + wr[1]) + (wr[2] + wr[3])) + ((wr[4] + wr[5]) + (wr[6] + wr[7]));
        mbar_wait(B_XS + 8 * c, 0);
#pragma unroll
        for (int r = 0; r < 4; r++) {
          const uint4 v = lds128(STG + c * 8192 + (ww * 4 + r) * 512 + lane * 16);
          const uint32_t xw[4] = {v.x, v.y, v.z, v.w};
#pragma unroll
          for (int i = 0; i < 4; i++) {
            const uint32_t dep = __float_as_uint(q[i ? r : (r + 3) & 3]);
            const float lo = __uint_as_float(prmt(xw[i], dep, 0x10ff)), hi = __uint_as_float(prmt(xw[i], dep, 0x32ff));
            s[r] += lo; q[r] = fmaf(lo, lo, q[r]); d[r] = fmaf(lo, wr[2 * i], d[r]);
            s[r] += hi; q[r] = fmaf(hi, hi, q[r]); d[r] = fmaf(hi, wr[2 * i + 1], d[r]);
          }
        }
      }
      STAMP_IF(leader, 16);
      const bool u16 = lane & 16, u8 = lane & 8, u4 = lane & 4, u2 = lane & 2;
      const float s1 = xred(xred(s[0], s[2], u16, 16), xred(s[1], s[3], u16, 16), u8, 8);
      const float q1 = xred(xred(q[0], q[2], u16, 16), xred(q[1], q[3], u16, 16), u8, 8);
      const float d1 = xred(xred(d[0], d[2], u16, 16), xred(d[1], d[3], u16, 16), u8, 8);
      wsum += __shfl_xor_sync(0xffffffffu, wsum, 16);
      wsum += __shfl_xor_sync(0xffffffffu, wsum, 8);
      float tot = xred(xred(s1, d1, u4, 4), xred(q1, wsum, u4, 4), u2, 2);
      tot += __shfl_xor_sync(0xffffffffu, tot, 1);
      const float qq = __shfl_down_sync(0xffffffffu, tot, 2), dd = __shfl_down_sync(0xffffffffu, tot, 4), ws = __shfl_down_sync(0xffffffffu, tot, 6);
      if ((lane & 7) == 0) {
        const float mean = tot * (1.f / 1024.f);
        const float var = fmaxf(fmaf(-mean, mean, qq * (1.f / 1024.f)), 0.f);
        float sd;
        asm("sqrt.approx.ftz.f32 %0, %1;" : "=f"(sd) : "f"(bf_round(bf_round(var) + 1e-5f)));
        const uint32_t ms = pack(sd, mean);
        const int row = tm * 128 + tn * 16 + ww * 4 + (lane >> 3);
        const uint32_t rbits = pack(0.f, fmaf(-bf_hi(ms), ws, dd) * rcp(bf_lo(ms)));
        const uint32_t key = (rbits ^ (((int)rbits >> 31 & 0x7fff0000u) | 0x80000000u)) | ((2047 - row) << 5) | (ep & 31u);
        asm volatile("{\n.reg .b64 x;\nmov.b64 x, {%1,%2};\nst.relaxed.gpu.global.b64 [%0], x;\n}" ::"l"(g_keys + row), "r"(key), "r"(ms) : "memory");
      }
      STAMP_IF(leader, 17);
      __nanosleep(400);
      uint32_t st[2];
      poll_pair(st, g_keys + tm * 128 + t, ep, 31u);
      asm volatile("st.shared.v2.f32 [%0], {%1,%2};" ::"r"(S_KSTAT + t * 8), "f"(bf_hi(st[1])), "f"(rcp(bf_lo(st[1])) * LOG2E) : "memory");
      nb_arrive(NB_FDONE, 416);
      STAMP_IF(leader, 10);
    }
    float a0[64], a1[64];
    reg_zero(a0); reg_zero(a1); reg_fence(a0); reg_fence(a1);
    STAMP_IF(leader, 18);
    nb_sync(NB_KV, 256);
    mainloop<true, 14>(a0, a1, 1, 1, 0, 0, leader);
    {
      auto half = [&](float (&a)[64], int s, int m) {
#pragma unroll
        for (int j = 0; j < 4; j++)
          wgmma_n128_ss<1, 0>(a, mkdesc(RING + s * SLOT + m * 8192 + j * 2048, 8192, 1024, 1), mkdesc(RING + s * SLOT + 16384 + j * 32, 16, 1024, 1), 1);
      };
      auto kvmma = [&](float (&a)[64], float (&c)[32], int m) {
        reg_fence(a);
        uint32_t f[32];
#pragma unroll
        for (int i = 0; i < 32; i++) f[i] = pack(a[2 * i], a[2 * i + 1]);
        reg_zero(c);
        wg_fence();
#pragma unroll
        for (int k = 0; k < 8; k++) {
          wgmma_n64_rs<0>(c, f[4 * k], f[4 * k + 1], f[4 * k + 2], f[4 * k + 3], mkdesc(STG + (k >> 2) * 16384 + m * 8192 + (k & 3) * 32, 16, 1024, 1), k != 0);
          if (m && k == HAND_K) nb_arrive(NB_VQ, 256);
        }
        wg_commit();
      };
      float c0[32], c1[32];
      mbar_wait(B_FULL, 0);
      wg_fence();
      half(a0, 0, 0);
      wg_commit();
      mbar_wait(B_FULL + 8, 0);
      wg_fence();
      half(a0, 1, 0);
      wg_commit();
      wg_wait<2>();
      if (leader) mbar_arrive(B_EMPTY + 32);
      wg_fence();
      half(a1, 0, 1);
      half(a1, 1, 1);
      wg_commit();
      nb_sync(NB_PK, 256);
      wg_wait<1>();
      kvmma(a0, c0, 0);
      wg_wait<1>();
      if (leader) { mbar_arrive(B_EMPTY); mbar_arrive(B_EMPTY + 8); }
      STAMP_IF(leader, 19);
      kvmma(a1, c1, 1);
      const bool hp = ww >> 1;
      float c[4];
      float2 tt[8];
#pragma unroll
      for (int i = 0; i < 8; i++) tt[i] = lds64f(S_CSK + ((i >> 2) * 64 + hp * 32 + (i & 3) * 8 + 2 * t4) * 4);
      mbar_wait(B_CSV, 0);
#pragma unroll
      for (int i = 0; i < 4; i++) c[i] = -__uint_as_float(lds32(S_CSV + ((i >> 1) * 64 + ww * 16 + (i & 1) * 8 + g) * 4));
      wg_wait<0>();
      reg_fence(c0);
      reg_fence(c1);
      if (leader) mbar_arrive(B_SFREE);
      STAMP_IF(leader, 20);
      uint4* pp = g_kvp + (tn * 16 + tm) * 512 + t;
      auto put = [&](int q, const float* d) {
        const float ca = c[q & 2], cb = c[q | 1];
        const float2 ta = tt[2 * q], tb = tt[2 * q + 1];
        st_unit(pp + q * 128, pack(fmaf(ca, ta.x, d[0]), fmaf(ca, ta.y, d[1])), pack(fmaf(cb, ta.x, d[2]), fmaf(cb, ta.y, d[3])),
                pack(fmaf(ca, tb.x, d[4]), fmaf(ca, tb.y, d[5])), pack(fmaf(cb, tb.x, d[6]), fmaf(cb, tb.y, d[7])), par);
      };
      if (!hp) { put(0, c0); put(1, c0 + 8); put(2, c1); put(3, c1 + 8); }
      else { put(0, c0 + 16); put(1, c0 + 24); put(2, c1 + 16); put(3, c1 + 24); }
      STAMP_IF(leader, 47);
      {
        uint32_t p[16];
        nb_sync(NB_WG1, 128);
        if (ww == 0) { e_signal(H_KVP + tn, tm); await(H_KVP + tn, 0xffffu, ep); }
        nb_sync(NB_WG1, 128);
        STAMP_IF(leader, 1);
        poll_kvp(p, g_kvp + (tn * 16 + (lane >> 3) * 4) * 512 + tm * 32 + ww * 8 + (lane & 7), par, 1u);
        float r[8];
#pragma unroll
        for (int i = 0; i < 4; i++) {
          r[2 * i] = (bf_lo(p[i]) + bf_lo(p[4 + i])) + (bf_lo(p[8 + i]) + bf_lo(p[12 + i]));
          r[2 * i + 1] = (bf_hi(p[i]) + bf_hi(p[4 + i])) + (bf_hi(p[8 + i]) + bf_hi(p[12 + i]));
        }
        const bool u16 = lane & 16, u8 = lane & 8;
        const uint32_t wd = pack(xred(xred(r[0], r[4], u16, 16), xred(r[2], r[6], u16, 16), u8, 8), xred(xred(r[1], r[5], u16, 16), xred(r[3], r[7], u16, 16), u8, 8));
        const uint32_t w1 = __shfl_down_sync(0xffffffffu, wd, 1), w2 = __shfl_down_sync(0xffffffffu, wd, 2), w3 = __shfl_down_sync(0xffffffffu, wd, 3);
        const int grp = (tm & 1) * 2 + ((lane >> 3) & 1), row = ww * 2 + ((lane >> 2) & 1);
        if (t4 == 0) st_unit(g_kv + tn * 512 + ((tm >> 3) * 4 + grp) * 64 + row * 8 + (((tm & 2) * 2 + ((tm >> 1) & 2) + (lane >> 4)) ^ row), wd, w1, w2, w3, par);
        nb_sync(NB_WG1, 128);
        if (ww == 0) { if (!KV_SPEC) e_signal(H_KV + tn, tm); e_arrive(B_WK); }
      }
      STAMP_IF(leader, 21);
    }
    const uint32_t sx = lane & 7, sc = lane >> 4;
    const uint32_t sa = STG + (ww * 16 + (lane & 15)) * 128;
    const uint32_t sw[4] = {sa + ((sc ^ sx) << 4), sa + (((2 + sc) ^ sx) << 4), sa + (((4 + sc) ^ sx) << 4), sa + (((6 + sc) ^ sx) << 4)};
    auto residual = [&]() {
      float ka[4], kb[4];
#pragma unroll
      for (int i = 0; i < 4; i++) {
        const float2 st = lds64f(S_KSTAT + ((i >> 1) * 64 + ww * 16 + (i & 1) * 8 + g) * 8);
        const float r = st.y * LN2;
        ka[i] = 1.f + r; kb[i] = -st.x * r;
      }
#pragma unroll
      for (int j = 0; j < 8; j++) {
        if ((j & 3) == 0) mbar_wait(B_XRES + 8 * (j >> 2), 0);
        const uint4 v = ldsm4(sw[j & 3] + (j >> 2) * 16384), u = ldsm4(sw[j & 3] + (j >> 2) * 16384 + 8192);
        const uint32_t vv[4] = {v.x, v.y, v.z, v.w}, uu[4] = {u.x, u.y, u.z, u.w};
#pragma unroll
        for (int i = 0; i < 4; i++) {
          a0[8 * j + 2 * i] = fmaf(bf_lo(vv[i]), ka[i & 1], kb[i & 1]);
          a0[8 * j + 2 * i + 1] = fmaf(bf_hi(vv[i]), ka[i & 1], kb[i & 1]);
          a1[8 * j + 2 * i] = fmaf(bf_lo(uu[i]), ka[2 + (i & 1)], kb[2 + (i & 1)]);
          a1[8 * j + 2 * i + 1] = fmaf(bf_hi(uu[i]), ka[2 + (i & 1)], kb[2 + (i & 1)]);
        }
      }
      reg_fence(a0);
      reg_fence(a1);
      STAMP_IF(leader, 22);
    };
    residual();
    nb_arrive(NB_KVB, 320);
    uint32_t oh[4];
    {
      mbar_wait(B_SEL, 0);
      const int r0 = key_token(lds32(S_SEL + t4 * 16)) - tm * 128, r1 = key_token(lds32(S_SEL + t4 * 16 + 8)) - tm * 128;
#pragma unroll
      for (int i = 0; i < 4; i++) {
        const int row = (i >> 1) * 64 + ww * 16 + (i & 1) * 8 + g;
        oh[i] = (r0 == row ? 0x3f00u : 0u) | (r1 == row ? 0x3f000000u : 0u);
      }
    }
    uint32_t va = RING + 16384 + sc * 8192 + (ww * 16 + (lane & 8)) * 128 + sx * 16 + (lane >> 3) * 4;
    asm volatile("" : "+r"(va));
    {
      auto own = [&](int r) {
        if (OWN_LATE != 1 || !r) nb_sync(NB_OWN0 + r, r ? 256 : 288);
        if (OWN_LATE == 1 && !r) nb_sync(NB_OWN1, 256);
        if (OWN_LATE > 1 && !r) nb_sync(NB_Y, 256);
        mbar_wait(B_FULL + 8 * (3 + r), 1);
        STAMP_IF(leader, 25 + r);
        const uint64_t dw = mkdesc(RING + (3 + r) * SLOT, 8192, 1024, 1), dx = mkdesc(STG + r * 16384, 16, 1024, 1);
        wg_fence();
#pragma unroll
        for (int j = 0; j < 4; j++) {
          wgmma_n128_ss<0, 1>(a0, dx + j * 2, dw + j * 128, 1);
          wgmma_n128_ss<0, 1>(a1, dx + j * 2 + 512, dw + j * 128, 1);
        }
        wg_commit();
      };
      own(0);
      if (!OWN_LATE) wg_wait<0>();
      if (!OWN_LATE && leader) mbar_arrive(B_EMPTY + 24);
      own(1);
      if (OWN_LATE) wg_wait<1>();
      if (OWN_LATE && leader) mbar_arrive(B_EMPTY + 24);
      auto check = [&](int r, int s) {
          uint32_t bad;
          asm volatile("{\n.reg .u32 a, b, c, d, e, f, g, h;\n.reg .pred p;\n"
                       "ld.shared.u32 a, [%1];\nld.shared.u32 b, [%1+128];\nld.shared.u32 c, [%1+256];\nld.shared.u32 d, [%1+384];\n"
                       "ld.shared.u32 e, [%1+512];\nld.shared.u32 f, [%1+640];\nld.shared.u32 g, [%1+768];\nld.shared.u32 h, [%1+896];\n"
                       "lop3.b32 a, a, b, %2, 0x7e;\nlop3.b32 c, c, d, %2, 0x7e;\nlop3.b32 e, e, f, %2, 0x7e;\nlop3.b32 g, g, h, %2, 0x7e;\n"
                       "lop3.b32 a, a, c, e, 0xfe;\nlop3.b32 a, a, g, 1, 0xa8;\nsetp.ne.u32 p, a, 0;\nvote.sync.any.pred p, p, 0xffffffff;\nselp.u32 %0, 1, 0, p;\n}"
                       : "=r"(bad) : "r"(va + s * SLOT), "r"(par) : "memory");
          if (__builtin_expect(bad, 0)) {
            const uint4* src = reinterpret_cast<const uint4*>(g_o + (tm * 128 + sc * 64 + ww * 16 + (lane & 15)) * 1024 + out_kblock(r, tn) * 64);
#pragma unroll 1
            for (int i = 0; i < 8; i++) {
              uint32_t v[4];
              asm volatile("{\n.reg .b64 x, y;\n.reg .b128 z;\n.reg .pred p, q, h;\n.reg .u32 c, b;\nmov.u32 c, 0;\nsetp.ne.u32 h, %6, 0;\nLW:\n"
                           "ld.relaxed.gpu.global.b128 z, [%4];\nmov.b128 {x, y}, z;\nmov.b64 {%0,%1}, x;\nmov.b64 {%2,%3}, y;\n"
                           "selp.b64 x, y, x, h;\nshr.b64 x, x, %7;\ncvt.u32.u64 b, x;\nand.b32 b, b, 1;\nsetp.eq.u32 p, b, %5;\n"
                           "vote.sync.all.pred p, p, 0xffffffff;\n@p bra.uni LD;\nadd.u32 c, c, 1;\nsetp.lt.u32 q, c, 1000000;\n@q bra.uni LW;\ntrap;\nLD:\n}"
                           : "=&r"(v[0]), "=&r"(v[1]), "=&r"(v[2]), "=&r"(v[3]) : "l"(src + i), "r"(par), "r"(sc), "r"((lane & 8) * 4) : "memory");
              sts128(RING + 16384 + s * SLOT + sc * 8192 + (ww * 16 + (lane & 15)) * 128 + ((i ^ sx) << 4), v[0], v[1], v[2], v[3]);
            }
            fence_async_smem();
            __syncwarp();
          }
      };
      int s = 0, ph = 0;
      uint32_t prev = B_EMPTY + 32;
#pragma unroll 1
      for (int r = 2; r < 12; r++) {
        mbar_wait(B_FULL + 8 * s, ph);
        check(r, s);
        if (!LITE || ((LITE_MASK >> 27) & 1)) STAMP_IF(leader && r == 2, 27);
        const uint64_t dw = mkdesc(RING, 8192, 1024, 1) + s * (SLOT >> 4), dx = mkdesc(RING + 16384, 16, 1024, 1) + s * (SLOT >> 4);
        wg_fence();
#pragma unroll
        for (int j = 0; j < 4; j++) {
          wgmma_n128_ss<0, 1>(a0, dx + j * 2, dw + j * 128, 1);
          wgmma_n128_ss<0, 1>(a1, dx + j * 2 + 512, dw + j * 128, 1);
        }
        wg_commit();
        wg_wait<1>();
        if (leader) mbar_arrive(prev);
        prev = B_EMPTY + 8 * s;
        if (++s == NST) { s = 0; ph ^= 1; }
      }
      auto half = [&](float (&a)[64], int s, int m) {
        const uint64_t dw = mkdesc(RING, 8192, 1024, 1) + s * (SLOT >> 4), dx = mkdesc(RING + 16384 + m * 8192, 16, 1024, 1) + s * (SLOT >> 4);
#pragma unroll
        for (int j = 0; j < 4; j++) wgmma_n128_ss<0, 1>(a, dx + j * 2, dw + j * 128, 1);
      };
      auto store = [&](float (&a)[64], int m) {
        reg_fence(a);
#pragma unroll
        for (int j = 0; j < 8; j++) {
          stsm4(sw[j & 3] + (j >> 2) * 16384 + m * 8192, pack(a[8 * j], a[8 * j + 1]), pack(a[8 * j + 2], a[8 * j + 3]), pack(a[8 * j + 4], a[8 * j + 5]), pack(a[8 * j + 6], a[8 * j + 7]));
          if ((j & 3) == 3) {
            fence_async_smem();
            e_store2d(&mp.m_out, tn * 128 + (j >> 2) * 64, tm * 128 + m * 64 + ww * 16, STG + (j >> 2) * 16384 + m * 8192 + ww * 2048);
          }
        }
      };
#pragma unroll 1
      for (int q = 0; q < 4; q++) {
        mbar_wait(B_FULL + 8 * q, 0);
        check(12 + q, q);
        wg_fence();
        half(a0, q, 0);
        wg_commit();
      }
      nb_sync(NB_ST, 288);
      wg_fence();
      wgmma_n128_rs<1>(a0, oh[0], oh[1], oh[0], oh[1], mkdesc(FR, 1024, 0, 1), 1);
      wg_commit();
      wg_fence();
      half(a1, 0, 1);
      half(a1, 1, 1);
      wg_commit();
      wg_wait<1>();
      store(a0, 0);
      wg_fence();
      half(a1, 2, 1);
      half(a1, 3, 1);
      wgmma_n128_rs<1>(a1, oh[2], oh[3], oh[2], oh[3], mkdesc(FR, 1024, 0, 1), 1);
      wg_commit();
      wg_wait<0>();
      STAMP_IF(leader, 28);
      store(a1, 1);
    }
    bulk_wait_read();
    if (bid == 0 && leader) st_relaxed(&g_epoch, ep);
    STAMP_IF(leader, 29);
  } else {
    asm volatile("setmaxnreg.inc.sync.aligned.u32 216;");
    const int g = lane >> 2, t4 = lane & 3;
    const bool leader = tid == 0;
    const uint32_t sx = lane & 7, sc = lane >> 4;
    const uint32_t sa = STG + (w * 16 + (lane & 15)) * 128;
    const uint32_t sw[4] = {sa + ((sc ^ sx) << 4), sa + (((2 + sc) ^ sx) << 4), sa + (((4 + sc) ^ sx) << 4), sa + (((6 + sc) ^ sx) << 4)};
    float a0[64], a1[64];
    reg_zero(a0); reg_zero(a1); reg_fence(a0); reg_fence(a1);
    mainloop<true>(a0, a1, 0, 0, NB_KV, 0, leader);
    STAMP_IF(leader, 33);
    {
      nb_sync(NB_FDONE, 416);
      STAMP_IF(leader, 34);
      const uint32_t par = lds32(S_EPOCH) & 1u;
#pragma unroll 1
      for (int m = 0;; m++) {
        const uint32_t ca = S_CSK + (m * 64 + w * 16 + g) * 4;
        const float c[2] = {-lds32v(ca), -lds32v(ca + 32)};
        float z[2] = {0.f, 0.f}, tt[2] = {0.f, 0.f};
#pragma unroll
        for (int j = 0; j < 8; j++) {
          const float4 s0 = lds128v(S_KSTAT + (j * 16 + 2 * t4) * 8), s1 = lds128v(S_KSTAT + (j * 16 + 8 + 2 * t4) * 8);
          const float mu[4] = {s0.x, s0.z, s1.x, s1.z}, rl[4] = {s0.y, s0.w, s1.y, s1.w};
          float p[8];
#pragma unroll
          for (int i = 0; i < 8; i++) {
            const int r = (i >> 1) & 1, cc = (i >> 2) * 2 + (i & 1);
            p[i] = phi2(fmaf(c[r], mu[cc], a0[8 * j + i]) * rl[cc]);
            a0[8 * j + i] = a1[8 * j + i];
            z[r] += p[i];
            p[i] *= rl[cc];
            tt[r] = fmaf(p[i], mu[cc], tt[r]);
          }
          stsm4(sw[j & 3] + (j >> 2) * 16384 + m * 8192, pack(p[0], p[1]), pack(p[2], p[3]), pack(p[4], p[5]), pack(p[6], p[7]));
        }
        const bool u2 = lane & 2, u1 = lane & 1;
        const float v = xred(xred(z[0], tt[0], u2, 2), xred(z[1], tt[1], u2, 2), u1, 1);
        if (u2) sts32(ca + (t4 & 1) * 32, __float_as_uint(v));
        else st_relaxed(g_z + tm * 1024 + tn * 128 + m * 64 + w * 16 + t4 * 8 + g, tagf(v * LOG2E, par));
        if (m) break;
      }
      fence_async_smem();
      nb_arrive(NB_PK, 256);
      nb_arrive(NB_Z, 160);
    }
    STAMP_IF(leader, 35);
    const uint32_t ep = lds32(S_EPOCH);
    uint32_t sd2[4];
    float es[4];
    {
      nb_sync(NB_CSQ, 160);
      float mu[4];
#pragma unroll
      for (int i = 0; i < 4; i++) {
        const float2 st = lds64f(S_KSTAT + ((i >> 1) * 64 + w * 16 + (i & 1) * 8 + g) * 8);
        mu[i] = -st.x;
        const float sd = LOG2E * rcp(st.y);
        sd2[i] = pack(sd, sd);
        es[i] = sd * (1e-6f * LOG2E);
      }
#pragma unroll
      for (int j = 0; j < 16; j++) {
        const float2 c = lds64f(S_CSQ + (j * 8 + 2 * t4) * 4);
        a0[4 * j] = mu[0] * c.x; a0[4 * j + 1] = mu[0] * c.y; a0[4 * j + 2] = mu[1] * c.x; a0[4 * j + 3] = mu[1] * c.y;
        a1[4 * j] = mu[2] * c.x; a1[4 * j + 1] = mu[2] * c.y; a1[4 * j + 2] = mu[3] * c.x; a1[4 * j + 3] = mu[3] * c.y;
      }
      reg_fence(a0); reg_fence(a1);
    }
    STAMP_IF(leader, 40);
    nb_sync(NB_VQ, 256);
    mainloop<false, 13>(a0, a1, 2, 0, 0, 4 + (tn & 3), leader);
    {
      uint32_t f[2][16];
      const uint32_t ra = S_KSTAT + (w * 16 + g) * 8 + 4;
      auto phi = [&](const float (&a)[64], int off, int m, int i0, int i1, uint32_t (&o)[16]) {
        const float r0 = lds32v(ra + m * 512), r1 = lds32v(ra + m * 512 + 64);
#pragma unroll
        for (int i = i0; i < i1; i++) o[i] = phi_pack(a[off + 2 * i], a[off + 2 * i + 1], i & 1 ? r1 : r0, sd2[2 * m + (i & 1)]);
      };
      auto half = [&](float (&a)[64], int s, int m) {
        const bool xr = ((13 + s) >> 1) == 4 + (tn & 3);
        if (!m) {
          mbar_wait(B_FULL + 8 * s, 1);
          if (xr) mbar_wait(B_XRES + 8 * (~s & 1), 0);
          wg_fence();
        }
        const uint64_t dx = mkdesc(m * 8192, 16, 1024, 1) + ((xr ? STG + (~s & 1) * 16384 : RING + s * SLOT + 16384) >> 4);
#pragma unroll
        for (int j = 0; j < 4; j++) wgmma_n128_ss<0, 1>(a, dx + j * 2, mkdesc(RING + s * SLOT + j * 2048, 8192, 1024, 1), 1);
      };
      half(a0, 0, 0);
      wg_commit();
      half(a0, 1, 0);
      wg_commit();
      wg_wait<2>();
      if (leader) mbar_arrive(B_EMPTY + 32);
      half(a0, 2, 0);
      wg_commit();
      wg_fence();
      half(a1, 0, 1);
      half(a1, 1, 1);
      wg_commit();
      wg_wait<1>();
      reg_fence(a0);
      phi(a0, 0, 0, 0, PHI_CUT, f[0]);
      wg_fence();
      half(a1, 2, 1);
      wg_commit();
      phi(a0, 0, 0, PHI_CUT, 16, f[0]);
      nb_sync(NB_KVB, 320);
      wg_wait<0>();
      if (leader) { mbar_arrive(B_EMPTY); mbar_arrive(B_EMPTY + 8); mbar_arrive(B_EMPTY + 16); }
      reg_fence(a1);
      STAMP_IF(leader, 36);
      const uint32_t mk[4] = {t4 == 0, t4 == 1, t4 == 2, t4 == 3};
      uint64_t db = mkdesc(KVB, 16, 1024, 1);
      uint32_t so = 0;
#pragma unroll 1
      for (int j = 0;; j++) {
        float oc[2][2][20];
        auto mma = [&](const uint32_t (&a)[16], float (&o)[2][20]) {
          reg_zero(o[0]); reg_zero(o[1]);
          wg_fence();
          wgmma_n40_rs<0>(o[0], a[0], a[1], a[2], a[3], db, 0);
          wgmma_n40_rs<0>(o[1], a[8], a[9], a[10], a[11], db + 4, 0);
          wgmma_n40_rs<0>(o[0], a[4], a[5], a[6], a[7], db + 2, 1);
          wgmma_n40_rs<0>(o[1], a[12], a[13], a[14], a[15], db + 6, 1);
          wg_commit();
        };
        auto fin = [&](int m, float (&o)[2][20]) {
          const uint32_t m0 = mk[2 * m], m1 = mk[2 * m + 1];
#pragma unroll
          for (int h = 0; h < 2; h++) {
            const float r0 = rcp(o[h][0] + es[2 * m]), r1 = rcp(o[h][2] + es[2 * m + 1]);
            {
#pragma unroll
              for (int q = 0; q < 2; q++)
                stsm4(sw[h * 2 + q] + so + m * 8192,
                      bsel(pack(o[h][4 + 8 * q] * r0, o[h][5 + 8 * q] * r0), ep, m0), bsel(pack(o[h][6 + 8 * q] * r1, o[h][7 + 8 * q] * r1), ep, m1),
                      bsel(pack(o[h][8 + 8 * q] * r0, o[h][9 + 8 * q] * r0), ep, m0), bsel(pack(o[h][10 + 8 * q] * r1, o[h][11 + 8 * q] * r1), ep, m1));
            }
          }
        };
        mma(f[0], oc[0]);
        if (OWN_LATE == 3 && j) nb_arrive(NB_Y, 256);
        STAMP_IF(leader && j, 37);
        phi(a1, 0, 1, 0, 16, f[1]);
        wg_wait<0>();
        reg_fence(oc[0][0]); reg_fence(oc[0][1]);
        mma(f[1], oc[1]);
        if (OWN_LATE == 2 && j) nb_arrive(NB_Y, 256);
        STAMP_IF(leader, 41 + 2 * j);
        fin(0, oc[0]);
        if (j == 0) { fence_async_smem(); nb_arrive(NB_Q0, 192); }
        wg_wait<0>();
        reg_fence(oc[1][0]); reg_fence(oc[1][1]);
        fin(1, oc[1]);
        fence_async_smem();
        if (j) break;
        nb_arrive(NB_OWN0, 288);
        STAMP_IF(leader, 38);
#pragma unroll
        for (int i = 0; i < 32; i++) a1[i] = a1[32 + i];
        phi(a0, 32, 0, 0, 16, f[0]);
        db = mkdesc(KVB + 5120, 16, 1024, 1);
        so = 16384;
      }
      nb_arrive(NB_OWN1, 256);
      nb_arrive(NB_H1, 160);
      STAMP_IF(leader, 39);
    }
  }
}

#undef CK
typedef CUresult (*EncodeFn)(CUtensorMap*, CUtensorMapDataType, cuuint32_t, void*, const cuuint64_t*, const cuuint64_t*, const cuuint32_t*,
                             const cuuint32_t*, CUtensorMapInterleave, CUtensorMapSwizzle, CUtensorMapL2promotion, CUtensorMapFloatOOBfill);

void make_map(EncodeFn enc, CUtensorMap* m, const void* p, int rank, uint64_t d0, uint64_t d1, uint64_t d2, uint64_t s1, uint64_t s2,
              uint32_t b0, uint32_t b1, uint32_t b2, CUtensorMapSwizzle sw) {
  cuuint64_t gd[3] = {d0, d1, d2}, gs[2] = {s1, s2};
  cuuint32_t bd[3] = {b0, b1, b2}, es[3] = {1, 1, 1};
  enc(m, CU_TENSOR_MAP_DATA_TYPE_BFLOAT16, rank, const_cast<void*>(p), gd, gs, bd, es, CU_TENSOR_MAP_INTERLEAVE_NONE, sw,
      CU_TENSOR_MAP_L2_PROMOTION_L2_128B, CU_TENSOR_MAP_FLOAT_OOB_FILL_NONE);
}

}

extern "C" void kernel_launch(void* const* d_in, const int* in_sizes, int n_in, void* d_out, int out_size) {
  (void)in_sizes; (void)n_in; (void)out_size;
  void* fn = nullptr;
  cudaDriverEntryPointQueryResult qr;
  cudaGetDriverEntryPoint("cuTensorMapEncodeTiled", &fn, cudaEnableDefault, &qr);
  EncodeFn enc = (EncodeFn)fn;
  void* o;
  cudaGetSymbolAddress(&o, g_o);
  const CUtensorMapSwizzle S128 = CU_TENSOR_MAP_SWIZZLE_128B, S64 = CU_TENSOR_MAP_SWIZZLE_64B, S0 = CU_TENSOR_MAP_SWIZZLE_NONE;
  Params mp;
  mp.x = (const char*)d_in[0]; mp.wqkv = (const char*)d_in[1]; mp.w_r = (const char*)d_in[4];
  mp.wg = (const char*)d_in[5]; mp.wu = (const char*)d_in[6]; mp.wd = (const char*)d_in[7]; mp.wo = (const char*)d_in[2];
  make_map(enc, &mp.m_wqkv, d_in[1], 3, 64, 1024, 48, 6144, 128, 64, 64, 2, S128);
  make_map(enc, &mp.m_x, d_in[0], 2, 1024, 2048, 1, 2048, 0, 64, 128, 1, S128);
  make_map(enc, &mp.m_os, o, 2, 1024, 2048, 1, 2048, 0, 64, 64, 1, S128);
  make_map(enc, &mp.m_o, o, 2, 1024, 2048, 1, 2048, 0, 64, 128, 1, S128);
  make_map(enc, &mp.m_wo, d_in[2], 3, 64, 1024, 16, 2048, 128, 64, 64, 2, S128);
  make_map(enc, &mp.m_xs, d_in[0], 2, 1024, 2048, 1, 2048, 0, 256, 16, 1, S0);
  const char *wg = (const char*)d_in[5], *wu = (const char*)d_in[6];
  make_map(enc, &mp.m_gu, wu < wg ? wu : wg, 3, 3584, 1024, 2, 7168, (uint64_t)(wu < wg ? wg - wu : wu - wg), 32, 64, 2, S64);
  make_map(enc, &mp.m_down, d_in[7], 2, 1024, 3584, 1, 2048, 0, 64, 64, 1, S128);
  make_map(enc, &mp.m_out, d_out, 2, 1024, 2048, 1, 2048, 0, 64, 16, 1, S128);
  int dev = 0, sms = 0;
  cudaGetDevice(&dev);
  cudaDeviceGetAttribute(&sms, cudaDevAttrMultiProcessorCount, dev);
  auto kern = sms == 132 ? fused_kernel<true> : fused_kernel<false>;
  cudaFuncSetAttribute(kern, cudaFuncAttributeMaxDynamicSharedMemorySize, SMEM_BYTES);
  kern<<<132, 512, SMEM_BYTES>>>(mp);
}
```

```cpp
#include <cuda_runtime.h>
#include <cuda.h>
#include <cuda_bf16.h>
#include <stdint.h>

namespace {

template <int TA, int TB>
__device__ __forceinline__ void wgmma_n8_ss(float (&d)[4], uint64_t da, uint64_t db, int sc) {
  asm volatile("{\n.reg .pred p;\nsetp.ne.b32 p, %6, 0;\n"
    "wgmma.mma_async.sync.aligned.m64n8k16.f32.bf16.bf16 {%0, %1, %2, %3}, %4, %5, p, 1, 1, %7, %8;\n}\n"
    : "+f"(d[0]), "+f"(d[1]), "+f"(d[2]), "+f"(d[3])
    : "l"(da), "l"(db), "r"(sc), "n"(TA), "n"(TB));
}
template <int TB>
__device__ __forceinline__ void wgmma_n40_rs(float (&d)[20], uint32_t a0, uint32_t a1, uint32_t a2, uint32_t a3, uint64_t db, int sc) {
  asm volatile("{\n.reg .pred p;\nsetp.ne.b32 p, %25, 0;\n"
    "wgmma.mma_async.sync.aligned.m64n40k16.f32.bf16.bf16 {%0, %1, %2, %3, %4, %5, %6, %7, %8, %9, %10, %11, %12, %13, %14, %15, %16, %17, %18, %19}, {%20,%21,%22,%23}, %24, p, 1, 1, %26;\n}\n"
    : "+f"(d[0]), "+f"(d[1]), "+f"(d[2]), "+f"(d[3]), "+f"(d[4]), "+f"(d[5]), "+f"(d[6]), "+f"(d[7]),
      "+f"(d[8]), "+f"(d[9]), "+f"(d[10]), "+f"(d[11]), "+f"(d[12]), "+f"(d[13]), "+f"(d[14]), "+f"(d[15]),
      "+f"(d[16]), "+f"(d[17]), "+f"(d[18]), "+f"(d[19])
    : "r"(a0), "r"(a1), "r"(a2), "r"(a3), "l"(db), "r"(sc), "n"(TB));
}
template <int TB>
__device__ __forceinline__ void wgmma_n64_rs(float (&d)[32], uint32_t a0, uint32_t a1, uint32_t a2, uint32_t a3, uint64_t db, int sc) {
  asm volatile("{\n.reg .pred p;\nsetp.ne.b32 p, %37, 0;\n"
    "wgmma.mma_async.sync.aligned.m64n64k16.f32.bf16.bf16 {%0, %1, %2, %3, %4, %5, %6, %7, %8, %9, %10, %11, %12, %13, %14, %15, %16, %17, %18, %19, %20, %21, %22, %23, %24, %25, %26, %27, %28, %29, %30, %31}, {%32,%33,%34,%35}, %36, p, 1, 1, %38;\n}\n"
    : "+f"(d[0]), "+f"(d[1]), "+f"(d[2]), "+f"(d[3]), "+f"(d[4]), "+f"(d[5]), "+f"(d[6]), "+f"(d[7]),
      "+f"(d[8]), "+f"(d[9]), "+f"(d[10]), "+f"(d[11]), "+f"(d[12]), "+f"(d[13]), "+f"(d[14]), "+f"(d[15]),
      "+f"(d[16]), "+f"(d[17]), "+f"(d[18]), "+f"(d[19]), "+f"(d[20]), "+f"(d[21]), "+f"(d[22]), "+f"(d[23]),
      "+f"(d[24]), "+f"(d[25]), "+f"(d[26]), "+f"(d[27]), "+f"(d[28]), "+f"(d[29]), "+f"(d[30]), "+f"(d[31])
    : "r"(a0), "r"(a1), "r"(a2), "r"(a3), "l"(db), "r"(sc), "n"(TB));
}
template <int TA, int TB>
__device__ __forceinline__ void wgmma_n128_ss(float (&d)[64], uint64_t da, uint64_t db, int sc) {
  asm volatile("{\n.reg .pred p;\nsetp.ne.b32 p, %66, 0;\n"
    "wgmma.mma_async.sync.aligned.m64n128k16.f32.bf16.bf16 {%0, %1, %2, %3, %4, %5, %6, %7, %8, %9, %10, %11, %12, %13, %14, %15, %16, %17, %18, %19, %20, %21, %22, %23, %24, %25, %26, %27, %28, %29, %30, %31, %32, %33, %34, %35, %36, %37, %38, %39, %40, %41, %42, %43, %44, %45, %46, %47, %48, %49, %50, %51, %52, %53, %54, %55, %56, %57, %58, %59, %60, %61, %62, %63}, %64, %65, p, 1, 1, %67, %68;\n}\n"
    : "+f"(d[0]), "+f"(d[1]), "+f"(d[2]), "+f"(d[3]), "+f"(d[4]), "+f"(d[5]), "+f"(d[6]), "+f"(d[7]),
      "+f"(d[8]), "+f"(d[9]), "+f"(d[10]), "+f"(d[11]), "+f"(d[12]), "+f"(d[13]), "+f"(d[14]), "+f"(d[15]),
      "+f"(d[16]), "+f"(d[17]), "+f"(d[18]), "+f"(d[19]), "+f"(d[20]), "+f"(d[21]), "+f"(d[22]), "+f"(d[23]),
      "+f"(d[24]), "+f"(d[25]), "+f"(d[26]), "+f"(d[27]), "+f"(d[28]), "+f"(d[29]), "+f"(d[30]), "+f"(d[31]),
      "+f"(d[32]), "+f"(d[33]), "+f"(d[34]), "+f"(d[35]), "+f"(d[36]), "+f"(d[37]), "+f"(d[38]), "+f"(d[39]),
      "+f"(d[40]), "+f"(d[41]), "+f"(d[42]), "+f"(d[43]), "+f"(d[44]), "+f"(d[45]), "+f"(d[46]), "+f"(d[47]),
      "+f"(d[48]), "+f"(d[49]), "+f"(d[50]), "+f"(d[51]), "+f"(d[52]), "+f"(d[53]), "+f"(d[54]), "+f"(d[55]),
      "+f"(d[56]), "+f"(d[57]), "+f"(d[58]), "+f"(d[59]), "+f"(d[60]), "+f"(d[61]), "+f"(d[62]), "+f"(d[63])
    : "l"(da), "l"(db), "r"(sc), "n"(TA), "n"(TB));
}
template <int TB>
__device__ __forceinline__ void wgmma_n128_rs(float (&d)[64], uint32_t a0, uint32_t a1, uint32_t a2, uint32_t a3, uint64_t db, int sc) {
  asm volatile("{\n.reg .pred p;\nsetp.ne.b32 p, %69, 0;\n"
    "wgmma.mma_async.sync.aligned.m64n128k16.f32.bf16.bf16 {%0, %1, %2, %3, %4, %5, %6, %7, %8, %9, %10, %11, %12, %13, %14, %15, %16, %17, %18, %19, %20, %21, %22, %23, %24, %25, %26, %27, %28, %29, %30, %31, %32, %33, %34, %35, %36, %37, %38, %39, %40, %41, %42, %43, %44, %45, %46, %47, %48, %49, %50, %51, %52, %53, %54, %55, %56, %57, %58, %59, %60, %61, %62, %63}, {%64,%65,%66,%67}, %68, p, 1, 1, %70;\n}\n"
    : "+f"(d[0]), "+f"(d[1]), "+f"(d[2]), "+f"(d[3]), "+f"(d[4]), "+f"(d[5]), "+f"(d[6]), "+f"(d[7]),
      "+f"(d[8]), "+f"(d[9]), "+f"(d[10]), "+f"(d[11]), "+f"(d[12]), "+f"(d[13]), "+f"(d[14]), "+f"(d[15]),
      "+f"(d[16]), "+f"(d[17]), "+f"(d[18]), "+f"(d[19]), "+f"(d[20]), "+f"(d[21]), "+f"(d[22]), "+f"(d[23]),
      "+f"(d[24]), "+f"(d[25]), "+f"(d[26]), "+f"(d[27]), "+f"(d[28]), "+f"(d[29]), "+f"(d[30]), "+f"(d[31]),
      "+f"(d[32]), "+f"(d[33]), "+f"(d[34]), "+f"(d[35]), "+f"(d[36]), "+f"(d[37]), "+f"(d[38]), "+f"(d[39]),
      "+f"(d[40]), "+f"(d[41]), "+f"(d[42]), "+f"(d[43]), "+f"(d[44]), "+f"(d[45]), "+f"(d[46]), "+f"(d[47]),
      "+f"(d[48]), "+f"(d[49]), "+f"(d[50]), "+f"(d[51]), "+f"(d[52]), "+f"(d[53]), "+f"(d[54]), "+f"(d[55]),
      "+f"(d[56]), "+f"(d[57]), "+f"(d[58]), "+f"(d[59]), "+f"(d[60]), "+f"(d[61]), "+f"(d[62]), "+f"(d[63])
    : "r"(a0), "r"(a1), "r"(a2), "r"(a3), "l"(db), "r"(sc), "n"(TB));
}

__device__ __forceinline__ void poll1f(uint32_t (&v)[1], const void* p, uint32_t tag, uint32_t mask) {
  asm volatile("{\n.reg .pred p, q;\n.reg .u32 c, b;\n.reg .b64 x, y;\n.reg .b128 z;\nmov.u32 c, 0;\nLW:\n"
               "ld.relaxed.gpu.global.u32 %0, [%1+0];\n"
               "xor.b32 b, %0, %2;\n"
               "and.b32 b, b, %3;\nsetp.eq.u32 p, b, 0;\nvote.sync.all.pred p, p, 0xffffffff;\n@p bra.uni LD;\n"
               "nanosleep.u32 50;\nadd.u32 c, c, 1;\nsetp.lt.u32 q, c, 1000000;\n@q bra.uni LW;\ntrap;\nLD:\n}"
               : "=&r"(v[0])
               : "l"(p), "r"(tag), "r"(mask) : "memory");
}
__device__ __forceinline__ void poll0(uint32_t (&v)[1], const void* p, uint32_t tag, uint32_t mask) {
  asm volatile("{\n.reg .pred p, q;\n.reg .u32 c, b;\n.reg .b64 x, y;\n.reg .b128 z;\nmov.u32 c, 0;\nLW:\n"
               "ld.relaxed.gpu.global.u32 %0, [%1+0];\n"
               "xor.b32 b, %0, %2;\n"
               "and.b32 b, b, %3;\nsetp.eq.u32 p, b, 0;\nvote.sync.all.pred p, p, 0xffffffff;\n@p bra.uni LD;\n"
               "add.u32 c, c, 1;\nsetp.lt.u32 q, c, 1000000;\n@q bra.uni LW;\ntrap;\nLD:\n}"
               : "=&r"(v[0])
               : "l"(p), "r"(tag), "r"(mask) : "memory");
}
__device__ __forceinline__ void poll_pair(uint32_t (&v)[2], const void* p, uint32_t tag, uint32_t mask) {
  asm volatile("{\n.reg .pred p, q;\n.reg .u32 c, b;\n.reg .b64 x, y;\n.reg .b128 z;\nmov.u32 c, 0;\nLW:\n"
               "ld.relaxed.gpu.global.b64 x, [%2+0];\nmov.b64 {%0,%1}, x;\n"
               "xor.b32 b, %0, %3;\n"
               "and.b32 b, b, %4;\nsetp.eq.u32 p, b, 0;\nvote.sync.all.pred p, p, 0xffffffff;\n@p bra.uni LD;\n"
               "nanosleep.u32 100;\nadd.u32 c, c, 1;\nsetp.lt.u32 q, c, 1000000;\n@q bra.uni LW;\ntrap;\nLD:\n}"
               : "=&r"(v[0]), "=&r"(v[1])
               : "l"(p), "r"(tag), "r"(mask) : "memory");
}
__device__ __forceinline__ void poll_quad(uint32_t (&v)[4], const void* p, uint32_t tag, uint32_t mask) {
  asm volatile("{\n.reg .pred p, q;\n.reg .u32 c, b;\n.reg .b64 x, y;\n.reg .b128 z;\nmov.u32 c, 0;\nLW:\n"
               "ld.relaxed.gpu.global.v4.u32 {%0,%1,%2,%3}, [%4+0];\n"
               "xor.b32 b, %0, %5;\n"
               "lop3.b32 b, b, %1, %5, 0xf6;\nlop3.b32 b, b, %2, %5, 0xf6;\nlop3.b32 b, b, %3, %5, 0xf6;\n"
               "and.b32 b, b, %6;\nsetp.eq.u32 p, b, 0;\nvote.sync.all.pred p, p, 0xffffffff;\n@p bra.uni LD;\n"
               "nanosleep.u32 200;\nadd.u32 c, c, 1;\nsetp.lt.u32 q, c, 1000000;\n@q bra.uni LW;\ntrap;\nLD:\n}"
               : "=&r"(v[0]), "=&r"(v[1]), "=&r"(v[2]), "=&r"(v[3])
               : "l"(p), "r"(tag), "r"(mask) : "memory");
}
__device__ __forceinline__ void poll8x4(uint32_t (&v)[32], const void* p, uint32_t tag, uint32_t mask) {
  asm volatile("{\n.reg .pred p, q;\n.reg .u32 c, b;\n.reg .b64 x, y;\n.reg .b128 z;\nmov.u32 c, 0;\nLW:\n"
               "ld.relaxed.gpu.global.v4.u32 {%0,%1,%2,%3}, [%32+0];\n"
               "ld.relaxed.gpu.global.v4.u32 {%4,%5,%6,%7}, [%32+2048];\n"
               "ld.relaxed.gpu.global.v4.u32 {%8,%9,%10,%11}, [%32+4096];\n"
               "ld.relaxed.gpu.global.v4.u32 {%12,%13,%14,%15}, [%32+6144];\n"
               "ld.relaxed.gpu.global.v4.u32 {%16,%17,%18,%19}, [%32+8192];\n"
               "ld.relaxed.gpu.global.v4.u32 {%20,%21,%22,%23}, [%32+10240];\n"
               "ld.relaxed.gpu.global.v4.u32 {%24,%25,%26,%27}, [%32+12288];\n"
               "ld.relaxed.gpu.global.v4.u32 {%28,%29,%30,%31}, [%32+14336];\n"
               "xor.b32 b, %0, %33;\n"
               "lop3.b32 b, b, %1, %33, 0xf6;\nlop3.b32 b, b, %2, %33, 0xf6;\nlop3.b32 b, b, %3, %33, 0xf6;\nlop3.b32 b, b, %4, %33, 0xf6;\n"
               "lop3.b32 b, b, %5, %33, 0xf6;\nlop3.b32 b, b, %6, %33, 0xf6;\nlop3.b32 b, b, %7, %33, 0xf6;\nlop3.b32 b, b, %8, %33, 0xf6;\n"
               "lop3.b32 b, b, %9, %33, 0xf6;\nlop3.b32 b, b, %10, %33, 0xf6;\nlop3.b32 b, b, %11, %33, 0xf6;\nlop3.b32 b, b, %12, %33, 0xf6;\n"
               "lop3.b32 b, b, %13, %33, 0xf6;\nlop3.b32 b, b, %14, %33, 0xf6;\nlop3.b32 b, b, %15, %33, 0xf6;\nlop3.b32 b, b, %16, %33, 0xf6;\n"
               "lop3.b32 b, b, %17, %33, 0xf6;\nlop3.b32 b, b, %18, %33, 0xf6;\nlop3.b32 b, b, %19, %33, 0xf6;\nlop3.b32 b, b, %20, %33, 0xf6;\n"
               "lop3.b32 b, b, %21, %33, 0xf6;\nlop3.b32 b, b, %22, %33, 0xf6;\nlop3.b32 b, b, %23, %33, 0xf6;\nlop3.b32 b, b, %24, %33, 0xf6;\n"
               "lop3.b32 b, b, %25, %33, 0xf6;\nlop3.b32 b, b, %26, %33, 0xf6;\nlop3.b32 b, b, %27, %33, 0xf6;\nlop3.b32 b, b, %28, %33, 0xf6;\n"
               "lop3.b32 b, b, %29, %33, 0xf6;\nlop3.b32 b, b, %30, %33, 0xf6;\nlop3.b32 b, b, %31, %33, 0xf6;\n"
               "and.b32 b, b, %34;\nsetp.eq.u32 p, b, 0;\nvote.sync.all.pred p, p, 0xffffffff;\n@p bra.uni LD;\n"
               "nanosleep.u32 50;\nadd.u32 c, c, 1;\nsetp.lt.u32 q, c, 1000000;\n@q bra.uni LW;\ntrap;\nLD:\n}"
               : "=&r"(v[0]), "=&r"(v[1]), "=&r"(v[2]), "=&r"(v[3]), "=&r"(v[4]), "=&r"(v[5]), "=&r"(v[6]), "=&r"(v[7]), "=&r"(v[8]), "=&r"(v[9]), "=&r"(v[10]), "=&r"(v[11]), "=&r"(v[12]), "=&r"(v[13]), "=&r"(v[14]), "=&r"(v[15]), "=&r"(v[16]), "=&r"(v[17]), "=&r"(v[18]), "=&r"(v[19]), "=&r"(v[20]), "=&r"(v[21]), "=&r"(v[22]), "=&r"(v[23]), "=&r"(v[24]), "=&r"(v[25]), "=&r"(v[26]), "=&r"(v[27]), "=&r"(v[28]), "=&r"(v[29]), "=&r"(v[30]), "=&r"(v[31])
               : "l"(p), "r"(tag), "r"(mask) : "memory");
}
__device__ __forceinline__ void poll16(uint32_t (&v)[16], const void* p, uint32_t tag, uint32_t mask) {
  asm volatile("{\n.reg .pred p, q;\n.reg .u32 c, b;\n.reg .b64 x, y;\n.reg .b128 z;\nmov.u32 c, 0;\nLW:\n"
               "ld.relaxed.gpu.global.u32 %0, [%16+0];\n"
               "ld.relaxed.gpu.global.u32 %1, [%16+4096];\n"
               "ld.relaxed.gpu.global.u32 %2, [%16+8192];\n"
               "ld.relaxed.gpu.global.u32 %3, [%16+12288];\n"
               "ld.relaxed.gpu.global.u32 %4, [%16+16384];\n"
               "ld.relaxed.gpu.global.u32 %5, [%16+20480];\n"
               "ld.relaxed.gpu.global.u32 %6, [%16+24576];\n"
               "ld.relaxed.gpu.global.u32 %7, [%16+28672];\n"
               "ld.relaxed.gpu.global.u32 %8, [%16+32768];\n"
               "ld.relaxed.gpu.global.u32 %9, [%16+36864];\n"
               "ld.relaxed.gpu.global.u32 %10, [%16+40960];\n"
               "ld.relaxed.gpu.global.u32 %11, [%16+45056];\n"
               "ld.relaxed.gpu.global.u32 %12, [%16+49152];\n"
               "ld.relaxed.gpu.global.u32 %13, [%16+53248];\n"
               "ld.relaxed.gpu.global.u32 %14, [%16+57344];\n"
               "ld.relaxed.gpu.global.u32 %15, [%16+61440];\n"
               "xor.b32 b, %0, %17;\n"
               "lop3.b32 b, b, %1, %17, 0xf6;\nlop3.b32 b, b, %2, %17, 0xf6;\nlop3.b32 b, b, %3, %17, 0xf6;\nlop3.b32 b, b, %4, %17, 0xf6;\n"
               "lop3.b32 b, b, %5, %17, 0xf6;\nlop3.b32 b, b, %6, %17, 0xf6;\nlop3.b32 b, b, %7, %17, 0xf6;\nlop3.b32 b, b, %8, %17, 0xf6;\n"
               "lop3.b32 b, b, %9, %17, 0xf6;\nlop3.b32 b, b, %10, %17, 0xf6;\nlop3.b32 b, b, %11, %17, 0xf6;\nlop3.b32 b, b, %12, %17, 0xf6;\n"
               "lop3.b32 b, b, %13, %17, 0xf6;\nlop3.b32 b, b, %14, %17, 0xf6;\nlop3.b32 b, b, %15, %17, 0xf6;\n"
               "and.b32 b, b, %18;\nsetp.eq.u32 p, b, 0;\nvote.sync.all.pred p, p, 0xffffffff;\n@p bra.uni LD;\n"
               "nanosleep.u32 200;\nadd.u32 c, c, 1;\nsetp.lt.u32 q, c, 1000000;\n@q bra.uni LW;\ntrap;\nLD:\n}"
               : "=&r"(v[0]), "=&r"(v[1]), "=&r"(v[2]), "=&r"(v[3]), "=&r"(v[4]), "=&r"(v[5]), "=&r"(v[6]), "=&r"(v[7]), "=&r"(v[8]), "=&r"(v[9]), "=&r"(v[10]), "=&r"(v[11]), "=&r"(v[12]), "=&r"(v[13]), "=&r"(v[14]), "=&r"(v[15])
               : "l"(p), "r"(tag), "r"(mask) : "memory");
}
__device__ __forceinline__ void poll_keys(uint32_t (&v)[16], const void* p, uint32_t tag, uint32_t mask) {
  asm volatile("{\n.reg .pred p, q;\n.reg .u32 c, b;\n.reg .b64 x, y;\n.reg .b128 z;\nmov.u32 c, 0;\nLW:\n"
               "ld.relaxed.gpu.global.v2.b64 {x, y}, [%16+0];\nmov.b64 {%0,%1}, x;\nmov.b64 {%2,%3}, y;\n"
               "ld.relaxed.gpu.global.v2.b64 {x, y}, [%16+4096];\nmov.b64 {%4,%5}, x;\nmov.b64 {%6,%7}, y;\n"
               "ld.relaxed.gpu.global.v2.b64 {x, y}, [%16+8192];\nmov.b64 {%8,%9}, x;\nmov.b64 {%10,%11}, y;\n"
               "ld.relaxed.gpu.global.v2.b64 {x, y}, [%16+12288];\nmov.b64 {%12,%13}, x;\nmov.b64 {%14,%15}, y;\n"
               "xor.b32 b, %0, %17;\n"
               "lop3.b32 b, b, %2, %17, 0xf6;\nlop3.b32 b, b, %4, %17, 0xf6;\nlop3.b32 b, b, %6, %17, 0xf6;\nlop3.b32 b, b, %8, %17, 0xf6;\n"
               "lop3.b32 b, b, %10, %17, 0xf6;\nlop3.b32 b, b, %12, %17, 0xf6;\nlop3.b32 b, b, %14, %17, 0xf6;\n"
               "and.b32 b, b, %18;\nsetp.eq.u32 p, b, 0;\nvote.sync.all.pred p, p, 0xffffffff;\n@p bra.uni LD;\n"
               "nanosleep.u32 20;\nadd.u32 c, c, 1;\nsetp.lt.u32 q, c, 1000000;\n@q bra.uni LW;\ntrap;\nLD:\n}"
               : "=&r"(v[0]), "=&r"(v[1]), "=&r"(v[2]), "=&r"(v[3]), "=&r"(v[4]), "=&r"(v[5]), "=&r"(v[6]), "=&r"(v[7]), "=&r"(v[8]), "=&r"(v[9]), "=&r"(v[10]), "=&r"(v[11]), "=&r"(v[12]), "=&r"(v[13]), "=&r"(v[14]), "=&r"(v[15])
               : "l"(p), "r"(tag), "r"(mask) : "memory");
}
__device__ __forceinline__ void poll_z(uint32_t (&v)[16], const void* p, uint32_t tag, uint32_t mask) {
  asm volatile("{\n.reg .pred p, q;\n.reg .u32 c, b;\n.reg .b64 x, y;\n.reg .b128 z;\nmov.u32 c, 0;\nLW:\n"
               "ld.relaxed.gpu.global.v4.u32 {%0,%1,%2,%3}, [%16+0];\n"
               "ld.relaxed.gpu.global.v4.u32 {%4,%5,%6,%7}, [%16+4096];\n"
               "ld.relaxed.gpu.global.v4.u32 {%8,%9,%10,%11}, [%16+8192];\n"
               "ld.relaxed.gpu.global.v4.u32 {%12,%13,%14,%15}, [%16+12288];\n"
               "xor.b32 b, %0, %17;\n"
               "lop3.b32 b, b, %1, %17, 0xf6;\nlop3.b32 b, b, %2, %17, 0xf6;\nlop3.b32 b, b, %3, %17, 0xf6;\nlop3.b32 b, b, %4, %17, 0xf6;\n"
               "lop3.b32 b, b, %5, %17, 0xf6;\nlop3.b32 b, b, %6, %17, 0xf6;\nlop3.b32 b, b, %7, %17, 0xf6;\nlop3.b32 b, b, %8, %17, 0xf6;\n"
               "lop3.b32 b, b, %9, %17, 0xf6;\nlop3.b32 b, b, %10, %17, 0xf6;\nlop3.b32 b, b, %11, %17, 0xf6;\nlop3.b32 b, b, %12, %17, 0xf6;\n"
               "lop3.b32 b, b, %13, %17, 0xf6;\nlop3.b32 b, b, %14, %17, 0xf6;\nlop3.b32 b, b, %15, %17, 0xf6;\n"
               "and.b32 b, b, %18;\nsetp.eq.u32 p, b, 0;\nvote.sync.all.pred p, p, 0xffffffff;\n@p bra.uni LD;\n"
               "nanosleep.u32 300;\nadd.u32 c, c, 1;\nsetp.lt.u32 q, c, 1000000;\n@q bra.uni LW;\ntrap;\nLD:\n}"
               : "=&r"(v[0]), "=&r"(v[1]), "=&r"(v[2]), "=&r"(v[3]), "=&r"(v[4]), "=&r"(v[5]), "=&r"(v[6]), "=&r"(v[7]), "=&r"(v[8]), "=&r"(v[9]), "=&r"(v[10]), "=&r"(v[11]), "=&r"(v[12]), "=&r"(v[13]), "=&r"(v[14]), "=&r"(v[15])
               : "l"(p), "r"(tag), "r"(mask) : "memory");
}
__device__ __forceinline__ void poll7x4(uint32_t (&v)[28], const void* p, uint32_t tag, uint32_t mask) {
  asm volatile("{\n.reg .pred p, q;\n.reg .u32 c, b;\n.reg .b64 x, y;\n.reg .b128 z;\nmov.u32 c, 0;\nLW:\n"
               "ld.relaxed.gpu.global.v4.u32 {%0,%1,%2,%3}, [%28+0];\n"
               "ld.relaxed.gpu.global.v4.u32 {%4,%5,%6,%7}, [%28+2048];\n"
               "ld.relaxed.gpu.global.v4.u32 {%8,%9,%10,%11}, [%28+4096];\n"
               "ld.relaxed.gpu.global.v4.u32 {%12,%13,%14,%15}, [%28+6144];\n"
               "ld.relaxed.gpu.global.v4.u32 {%16,%17,%18,%19}, [%28+8192];\n"
               "ld.relaxed.gpu.global.v4.u32 {%20,%21,%22,%23}, [%28+10240];\n"
               "ld.relaxed.gpu.global.v4.u32 {%24,%25,%26,%27}, [%28+12288];\n"
               "xor.b32 b, %0, %29;\n"
               "lop3.b32 b, b, %1, %29, 0xf6;\nlop3.b32 b, b, %2, %29, 0xf6;\nlop3.b32 b, b, %3, %29, 0xf6;\nlop3.b32 b, b, %4, %29, 0xf6;\n"
               "lop3.b32 b, b, %5, %29, 0xf6;\nlop3.b32 b, b, %6, %29, 0xf6;\nlop3.b32 b, b, %7, %29, 0xf6;\nlop3.b32 b, b, %8, %29, 0xf6;\n"
               "lop3.b32 b, b, %9, %29, 0xf6;\nlop3.b32 b, b, %10, %29, 0xf6;\nlop3.b32 b, b, %11, %29, 0xf6;\nlop3.b32 b, b, %12, %29, 0xf6;\n"
               "lop3.b32 b, b, %13, %29, 0xf6;\nlop3.b32 b, b, %14, %29, 0xf6;\nlop3.b32 b, b, %15, %29, 0xf6;\nlop3.b32 b, b, %16, %29, 0xf6;\n"
               "lop3.b32 b, b, %17, %29, 0xf6;\nlop3.b32 b, b, %18, %29, 0xf6;\nlop3.b32 b, b, %19, %29, 0xf6;\nlop3.b32 b, b, %20, %29, 0xf6;\n"
               "lop3.b32 b, b, %21, %29, 0xf6;\nlop3.b32 b, b, %22, %29, 0xf6;\nlop3.b32 b, b, %23, %29, 0xf6;\nlop3.b32 b, b, %24, %29, 0xf6;\n"
               "lop3.b32 b, b, %25, %29, 0xf6;\nlop3.b32 b, b, %26, %29, 0xf6;\nlop3.b32 b, b, %27, %29, 0xf6;\n"
               "and.b32 b, b, %30;\nsetp.eq.u32 p, b, 0;\nvote.sync.all.pred p, p, 0xffffffff;\n@p bra.uni LD;\n"
               "nanosleep.u32 50;\nadd.u32 c, c, 1;\nsetp.lt.u32 q, c, 1000000;\n@q bra.uni LW;\ntrap;\nLD:\n}"
               : "=&r"(v[0]), "=&r"(v[1]), "=&r"(v[2]), "=&r"(v[3]), "=&r"(v[4]), "=&r"(v[5]), "=&r"(v[6]), "=&r"(v[7]), "=&r"(v[8]), "=&r"(v[9]), "=&r"(v[10]), "=&r"(v[11]), "=&r"(v[12]), "=&r"(v[13]), "=&r"(v[14]), "=&r"(v[15]), "=&r"(v[16]), "=&r"(v[17]), "=&r"(v[18]), "=&r"(v[19]), "=&r"(v[20]), "=&r"(v[21]), "=&r"(v[22]), "=&r"(v[23]), "=&r"(v[24]), "=&r"(v[25]), "=&r"(v[26]), "=&r"(v[27])
               : "l"(p), "r"(tag), "r"(mask) : "memory");
}
__device__ __forceinline__ void poll_kvp(uint32_t (&v)[16], const void* p, uint32_t tag, uint32_t mask) {
  asm volatile("{\n.reg .pred p, q;\n.reg .u32 c, b;\n.reg .b64 x, y;\n.reg .b128 z;\nmov.u32 c, 0;\nLW:\n"
               "ld.relaxed.gpu.global.b128 z, [%16+0];\nmov.b128 {x, y}, z;\nmov.b64 {%0,%1}, x;\nmov.b64 {%2,%3}, y;\n"
               "ld.relaxed.gpu.global.b128 z, [%16+8192];\nmov.b128 {x, y}, z;\nmov.b64 {%4,%5}, x;\nmov.b64 {%6,%7}, y;\n"
               "ld.relaxed.gpu.global.b128 z, [%16+16384];\nmov.b128 {x, y}, z;\nmov.b64 {%8,%9}, x;\nmov.b64 {%10,%11}, y;\n"
               "ld.relaxed.gpu.global.b128 z, [%16+24576];\nmov.b128 {x, y}, z;\nmov.b64 {%12,%13}, x;\nmov.b64 {%14,%15}, y;\n"
               "xor.b32 b, %0, %17;\n"
               "lop3.b32 b, b, %4, %17, 0xf6;\nlop3.b32 b, b, %8, %17, 0xf6;\nlop3.b32 b, b, %12, %17, 0xf6;\n"
               "and.b32 b, b, %18;\nsetp.eq.u32 p, b, 0;\nvote.sync.all.pred p, p, 0xffffffff;\n@p bra.uni LD;\n"
               "nanosleep.u32 50;\nadd.u32 c, c, 1;\nsetp.lt.u32 q, c, 1000000;\n@q bra.uni LW;\ntrap;\nLD:\n}"
               : "=&r"(v[0]), "=&r"(v[1]), "=&r"(v[2]), "=&r"(v[3]), "=&r"(v[4]), "=&r"(v[5]), "=&r"(v[6]), "=&r"(v[7]), "=&r"(v[8]), "=&r"(v[9]), "=&r"(v[10]), "=&r"(v[11]), "=&r"(v[12]), "=&r"(v[13]), "=&r"(v[14]), "=&r"(v[15])
               : "l"(p), "r"(tag), "r"(mask) : "memory");
}

__device__ __align__(1024) __nv_bfloat16 g_o[2048 * 1024];
__device__ __align__(128) uint2 g_keys[2048];
__device__ __align__(128) uint32_t g_csum[18 * 1024];
__device__ __align__(128) uint32_t g_z[16 * 1024];
__device__ __align__(128) uint4 g_kvp[128 * 512];
__device__ __align__(128) uint4 g_kv[8 * 512];
__device__ __align__(128) uint32_t g_h[112 * 256];
__device__ __align__(128) uint32_t g_yp[128 * 512];
__device__ __align__(128) uint2 g_sel[8 * 16];
enum { H_CS = 0, H_KVP = 8, H_KV = 16, H_H = 24, H_Y = 32, H_O = 40, H_Z = 56 };
__device__ __align__(128) uint32_t g_sig[64 * 32];
__device__ uint32_t g_epoch;

constexpr uint32_t RING = 1024, SLOT = 32768, SMEM_BYTES = 232448;
constexpr int NST = 5, HST = 7;
constexpr uint32_t STG = RING + 163840, AUX = RING + 196608, FR = RING + 212992, MISC = RING + 229376;
constexpr uint32_t B_FULL = MISC, B_EMPTY = MISC + 56, B_XS = MISC + 112, B_SEL = MISC + 144, B_WK = MISC + 160, B_CSDN = MISC + 168,
                   B_FR = MISC + 176, B_FE = MISC + 200, B_DR = MISC + 224, B_CSV = MISC + 248,
                   B_DND = MISC + 256, B_XRES = MISC + 264, B_PFREE = MISC + 280, B_SFREE = MISC + 288, B_KVL = MISC + 296, NBAR = 38;
constexpr uint32_t S_EPOCH = MISC + 352, S_NCAND = MISC + 356, S_SEL = MISC + 368, S_WMAX = MISC + 432,
                   S_KSTAT = MISC + 512, S_CSK = MISC + 1536, S_CSV = MISC + 2048, S_CSQ = MISC + 2560, S_ONES = MISC + 512;
constexpr uint32_t KVB = AUX, HOP = AUX + 10240, GR = FR - 8192;
enum { NB_Z = 0, NB_KV = 1, NB_VQ = 2, NB_WG0 = 3, NB_FDONE = 4, NB_PK = 5, NB_KVB = 6, NB_WG1 = 7, NB_WG2 = 8, NB_CSQ = 9,
       NB_Y = 10, NB_ST = 11, NB_OWN0 = 12, NB_OWN1 = 13, NB_Q0 = 14, NB_H1 = 15 };

#define XS_FLY 2
#define FFN_GAP 400
#define PF_GAP 200
#define PF_WAIT 1000
#define GPCMAP 0x75143620u
#define KV_SPEC 200
#define HAND_K 5
#define PF_V 0
#define PF_O 0
#define PHI_CUT 11
#define SIG_EARLY 50
constexpr uint64_t EVICT_FIRST = 0x12f0000000000000ull;
constexpr float LOG2E = 1.4426950408889634f, LN2 = 0.6931471805599453f;

#define ELECT "{\n.reg .pred p;\nelect.sync _|p, 0xffffffff;\n"
#define TMA2D "cp.async.bulk.tensor.2d.shared::cluster.global.mbarrier::complete_tx::bytes"
#define TMA3D "cp.async.bulk.tensor.3d.shared::cluster.global.mbarrier::complete_tx::bytes"
__device__ __forceinline__ void e_expect(uint32_t b, uint32_t n) {
  asm volatile(ELECT "@p mbarrier.arrive.expect_tx.shared::cta.b64 _, [%0], %1;\n}" ::"r"(b), "r"(n) : "memory");
}
__device__ __forceinline__ void e_arrive(uint32_t b) { asm volatile(ELECT "@p mbarrier.arrive.shared::cta.b64 _, [%0];\n}" ::"r"(b) : "memory"); }
__device__ __forceinline__ void e_tma2d(uint32_t dst, const CUtensorMap* m, int c0, int c1, uint32_t bar) {
  asm volatile(ELECT "@p " TMA2D " [%0], [%1, {%3, %4}], [%2];\n}" ::"r"(dst), "l"(m), "r"(bar), "r"(c0), "r"(c1) : "memory");
}
__device__ __forceinline__ void e_tma2d_ef(uint32_t dst, const CUtensorMap* m, int c0, int c1, uint32_t bar, uint64_t pol) {
  asm volatile(ELECT "@p " TMA2D ".L2::cache_hint [%0], [%1, {%3, %4}], [%2], %5;\n}" ::"r"(dst), "l"(m), "r"(bar), "r"(c0), "r"(c1), "l"(pol) : "memory");
}
__device__ __forceinline__ void e_tma3d(uint32_t dst, const CUtensorMap* m, int c1, int c2, uint32_t bar) {
  asm volatile(ELECT "@p " TMA3D " [%0], [%1, {0, %3, %4}], [%2];\n}" ::"r"(dst), "l"(m), "r"(bar), "r"(c1), "r"(c2) : "memory");
}
__device__ __forceinline__ void e_store2d(const CUtensorMap* m, int c0, int c1, uint32_t src) {
  asm volatile(ELECT "@p cp.async.bulk.tensor.2d.global.shared::cta.bulk_group [%0, {%2, %3}], [%1];\n}" ::"l"(m), "r"(src), "r"(c0), "r"(c1) : "memory");
}
__device__ __forceinline__ void e_tma3d_ef(uint32_t dst, const CUtensorMap* m, int c0, int c1, uint32_t bar, uint64_t pol) {
  asm volatile(ELECT "@p " TMA3D ".L2::cache_hint [%0], [%1, {%3, %4, 0}], [%2], %5;\n}" ::"r"(dst), "l"(m), "r"(bar), "r"(c0), "r"(c1), "l"(pol) : "memory");
}
__device__ __forceinline__ void e_load(uint32_t dst, const void* src, uint32_t n, uint32_t bar) {
  asm volatile(ELECT "@p cp.async.bulk.shared::cluster.global.mbarrier::complete_tx::bytes [%0], [%1], %2, [%3];\n}" ::"r"(dst), "l"(src), "r"(n), "r"(bar) : "memory");
}
__device__ __forceinline__ void e_pfmap(const CUtensorMap* m) { asm volatile(ELECT "@p prefetch.tensormap [%0];\n}" ::"l"(m) : "memory"); }
__device__ __forceinline__ void bulk_wait_read() { asm volatile("cp.async.bulk.commit_group;\ncp.async.bulk.wait_group.read 0;" ::: "memory"); }
__device__ __forceinline__ void e_signal(int word, int bit) {
  asm volatile(ELECT "@p red.relaxed.gpu.global.xor.b32 [%0], %1;\n}" ::"l"(g_sig + word * 32), "r"(1u << bit) : "memory");
}
__device__ __forceinline__ void await(int word, uint32_t mask, uint32_t ep) {
  uint32_t f[1];
  poll1f(f, g_sig + word * 32, 0u - (ep & 1u), mask);
}

__device__ __forceinline__ void mbar_arrive(uint32_t b) { asm volatile("mbarrier.arrive.shared::cta.b64 _, [%0];" ::"r"(b) : "memory"); }
__device__ __forceinline__ void mbar_wait(uint32_t b, uint32_t ph) {
  asm volatile("{\n.reg .pred p, q;\n.reg .u32 c;\nmov.u32 c, 0;\nLW:\nmbarrier.try_wait.parity.shared::cta.b64 p, [%0], %1;\n@p bra LD;\n"
               "add.u32 c, c, 1;\nsetp.lt.u32 q, c, 100000;\n@q bra LW;\ntrap;\nLD:\n}" ::"r"(b), "r"(ph) : "memory");
}
#define WAIT01 "{\n.reg .pred p, q;\n.reg .u32 c;\nmov.u32 c, 0;\nLW:\nmbarrier.try_wait.parity.shared::cta.b64 p, [%0], %1;\n@p bra LD;\n" \
               "add.u32 c, c, 1;\nsetp.lt.u32 q, c, 100000;\n@q bra LW;\ntrap;\nLD:\nelect.sync _|p, 0xffffffff;\n"
__device__ __forceinline__ void refill_wx(uint32_t eb, uint32_t ph, uint32_t fb, uint32_t bytes, uint32_t dw, const CUtensorMap* mw, int k0, int c,
                                          uint32_t dx, const CUtensorMap* mx, int row, uint32_t xb) {
  asm volatile(WAIT01 "@p " TMA3D " [%4], [%5, {0, %6, %7}], [%2];\n@p " TMA2D " [%8], [%9, {%6, %10}], [%11];\n"
               "@p mbarrier.arrive.expect_tx.shared::cta.b64 _, [%2], %3;\n}"
               ::"r"(eb), "r"(ph), "r"(fb), "r"(bytes), "r"(dw), "l"(mw), "r"(k0), "r"(c), "r"(dx), "l"(mx), "r"(row), "r"(xb) : "memory");
}
__device__ __forceinline__ void refill_w(uint32_t eb, uint32_t ph, uint32_t fb, uint32_t bytes, uint32_t dw, const CUtensorMap* mw, int k0, int c) {
  asm volatile(WAIT01 "@p " TMA3D " [%4], [%5, {0, %6, %7}], [%2];\n@p mbarrier.arrive.expect_tx.shared::cta.b64 _, [%2], %3;\n}"
               ::"r"(eb), "r"(ph), "r"(fb), "r"(bytes), "r"(dw), "l"(mw), "r"(k0), "r"(c) : "memory");
}
__device__ __forceinline__ void refill_x(uint32_t eb, uint32_t ph, uint32_t fb, uint32_t dx, const CUtensorMap* mx, int k0, int row) {
  asm volatile(WAIT01 "@p " TMA2D " [%3], [%4, {%5, %6}], [%2];\n}" ::"r"(eb), "r"(ph), "r"(fb), "r"(dx), "l"(mx), "r"(k0), "r"(row) : "memory");
}
__device__ __forceinline__ void refill_g(uint32_t eb, uint32_t ph, uint32_t fb, uint32_t dw, const CUtensorMap* mw, int c0, int k0) {
  asm volatile(WAIT01 "@p " TMA3D ".L2::cache_hint [%3], [%4, {%5, %6, 0}], [%2], %7;\n@p mbarrier.arrive.expect_tx.shared::cta.b64 _, [%2], 8192;\n}"
               ::"r"(eb), "r"(ph), "r"(fb), "r"(dw), "l"(mw), "r"(c0), "r"(k0), "l"(EVICT_FIRST) : "memory");
}
__device__ __forceinline__ void nb_sync(int id, int n) { asm volatile("bar.sync %0, %1;" ::"r"(id), "r"(n) : "memory"); }
__device__ __forceinline__ void nb_arrive(int id, int n) { asm volatile("bar.arrive %0, %1;" ::"r"(id), "r"(n) : "memory"); }
__device__ __forceinline__ void wg_fence() { asm volatile("wgmma.fence.sync.aligned;" ::: "memory"); }
__device__ __forceinline__ void wg_commit() { asm volatile("wgmma.commit_group.sync.aligned;" ::: "memory"); }
template <int N> __device__ __forceinline__ void wg_wait() { asm volatile("wgmma.wait_group.sync.aligned %0;" ::"n"(N) : "memory"); }
template <int N> __device__ __forceinline__ void reg_fence(float (&a)[N]) {
#pragma unroll
  for (int i = 0; i < N; i++) asm volatile("" : "+f"(a[i])::"memory");
}
template <int N> __device__ __forceinline__ void reg_zero(float (&a)[N]) {
#pragma unroll
  for (int i = 0; i < N; i++) a[i] = 0.f;
}
__device__ __forceinline__ constexpr uint64_t mkdesc(uint32_t addr, uint32_t lbo, uint32_t sbo, uint32_t swz) {
  return (uint64_t)(addr >> 4) | ((uint64_t)(lbo >> 4) << 16) | ((uint64_t)(sbo >> 4) << 32) | ((uint64_t)swz << 62);
}
__device__ __forceinline__ void fence_async_smem() { asm volatile("fence.proxy.async.shared::cta;" ::: "memory"); }
__device__ __forceinline__ void st_relaxed(uint32_t* p, uint32_t v) { asm volatile("st.relaxed.gpu.global.u32 [%0], %1;" ::"l"(p), "r"(v) : "memory"); }
__device__ __forceinline__ uint32_t ld_relaxed(const uint32_t* p) { uint32_t v; asm volatile("ld.relaxed.gpu.global.u32 %0, [%1];" : "=r"(v) : "l"(p) : "memory"); return v; }
__device__ __forceinline__ void st_unit(uint4* p, uint32_t a, uint32_t b, uint32_t c, uint32_t d, uint32_t par) {
  asm volatile("{\n.reg .b64 x, y;\n.reg .b128 z;\nmov.b64 x, {%1,%2};\nmov.b64 y, {%3,%4};\nmov.b128 z, {x, y};\nst.relaxed.gpu.global.b128 [%0], z;\n}"
               ::"l"(p), "r"((a & ~1u) | par), "r"(b), "r"(c), "r"(d) : "memory");
}
__device__ __forceinline__ uint4 lds128(uint32_t a) { uint4 v; asm volatile("ld.shared.v4.u32 {%0,%1,%2,%3}, [%4];" : "=r"(v.x), "=r"(v.y), "=r"(v.z), "=r"(v.w) : "r"(a)); return v; }
__device__ __forceinline__ float4 lds128f(uint32_t a) { float4 v; asm volatile("ld.shared.v4.f32 {%0,%1,%2,%3}, [%4];" : "=f"(v.x), "=f"(v.y), "=f"(v.z), "=f"(v.w) : "r"(a)); return v; }
__device__ __forceinline__ float4 lds128v(uint32_t a) { float4 v; asm volatile("ld.volatile.shared.v4.f32 {%0,%1,%2,%3}, [%4];" : "=f"(v.x), "=f"(v.y), "=f"(v.z), "=f"(v.w) : "r"(a) : "memory"); return v; }
__device__ __forceinline__ float lds32v(uint32_t a) { float v; asm volatile("ld.volatile.shared.f32 %0, [%1];" : "=f"(v) : "r"(a) : "memory"); return v; }
__device__ __forceinline__ float2 lds64f(uint32_t a) { float2 v; asm volatile("ld.shared.v2.f32 {%0,%1}, [%2];" : "=f"(v.x), "=f"(v.y) : "r"(a)); return v; }
__device__ __forceinline__ uint32_t lds32(uint32_t a) { uint32_t v; asm volatile("ld.shared.u32 %0, [%1];" : "=r"(v) : "r"(a)); return v; }
__device__ __forceinline__ void sts128(uint32_t a, uint32_t x, uint32_t y, uint32_t z, uint32_t w) { asm volatile("st.shared.v4.u32 [%0], {%1,%2,%3,%4};" ::"r"(a), "r"(x), "r"(y), "r"(z), "r"(w) : "memory"); }
__device__ __forceinline__ void sts128f(uint32_t a, float x, float y, float z, float w) { asm volatile("st.shared.v4.f32 [%0], {%1,%2,%3,%4};" ::"r"(a), "f"(x), "f"(y), "f"(z), "f"(w) : "memory"); }
__device__ __forceinline__ void sts64(uint32_t a, uint32_t x, uint32_t y) { asm volatile("st.shared.v2.u32 [%0], {%1,%2};" ::"r"(a), "r"(x), "r"(y) : "memory"); }
__device__ __forceinline__ void sts32(uint32_t a, uint32_t x) { asm volatile("st.shared.u32 [%0], %1;" ::"r"(a), "r"(x) : "memory"); }
__device__ __forceinline__ void stsm4(uint32_t a, uint32_t r0, uint32_t r1, uint32_t r2, uint32_t r3) {
  asm volatile("stmatrix.sync.aligned.m8n8.x4.shared.b16 [%0], {%1,%2,%3,%4};" ::"r"(a), "r"(r0), "r"(r1), "r"(r2), "r"(r3) : "memory");
}
__device__ __forceinline__ uint4 ldsm4(uint32_t a) {
  uint4 v; asm volatile("ldmatrix.sync.aligned.m8n8.x4.shared.b16 {%0,%1,%2,%3}, [%4];" : "=r"(v.x), "=r"(v.y), "=r"(v.z), "=r"(v.w) : "r"(a) : "memory"); return v;
}
__device__ __forceinline__ uint32_t pack(float lo, float hi) { uint32_t r; asm("cvt.rn.bf16x2.f32 %0, %1, %2;" : "=r"(r) : "f"(hi), "f"(lo)); return r; }
__device__ __forceinline__ float bf_lo(uint32_t w) { return __uint_as_float(w << 16); }
__device__ __forceinline__ float bf_hi(uint32_t w) { return __uint_as_float(w & 0xffff0000u); }
__device__ __forceinline__ float bf_round(float x) { return bf_lo(pack(x, x)); }
__device__ __forceinline__ float ex2(float x) { float v; asm("ex2.approx.ftz.f32 %0, %1;" : "=f"(v) : "f"(x)); return v; }
__device__ __forceinline__ float rcp(float x) { float v; asm("rcp.approx.ftz.f32 %0, %1;" : "=f"(v) : "f"(x)); return v; }
__device__ __forceinline__ float addsat(float a, float b) { float v; asm("add.sat.f32 %0, %1, %2;" : "=f"(v) : "f"(a), "f"(b)); return v; }
__device__ __forceinline__ float phi2(float a) { return fmaf(fmaxf(a, 0.f), LN2, addsat(ex2(a), 1e-6f)); }
__device__ __forceinline__ uint32_t phi_pack(float u0, float u1, float rl, uint32_t sd2) {
  uint32_t r;
  asm("{\n.reg .b32 m;\ncvt.rn.relu.bf16x2.f32 m, %2, %1;\nfma.rn.bf16x2 %0, %3, %4, m;\n}"
      : "=r"(r) : "f"(u0), "f"(u1), "r"(pack(addsat(ex2(u0 * rl), 1e-6f), addsat(ex2(u1 * rl), 1e-6f))), "r"(sd2));
  return r;
}
__device__ __forceinline__ uint32_t sub2(uint32_t a, uint32_t b) { uint32_t r; asm("sub.rn.bf16x2 %0, %1, %2;" : "=r"(r) : "r"(a), "r"(b)); return r; }
__device__ __forceinline__ float key_score(uint32_t key) { uint32_t u = key >> 16; u = (u & 0x8000u) ? (u & 0x7fffu) : (~u & 0xffffu); return __uint_as_float(u << 16); }
__device__ __forceinline__ int key_token(uint32_t key) { return 2047 - (int)((key >> 5) & 2047u); }
__device__ __forceinline__ uint32_t bsel(uint32_t a, uint32_t b, uint32_t m) { uint32_t r; asm("lop3.b32 %0, %1, %2, %3, 0xd8;" : "=r"(r) : "r"(a), "r"(b), "r"(m)); return r; }
__device__ __forceinline__ uint32_t prmt(uint32_t a, uint32_t b, uint32_t c) { uint32_t r; asm("prmt.b32 %0, %1, %2, %3;" : "=r"(r) : "r"(a), "r"(b), "r"(c)); return r; }
__device__ __forceinline__ uint32_t tagf(float v, uint32_t par) { return (__float_as_uint(v) & ~1u) | par; }
__device__ __forceinline__ float xred(float a, float b, bool up, int o) { return (up ? b : a) + __shfl_xor_sync(0xffffffffu, up ? a : b, o); }

#define STAMP(id)
#define STAMP_IF(c, id)
#define STAMP2(i)
#define LITE 1
#define LITE_MASK 0ull

template <bool TRANS, int NK = 16>
__device__ __forceinline__ void mainloop(float (&a0)[64], float (&a1)[64], int s, int ph, int handoff, int xpair, bool leader) {
  uint32_t prev = 0;
#pragma unroll 1
  for (int kt = 0; kt < NK; kt++) {
    const bool xr = !TRANS && (kt >> 1) == xpair;
    mbar_wait(B_FULL + 8 * s, ph);
    const uint64_t dw = mkdesc(RING, 8192, 1024, 1) + s * (SLOT >> 4), dx = mkdesc(0, 16, 1024, 1) + (xr ? (STG >> 4) + (kt & 1) * 1024 : ((RING + 16384) >> 4) + s * (SLOT >> 4));
    if (xr) mbar_wait(B_XRES + 8 * (kt & 1), 0);
    wg_fence();
#pragma unroll
    for (int j = 0; j < 4; j++) {
      if (TRANS) {
        wgmma_n128_ss<1, 0>(a0, dw + j * 128, dx + j * 2, 1);
        wgmma_n128_ss<1, 0>(a1, dw + j * 128 + 512, dx + j * 2, 1);
      } else {
        wgmma_n128_ss<0, 1>(a0, dx + j * 2, dw + j * 128, 1);
        wgmma_n128_ss<0, 1>(a1, dx + j * 2 + 512, dw + j * 128, 1);
      }
    }
    wg_commit();
    if (handoff && kt == 15) nb_arrive(handoff, 256);
    wg_wait<1>();
    if (prev && leader) mbar_arrive(prev);
    prev = B_EMPTY + 8 * s;
    if (++s == NST) { s = 0; ph ^= 1; }
  }
  if (NK < 16) return;
  wg_wait<0>();
  if (leader) mbar_arrive(prev);
  reg_fence(a0);
  reg_fence(a1);
}

__device__ __forceinline__ int out_kblock(int r, int tn) {
  const int q = r - 2, half = q >= 7, pi = q - 7 * half;
  return r < 2 ? 2 * tn + r : 2 * ((pi + (pi >= (tn & 3))) ^ (tn & 4)) + half;
}

struct Params {
  const char *x, *wqkv, *w_r, *wg, *wu, *wd, *wo;
  CUtensorMap m_wqkv, m_x, m_xs, m_o, m_os, m_wo, m_gu, m_down, m_out;
};

template <bool BY_SMID>
__global__ void __launch_bounds__(512, 1) fused_kernel(const __grid_constant__ Params mp) {
  extern __shared__ __align__(1024) uint8_t smem_raw[];
#define CK(i)
  CK(0);
  const int tid = threadIdx.x, lane = tid & 31;
  const int w = __shfl_sync(0xffffffffu, tid >> 5, 0);
  int bid = blockIdx.x;
  if (BY_SMID) {
    uint32_t sm;
    asm volatile("mov.u32 %0, %%smid;" : "=r"(sm));
    const uint32_t p = sm >> 1, q = ((p - 32) * 37) >> 8;
    const uint32_t gpc = p < 32 ? p & 7 : p < 60 ? p - 31 - 7 * q : 0, tpc = p < 32 ? p >> 3 : p < 60 ? 4 + q : p - 58;
    bid = (p >> 1) == 30 ? 128 + ((0x9cu >> (2 * (sm & 3))) & 3) : ((GPCMAP >> (4 * gpc)) & 7) * 16 + tpc * 2 + (sm & 1);
  }
  const int tn = (bid & 3) + 4 * (bid >> 6), tm = (bid >> 2) & 15;

  CK(1);
  if (w == 0) {
#pragma unroll 1
    for (int s = 0; s < NST; s++) {
      asm volatile(ELECT "@p mbarrier.init.shared::cta.b64 [%0], 1;\n}" ::"r"(B_FULL + 8 * s) : "memory");
      if (bid < 128) {
        e_expect(B_FULL + 8 * s, 32768);
        e_tma2d(RING + s * SLOT + 16384, &mp.m_x, s * 64, tm * 128, B_FULL + 8 * s);
        e_tma3d(RING + s * SLOT, &mp.m_wqkv, s * 64, 16 + 2 * tn, B_FULL + 8 * s);
      }
      if (s == 0) CK(2);
    }
  }
  if (w == 1) e_pfmap(&mp.m_wqkv);
  if (w == 2) e_pfmap(&mp.m_xs);
  if (w >= 4) {
#pragma unroll 1
    for (uint32_t b = MISC + 8 * (w + 1); b < MISC + 8 * NBAR; b += 96)
      asm volatile(ELECT "@p mbarrier.init.shared::cta.b64 [%0], %1;\n}" ::"r"(b), "r"(b == B_CSDN ? 4 : 1) : "memory");
    if (w == 15) sts32(S_NCAND, 0);
  }
  CK(3);
  asm volatile("fence.mbarrier_init.release.cluster;" ::: "memory");
  __syncthreads();

  if (bid >= 128) {
    const int h0 = bid == 128 ? 14 : bid - 129, hs = bid == 128 ? 1 : 3, h1 = bid == 128 ? 16 : 14;
    if (w == 12) {
      int s = 0, ph = 1;
#pragma unroll 1
      for (int h = h0; h < h1; h += hs) {
        const int c = 2 * h + (h & 8) * 2;
        if (h == 14) mbar_wait(B_SEL, 0);
#pragma unroll 1
        for (int kt = 0; kt < 16; kt += 2) {
          mbar_wait(B_EMPTY + 8 * s, ph);
          e_expect(B_FULL + 8 * s, 32768);
          e_tma3d(RING + s * SLOT, &mp.m_wqkv, kt * 64, c, B_FULL + 8 * s);
          e_tma3d(RING + s * SLOT + 16384, &mp.m_wqkv, kt * 64 + 64, c, B_FULL + 8 * s);
          if (++s == HST) { s = 0; ph ^= 1; }
        }
      }
    } else if (w < 4) {
      const uint32_t par = (ld_relaxed(&g_epoch) + 1) & 1u;
      sts32(S_ONES + tid * 4, 0x3f803f80u);
      fence_async_smem();
      nb_sync(NB_WG0, 128);
      int s = 0, ph = 0;
#pragma unroll 1
      for (int h = h0; h < h1; h += hs) {
        float c[4][4];
#pragma unroll
        for (int q = 0; q < 4; q++) reg_zero(c[q]);
        uint32_t prev = 0;
#pragma unroll 1
        for (int kt = 0; kt < 8; kt++) {
          mbar_wait(B_FULL + 8 * s, ph);
          const uint64_t dw = mkdesc(RING, 8192, 1024, 1) + s * (SLOT >> 4);
          wg_fence();
#pragma unroll
          for (int j = 0; j < 16; j++) wgmma_n8_ss<1, 0>(c[j & 3], dw + (j & 3) * 512 + (j >> 2) * 128, mkdesc(S_ONES, 128, 128, 0), 1);
          wg_commit();
          wg_wait<1>();
          if (prev && tid == 0) mbar_arrive(prev);
          prev = B_EMPTY + 8 * s;
          if (++s == HST) { s = 0; ph ^= 1; }
        }
        wg_wait<0>();
        if (tid == 0) mbar_arrive(prev);
#pragma unroll
        for (int q = 0; q < 4; q++) reg_fence(c[q]);
        const bool u2 = lane & 2, u1 = lane & 1;
        const float lo = u2 ? c[1][0] + c[3][0] : c[0][0] + c[2][0], hi = u2 ? c[1][2] + c[3][2] : c[0][2] + c[2][2];
        st_relaxed(g_csum + h * 128 + (lane & 2) * 32 + w * 16 + (lane & 1) * 8 + (lane >> 2), tagf(u1 ? hi : lo, par));
        STAMP_IF(tid == 0, h >= 8 ? 6 : 30);
      }
    } else if (w < 12 && bid == 128) {
      const int t = tid - 128, j = w - 4;
      const uint32_t ep = ld_relaxed(&g_epoch) + 1;
      uint32_t kk[16];
      poll_keys(kk, g_keys + t * 2, ep, 31u);
      STAMP_IF(t == 0, 42);
      const uint32_t m = __reduce_max_sync(0xffffffffu, max(max(max(kk[0], kk[2]), max(kk[4], kk[6])), max(max(kk[8], kk[10]), max(kk[12], kk[14]))));
      if (lane == 0) sts32(S_WMAX + j * 4, m);
      nb_sync(NB_WG1, 256);
      const uint32_t T = __reduce_min_sync(0xffffffffu, lds32(S_WMAX + (lane & 7) * 4));
      uint32_t cnt = 0;
#pragma unroll
      for (int i = 0; i < 8; i++) cnt += kk[2 * i] >= T;
      if (cnt) {
        uint32_t pos;
        asm volatile("atom.shared.add.u32 %0, [%1], %2;" : "=r"(pos) : "r"(S_NCAND), "r"(cnt * 8) : "memory");
#pragma unroll
        for (int i = 0; i < 8; i++)
          if (kk[2 * i] >= T) { sts64(AUX + pos, kk[2 * i], kk[2 * i + 1]); pos += 8; }
      }
      nb_sync(NB_WG1, 256);
      const uint32_t n8 = lds32(S_NCAND);
#pragma unroll 1
      for (uint32_t i = j * 8; i < n8; i += 64) {
        const float2 c = lds64f(AUX + i);
        uint32_t rank = 0;
#pragma unroll 1
        for (uint32_t q = lane * 8; q < n8 + lane * 8; q += 256) rank += __popc(__ballot_sync(0xffffffffu, q < n8 && lds32(AUX + q) > __float_as_uint(c.x)));
        if (rank < 8) sts64(S_SEL + rank * 8, __float_as_uint(c.x), __float_as_uint(c.y));
      }
      fence_async_smem();
      nb_sync(NB_WG1, 256);
      if (j == 0) {
        const uint4 v = lds128(S_SEL + (lane & 3) * 16);
        asm volatile("{\n.reg .b64 x, y;\nmov.b64 x, {%1,%2};\nmov.b64 y, {%3,%4};\nst.relaxed.gpu.global.v2.b64 [%0], {x, y};\n}"
                     ::"l"(g_sel + (lane >> 2) * 16 + (lane & 3) * 2), "r"(v.x), "r"(v.y), "r"(v.z), "r"(v.w) : "memory");
        e_arrive(B_SEL);
      }
      STAMP_IF(t == 0, 45);
    }
  } else if (w >= 12) {
    asm volatile("setmaxnreg.dec.sync.aligned.u32 32;");
    if (w == 12) {
      int s = 0, ph = 0;
#pragma unroll 1
      for (int it = NST; it < 48; it++) {
        const int c = (it < 32 ? (it & 16) + 16 : 0) + 2 * tn;
        const int k0 = ((it + (it >= 32 && tn < 4 ? 8 : 0)) & 15) * 64;
        const bool xr = (it >> 1) == 20 + (tn & 3);
        if (xr) { mbar_wait(B_SFREE, 0); e_expect(B_XRES + 8 * (it & 1), 16384); }
        refill_wx(B_EMPTY + 8 * s, ph, B_FULL + 8 * s, xr ? 16384 : 32768, RING + s * SLOT, &mp.m_wqkv, k0, c,
                  xr ? STG + (it & 1) * 16384 : RING + s * SLOT + 16384, &mp.m_x, tm * 128, xr ? B_XRES + 8 * (it & 1) : B_FULL + 8 * s);
        if (it >= NST) STAMP2(it - NST);
        if (++s == NST) { s = 0; ph ^= 1; }
      }
#pragma unroll 1
      for (int r = 0; r < 16; r++) {
        const int kb = out_kblock(r, tn);
        refill_w(B_EMPTY + 8 * s, ph, B_FULL + 8 * s, r < 2 ? 16384 : 32768, RING + s * SLOT, &mp.m_wo, kb * 64, 2 * tn);
        if (r < 2 || r == 4) {
          const uint32_t bar = B_DR + (r < 2 ? 16 : 8);
          const int k0 = (bid >> 4) * 448 + 128 + min(r, 2) * 128;
          if (r != 1) e_expect(bar, r ? 8192 : 32768);
          e_tma2d_ef(RING + s * SLOT + 16384, &mp.m_down, (bid & 15) * 64, k0, bar, EVICT_FIRST);
          if (r < 2) e_tma2d_ef(RING + s * SLOT + 24576, &mp.m_down, (bid & 15) * 64, k0 + 64, bar, EVICT_FIRST);
        }
        STAMP2(r + 48 - NST);
        if (++s == NST) { s = 0; ph ^= 1; }
      }
    } else if (w == 13) {
      mbar_wait(B_FULL, 0);
#pragma unroll 1
      for (int c = 0; c < 4; c++) {
        if (c >= XS_FLY) mbar_wait(B_XS + 8 * (c - XS_FLY), 0);
        if (c == (tm >> 2)) {
          e_expect(B_WK, 16384);
          e_tma3d(FR, &mp.m_wqkv, tm * 64, 16 + 2 * tn, B_WK);
        }
        e_expect(B_XS + 8 * c, 8192);
        e_tma2d(STG + c * 8192, &mp.m_xs, c * 256, tm * 128 + tn * 16, B_XS + 8 * c);
      }
      {
        const char* pv = mp.wqkv + (tm * 16 + (lane >> 1)) * 6144 + 4096 + tn * 256 + (lane & 1) * 128;
        const char* pd = mp.wd + (bid & 15) * 128 + ((bid >> 4) * 448 + lane) * 2048;
        const char* po = mp.wo + bid * 16384 + lane * 128;
        mbar_wait(B_XS + 24, 0);
        __nanosleep(PF_WAIT);
#pragma unroll 1
        for (int i = PF_V ? 0 : 4; i < (PF_O ? 22 : 18); i++) {
          asm volatile("prefetch.global.L2 [%0];" ::"l"(i < 4 ? pv + i * (256 * 6144) : i < 18 ? pd + (i - 4) * 65536 : po + (i - 18) * 4096));
          __nanosleep(PF_GAP);
        }
      }
      nb_sync(NB_Z, 160);
      const uint32_t ep = lds32(S_EPOCH);
      {
        float z[4] = {0.f, 0.f, 0.f, 0.f};
        e_signal(H_Z + tn, tm);
        await(H_Z + tn, 0xffffu, ep);
#pragma unroll 1
        for (int i = 0; i < 4; i++) {
          uint32_t p[16];
          poll_z(p, g_z + i * 4096 + tn * 128 + lane * 4, ep, 1u);
#pragma unroll
          for (int q = 0; q < 4; q++) z[q] += (__uint_as_float(p[q]) + __uint_as_float(p[4 + q])) + (__uint_as_float(p[8 + q]) + __uint_as_float(p[12 + q]));
        }
        const uint32_t z01 = pack(z[0], z[1]), z23 = pack(z[2], z[3]);
        if (bid < 112) mbar_wait(B_PFREE, 0);
#pragma unroll
        for (int n = 0; n < 8; n++) sts64(KVB + (lane >> 4) * 5120 + n * 128 + ((((lane >> 1) & 7) ^ n) << 4) + (lane & 1) * 8, z01, z23);
        fence_async_smem();
        nb_arrive(NB_KVB, 320);
        STAMP_IF(lane == 0, 46);
      }
      nb_sync(NB_Q0, 192);
      e_store2d(&mp.m_os, tn * 128, tm * 128, STG);
      nb_sync(NB_OWN0, 160);
      e_store2d(&mp.m_os, tn * 128, tm * 128 + 64, STG + 8192);
      if (!SIG_EARLY) bulk_wait_read(); else if (SIG_EARLY > 1) __nanosleep(SIG_EARLY);
      e_signal(H_O + tm, 2 * tn);
      STAMP_IF(lane == 0, 4);
      nb_sync(NB_H1, 160);
      e_store2d(&mp.m_os, tn * 128 + 64, tm * 128, STG + 16384);
      e_store2d(&mp.m_os, tn * 128 + 64, tm * 128 + 64, STG + 24576);
      bulk_wait_read();
      e_signal(H_O + tm, 2 * tn + 1);
      STAMP_IF(lane == 0, 5);
      nb_arrive(NB_ST, 288);
    } else if (w == 14) {
      e_pfmap(&mp.m_gu); e_pfmap(&mp.m_o); e_pfmap(&mp.m_os); e_pfmap(&mp.m_wo); e_pfmap(&mp.m_down); e_pfmap(&mp.m_out);
      const uint32_t ep = ld_relaxed(&g_epoch) + 1;
      nb_sync(NB_FDONE, 416);
      {
        uint32_t c[4];
        poll_quad(c, g_csum + tn * 128 + lane * 4, ep, 1u);
        sts128(S_CSQ + lane * 16, c[0], c[1], c[2], c[3]);
        nb_arrive(NB_CSQ, 160);
        poll_quad(c, g_csum + 1024 + tn * 128 + lane * 4, ep, 1u);
        sts128(S_CSV + lane * 16, c[0], c[1], c[2], c[3]);
        __syncwarp();
        e_arrive(B_CSV);
      }
      {
        mbar_wait(B_WK, 1);
        if (KV_SPEC) __nanosleep(KV_SPEC); else await(H_KV + tn, 0xffffu, ep);
        STAMP_IF(lane == 0, 7);
        if (bid < 112) mbar_wait(B_PFREE, 0);
        STAMP_IF(lane == 0, 23);
        uint32_t bad, ph = 0;
        do {
          e_expect(B_KVL, 8192);
          e_load(KVB + 1024, g_kv + tn * 512, 4096, B_KVL);
          e_load(KVB + 6144, g_kv + tn * 512 + 256, 4096, B_KVL);
          mbar_wait(B_KVL, ph & 1);
          bad = 0;
#pragma unroll
          for (int i = 0; i < 16; i++) bad |= __float_as_uint(lds32v(KVB + 1024 + (i & 8) * 128 + i * 512 + lane * 16)) ^ ep;
          bad = __any_sync(0xffffffffu, bad & 1u);
          if (bad) fence_async_smem();
        } while (bad && ++ph < 100000);
        nb_arrive(NB_KVB, 320);
        STAMP_IF(lane == 0, 24);
      }
      nb_sync(NB_Q0, 192);
      uint32_t ready = 0;
      int s = 0, ph = 1;
#pragma unroll 1
      for (int r = 2; r < 16; r++) {
        const int kb = out_kblock(r, tn);
        if (!((ready >> kb) & 1)) {
          uint32_t f[1];
          poll0(f, g_sig + (H_O + tm) * 32, 0u - (ep & 1u), 1u << kb);
          ready = f[0] ^ ((ep & 1u) - 1u);
        }
        if (r == 4) mbar_wait(B_DND, 0);
        refill_x(B_EMPTY + 8 * s, ph, B_FULL + 8 * s, RING + s * SLOT + 16384, &mp.m_o, kb * 64, tm * 128);
        STAMP_IF(lane == 0 && r == 2, 2);
        STAMP_IF(lane == 0 && r == 9, 3);
        if (++s == NST) { s = 0; ph ^= 1; }
      }
    } else {
      uint32_t nsm = 132;
      if (BY_SMID) asm volatile("mov.u32 %0, %%nsmid;" : "=r"(nsm));
      asm volatile("{\n.reg .pred q;\nsetp.eq.u32 q, %0, 1156;\n@q bra LOK;\ntrap;\nLOK:\n}" ::"r"((uint32_t)__cvta_generic_to_shared(smem_raw) + nsm));
      const uint32_t ep = ld_relaxed(&g_epoch) + 1;
      mbar_wait(B_CSDN, 0);
#pragma unroll 1
      for (int n = 0; n < 3 && bid < 112; n++) {
        __nanosleep(FFN_GAP);
        e_expect(B_FR + 8 * n, 8192);
        e_tma3d_ef(GR + n * 8192, &mp.m_gu, bid * 32, n * 64, B_FR + 8 * n, EVICT_FIRST);
      }
      uint32_t sel[2];
      poll_pair(sel, g_sel + (bid >> 4) * 16 + (lane >> 2), ep, 31u);
      if ((lane & 3) == 0) sts64(S_SEL + lane * 2, sel[0], sel[1]);
      __syncwarp();
      e_arrive(B_SEL);
      if (bid < 112) {
        int s = 0, ph = 0;
#pragma unroll 1
        for (int n = 3; n < 16; n++) {
          refill_g(B_FE + 8 * s, ph, B_FR + 8 * s, GR + s * 8192, &mp.m_gu, bid * 32, n * 64);
          STAMP2(64 + n);
          if (++s == 3) { s = 0; ph ^= 1; }
        }
      }
      e_expect(B_DR, 16384);
      if (bid < 112) mbar_wait(B_FE + 8, 0);
      e_tma2d_ef(FR, &mp.m_down, (bid & 15) * 64, (bid >> 4) * 448, B_DR, EVICT_FIRST);
      if (bid < 112) mbar_wait(B_FE + 16, 0);
      e_tma2d_ef(FR + 8192, &mp.m_down, (bid & 15) * 64, (bid >> 4) * 448 + 64, B_DR, EVICT_FIRST);
    }
  } else if (w >= 8) {
    asm volatile("setmaxnreg.dec.sync.aligned.u32 56;");
    const int t = tid - 256, ww = w - 8;
    const uint32_t ep = ld_relaxed(&g_epoch) + 1, par = ep & 1u;
    {
      const int r0 = (lane >> 3) + (lane & 4);
      const uint32_t a = FR + (ww >> 1) * 8192 + r0 * 128 + ((((ww & 1) * 4 + (lane & 3)) ^ r0) << 4);
      float c[8];
      reg_zero(c);
      mbar_wait(B_WK, 0);
#pragma unroll 2
      for (int i = 0; i < 8; i++) {
        const uint4 v = lds128(a + i * 1024);
        c[0] += bf_lo(v.x); c[1] += bf_hi(v.x); c[2] += bf_lo(v.y); c[3] += bf_hi(v.y);
        c[4] += bf_lo(v.z); c[5] += bf_hi(v.z); c[6] += bf_lo(v.w); c[7] += bf_hi(v.w);
      }
      const bool u16 = lane & 16, u8 = lane & 8, u4 = lane & 4;
      const float d0 = xred(c[0], c[4], u16, 16), d1 = xred(c[1], c[5], u16, 16), d2 = xred(c[2], c[6], u16, 16), d3 = xred(c[3], c[7], u16, 16);
      fence_async_smem();
      e_arrive(B_CSDN);
      const float sum = xred(xred(d0, d2, u8, 8), xred(d1, d3, u8, 8), u4, 4);
      st_relaxed(g_csum + (2 + tm) * 1024 + tn * 128 + ww * 32 + (lane & 3) * 8 + (lane >> 2), tagf(sum, par));
      STAMP_IF(t == 0, 8);
      nb_sync(NB_WG2, 128);
      if (ww == 0) { e_signal(H_CS + tn, tm); await(H_CS + tn, 0xffffu, ep); }
      nb_sync(NB_WG2, 128);
      uint32_t p[16];
      poll16(p, g_csum + 2048 + tn * 128 + t, par, 1u);
      float tot = 0.f;
#pragma unroll
      for (int i = 0; i < 16; i += 4) tot += (__uint_as_float(p[i]) + __uint_as_float(p[i + 1])) + (__uint_as_float(p[i + 2]) + __uint_as_float(p[i + 3]));
      sts32(S_CSK + t * 4, __float_as_uint(tot));
      nb_arrive(NB_FDONE, 416);
      STAMP_IF(t == 0, 9);
    }
    const int ks = bid >> 4, nt = bid & 15;
    if (bid < 112) {
      float fg[4];
      reg_zero(fg);
      mbar_wait(B_SEL, 0);
      const float2 sel = lds64f(S_SEL + (t >> 4) * 8);
      const uint4* xs = reinterpret_cast<const uint4*>(mp.x + key_token(__float_as_uint(sel.x)) * 2048) + (t & 15);
      const uint32_t xd = AUX + (t & 8) * 128 + (t >> 4) * 128 + (((t ^ (t >> 4)) & 7) << 4), m2 = __byte_perm(__float_as_uint(sel.y), 0, 0x3232);
      uint4 v[4], u[4];
#pragma unroll
      for (int i = 0; i < 4; i++) v[i] = __ldg(xs + i * 16);
#pragma unroll
      for (int i = 0; i < 4; i++) u[i] = __ldg(xs + 64 + i * 16);
      constexpr uint64_t DA0 = mkdesc(GR, 4096, 512, 2);
      uint64_t da = DA0;
      uint32_t bar = B_FR, ph = 0;
#pragma unroll 1
      for (int b = 0; b < 2; b++) {
        if (b) nb_sync(NB_WG2, 128);
#pragma unroll
        for (int i = 0; i < 4; i++) {
          sts128(xd + i * 2048, sub2(v[i].x, m2), sub2(v[i].y, m2), sub2(v[i].z, m2), sub2(v[i].w, m2));
          v[i] = u[i];
        }
        fence_async_smem();
        nb_sync(NB_WG2, 128);
        uint64_t db = mkdesc(AUX, 16, 1024, 1);
#pragma unroll 1
        for (int n = 0; n < 8; n++) {
          mbar_wait(bar, ph);
          wg_fence();
#pragma unroll
          for (int q = 0; q < 4; q++) wgmma_n8_ss<1, 0>(fg, da + q * 64, db + q * 2, 1);
          wg_commit();
          const uint32_t rel = bar + (B_FE - B_FR);
          const bool wrap = bar == B_FR + 16;
          da = wrap ? DA0 : da + 512;
          db += 64;
          bar = wrap ? B_FR : bar + 8;
          ph ^= wrap;
          wg_wait<0>();
          if (t == 0) mbar_arrive(rel);
        }
      }
      if (t == 0) mbar_arrive(B_PFREE);
      const uint4 st = lds128(S_SEL + (lane & 3) * 16);
      const float r0 = rcp(bf_lo(st.y)), r1 = rcp(bf_lo(st.w));
      reg_fence(fg);
      const float fa[4] = {fg[0] * r0, fg[1] * r1, fg[2] * r0, fg[3] * r1};
      STAMP_IF(t == 0, 12);
      const bool isup = (ww >> 1) != (mp.wu < mp.wg);
      nb_sync(NB_WG2, 128);
      if (isup) sts128f(HOP + (t & 63) * 16, fa[0], fa[1], fa[2], fa[3]);
      nb_sync(NB_WG2, 128);
      if (!isup) {
        const float4 u = lds128f(HOP + (t & 63) * 16);
        const float uu[4] = {u.x, u.y, u.z, u.w};
        uint32_t* hp = g_h + bid * 256 + (lane & 3) * 64 + (ww & 1) * 16 + (lane >> 2);
#pragma unroll
        for (int i = 0; i < 4; i++) {
          const float g = fa[i], hv = g * rcp(1.f + ex2(-g * LOG2E)) * uu[i];
          st_relaxed(hp + (i & 1) * 32 + (i >> 1) * 8, __byte_perm(pack(hv, hv), ep, 0x3254));
        }
      }
      nb_sync(NB_WG2, 128);
      if (ww == 0) e_signal(H_H + bid / 14, bid % 14);
    }
    {
      uint32_t v[28];
      if (ww == 0) await(H_H + ks, 0x3fffu, ep);
      nb_sync(NB_WG2, 128);
      poll7x4(v, g_h + ks * 3584 + t * 4, ep, 0xffffu);
      mbar_wait(B_WK, 1);
#pragma unroll
      for (int q = 0; q < 7; q++)
        asm volatile("st.shared.v2.u32 [%0], {%1,%2};" ::"r"((q < 6 ? HOP + q * 1024 : S_CSK) + (t >> 3) * 64 + ((((t >> 1) & 3) ^ ((t >> 4) & 3)) << 4) + (t & 1) * 8),
                     "r"(__byte_perm(v[4 * q], v[4 * q + 1], 0x7632)), "r"(__byte_perm(v[4 * q + 2], v[4 * q + 3], 0x7632)) : "memory");
      fence_async_smem();
      nb_sync(NB_WG2, 128);
    }
    STAMP_IF(t == 0, 13);
    float fa[4] = {0.f, 0.f, 0.f, 0.f};
    auto down = [&](uint32_t a, int k0, int nk) {
#pragma unroll
      for (int q = 0; q < nk; q++) wgmma_n8_ss<1, 0>(fa, mkdesc(a + q * 2048, 4096, 1024, 1), mkdesc((k0 < 24 ? HOP : S_CSK - 6144) + ((k0 + q) >> 1) * 512 + (q & 1) * 32, 16, 512, 2), 1);
    };
    mbar_wait(B_DR, 0);
    mbar_wait(B_DR + 16, 0);
    mbar_wait(B_DR + 8, 0);
    wg_fence();
    down(RING + 2 * SLOT + 16384, 24, 4);
    down(RING + 3 * SLOT + 16384, 8, 8);
    down(RING + 4 * SLOT + 16384, 16, 8);
    wg_commit();
    wg_fence();
    down(FR, 0, 8);
    wg_commit();
    wg_wait<1>();
    if (t == 0) mbar_arrive(B_DND);
    wg_wait<0>();
    reg_fence(fa);
    STAMP_IF(t == 0, 14);
    {
      uint32_t* yp = g_yp + (nt * 8 + ks) * 512 + (lane & 3) * 128 + ww * 16 + (lane >> 2);
#pragma unroll
      for (int i = 0; i < 4; i++) st_relaxed(yp + (i & 1) * 64 + (i >> 1) * 8, tagf(fa[i], par));
    }
    nb_sync(NB_WG2, 128);
    if (ww == 0) e_signal(H_Y + (nt >> 1), (nt & 1) * 8 + ks);
    mbar_wait(B_SEL, 0);
    const uint32_t mykey = lds32(S_SEL + (lane & 7) * 8);
    const uint32_t inmask = __ballot_sync(0xffffffffu, (key_token(mykey) >> 7) == tm) & 0xffu;
    sts128(FR + t * 16, 0u, 0u, 0u, 0u);
    if (inmask) {
      if (ww == 0) await(H_Y + tn, 0xffffu, ep);
      nb_sync(NB_WG2, 128);
      const float sg = rcp(1.f + ex2(-key_score(mykey) * LOG2E));
#pragma unroll 1
      for (uint32_t mine = __ballot_sync(0xffffffffu, ((inmask >> lane) & 1) && (__popc(inmask & ((1u << lane) - 1)) & 3) == ww); mine; mine &= mine - 1) {
        const int j = __ffs(mine) - 1;
        uint32_t p[32];
        poll8x4(p, g_yp + (tn * 2 + (lane >> 4)) * 4096 + j * 64 + (lane & 15) * 4, par, 1u);
        float y[4];
        const float sj = __shfl_sync(0xffffffffu, sg, j);
#pragma unroll
        for (int i = 0; i < 4; i++)
          y[i] = sj * (((__uint_as_float(p[i]) + __uint_as_float(p[4 + i])) + (__uint_as_float(p[8 + i]) + __uint_as_float(p[12 + i]))) +
                       ((__uint_as_float(p[16 + i]) + __uint_as_float(p[20 + i])) + (__uint_as_float(p[24 + i]) + __uint_as_float(p[28 + i]))));
        asm volatile("st.shared.v2.u32 [%0], {%1,%2};" ::"r"(FR + (lane >> 4) * 1024 + j * 128 + ((((lane >> 1) & 7) ^ j) << 4) + (lane & 1) * 8),
                     "r"(pack(y[0], y[1])), "r"(pack(y[2], y[3])) : "memory");
      }
    }
    fence_async_smem();
    nb_arrive(NB_ST, 288);
    STAMP_IF(t == 0, 15);
  } else if (w >= 4) {
    asm volatile("setmaxnreg.inc.sync.aligned.u32 208;");
    const int t = tid - 128, ww = w - 4, g = lane >> 2, t4 = lane & 3;
    const bool leader = t == 0;
    const uint32_t ep = ld_relaxed(&g_epoch) + 1, par = ep & 1u;
    {
      const uint4* wp = reinterpret_cast<const uint4*>(mp.w_r) + lane;
      uint4 w0 = __ldg(wp), w1 = __ldg(wp + 32), w2 = __ldg(wp + 64), w3 = __ldg(wp + 96);
      if (leader) sts32(S_EPOCH, ep);
      if (KV_SPEC && t4 == 0) {
        const int grp = (tm & 1) * 2 + ((lane >> 3) & 1), row = ww * 2 + ((lane >> 2) & 1);
        st_unit(g_kv + tn * 512 + ((tm >> 3) * 4 + grp) * 64 + row * 8 + (((tm & 2) * 2 + ((tm >> 1) & 2) + (lane >> 4)) ^ row), 0u, 0u, 0u, 0u, par ^ 1u);
      }
      float s[4] = {0.f, 0.f, 0.f, 0.f}, q[4] = {0.f, 0.f, 0.f, 0.f}, d[4] = {0.f, 0.f, 0.f, 0.f}, wsum = 0.f;
#pragma unroll 1
      for (int c = 0; c < 4; c++) {
        const float wr[8] = {bf_lo(w0.x), bf_hi(w0.x), bf_lo(w0.y), bf_hi(w0.y), bf_lo(w0.z), bf_hi(w0.z), bf_lo(w0.w), bf_hi(w0.w)};
        w0 = w1; w1 = w2; w2 = w3;
        wsum += ((wr[0] + wr[1]) + (wr[2] + wr[3])) + ((wr[4] + wr[5]) + (wr[6] + wr[7]));
        mbar_wait(B_XS + 8 * c, 0);
#pragma unroll
        for (int r = 0; r < 4; r++) {
          const uint4 v = lds128(STG + c * 8192 + (ww * 4 + r) * 512 + lane * 16);
          const uint32_t xw[4] = {v.x, v.y, v.z, v.w};
#pragma unroll
          for (int i = 0; i < 4; i++) {
            const uint32_t dep = __float_as_uint(q[i ? r : (r + 3) & 3]);
            const float lo = __uint_as_float(prmt(xw[i], dep, 0x10ff)), hi = __uint_as_float(prmt(xw[i], dep, 0x32ff));
            s[r] += lo; q[r] = fmaf(lo, lo, q[r]); d[r] = fmaf(lo, wr[2 * i], d[r]);
            s[r] += hi; q[r] = fmaf(hi, hi, q[r]); d[r] = fmaf(hi, wr[2 * i + 1], d[r]);
          }
        }
      }
      STAMP_IF(leader, 16);
      const bool u16 = lane & 16, u8 = lane & 8, u4 = lane & 4, u2 = lane & 2;
      const float s1 = xred(xred(s[0], s[2], u16, 16), xred(s[1], s[3], u16, 16), u8, 8);
      const float q1 = xred(xred(q[0], q[2], u16, 16), xred(q[1], q[3], u16, 16), u8, 8);
      const float d1 = xred(xred(d[0], d[2], u16, 16), xred(d[1], d[3], u16, 16), u8, 8);
      wsum += __shfl_xor_sync(0xffffffffu, wsum, 16);
      wsum += __shfl_xor_sync(0xffffffffu, wsum, 8);
      float tot = xred(xred(s1, d1, u4, 4), xred(q1, wsum, u4, 4), u2, 2);
      tot += __shfl_xor_sync(0xffffffffu, tot, 1);
      const float qq = __shfl_down_sync(0xffffffffu, tot, 2), dd = __shfl_down_sync(0xffffffffu, tot, 4), ws = __shfl_down_sync(0xffffffffu, tot, 6);
      if ((lane & 7) == 0) {
        const float mean = tot * (1.f / 1024.f);
        const float var = fmaxf(fmaf(-mean, mean, qq * (1.f / 1024.f)), 0.f);
        float sd;
        asm("sqrt.approx.ftz.f32 %0, %1;" : "=f"(sd) : "f"(bf_round(bf_round(var) + 1e-5f)));
        const uint32_t ms = pack(sd, mean);
        const int row = tm * 128 + tn * 16 + ww * 4 + (lane >> 3);
        const uint32_t rbits = pack(0.f, fmaf(-bf_hi(ms), ws, dd) * rcp(bf_lo(ms)));
        const uint32_t key = (rbits ^ (((int)rbits >> 31 & 0x7fff0000u) | 0x80000000u)) | ((2047 - row) << 5) | (ep & 31u);
        asm volatile("{\n.reg .b64 x;\nmov.b64 x, {%1,%2};\nst.relaxed.gpu.global.b64 [%0], x;\n}" ::"l"(g_keys + row), "r"(key), "r"(ms) : "memory");
      }
      STAMP_IF(leader, 17);
      __nanosleep(400);
      uint32_t st[2];
      poll_pair(st, g_keys + tm * 128 + t, ep, 31u);
      asm volatile("st.shared.v2.f32 [%0], {%1,%2};" ::"r"(S_KSTAT + t * 8), "f"(bf_hi(st[1])), "f"(rcp(bf_lo(st[1])) * LOG2E) : "memory");
      nb_arrive(NB_FDONE, 416);
      STAMP_IF(leader, 10);
    }
    float a0[64], a1[64];
    reg_zero(a0); reg_zero(a1); reg_fence(a0); reg_fence(a1);
    STAMP_IF(leader, 18);
    nb_sync(NB_KV, 256);
    mainloop<true, 14>(a0, a1, 1, 1, 0, 0, leader);
    {
      auto half = [&](float (&a)[64], int s, int m) {
#pragma unroll
        for (int j = 0; j < 4; j++)
          wgmma_n128_ss<1, 0>(a, mkdesc(RING + s * SLOT + m * 8192 + j * 2048, 8192, 1024, 1), mkdesc(RING + s * SLOT + 16384 + j * 32, 16, 1024, 1), 1);
      };
      auto kvmma = [&](float (&a)[64], float (&c)[32], int m) {
        reg_fence(a);
        uint32_t f[32];
#pragma unroll
        for (int i = 0; i < 32; i++) f[i] = pack(a[2 * i], a[2 * i + 1]);
        reg_zero(c);
        wg_fence();
#pragma unroll
        for (int k = 0; k < 8; k++) {
          wgmma_n64_rs<0>(c, f[4 * k], f[4 * k + 1], f[4 * k + 2], f[4 * k + 3], mkdesc(STG + (k >> 2) * 16384 + m * 8192 + (k & 3) * 32, 16, 1024, 1), k != 0);
          if (m && k == HAND_K) nb_arrive(NB_VQ, 256);
        }
        wg_commit();
      };
      float c0[32], c1[32];
      mbar_wait(B_FULL, 0);
      wg_fence();
      half(a0, 0, 0);
      wg_commit();
      mbar_wait(B_FULL + 8, 0);
      wg_fence();
      half(a0, 1, 0);
      wg_commit();
      wg_wait<2>();
      if (leader) mbar_arrive(B_EMPTY + 32);
      wg_fence();
      half(a1, 0, 1);
      half(a1, 1, 1);
      wg_commit();
      nb_sync(NB_PK, 256);
      wg_wait<1>();
      kvmma(a0, c0, 0);
      wg_wait<1>();
      if (leader) { mbar_arrive(B_EMPTY); mbar_arrive(B_EMPTY + 8); }
      STAMP_IF(leader, 19);
      kvmma(a1, c1, 1);
      const bool hp = ww >> 1;
      float c[4];
      float2 tt[8];
#pragma unroll
      for (int i = 0; i < 8; i++) tt[i] = lds64f(S_CSK + ((i >> 2) * 64 + hp * 32 + (i & 3) * 8 + 2 * t4) * 4);
      mbar_wait(B_CSV, 0);
#pragma unroll
      for (int i = 0; i < 4; i++) c[i] = -__uint_as_float(lds32(S_CSV + ((i >> 1) * 64 + ww * 16 + (i & 1) * 8 + g) * 4));
      wg_wait<0>();
      reg_fence(c0);
      reg_fence(c1);
      if (leader) mbar_arrive(B_SFREE);
      STAMP_IF(leader, 20);
      uint4* pp = g_kvp + (tn * 16 + tm) * 512 + t;
      auto put = [&](int q, const float* d) {
        const float ca = c[q & 2], cb = c[q | 1];
        const float2 ta = tt[2 * q], tb = tt[2 * q + 1];
        st_unit(pp + q * 128, pack(fmaf(ca, ta.x, d[0]), fmaf(ca, ta.y, d[1])), pack(fmaf(cb, ta.x, d[2]), fmaf(cb, ta.y, d[3])),
                pack(fmaf(ca, tb.x, d[4]), fmaf(ca, tb.y, d[5])), pack(fmaf(cb, tb.x, d[6]), fmaf(cb, tb.y, d[7])), par);
      };
      if (!hp) { put(0, c0); put(1, c0 + 8); put(2, c1); put(3, c1 + 8); }
      else { put(0, c0 + 16); put(1, c0 + 24); put(2, c1 + 16); put(3, c1 + 24); }
      STAMP_IF(leader, 47);
      {
        uint32_t p[16];
        nb_sync(NB_WG1, 128);
        if (ww == 0) { e_signal(H_KVP + tn, tm); await(H_KVP + tn, 0xffffu, ep); }
        nb_sync(NB_WG1, 128);
        STAMP_IF(leader, 1);
        poll_kvp(p, g_kvp + (tn * 16 + (lane >> 3) * 4) * 512 + tm * 32 + ww * 8 + (lane & 7), par, 1u);
        float r[8];
#pragma unroll
        for (int i = 0; i < 4; i++) {
          r[2 * i] = (bf_lo(p[i]) + bf_lo(p[4 + i])) + (bf_lo(p[8 + i]) + bf_lo(p[12 + i]));
          r[2 * i + 1] = (bf_hi(p[i]) + bf_hi(p[4 + i])) + (bf_hi(p[8 + i]) + bf_hi(p[12 + i]));
        }
        const bool u16 = lane & 16, u8 = lane & 8;
        const uint32_t wd = pack(xred(xred(r[0], r[4], u16, 16), xred(r[2], r[6], u16, 16), u8, 8), xred(xred(r[1], r[5], u16, 16), xred(r[3], r[7], u16, 16), u8, 8));
        const uint32_t w1 = __shfl_down_sync(0xffffffffu, wd, 1), w2 = __shfl_down_sync(0xffffffffu, wd, 2), w3 = __shfl_down_sync(0xffffffffu, wd, 3);
        const int grp = (tm & 1) * 2 + ((lane >> 3) & 1), row = ww * 2 + ((lane >> 2) & 1);
        if (t4 == 0) st_unit(g_kv + tn * 512 + ((tm >> 3) * 4 + grp) * 64 + row * 8 + (((tm & 2) * 2 + ((tm >> 1) & 2) + (lane >> 4)) ^ row), wd, w1, w2, w3, par);
        nb_sync(NB_WG1, 128);
        if (ww == 0) { if (!KV_SPEC) e_signal(H_KV + tn, tm); e_arrive(B_WK); }
      }
      STAMP_IF(leader, 21);
    }
    const uint32_t sx = lane & 7, sc = lane >> 4;
    const uint32_t sa = STG + (ww * 16 + (lane & 15)) * 128;
    const uint32_t sw[4] = {sa + ((sc ^ sx) << 4), sa + (((2 + sc) ^ sx) << 4), sa + (((4 + sc) ^ sx) << 4), sa + (((6 + sc) ^ sx) << 4)};
    auto residual = [&]() {
      float ka[4], kb[4];
#pragma unroll
      for (int i = 0; i < 4; i++) {
        const float2 st = lds64f(S_KSTAT + ((i >> 1) * 64 + ww * 16 + (i & 1) * 8 + g) * 8);
        const float r = st.y * LN2;
        ka[i] = 1.f + r; kb[i] = -st.x * r;
      }
#pragma unroll
      for (int j = 0; j < 8; j++) {
        if ((j & 3) == 0) mbar_wait(B_XRES + 8 * (j >> 2), 0);
        const uint4 v = ldsm4(sw[j & 3] + (j >> 2) * 16384), u = ldsm4(sw[j & 3] + (j >> 2) * 16384 + 8192);
        const uint32_t vv[4] = {v.x, v.y, v.z, v.w}, uu[4] = {u.x, u.y, u.z, u.w};
#pragma unroll
        for (int i = 0; i < 4; i++) {
          a0[8 * j + 2 * i] = fmaf(bf_lo(vv[i]), ka[i & 1], kb[i & 1]);
          a0[8 * j + 2 * i + 1] = fmaf(bf_hi(vv[i]), ka[i & 1], kb[i & 1]);
          a1[8 * j + 2 * i] = fmaf(bf_lo(uu[i]), ka[2 + (i & 1)], kb[2 + (i & 1)]);
          a1[8 * j + 2 * i + 1] = fmaf(bf_hi(uu[i]), ka[2 + (i & 1)], kb[2 + (i & 1)]);
        }
      }
      reg_fence(a0);
      reg_fence(a1);
      STAMP_IF(leader, 22);
    };
    residual();
    nb_arrive(NB_KVB, 320);
    uint32_t oh[4];
    {
      mbar_wait(B_SEL, 0);
      const int r0 = key_token(lds32(S_SEL + t4 * 16)) - tm * 128, r1 = key_token(lds32(S_SEL + t4 * 16 + 8)) - tm * 128;
#pragma unroll
      for (int i = 0; i < 4; i++) {
        const int row = (i >> 1) * 64 + ww * 16 + (i & 1) * 8 + g;
        oh[i] = (r0 == row ? 0x3f00u : 0u) | (r1 == row ? 0x3f000000u : 0u);
      }
    }
    uint32_t va = RING + 16384 + sc * 8192 + (ww * 16 + (lane & 8)) * 128 + sx * 16 + (lane >> 3) * 4;
    asm volatile("" : "+r"(va));
    {
      auto own = [&](int r) {
        nb_sync(r ? NB_OWN1 : NB_Y, 256);
        mbar_wait(B_FULL + 8 * (3 + r), 1);
        STAMP_IF(leader, 25 + r);
        const uint64_t dw = mkdesc(RING + (3 + r) * SLOT, 8192, 1024, 1), dx = mkdesc(STG + r * 16384, 16, 1024, 1);
        wg_fence();
#pragma unroll
        for (int j = 0; j < 4; j++) {
          wgmma_n128_ss<0, 1>(a0, dx + j * 2, dw + j * 128, 1);
          wgmma_n128_ss<0, 1>(a1, dx + j * 2 + 512, dw + j * 128, 1);
        }
        wg_commit();
      };
      own(0);
      own(1);
      wg_wait<1>();
      if (leader) mbar_arrive(B_EMPTY + 24);
      auto check = [&](int r, int s) {
          uint32_t bad;
          asm volatile("{\n.reg .u32 a, b, c, d, e, f, g, h;\n.reg .pred p;\n"
                       "ld.shared.u32 a, [%1];\nld.shared.u32 b, [%1+128];\nld.shared.u32 c, [%1+256];\nld.shared.u32 d, [%1+384];\n"
                       "ld.shared.u32 e, [%1+512];\nld.shared.u32 f, [%1+640];\nld.shared.u32 g, [%1+768];\nld.shared.u32 h, [%1+896];\n"
                       "lop3.b32 a, a, b, %2, 0x7e;\nlop3.b32 c, c, d, %2, 0x7e;\nlop3.b32 e, e, f, %2, 0x7e;\nlop3.b32 g, g, h, %2, 0x7e;\n"
                       "lop3.b32 a, a, c, e, 0xfe;\nlop3.b32 a, a, g, 1, 0xa8;\nsetp.ne.u32 p, a, 0;\nvote.sync.any.pred p, p, 0xffffffff;\nselp.u32 %0, 1, 0, p;\n}"
                       : "=r"(bad) : "r"(va + s * SLOT), "r"(par) : "memory");
          if (__builtin_expect(bad, 0)) {
            const uint4* src = reinterpret_cast<const uint4*>(g_o + (tm * 128 + sc * 64 + ww * 16 + (lane & 15)) * 1024 + out_kblock(r, tn) * 64);
#pragma unroll 1
            for (int i = 0; i < 8; i++) {
              uint32_t v[4];
              asm volatile("{\n.reg .b64 x, y;\n.reg .b128 z;\n.reg .pred p, q, h;\n.reg .u32 c, b;\nmov.u32 c, 0;\nsetp.ne.u32 h, %6, 0;\nLW:\n"
                           "ld.relaxed.gpu.global.b128 z, [%4];\nmov.b128 {x, y}, z;\nmov.b64 {%0,%1}, x;\nmov.b64 {%2,%3}, y;\n"
                           "selp.b64 x, y, x, h;\nshr.b64 x, x, %7;\ncvt.u32.u64 b, x;\nand.b32 b, b, 1;\nsetp.eq.u32 p, b, %5;\n"
                           "vote.sync.all.pred p, p, 0xffffffff;\n@p bra.uni LD;\nadd.u32 c, c, 1;\nsetp.lt.u32 q, c, 1000000;\n@q bra.uni LW;\ntrap;\nLD:\n}"
                           : "=&r"(v[0]), "=&r"(v[1]), "=&r"(v[2]), "=&r"(v[3]) : "l"(src + i), "r"(par), "r"(sc), "r"((lane & 8) * 4) : "memory");
              sts128(RING + 16384 + s * SLOT + sc * 8192 + (ww * 16 + (lane & 15)) * 128 + ((i ^ sx) << 4), v[0], v[1], v[2], v[3]);
            }
            fence_async_smem();
            __syncwarp();
          }
      };
      int s = 0, ph = 0;
      uint32_t prev = B_EMPTY + 32;
#pragma unroll 1
      for (int r = 2; r < 12; r++) {
        mbar_wait(B_FULL + 8 * s, ph);
        check(r, s);
        if (!LITE || ((LITE_MASK >> 27) & 1)) STAMP_IF(leader && r == 2, 27);
        const uint64_t dw = mkdesc(RING, 8192, 1024, 1) + s * (SLOT >> 4), dx = mkdesc(RING + 16384, 16, 1024, 1) + s * (SLOT >> 4);
        wg_fence();
#pragma unroll
        for (int j = 0; j < 4; j++) {
          wgmma_n128_ss<0, 1>(a0, dx + j * 2, dw + j * 128, 1);
          wgmma_n128_ss<0, 1>(a1, dx + j * 2 + 512, dw + j * 128, 1);
        }
        wg_commit();
        wg_wait<1>();
        if (leader) mbar_arrive(prev);
        prev = B_EMPTY + 8 * s;
        if (++s == NST) { s = 0; ph ^= 1; }
      }
      auto half = [&](float (&a)[64], int s, int m) {
        const uint64_t dw = mkdesc(RING, 8192, 1024, 1) + s * (SLOT >> 4), dx = mkdesc(RING + 16384 + m * 8192, 16, 1024, 1) + s * (SLOT >> 4);
#pragma unroll
        for (int j = 0; j < 4; j++) wgmma_n128_ss<0, 1>(a, dx + j * 2, dw + j * 128, 1);
      };
      auto store = [&](float (&a)[64], int m, int c) {
#pragma unroll
        for (int i = 0; i < 32; i++) asm volatile("" : "+f"(a[32 * c + i])::"memory");
#pragma unroll
        for (int j = 4 * c; j < 4 * c + 4; j++)
          stsm4(sw[j & 3] + c * 16384 + m * 8192, pack(a[8 * j], a[8 * j + 1]), pack(a[8 * j + 2], a[8 * j + 3]), pack(a[8 * j + 4], a[8 * j + 5]), pack(a[8 * j + 6], a[8 * j + 7]));
        fence_async_smem();
        e_store2d(&mp.m_out, tn * 128 + c * 64, tm * 128 + m * 64 + ww * 16, STG + c * 16384 + m * 8192 + ww * 2048);
      };
#pragma unroll 1
      for (int q = 0; q < 4; q++) {
        mbar_wait(B_FULL + 8 * q, 0);
        check(12 + q, q);
        wg_fence();
        half(a0, q, 0);
        wg_commit();
      }
      nb_sync(NB_ST, 288);
      wg_fence();
      wgmma_n128_rs<1>(a0, oh[0], oh[1], oh[0], oh[1], mkdesc(FR, 1024, 0, 1), 1);
      wg_commit();
      wg_fence();
      half(a1, 0, 1);
      half(a1, 1, 1);
      wg_commit();
      wg_wait<1>();
      store(a0, 0, 0);
      store(a0, 0, 1);
      wg_fence();
      half(a1, 2, 1);
      half(a1, 3, 1);
      wgmma_n128_rs<1>(a1, oh[2], oh[3], oh[2], oh[3], mkdesc(FR, 1024, 0, 1), 1);
      wg_commit();
      wg_wait<0>();
      STAMP_IF(leader, 28);
      store(a1, 1, 0);
      store(a1, 1, 1);
    }
    bulk_wait_read();
    if (bid == 0 && leader) st_relaxed(&g_epoch, ep);
    STAMP_IF(leader, 29);
  } else {
    asm volatile("setmaxnreg.inc.sync.aligned.u32 216;");
    const int g = lane >> 2, t4 = lane & 3;
    const bool leader = tid == 0;
    const uint32_t sx = lane & 7, sc = lane >> 4;
    const uint32_t sa = STG + (w * 16 + (lane & 15)) * 128;
    const uint32_t sw[4] = {sa + ((sc ^ sx) << 4), sa + (((2 + sc) ^ sx) << 4), sa + (((4 + sc) ^ sx) << 4), sa + (((6 + sc) ^ sx) << 4)};
    float a0[64], a1[64];
    reg_zero(a0); reg_zero(a1); reg_fence(a0); reg_fence(a1);
    mainloop<true>(a0, a1, 0, 0, NB_KV, 0, leader);
    STAMP_IF(leader, 33);
    {
      nb_sync(NB_FDONE, 416);
      STAMP_IF(leader, 34);
      const uint32_t par = lds32(S_EPOCH) & 1u;
#pragma unroll 1
      for (int m = 0;; m++) {
        const uint32_t ca = S_CSK + (m * 64 + w * 16 + g) * 4;
        const float c[2] = {-lds32v(ca), -lds32v(ca + 32)};
        float z[2] = {0.f, 0.f}, tt[2] = {0.f, 0.f};
#pragma unroll
        for (int j = 0; j < 8; j++) {
          const float4 s0 = lds128v(S_KSTAT + (j * 16 + 2 * t4) * 8), s1 = lds128v(S_KSTAT + (j * 16 + 8 + 2 * t4) * 8);
          const float mu[4] = {s0.x, s0.z, s1.x, s1.z}, rl[4] = {s0.y, s0.w, s1.y, s1.w};
          float p[8];
#pragma unroll
          for (int i = 0; i < 8; i++) {
            const int r = (i >> 1) & 1, cc = (i >> 2) * 2 + (i & 1);
            p[i] = phi2(fmaf(c[r], mu[cc], a0[8 * j + i]) * rl[cc]);
            a0[8 * j + i] = a1[8 * j + i];
            z[r] += p[i];
            p[i] *= rl[cc];
            tt[r] = fmaf(p[i], mu[cc], tt[r]);
          }
          stsm4(sw[j & 3] + (j >> 2) * 16384 + m * 8192, pack(p[0], p[1]), pack(p[2], p[3]), pack(p[4], p[5]), pack(p[6], p[7]));
        }
        const bool u2 = lane & 2, u1 = lane & 1;
        const float v = xred(xred(z[0], tt[0], u2, 2), xred(z[1], tt[1], u2, 2), u1, 1);
        if (u2) sts32(ca + (t4 & 1) * 32, __float_as_uint(v));
        else st_relaxed(g_z + tm * 1024 + tn * 128 + m * 64 + w * 16 + t4 * 8 + g, tagf(v * LOG2E, par));
        if (m) break;
      }
      fence_async_smem();
      nb_arrive(NB_PK, 256);
      nb_arrive(NB_Z, 160);
    }
    STAMP_IF(leader, 35);
    const uint32_t ep = lds32(S_EPOCH);
    uint32_t sd2[4];
    float es[4];
    {
      nb_sync(NB_CSQ, 160);
      float mu[4];
#pragma unroll
      for (int i = 0; i < 4; i++) {
        const float2 st = lds64f(S_KSTAT + ((i >> 1) * 64 + w * 16 + (i & 1) * 8 + g) * 8);
        mu[i] = -st.x;
        const float sd = LOG2E * rcp(st.y);
        sd2[i] = pack(sd, sd);
        es[i] = sd * (1e-6f * LOG2E);
      }
#pragma unroll
      for (int j = 0; j < 16; j++) {
        const float2 c = lds64f(S_CSQ + (j * 8 + 2 * t4) * 4);
        a0[4 * j] = mu[0] * c.x; a0[4 * j + 1] = mu[0] * c.y; a0[4 * j + 2] = mu[1] * c.x; a0[4 * j + 3] = mu[1] * c.y;
        a1[4 * j] = mu[2] * c.x; a1[4 * j + 1] = mu[2] * c.y; a1[4 * j + 2] = mu[3] * c.x; a1[4 * j + 3] = mu[3] * c.y;
      }
      reg_fence(a0); reg_fence(a1);
    }
    STAMP_IF(leader, 40);
    nb_sync(NB_VQ, 256);
    mainloop<false, 13>(a0, a1, 2, 0, 0, 4 + (tn & 3), leader);
    {
      uint32_t f[2][16];
      const uint32_t ra = S_KSTAT + (w * 16 + g) * 8 + 4;
      auto phi = [&](const float (&a)[64], int off, int m, int i0, int i1, uint32_t (&o)[16]) {
        const float r0 = lds32v(ra + m * 512), r1 = lds32v(ra + m * 512 + 64);
#pragma unroll
        for (int i = i0; i < i1; i++) o[i] = phi_pack(a[off + 2 * i], a[off + 2 * i + 1], i & 1 ? r1 : r0, sd2[2 * m + (i & 1)]);
      };
      auto half = [&](float (&a)[64], int s, int m) {
        const bool xr = ((13 + s) >> 1) == 4 + (tn & 3);
        if (!m) {
          mbar_wait(B_FULL + 8 * s, 1);
          if (xr) mbar_wait(B_XRES + 8 * (~s & 1), 0);
          wg_fence();
        }
        const uint64_t dx = mkdesc(m * 8192, 16, 1024, 1) + ((xr ? STG + (~s & 1) * 16384 : RING + s * SLOT + 16384) >> 4);
#pragma unroll
        for (int j = 0; j < 4; j++) wgmma_n128_ss<0, 1>(a, dx + j * 2, mkdesc(RING + s * SLOT + j * 2048, 8192, 1024, 1), 1);
      };
      half(a0, 0, 0);
      wg_commit();
      half(a0, 1, 0);
      wg_commit();
      wg_wait<2>();
      if (leader) mbar_arrive(B_EMPTY + 32);
      half(a0, 2, 0);
      wg_commit();
      wg_fence();
      half(a1, 0, 1);
      half(a1, 1, 1);
      wg_commit();
      wg_wait<1>();
      reg_fence(a0);
      phi(a0, 0, 0, 0, PHI_CUT, f[0]);
      wg_fence();
      half(a1, 2, 1);
      wg_commit();
      phi(a0, 0, 0, PHI_CUT, 16, f[0]);
      nb_sync(NB_KVB, 320);
      wg_wait<0>();
      if (leader) { mbar_arrive(B_EMPTY); mbar_arrive(B_EMPTY + 8); mbar_arrive(B_EMPTY + 16); }
      reg_fence(a1);
      STAMP_IF(leader, 36);
      const uint32_t mk[4] = {t4 == 0, t4 == 1, t4 == 2, t4 == 3};
      uint64_t db = mkdesc(KVB, 16, 1024, 1);
      uint32_t so = 0;
#pragma unroll 1
      for (int j = 0;; j++) {
        float oc[2][2][20];
        auto mma = [&](const uint32_t (&a)[16], float (&o)[2][20]) {
          reg_zero(o[0]); reg_zero(o[1]);
          wg_fence();
          wgmma_n40_rs<0>(o[0], a[0], a[1], a[2], a[3], db, 0);
          wgmma_n40_rs<0>(o[1], a[8], a[9], a[10], a[11], db + 4, 0);
          wgmma_n40_rs<0>(o[0], a[4], a[5], a[6], a[7], db + 2, 1);
          wgmma_n40_rs<0>(o[1], a[12], a[13], a[14], a[15], db + 6, 1);
          wg_commit();
        };
        auto fin = [&](int m, float (&o)[2][20]) {
          const uint32_t m0 = mk[2 * m], m1 = mk[2 * m + 1];
#pragma unroll
          for (int h = 0; h < 2; h++) {
            const float r0 = rcp(o[h][0] + es[2 * m]), r1 = rcp(o[h][2] + es[2 * m + 1]);
            {
#pragma unroll
              for (int q = 0; q < 2; q++)
                stsm4(sw[h * 2 + q] + so + m * 8192,
                      bsel(pack(o[h][4 + 8 * q] * r0, o[h][5 + 8 * q] * r0), ep, m0), bsel(pack(o[h][6 + 8 * q] * r1, o[h][7 + 8 * q] * r1), ep, m1),
                      bsel(pack(o[h][8 + 8 * q] * r0, o[h][9 + 8 * q] * r0), ep, m0), bsel(pack(o[h][10 + 8 * q] * r1, o[h][11 + 8 * q] * r1), ep, m1));
            }
          }
        };
        mma(f[0], oc[0]);
        if (j) nb_arrive(NB_Y, 256);
        phi(a1, 0, 1, 0, 16, f[1]);
        wg_wait<0>();
        reg_fence(oc[0][0]); reg_fence(oc[0][1]);
        mma(f[1], oc[1]);
        fin(0, oc[0]);
        if (j == 0) { fence_async_smem(); nb_arrive(NB_Q0, 192); }
        wg_wait<0>();
        reg_fence(oc[1][0]); reg_fence(oc[1][1]);
        fin(1, oc[1]);
        fence_async_smem();
        if (j) break;
        nb_arrive(NB_OWN0, 160);
        STAMP_IF(leader, 38);
#pragma unroll
        for (int i = 0; i < 32; i++) a1[i] = a1[32 + i];
        phi(a0, 32, 0, 0, 16, f[0]);
        db = mkdesc(KVB + 5120, 16, 1024, 1);
        so = 16384;
      }
      nb_arrive(NB_OWN1, 256);
      nb_arrive(NB_H1, 160);
      STAMP_IF(leader, 39);
    }
  }
}

#undef CK
typedef CUresult (*EncodeFn)(CUtensorMap*, CUtensorMapDataType, cuuint32_t, void*, const cuuint64_t*, const cuuint64_t*, const cuuint32_t*,
                             const cuuint32_t*, CUtensorMapInterleave, CUtensorMapSwizzle, CUtensorMapL2promotion, CUtensorMapFloatOOBfill);

void make_map(EncodeFn enc, CUtensorMap* m, const void* p, int rank, uint64_t d0, uint64_t d1, uint64_t d2, uint64_t s1, uint64_t s2,
              uint32_t b0, uint32_t b1, uint32_t b2, CUtensorMapSwizzle sw) {
  cuuint64_t gd[3] = {d0, d1, d2}, gs[2] = {s1, s2};
  cuuint32_t bd[3] = {b0, b1, b2}, es[3] = {1, 1, 1};
  enc(m, CU_TENSOR_MAP_DATA_TYPE_BFLOAT16, rank, const_cast<void*>(p), gd, gs, bd, es, CU_TENSOR_MAP_INTERLEAVE_NONE, sw,
      CU_TENSOR_MAP_L2_PROMOTION_L2_128B, CU_TENSOR_MAP_FLOAT_OOB_FILL_NONE);
}

}

extern "C" void kernel_launch(void* const* d_in, const int* in_sizes, int n_in, void* d_out, int out_size) {
  (void)in_sizes; (void)n_in; (void)out_size;
  void* fn = nullptr;
  cudaDriverEntryPointQueryResult qr;
  cudaGetDriverEntryPoint("cuTensorMapEncodeTiled", &fn, cudaEnableDefault, &qr);
  EncodeFn enc = (EncodeFn)fn;
  void* o;
  cudaGetSymbolAddress(&o, g_o);
  const CUtensorMapSwizzle S128 = CU_TENSOR_MAP_SWIZZLE_128B, S64 = CU_TENSOR_MAP_SWIZZLE_64B, S0 = CU_TENSOR_MAP_SWIZZLE_NONE;
  Params mp;
  mp.x = (const char*)d_in[0]; mp.wqkv = (const char*)d_in[1]; mp.w_r = (const char*)d_in[4];
  mp.wg = (const char*)d_in[5]; mp.wu = (const char*)d_in[6]; mp.wd = (const char*)d_in[7]; mp.wo = (const char*)d_in[2];
  make_map(enc, &mp.m_wqkv, d_in[1], 3, 64, 1024, 48, 6144, 128, 64, 64, 2, S128);
  make_map(enc, &mp.m_x, d_in[0], 2, 1024, 2048, 1, 2048, 0, 64, 128, 1, S128);
  make_map(enc, &mp.m_os, o, 2, 1024, 2048, 1, 2048, 0, 64, 64, 1, S128);
  make_map(enc, &mp.m_o, o, 2, 1024, 2048, 1, 2048, 0, 64, 128, 1, S128);
  make_map(enc, &mp.m_wo, d_in[2], 3, 64, 1024, 16, 2048, 128, 64, 64, 2, S128);
  make_map(enc, &mp.m_xs, d_in[0], 2, 1024, 2048, 1, 2048, 0, 256, 16, 1, S0);
  const char *wg = (const char*)d_in[5], *wu = (const char*)d_in[6];
  make_map(enc, &mp.m_gu, wu < wg ? wu : wg, 3, 3584, 1024, 2, 7168, (uint64_t)(wu < wg ? wg - wu : wu - wg), 32, 64, 2, S64);
  make_map(enc, &mp.m_down, d_in[7], 2, 1024, 3584, 1, 2048, 0, 64, 64, 1, S128);
  make_map(enc, &mp.m_out, d_out, 2, 1024, 2048, 1, 2048, 0, 64, 16, 1, S128);
  int dev = 0, sms = 0;
  cudaGetDevice(&dev);
  cudaDeviceGetAttribute(&sms, cudaDevAttrMultiProcessorCount, dev);
  auto kern = sms == 132 ? fused_kernel<true> : fused_kernel<false>;
  cudaFuncSetAttribute(kern, cudaFuncAttributeMaxDynamicSharedMemorySize, SMEM_BYTES);
  kern<<<132, 512, SMEM_BYTES>>>(mp);
}
```

```cpp
#include <cuda_runtime.h>
#include <cuda.h>
#include <cuda_bf16.h>
#include <stdint.h>

namespace {

template <int TA, int TB>
__device__ __forceinline__ void wgmma_n8_ss(float (&d)[4], uint64_t da, uint64_t db, int sc) {
  asm volatile("{\n.reg .pred p;\nsetp.ne.b32 p, %6, 0;\n"
    "wgmma.mma_async.sync.aligned.m64n8k16.f32.bf16.bf16 {%0, %1, %2, %3}, %4, %5, p, 1, 1, %7, %8;\n}\n"
    : "+f"(d[0]), "+f"(d[1]), "+f"(d[2]), "+f"(d[3])
    : "l"(da), "l"(db), "r"(sc), "n"(TA), "n"(TB));
}
template <int TB>
__device__ __forceinline__ void wgmma_n40_rs(float (&d)[20], uint32_t a0, uint32_t a1, uint32_t a2, uint32_t a3, uint64_t db, int sc) {
  asm volatile("{\n.reg .pred p;\nsetp.ne.b32 p, %25, 0;\n"
    "wgmma.mma_async.sync.aligned.m64n40k16.f32.bf16.bf16 {%0, %1, %2, %3, %4, %5, %6, %7, %8, %9, %10, %11, %12, %13, %14, %15, %16, %17, %18, %19}, {%20,%21,%22,%23}, %24, p, 1, 1, %26;\n}\n"
    : "+f"(d[0]), "+f"(d[1]), "+f"(d[2]), "+f"(d[3]), "+f"(d[4]), "+f"(d[5]), "+f"(d[6]), "+f"(d[7]),
      "+f"(d[8]), "+f"(d[9]), "+f"(d[10]), "+f"(d[11]), "+f"(d[12]), "+f"(d[13]), "+f"(d[14]), "+f"(d[15]),
      "+f"(d[16]), "+f"(d[17]), "+f"(d[18]), "+f"(d[19])
    : "r"(a0), "r"(a1), "r"(a2), "r"(a3), "l"(db), "r"(sc), "n"(TB));
}
template <int TB>
__device__ __forceinline__ void wgmma_n64_rs(float (&d)[32], uint32_t a0, uint32_t a1, uint32_t a2, uint32_t a3, uint64_t db, int sc) {
  asm volatile("{\n.reg .pred p;\nsetp.ne.b32 p, %37, 0;\n"
    "wgmma.mma_async.sync.aligned.m64n64k16.f32.bf16.bf16 {%0, %1, %2, %3, %4, %5, %6, %7, %8, %9, %10, %11, %12, %13, %14, %15, %16, %17, %18, %19, %20, %21, %22, %23, %24, %25, %26, %27, %28, %29, %30, %31}, {%32,%33,%34,%35}, %36, p, 1, 1, %38;\n}\n"
    : "+f"(d[0]), "+f"(d[1]), "+f"(d[2]), "+f"(d[3]), "+f"(d[4]), "+f"(d[5]), "+f"(d[6]), "+f"(d[7]),
      "+f"(d[8]), "+f"(d[9]), "+f"(d[10]), "+f"(d[11]), "+f"(d[12]), "+f"(d[13]), "+f"(d[14]), "+f"(d[15]),
      "+f"(d[16]), "+f"(d[17]), "+f"(d[18]), "+f"(d[19]), "+f"(d[20]), "+f"(d[21]), "+f"(d[22]), "+f"(d[23]),
      "+f"(d[24]), "+f"(d[25]), "+f"(d[26]), "+f"(d[27]), "+f"(d[28]), "+f"(d[29]), "+f"(d[30]), "+f"(d[31])
    : "r"(a0), "r"(a1), "r"(a2), "r"(a3), "l"(db), "r"(sc), "n"(TB));
}
template <int TA, int TB>
__device__ __forceinline__ void wgmma_n128_ss(float (&d)[64], uint64_t da, uint64_t db, int sc) {
  asm volatile("{\n.reg .pred p;\nsetp.ne.b32 p, %66, 0;\n"
    "wgmma.mma_async.sync.aligned.m64n128k16.f32.bf16.bf16 {%0, %1, %2, %3, %4, %5, %6, %7, %8, %9, %10, %11, %12, %13, %14, %15, %16, %17, %18, %19, %20, %21, %22, %23, %24, %25, %26, %27, %28, %29, %30, %31, %32, %33, %34, %35, %36, %37, %38, %39, %40, %41, %42, %43, %44, %45, %46, %47, %48, %49, %50, %51, %52, %53, %54, %55, %56, %57, %58, %59, %60, %61, %62, %63}, %64, %65, p, 1, 1, %67, %68;\n}\n"
    : "+f"(d[0]), "+f"(d[1]), "+f"(d[2]), "+f"(d[3]), "+f"(d[4]), "+f"(d[5]), "+f"(d[6]), "+f"(d[7]),
      "+f"(d[8]), "+f"(d[9]), "+f"(d[10]), "+f"(d[11]), "+f"(d[12]), "+f"(d[13]), "+f"(d[14]), "+f"(d[15]),
      "+f"(d[16]), "+f"(d[17]), "+f"(d[18]), "+f"(d[19]), "+f"(d[20]), "+f"(d[21]), "+f"(d[22]), "+f"(d[23]),
      "+f"(d[24]), "+f"(d[25]), "+f"(d[26]), "+f"(d[27]), "+f"(d[28]), "+f"(d[29]), "+f"(d[30]), "+f"(d[31]),
      "+f"(d[32]), "+f"(d[33]), "+f"(d[34]), "+f"(d[35]), "+f"(d[36]), "+f"(d[37]), "+f"(d[38]), "+f"(d[39]),
      "+f"(d[40]), "+f"(d[41]), "+f"(d[42]), "+f"(d[43]), "+f"(d[44]), "+f"(d[45]), "+f"(d[46]), "+f"(d[47]),
      "+f"(d[48]), "+f"(d[49]), "+f"(d[50]), "+f"(d[51]), "+f"(d[52]), "+f"(d[53]), "+f"(d[54]), "+f"(d[55]),
      "+f"(d[56]), "+f"(d[57]), "+f"(d[58]), "+f"(d[59]), "+f"(d[60]), "+f"(d[61]), "+f"(d[62]), "+f"(d[63])
    : "l"(da), "l"(db), "r"(sc), "n"(TA), "n"(TB));
}
template <int TB>
__device__ __forceinline__ void wgmma_n128_rs(float (&d)[64], uint32_t a0, uint32_t a1, uint32_t a2, uint32_t a3, uint64_t db, int sc) {
  asm volatile("{\n.reg .pred p;\nsetp.ne.b32 p, %69, 0;\n"
    "wgmma.mma_async.sync.aligned.m64n128k16.f32.bf16.bf16 {%0, %1, %2, %3, %4, %5, %6, %7, %8, %9, %10, %11, %12, %13, %14, %15, %16, %17, %18, %19, %20, %21, %22, %23, %24, %25, %26, %27, %28, %29, %30, %31, %32, %33, %34, %35, %36, %37, %38, %39, %40, %41, %42, %43, %44, %45, %46, %47, %48, %49, %50, %51, %52, %53, %54, %55, %56, %57, %58, %59, %60, %61, %62, %63}, {%64,%65,%66,%67}, %68, p, 1, 1, %70;\n}\n"
    : "+f"(d[0]), "+f"(d[1]), "+f"(d[2]), "+f"(d[3]), "+f"(d[4]), "+f"(d[5]), "+f"(d[6]), "+f"(d[7]),
      "+f"(d[8]), "+f"(d[9]), "+f"(d[10]), "+f"(d[11]), "+f"(d[12]), "+f"(d[13]), "+f"(d[14]), "+f"(d[15]),
      "+f"(d[16]), "+f"(d[17]), "+f"(d[18]), "+f"(d[19]), "+f"(d[20]), "+f"(d[21]), "+f"(d[22]), "+f"(d[23]),
      "+f"(d[24]), "+f"(d[25]), "+f"(d[26]), "+f"(d[27]), "+f"(d[28]), "+f"(d[29]), "+f"(d[30]), "+f"(d[31]),
      "+f"(d[32]), "+f"(d[33]), "+f"(d[34]), "+f"(d[35]), "+f"(d[36]), "+f"(d[37]), "+f"(d[38]), "+f"(d[39]),
      "+f"(d[40]), "+f"(d[41]), "+f"(d[42]), "+f"(d[43]), "+f"(d[44]), "+f"(d[45]), "+f"(d[46]), "+f"(d[47]),
      "+f"(d[48]), "+f"(d[49]), "+f"(d[50]), "+f"(d[51]), "+f"(d[52]), "+f"(d[53]), "+f"(d[54]), "+f"(d[55]),
      "+f"(d[56]), "+f"(d[57]), "+f"(d[58]), "+f"(d[59]), "+f"(d[60]), "+f"(d[61]), "+f"(d[62]), "+f"(d[63])
    : "r"(a0), "r"(a1), "r"(a2), "r"(a3), "l"(db), "r"(sc), "n"(TB));
}

__device__ __forceinline__ void poll1f(uint32_t (&v)[1], const void* p, uint32_t tag, uint32_t mask) {
  asm volatile("{\n.reg .pred p, q;\n.reg .u32 c, b;\n.reg .b64 x, y;\n.reg .b128 z;\nmov.u32 c, 0;\nLW:\n"
               "ld.relaxed.gpu.global.u32 %0, [%1+0];\n"
               "xor.b32 b, %0, %2;\n"
               "and.b32 b, b, %3;\nsetp.eq.u32 p, b, 0;\nvote.sync.all.pred p, p, 0xffffffff;\n@p bra.uni LD;\n"
               "nanosleep.u32 50;\nadd.u32 c, c, 1;\nsetp.lt.u32 q, c, 1000000;\n@q bra.uni LW;\ntrap;\nLD:\n}"
               : "=&r"(v[0])
               : "l"(p), "r"(tag), "r"(mask) : "memory");
}
__device__ __forceinline__ void poll0(uint32_t (&v)[1], const void* p, uint32_t tag, uint32_t mask) {
  asm volatile("{\n.reg .pred p, q;\n.reg .u32 c, b;\n.reg .b64 x, y;\n.reg .b128 z;\nmov.u32 c, 0;\nLW:\n"
               "ld.relaxed.gpu.global.u32 %0, [%1+0];\n"
               "xor.b32 b, %0, %2;\n"
               "and.b32 b, b, %3;\nsetp.eq.u32 p, b, 0;\nvote.sync.all.pred p, p, 0xffffffff;\n@p bra.uni LD;\n"
               "add.u32 c, c, 1;\nsetp.lt.u32 q, c, 1000000;\n@q bra.uni LW;\ntrap;\nLD:\n}"
               : "=&r"(v[0])
               : "l"(p), "r"(tag), "r"(mask) : "memory");
}
__device__ __forceinline__ void poll_pair(uint32_t (&v)[2], const void* p, uint32_t tag, uint32_t mask) {
  asm volatile("{\n.reg .pred p, q;\n.reg .u32 c, b;\n.reg .b64 x, y;\n.reg .b128 z;\nmov.u32 c, 0;\nLW:\n"
               "ld.relaxed.gpu.global.b64 x, [%2+0];\nmov.b64 {%0,%1}, x;\n"
               "xor.b32 b, %0, %3;\n"
               "and.b32 b, b, %4;\nsetp.eq.u32 p, b, 0;\nvote.sync.all.pred p, p, 0xffffffff;\n@p bra.uni LD;\n"
               "nanosleep.u32 100;\nadd.u32 c, c, 1;\nsetp.lt.u32 q, c, 1000000;\n@q bra.uni LW;\ntrap;\nLD:\n}"
               : "=&r"(v[0]), "=&r"(v[1])
               : "l"(p), "r"(tag), "r"(mask) : "memory");
}
__device__ __forceinline__ void poll_quad(uint32_t (&v)[4], const void* p, uint32_t tag, uint32_t mask) {
  asm volatile("{\n.reg .pred p, q;\n.reg .u32 c, b;\n.reg .b64 x, y;\n.reg .b128 z;\nmov.u32 c, 0;\nLW:\n"
               "ld.relaxed.gpu.global.v4.u32 {%0,%1,%2,%3}, [%4+0];\n"
               "xor.b32 b, %0, %5;\n"
               "lop3.b32 b, b, %1, %5, 0xf6;\nlop3.b32 b, b, %2, %5, 0xf6;\nlop3.b32 b, b, %3, %5, 0xf6;\n"
               "and.b32 b, b, %6;\nsetp.eq.u32 p, b, 0;\nvote.sync.all.pred p, p, 0xffffffff;\n@p bra.uni LD;\n"
               "nanosleep.u32 200;\nadd.u32 c, c, 1;\nsetp.lt.u32 q, c, 1000000;\n@q bra.uni LW;\ntrap;\nLD:\n}"
               : "=&r"(v[0]), "=&r"(v[1]), "=&r"(v[2]), "=&r"(v[3])
               : "l"(p), "r"(tag), "r"(mask) : "memory");
}
__device__ __forceinline__ void poll8x4(uint32_t (&v)[32], const void* p, uint32_t tag, uint32_t mask) {
  asm volatile("{\n.reg .pred p, q;\n.reg .u32 c, b;\n.reg .b64 x, y;\n.reg .b128 z;\nmov.u32 c, 0;\nLW:\n"
               "ld.relaxed.gpu.global.v4.u32 {%0,%1,%2,%3}, [%32+0];\n"
               "ld.relaxed.gpu.global.v4.u32 {%4,%5,%6,%7}, [%32+2048];\n"
               "ld.relaxed.gpu.global.v4.u32 {%8,%9,%10,%11}, [%32+4096];\n"
               "ld.relaxed.gpu.global.v4.u32 {%12,%13,%14,%15}, [%32+6144];\n"
               "ld.relaxed.gpu.global.v4.u32 {%16,%17,%18,%19}, [%32+8192];\n"
               "ld.relaxed.gpu.global.v4.u32 {%20,%21,%22,%23}, [%32+10240];\n"
               "ld.relaxed.gpu.global.v4.u32 {%24,%25,%26,%27}, [%32+12288];\n"
               "ld.relaxed.gpu.global.v4.u32 {%28,%29,%30,%31}, [%32+14336];\n"
               "xor.b32 b, %0, %33;\n"
               "lop3.b32 b, b, %1, %33, 0xf6;\nlop3.b32 b, b, %2, %33, 0xf6;\nlop3.b32 b, b, %3, %33, 0xf6;\nlop3.b32 b, b, %4, %33, 0xf6;\n"
               "lop3.b32 b, b, %5, %33, 0xf6;\nlop3.b32 b, b, %6, %33, 0xf6;\nlop3.b32 b, b, %7, %33, 0xf6;\nlop3.b32 b, b, %8, %33, 0xf6;\n"
               "lop3.b32 b, b, %9, %33, 0xf6;\nlop3.b32 b, b, %10, %33, 0xf6;\nlop3.b32 b, b, %11, %33, 0xf6;\nlop3.b32 b, b, %12, %33, 0xf6;\n"
               "lop3.b32 b, b, %13, %33, 0xf6;\nlop3.b32 b, b, %14, %33, 0xf6;\nlop3.b32 b, b, %15, %33, 0xf6;\nlop3.b32 b, b, %16, %33, 0xf6;\n"
               "lop3.b32 b, b, %17, %33, 0xf6;\nlop3.b32 b, b, %18, %33, 0xf6;\nlop3.b32 b, b, %19, %33, 0xf6;\nlop3.b32 b, b, %20, %33, 0xf6;\n"
               "lop3.b32 b, b, %21, %33, 0xf6;\nlop3.b32 b, b, %22, %33, 0xf6;\nlop3.b32 b, b, %23, %33, 0xf6;\nlop3.b32 b, b, %24, %33, 0xf6;\n"
               "lop3.b32 b, b, %25, %33, 0xf6;\nlop3.b32 b, b, %26, %33, 0xf6;\nlop3.b32 b, b, %27, %33, 0xf6;\nlop3.b32 b, b, %28, %33, 0xf6;\n"
               "lop3.b32 b, b, %29, %33, 0xf6;\nlop3.b32 b, b, %30, %33, 0xf6;\nlop3.b32 b, b, %31, %33, 0xf6;\n"
               "and.b32 b, b, %34;\nsetp.eq.u32 p, b, 0;\nvote.sync.all.pred p, p, 0xffffffff;\n@p bra.uni LD;\n"
               "nanosleep.u32 50;\nadd.u32 c, c, 1;\nsetp.lt.u32 q, c, 1000000;\n@q bra.uni LW;\ntrap;\nLD:\n}"
               : "=&r"(v[0]), "=&r"(v[1]), "=&r"(v[2]), "=&r"(v[3]), "=&r"(v[4]), "=&r"(v[5]), "=&r"(v[6]), "=&r"(v[7]), "=&r"(v[8]), "=&r"(v[9]), "=&r"(v[10]), "=&r"(v[11]), "=&r"(v[12]), "=&r"(v[13]), "=&r"(v[14]), "=&r"(v[15]), "=&r"(v[16]), "=&r"(v[17]), "=&r"(v[18]), "=&r"(v[19]), "=&r"(v[20]), "=&r"(v[21]), "=&r"(v[22]), "=&r"(v[23]), "=&r"(v[24]), "=&r"(v[25]), "=&r"(v[26]), "=&r"(v[27]), "=&r"(v[28]), "=&r"(v[29]), "=&r"(v[30]), "=&r"(v[31])
               : "l"(p), "r"(tag), "r"(mask) : "memory");
}
__device__ __forceinline__ void poll16(uint32_t (&v)[16], const void* p, uint32_t tag, uint32_t mask) {
  asm volatile("{\n.reg .pred p, q;\n.reg .u32 c, b;\n.reg .b64 x, y;\n.reg .b128 z;\nmov.u32 c, 0;\nLW:\n"
               "ld.relaxed.gpu.global.u32 %0, [%16+0];\n"
               "ld.relaxed.gpu.global.u32 %1, [%16+4096];\n"
               "ld.relaxed.gpu.global.u32 %2, [%16+8192];\n"
               "ld.relaxed.gpu.global.u32 %3, [%16+12288];\n"
               "ld.relaxed.gpu.global.u32 %4, [%16+16384];\n"
               "ld.relaxed.gpu.global.u32 %5, [%16+20480];\n"
               "ld.relaxed.gpu.global.u32 %6, [%16+24576];\n"
               "ld.relaxed.gpu.global.u32 %7, [%16+28672];\n"
               "ld.relaxed.gpu.global.u32 %8, [%16+32768];\n"
               "ld.relaxed.gpu.global.u32 %9, [%16+36864];\n"
               "ld.relaxed.gpu.global.u32 %10, [%16+40960];\n"
               "ld.relaxed.gpu.global.u32 %11, [%16+45056];\n"
               "ld.relaxed.gpu.global.u32 %12, [%16+49152];\n"
               "ld.relaxed.gpu.global.u32 %13, [%16+53248];\n"
               "ld.relaxed.gpu.global.u32 %14, [%16+57344];\n"
               "ld.relaxed.gpu.global.u32 %15, [%16+61440];\n"
               "xor.b32 b, %0, %17;\n"
               "lop3.b32 b, b, %1, %17, 0xf6;\nlop3.b32 b, b, %2, %17, 0xf6;\nlop3.b32 b, b, %3, %17, 0xf6;\nlop3.b32 b, b, %4, %17, 0xf6;\n"
               "lop3.b32 b, b, %5, %17, 0xf6;\nlop3.b32 b, b, %6, %17, 0xf6;\nlop3.b32 b, b, %7, %17, 0xf6;\nlop3.b32 b, b, %8, %17, 0xf6;\n"
               "lop3.b32 b, b, %9, %17, 0xf6;\nlop3.b32 b, b, %10, %17, 0xf6;\nlop3.b32 b, b, %11, %17, 0xf6;\nlop3.b32 b, b, %12, %17, 0xf6;\n"
               "lop3.b32 b, b, %13, %17, 0xf6;\nlop3.b32 b, b, %14, %17, 0xf6;\nlop3.b32 b, b, %15, %17, 0xf6;\n"
               "and.b32 b, b, %18;\nsetp.eq.u32 p, b, 0;\nvote.sync.all.pred p, p, 0xffffffff;\n@p bra.uni LD;\n"
               "nanosleep.u32 200;\nadd.u32 c, c, 1;\nsetp.lt.u32 q, c, 1000000;\n@q bra.uni LW;\ntrap;\nLD:\n}"
               : "=&r"(v[0]), "=&r"(v[1]), "=&r"(v[2]), "=&r"(v[3]), "=&r"(v[4]), "=&r"(v[5]), "=&r"(v[6]), "=&r"(v[7]), "=&r"(v[8]), "=&r"(v[9]), "=&r"(v[10]), "=&r"(v[11]), "=&r"(v[12]), "=&r"(v[13]), "=&r"(v[14]), "=&r"(v[15])
               : "l"(p), "r"(tag), "r"(mask) : "memory");
}
__device__ __forceinline__ void poll_keys(uint32_t (&v)[16], const void* p, uint32_t tag, uint32_t mask) {
  asm volatile("{\n.reg .pred p, q;\n.reg .u32 c, b;\n.reg .b64 x, y;\n.reg .b128 z;\nmov.u32 c, 0;\nLW:\n"
               "ld.relaxed.gpu.global.v2.b64 {x, y}, [%16+0];\nmov.b64 {%0,%1}, x;\nmov.b64 {%2,%3}, y;\n"
               "ld.relaxed.gpu.global.v2.b64 {x, y}, [%16+4096];\nmov.b64 {%4,%5}, x;\nmov.b64 {%6,%7}, y;\n"
               "ld.relaxed.gpu.global.v2.b64 {x, y}, [%16+8192];\nmov.b64 {%8,%9}, x;\nmov.b64 {%10,%11}, y;\n"
               "ld.relaxed.gpu.global.v2.b64 {x, y}, [%16+12288];\nmov.b64 {%12,%13}, x;\nmov.b64 {%14,%15}, y;\n"
               "xor.b32 b, %0, %17;\n"
               "lop3.b32 b, b, %2, %17, 0xf6;\nlop3.b32 b, b, %4, %17, 0xf6;\nlop3.b32 b, b, %6, %17, 0xf6;\nlop3.b32 b, b, %8, %17, 0xf6;\n"
               "lop3.b32 b, b, %10, %17, 0xf6;\nlop3.b32 b, b, %12, %17, 0xf6;\nlop3.b32 b, b, %14, %17, 0xf6;\n"
               "and.b32 b, b, %18;\nsetp.eq.u32 p, b, 0;\nvote.sync.all.pred p, p, 0xffffffff;\n@p bra.uni LD;\n"
               "nanosleep.u32 20;\nadd.u32 c, c, 1;\nsetp.lt.u32 q, c, 1000000;\n@q bra.uni LW;\ntrap;\nLD:\n}"
               : "=&r"(v[0]), "=&r"(v[1]), "=&r"(v[2]), "=&r"(v[3]), "=&r"(v[4]), "=&r"(v[5]), "=&r"(v[6]), "=&r"(v[7]), "=&r"(v[8]), "=&r"(v[9]), "=&r"(v[10]), "=&r"(v[11]), "=&r"(v[12]), "=&r"(v[13]), "=&r"(v[14]), "=&r"(v[15])
               : "l"(p), "r"(tag), "r"(mask) : "memory");
}
__device__ __forceinline__ void poll_z(uint32_t (&v)[16], const void* p, uint32_t tag, uint32_t mask) {
  asm volatile("{\n.reg .pred p, q;\n.reg .u32 c, b;\n.reg .b64 x, y;\n.reg .b128 z;\nmov.u32 c, 0;\nLW:\n"
               "ld.relaxed.gpu.global.v4.u32 {%0,%1,%2,%3}, [%16+0];\n"
               "ld.relaxed.gpu.global.v4.u32 {%4,%5,%6,%7}, [%16+4096];\n"
               "ld.relaxed.gpu.global.v4.u32 {%8,%9,%10,%11}, [%16+8192];\n"
               "ld.relaxed.gpu.global.v4.u32 {%12,%13,%14,%15}, [%16+12288];\n"
               "xor.b32 b, %0, %17;\n"
               "lop3.b32 b, b, %1, %17, 0xf6;\nlop3.b32 b, b, %2, %17, 0xf6;\nlop3.b32 b, b, %3, %17, 0xf6;\nlop3.b32 b, b, %4, %17, 0xf6;\n"
               "lop3.b32 b, b, %5, %17, 0xf6;\nlop3.b32 b, b, %6, %17, 0xf6;\nlop3.b32 b, b, %7, %17, 0xf6;\nlop3.b32 b, b, %8, %17, 0xf6;\n"
               "lop3.b32 b, b, %9, %17, 0xf6;\nlop3.b32 b, b, %10, %17, 0xf6;\nlop3.b32 b, b, %11, %17, 0xf6;\nlop3.b32 b, b, %12, %17, 0xf6;\n"
               "lop3.b32 b, b, %13, %17, 0xf6;\nlop3.b32 b, b, %14, %17, 0xf6;\nlop3.b32 b, b, %15, %17, 0xf6;\n"
               "and.b32 b, b, %18;\nsetp.eq.u32 p, b, 0;\nvote.sync.all.pred p, p, 0xffffffff;\n@p bra.uni LD;\n"
               "nanosleep.u32 300;\nadd.u32 c, c, 1;\nsetp.lt.u32 q, c, 1000000;\n@q bra.uni LW;\ntrap;\nLD:\n}"
               : "=&r"(v[0]), "=&r"(v[1]), "=&r"(v[2]), "=&r"(v[3]), "=&r"(v[4]), "=&r"(v[5]), "=&r"(v[6]), "=&r"(v[7]), "=&r"(v[8]), "=&r"(v[9]), "=&r"(v[10]), "=&r"(v[11]), "=&r"(v[12]), "=&r"(v[13]), "=&r"(v[14]), "=&r"(v[15])
               : "l"(p), "r"(tag), "r"(mask) : "memory");
}
__device__ __forceinline__ void poll_kvp(uint32_t (&v)[16], const void* p, uint32_t tag, uint32_t mask) {
  asm volatile("{\n.reg .pred p, q;\n.reg .u32 c, b;\n.reg .b64 x, y;\n.reg .b128 z;\nmov.u32 c, 0;\nLW:\n"
               "ld.relaxed.gpu.global.b128 z, [%16+0];\nmov.b128 {x, y}, z;\nmov.b64 {%0,%1}, x;\nmov.b64 {%2,%3}, y;\n"
               "ld.relaxed.gpu.global.b128 z, [%16+8192];\nmov.b128 {x, y}, z;\nmov.b64 {%4,%5}, x;\nmov.b64 {%6,%7}, y;\n"
               "ld.relaxed.gpu.global.b128 z, [%16+16384];\nmov.b128 {x, y}, z;\nmov.b64 {%8,%9}, x;\nmov.b64 {%10,%11}, y;\n"
               "ld.relaxed.gpu.global.b128 z, [%16+24576];\nmov.b128 {x, y}, z;\nmov.b64 {%12,%13}, x;\nmov.b64 {%14,%15}, y;\n"
               "xor.b32 b, %0, %17;\n"
               "lop3.b32 b, b, %4, %17, 0xf6;\nlop3.b32 b, b, %8, %17, 0xf6;\nlop3.b32 b, b, %12, %17, 0xf6;\n"
               "and.b32 b, b, %18;\nsetp.eq.u32 p, b, 0;\nvote.sync.all.pred p, p, 0xffffffff;\n@p bra.uni LD;\n"
               "nanosleep.u32 50;\nadd.u32 c, c, 1;\nsetp.lt.u32 q, c, 1000000;\n@q bra.uni LW;\ntrap;\nLD:\n}"
               : "=&r"(v[0]), "=&r"(v[1]), "=&r"(v[2]), "=&r"(v[3]), "=&r"(v[4]), "=&r"(v[5]), "=&r"(v[6]), "=&r"(v[7]), "=&r"(v[8]), "=&r"(v[9]), "=&r"(v[10]), "=&r"(v[11]), "=&r"(v[12]), "=&r"(v[13]), "=&r"(v[14]), "=&r"(v[15])
               : "l"(p), "r"(tag), "r"(mask) : "memory");
}

__device__ __align__(1024) __nv_bfloat16 g_o[2048 * 1024];
__device__ __align__(128) uint2 g_keys[2048];
__device__ __align__(128) uint32_t g_csum[18 * 1024];
__device__ __align__(128) uint32_t g_z[16 * 1024];
__device__ __align__(128) uint4 g_kvp[128 * 512];
__device__ __align__(128) uint4 g_kv[8 * 512];
__device__ __align__(128) uint4 g_h[112 * 32];
__device__ __align__(128) uint32_t g_yp[128 * 512];
__device__ __align__(128) uint2 g_sel[32 * 16];
enum { H_CS = 0, H_KVP = 8, H_KV = 16, H_H = 24, H_Y = 32, H_O = 40, H_Z = 56 };
__device__ __align__(128) uint32_t g_sig[64 * 32];
__device__ uint32_t g_epoch;

constexpr uint32_t RING = 1024, SLOT = 32768, SMEM_BYTES = 232448;
constexpr int NST = 5, HST = 7;
constexpr uint32_t STG = RING + 163840, AUX = RING + 196608, FR = RING + 212992, MISC = RING + 229376;
constexpr uint32_t B_FULL = MISC, B_EMPTY = MISC + 56, B_XS = MISC + 112, B_SEL = MISC + 144, B_WK = MISC + 160, B_CSDN = MISC + 168,
                   B_FR = MISC + 176, B_FE = MISC + 200, B_DR = MISC + 224, B_CSV = MISC + 248,
                   B_DND = MISC + 256, B_XRES = MISC + 264, B_PFREE = MISC + 280, B_SFREE = MISC + 288, B_KVL = MISC + 296, B_HL = MISC + 304, B_HOK = MISC + 312, B_HGO = MISC + 320, NBAR = 41;
constexpr uint32_t S_EPOCH = MISC + 352, S_NCAND = MISC + 356, S_SEL = MISC + 368, S_WMAX = MISC + 432,
                   S_KSTAT = MISC + 512, S_CSK = MISC + 1536, S_CSV = MISC + 2048, S_CSQ = MISC + 2560, S_ONES = MISC + 512;
constexpr uint32_t KVB = FR, HOP = FR + 10240, GR = FR - 8192;
enum { NB_Z = 0, NB_KV = 1, NB_VQ = 2, NB_WG0 = 3, NB_FDONE = 4, NB_PK = 5, NB_KVB = 6, NB_WG1 = 7, NB_WG2 = 8, NB_CSQ = 9,
       NB_Y = 10, NB_ST = 11, NB_OWN0 = 12, NB_OWN1 = 13, NB_Q0 = 14, NB_H1 = 15 };

#define XS_FLY 2
#define FFN_GAP 400
#define PF_GAP 200
#define PF_WAIT 1000
#define GPCMAP 0x75143620u
#define KV_SPEC 200
#define HAND_K 5
#define PHI_CUT 11
#define SIG_EARLY 50
constexpr uint64_t EVICT_FIRST = 0x12f0000000000000ull;
constexpr float LOG2E = 1.4426950408889634f, LN2 = 0.6931471805599453f;

#define ELECT "{\n.reg .pred p;\nelect.sync _|p, 0xffffffff;\n"
#define TMA2D "cp.async.bulk.tensor.2d.shared::cluster.global.mbarrier::complete_tx::bytes"
#define TMA3D "cp.async.bulk.tensor.3d.shared::cluster.global.mbarrier::complete_tx::bytes"
__device__ __forceinline__ void e_expect(uint32_t b, uint32_t n) {
  asm volatile(ELECT "@p mbarrier.arrive.expect_tx.shared::cta.b64 _, [%0], %1;\n}" ::"r"(b), "r"(n) : "memory");
}
__device__ __forceinline__ void e_arrive(uint32_t b) { asm volatile(ELECT "@p mbarrier.arrive.shared::cta.b64 _, [%0];\n}" ::"r"(b) : "memory"); }
__device__ __forceinline__ void e_tma2d(uint32_t dst, const CUtensorMap* m, int c0, int c1, uint32_t bar) {
  asm volatile(ELECT "@p " TMA2D " [%0], [%1, {%3, %4}], [%2];\n}" ::"r"(dst), "l"(m), "r"(bar), "r"(c0), "r"(c1) : "memory");
}
__device__ __forceinline__ void e_tma2d_ef(uint32_t dst, const CUtensorMap* m, int c0, int c1, uint32_t bar, uint64_t pol) {
  asm volatile(ELECT "@p " TMA2D ".L2::cache_hint [%0], [%1, {%3, %4}], [%2], %5;\n}" ::"r"(dst), "l"(m), "r"(bar), "r"(c0), "r"(c1), "l"(pol) : "memory");
}
__device__ __forceinline__ void e_tma3d(uint32_t dst, const CUtensorMap* m, int c1, int c2, uint32_t bar) {
  asm volatile(ELECT "@p " TMA3D " [%0], [%1, {0, %3, %4}], [%2];\n}" ::"r"(dst), "l"(m), "r"(bar), "r"(c1), "r"(c2) : "memory");
}
__device__ __forceinline__ void e_store2d(const CUtensorMap* m, int c0, int c1, uint32_t src) {
  asm volatile(ELECT "@p cp.async.bulk.tensor.2d.global.shared::cta.bulk_group [%0, {%2, %3}], [%1];\n}" ::"l"(m), "r"(src), "r"(c0), "r"(c1) : "memory");
}
__device__ __forceinline__ void e_tma3d_ef(uint32_t dst, const CUtensorMap* m, int c0, int c1, uint32_t bar, uint64_t pol) {
  asm volatile(ELECT "@p " TMA3D ".L2::cache_hint [%0], [%1, {%3, %4, 0}], [%2], %5;\n}" ::"r"(dst), "l"(m), "r"(bar), "r"(c0), "r"(c1), "l"(pol) : "memory");
}
__device__ __forceinline__ void e_load(uint32_t dst, const void* src, uint32_t n, uint32_t bar) {
  asm volatile(ELECT "@p cp.async.bulk.shared::cluster.global.mbarrier::complete_tx::bytes [%0], [%1], %2, [%3];\n}" ::"r"(dst), "l"(src), "r"(n), "r"(bar) : "memory");
}
__device__ __forceinline__ void e_pfmap(const CUtensorMap* m) { asm volatile(ELECT "@p prefetch.tensormap [%0];\n}" ::"l"(m) : "memory"); }
__device__ __forceinline__ void bulk_wait_read() { asm volatile("cp.async.bulk.commit_group;\ncp.async.bulk.wait_group.read 0;" ::: "memory"); }
__device__ __forceinline__ void e_signal(int word, int bit) {
  asm volatile(ELECT "@p red.relaxed.gpu.global.xor.b32 [%0], %1;\n}" ::"l"(g_sig + word * 32), "r"(1u << bit) : "memory");
}
__device__ __forceinline__ void await(int word, uint32_t mask, uint32_t ep) {
  uint32_t f[1];
  poll1f(f, g_sig + word * 32, 0u - (ep & 1u), mask);
}

__device__ __forceinline__ void mbar_arrive(uint32_t b) { asm volatile("mbarrier.arrive.shared::cta.b64 _, [%0];" ::"r"(b) : "memory"); }
__device__ __forceinline__ void mbar_wait(uint32_t b, uint32_t ph) {
  asm volatile("{\n.reg .pred p, q;\n.reg .u32 c;\nmov.u32 c, 0;\nLW:\nmbarrier.try_wait.parity.shared::cta.b64 p, [%0], %1;\n@p bra LD;\n"
               "add.u32 c, c, 1;\nsetp.lt.u32 q, c, 100000;\n@q bra LW;\ntrap;\nLD:\n}" ::"r"(b), "r"(ph) : "memory");
}
#define WAIT01 "{\n.reg .pred p, q;\n.reg .u32 c;\nmov.u32 c, 0;\nLW:\nmbarrier.try_wait.parity.shared::cta.b64 p, [%0], %1;\n@p bra LD;\n" \
               "add.u32 c, c, 1;\nsetp.lt.u32 q, c, 100000;\n@q bra LW;\ntrap;\nLD:\nelect.sync _|p, 0xffffffff;\n"
__device__ __forceinline__ void refill_wx(uint32_t eb, uint32_t ph, uint32_t fb, uint32_t bytes, uint32_t dw, const CUtensorMap* mw, int k0, int c,
                                          uint32_t dx, const CUtensorMap* mx, int row, uint32_t xb) {
  asm volatile(WAIT01 "@p " TMA3D " [%4], [%5, {0, %6, %7}], [%2];\n@p " TMA2D " [%8], [%9, {%6, %10}], [%11];\n"
               "@p mbarrier.arrive.expect_tx.shared::cta.b64 _, [%2], %3;\n}"
               ::"r"(eb), "r"(ph), "r"(fb), "r"(bytes), "r"(dw), "l"(mw), "r"(k0), "r"(c), "r"(dx), "l"(mx), "r"(row), "r"(xb) : "memory");
}
__device__ __forceinline__ void refill_w(uint32_t eb, uint32_t ph, uint32_t fb, uint32_t bytes, uint32_t dw, const CUtensorMap* mw, int k0, int c) {
  asm volatile(WAIT01 "@p " TMA3D " [%4], [%5, {0, %6, %7}], [%2];\n@p mbarrier.arrive.expect_tx.shared::cta.b64 _, [%2], %3;\n}"
               ::"r"(eb), "r"(ph), "r"(fb), "r"(bytes), "r"(dw), "l"(mw), "r"(k0), "r"(c) : "memory");
}
__device__ __forceinline__ void refill_x(uint32_t eb, uint32_t ph, uint32_t fb, uint32_t dx, const CUtensorMap* mx, int k0, int row) {
  asm volatile(WAIT01 "@p " TMA2D " [%3], [%4, {%5, %6}], [%2];\n}" ::"r"(eb), "r"(ph), "r"(fb), "r"(dx), "l"(mx), "r"(k0), "r"(row) : "memory");
}
__device__ __forceinline__ void refill_g(uint32_t eb, uint32_t ph, uint32_t fb, uint32_t dw, const CUtensorMap* mw, int c0, int k0) {
  asm volatile(WAIT01 "@p " TMA3D ".L2::cache_hint [%3], [%4, {%5, %6, 0}], [%2], %7;\n@p mbarrier.arrive.expect_tx.shared::cta.b64 _, [%2], 8192;\n}"
               ::"r"(eb), "r"(ph), "r"(fb), "r"(dw), "l"(mw), "r"(c0), "r"(k0), "l"(EVICT_FIRST) : "memory");
}
__device__ __forceinline__ void nb_sync(int id, int n) { asm volatile("bar.sync %0, %1;" ::"r"(id), "r"(n) : "memory"); }
__device__ __forceinline__ void nb_arrive(int id, int n) { asm volatile("bar.arrive %0, %1;" ::"r"(id), "r"(n) : "memory"); }
__device__ __forceinline__ void wg_fence() { asm volatile("wgmma.fence.sync.aligned;" ::: "memory"); }
__device__ __forceinline__ void wg_commit() { asm volatile("wgmma.commit_group.sync.aligned;" ::: "memory"); }
template <int N> __device__ __forceinline__ void wg_wait() { asm volatile("wgmma.wait_group.sync.aligned %0;" ::"n"(N) : "memory"); }
template <int N> __device__ __forceinline__ void reg_fence(float (&a)[N]) {
#pragma unroll
  for (int i = 0; i < N; i++) asm volatile("" : "+f"(a[i])::"memory");
}
template <int N> __device__ __forceinline__ void reg_zero(float (&a)[N]) {
#pragma unroll
  for (int i = 0; i < N; i++) a[i] = 0.f;
}
__device__ __forceinline__ constexpr uint64_t mkdesc(uint32_t addr, uint32_t lbo, uint32_t sbo, uint32_t swz) {
  return (uint64_t)(addr >> 4) | ((uint64_t)(lbo >> 4) << 16) | ((uint64_t)(sbo >> 4) << 32) | ((uint64_t)swz << 62);
}
__device__ __forceinline__ void fence_async_smem() { asm volatile("fence.proxy.async.shared::cta;" ::: "memory"); }
__device__ __forceinline__ void st_relaxed(uint32_t* p, uint32_t v) { asm volatile("st.relaxed.gpu.global.u32 [%0], %1;" ::"l"(p), "r"(v) : "memory"); }
__device__ __forceinline__ uint32_t ld_relaxed(const uint32_t* p) { uint32_t v; asm volatile("ld.relaxed.gpu.global.u32 %0, [%1];" : "=r"(v) : "l"(p) : "memory"); return v; }
__device__ __forceinline__ void st_unit(uint4* p, uint32_t a, uint32_t b, uint32_t c, uint32_t d, uint32_t par) {
  asm volatile("{\n.reg .b64 x, y;\n.reg .b128 z;\nmov.b64 x, {%1,%2};\nmov.b64 y, {%3,%4};\nmov.b128 z, {x, y};\nst.relaxed.gpu.global.b128 [%0], z;\n}"
               ::"l"(p), "r"((a & ~1u) | par), "r"(b), "r"(c), "r"(d) : "memory");
}
__device__ __forceinline__ uint4 lds128(uint32_t a) { uint4 v; asm volatile("ld.shared.v4.u32 {%0,%1,%2,%3}, [%4];" : "=r"(v.x), "=r"(v.y), "=r"(v.z), "=r"(v.w) : "r"(a)); return v; }
__device__ __forceinline__ float4 lds128f(uint32_t a) { float4 v; asm volatile("ld.shared.v4.f32 {%0,%1,%2,%3}, [%4];" : "=f"(v.x), "=f"(v.y), "=f"(v.z), "=f"(v.w) : "r"(a)); return v; }
__device__ __forceinline__ float4 lds128v(uint32_t a) { float4 v; asm volatile("ld.volatile.shared.v4.f32 {%0,%1,%2,%3}, [%4];" : "=f"(v.x), "=f"(v.y), "=f"(v.z), "=f"(v.w) : "r"(a) : "memory"); return v; }
__device__ __forceinline__ float lds32v(uint32_t a) { float v; asm volatile("ld.volatile.shared.f32 %0, [%1];" : "=f"(v) : "r"(a) : "memory"); return v; }
__device__ __forceinline__ float2 lds64f(uint32_t a) { float2 v; asm volatile("ld.shared.v2.f32 {%0,%1}, [%2];" : "=f"(v.x), "=f"(v.y) : "r"(a)); return v; }
__device__ __forceinline__ uint32_t lds32(uint32_t a) { uint32_t v; asm volatile("ld.shared.u32 %0, [%1];" : "=r"(v) : "r"(a)); return v; }
__device__ __forceinline__ void sts128(uint32_t a, uint32_t x, uint32_t y, uint32_t z, uint32_t w) { asm volatile("st.shared.v4.u32 [%0], {%1,%2,%3,%4};" ::"r"(a), "r"(x), "r"(y), "r"(z), "r"(w) : "memory"); }
__device__ __forceinline__ void sts128f(uint32_t a, float x, float y, float z, float w) { asm volatile("st.shared.v4.f32 [%0], {%1,%2,%3,%4};" ::"r"(a), "f"(x), "f"(y), "f"(z), "f"(w) : "memory"); }
__device__ __forceinline__ void sts64(uint32_t a, uint32_t x, uint32_t y) { asm volatile("st.shared.v2.u32 [%0], {%1,%2};" ::"r"(a), "r"(x), "r"(y) : "memory"); }
__device__ __forceinline__ void sts32(uint32_t a, uint32_t x) { asm volatile("st.shared.u32 [%0], %1;" ::"r"(a), "r"(x) : "memory"); }
__device__ __forceinline__ void stsm4(uint32_t a, uint32_t r0, uint32_t r1, uint32_t r2, uint32_t r3) {
  asm volatile("stmatrix.sync.aligned.m8n8.x4.shared.b16 [%0], {%1,%2,%3,%4};" ::"r"(a), "r"(r0), "r"(r1), "r"(r2), "r"(r3) : "memory");
}
__device__ __forceinline__ uint4 ldsm4(uint32_t a) {
  uint4 v; asm volatile("ldmatrix.sync.aligned.m8n8.x4.shared.b16 {%0,%1,%2,%3}, [%4];" : "=r"(v.x), "=r"(v.y), "=r"(v.z), "=r"(v.w) : "r"(a) : "memory"); return v;
}
__device__ __forceinline__ uint32_t pack(float lo, float hi) { uint32_t r; asm("cvt.rn.bf16x2.f32 %0, %1, %2;" : "=r"(r) : "f"(hi), "f"(lo)); return r; }
__device__ __forceinline__ float bf_lo(uint32_t w) { return __uint_as_float(w << 16); }
__device__ __forceinline__ float bf_hi(uint32_t w) { return __uint_as_float(w & 0xffff0000u); }
__device__ __forceinline__ float bf_round(float x) { return bf_lo(pack(x, x)); }
__device__ __forceinline__ float ex2(float x) { float v; asm("ex2.approx.ftz.f32 %0, %1;" : "=f"(v) : "f"(x)); return v; }
__device__ __forceinline__ float rcp(float x) { float v; asm("rcp.approx.ftz.f32 %0, %1;" : "=f"(v) : "f"(x)); return v; }
__device__ __forceinline__ float addsat(float a, float b) { float v; asm("add.sat.f32 %0, %1, %2;" : "=f"(v) : "f"(a), "f"(b)); return v; }
__device__ __forceinline__ float phi2(float a) { return fmaf(fmaxf(a, 0.f), LN2, addsat(ex2(a), 1e-6f)); }
__device__ __forceinline__ uint32_t phi_pack(float u0, float u1, float rl, uint32_t sd2) {
  uint32_t r;
  asm("{\n.reg .b32 m;\ncvt.rn.relu.bf16x2.f32 m, %2, %1;\nfma.rn.bf16x2 %0, %3, %4, m;\n}"
      : "=r"(r) : "f"(u0), "f"(u1), "r"(pack(addsat(ex2(u0 * rl), 1e-6f), addsat(ex2(u1 * rl), 1e-6f))), "r"(sd2));
  return r;
}
__device__ __forceinline__ uint32_t sub2(uint32_t a, uint32_t b) { uint32_t r; asm("sub.rn.bf16x2 %0, %1, %2;" : "=r"(r) : "r"(a), "r"(b)); return r; }
__device__ __forceinline__ float key_score(uint32_t key) { uint32_t u = key >> 16; u = (u & 0x8000u) ? (u & 0x7fffu) : (~u & 0xffffu); return __uint_as_float(u << 16); }
__device__ __forceinline__ int key_token(uint32_t key) { return 2047 - (int)((key >> 5) & 2047u); }
__device__ __forceinline__ uint32_t bsel(uint32_t a, uint32_t b, uint32_t m) { uint32_t r; asm("lop3.b32 %0, %1, %2, %3, 0xd8;" : "=r"(r) : "r"(a), "r"(b), "r"(m)); return r; }
__device__ __forceinline__ uint32_t prmt(uint32_t a, uint32_t b, uint32_t c) { uint32_t r; asm("prmt.b32 %0, %1, %2, %3;" : "=r"(r) : "r"(a), "r"(b), "r"(c)); return r; }
__device__ __forceinline__ uint32_t tagf(float v, uint32_t par) { return (__float_as_uint(v) & ~1u) | par; }
__device__ __forceinline__ float xred(float a, float b, bool up, int o) { return (up ? b : a) + __shfl_xor_sync(0xffffffffu, up ? a : b, o); }

#define STAMP(id)
#define STAMP_IF(c, id)
#define STAMP2(i)
#define LITE 1
#define LITE_MASK 0ull

template <bool TRANS, int NK = 16>
__device__ __forceinline__ void mainloop(float (&a0)[64], float (&a1)[64], int s, int ph, int handoff, int xpair, bool leader) {
  uint32_t prev = 0;
#pragma unroll 1
  for (int kt = 0; kt < NK; kt++) {
    const bool xr = !TRANS && (kt >> 1) == xpair;
    mbar_wait(B_FULL + 8 * s, ph);
    const uint64_t dw = mkdesc(RING, 8192, 1024, 1) + s * (SLOT >> 4), dx = mkdesc(0, 16, 1024, 1) + (xr ? (STG >> 4) + (kt & 1) * 1024 : ((RING + 16384) >> 4) + s * (SLOT >> 4));
    if (xr) mbar_wait(B_XRES + 8 * (kt & 1), 0);
    wg_fence();
#pragma unroll
    for (int j = 0; j < 4; j++) {
      if (TRANS) {
        wgmma_n128_ss<1, 0>(a0, dw + j * 128, dx + j * 2, 1);
        wgmma_n128_ss<1, 0>(a1, dw + j * 128 + 512, dx + j * 2, 1);
      } else {
        wgmma_n128_ss<0, 1>(a0, dx + j * 2, dw + j * 128, 1);
        wgmma_n128_ss<0, 1>(a1, dx + j * 2 + 512, dw + j * 128, 1);
      }
    }
    wg_commit();
    if (handoff && kt == 15) nb_arrive(handoff, 256);
    wg_wait<1>();
    if (prev && leader) mbar_arrive(prev);
    prev = B_EMPTY + 8 * s;
    if (++s == NST) { s = 0; ph ^= 1; }
  }
  if (NK < 16) return;
  wg_wait<0>();
  if (leader) mbar_arrive(prev);
  reg_fence(a0);
  reg_fence(a1);
}

__device__ __forceinline__ int out_kblock(int r, int tn) {
  const int q = r - 2, half = q >= 7, pi = q - 7 * half;
  return r < 2 ? 2 * tn + r : 2 * ((pi + (pi >= (tn & 3))) ^ (tn & 4)) + half;
}

struct Params {
  const char *x, *w_r, *wg, *wu, *wd;
  CUtensorMap m_wqkv, m_x, m_xs, m_o, m_os, m_wo, m_gu, m_down, m_out;
};

template <bool BY_SMID>
__global__ void __launch_bounds__(512, 1) fused_kernel(const __grid_constant__ Params mp) {
  extern __shared__ __align__(1024) uint8_t smem_raw[];
#define CK(i)
  CK(0);
  const int tid = threadIdx.x, lane = tid & 31;
  const int w = __shfl_sync(0xffffffffu, tid >> 5, 0);
  int bid = blockIdx.x;
  if (BY_SMID) {
    uint32_t sm;
    asm volatile("mov.u32 %0, %%smid;" : "=r"(sm));
    const uint32_t p = sm >> 1, q = ((p - 32) * 37) >> 8;
    const uint32_t gpc = p < 32 ? p & 7 : p < 60 ? p - 31 - 7 * q : 0, tpc = p < 32 ? p >> 3 : p < 60 ? 4 + q : p - 58;
    bid = (p >> 1) == 30 ? 128 + ((0x9cu >> (2 * (sm & 3))) & 3) : ((GPCMAP >> (4 * gpc)) & 7) * 16 + tpc * 2 + (sm & 1);
  }
  const int tn = (bid & 3) + 4 * (bid >> 6), tm = (bid >> 2) & 15;

  CK(1);
  if (w == 0) {
#pragma unroll 1
    for (int s = 0; s < NST; s++) {
      asm volatile(ELECT "@p mbarrier.init.shared::cta.b64 [%0], 1;\n}" ::"r"(B_FULL + 8 * s) : "memory");
      if (bid < 128) {
        e_expect(B_FULL + 8 * s, 32768);
        e_tma2d(RING + s * SLOT + 16384, &mp.m_x, s * 64, tm * 128, B_FULL + 8 * s);
        e_tma3d(RING + s * SLOT, &mp.m_wqkv, s * 64, 16 + 2 * tn, B_FULL + 8 * s);
      }
      if (s == 0) CK(2);
    }
  }
  if (w == 1) e_pfmap(&mp.m_wqkv);
  if (w == 2) e_pfmap(&mp.m_xs);
  if (w >= 4) {
#pragma unroll 1
    for (uint32_t b = MISC + 8 * (w + 1); b < MISC + 8 * NBAR; b += 96)
      asm volatile(ELECT "@p mbarrier.init.shared::cta.b64 [%0], %1;\n}" ::"r"(b), "r"(b == B_CSDN ? 4 : 1) : "memory");
    if (w == 15) sts32(S_NCAND, 0);
  }
  CK(3);
  asm volatile("fence.mbarrier_init.release.cluster;" ::: "memory");
  __syncthreads();

  if (bid >= 128) {
    const int h0 = bid == 128 ? 14 : bid - 129, hs = bid == 128 ? 1 : 3, h1 = bid == 128 ? 16 : 14;
    if (w == 12) {
      int s = 0, ph = 1;
#pragma unroll 1
      for (int h = h0; h < h1; h += hs) {
        const int c = 2 * h + (h & 8) * 2;
        if (h == 14) mbar_wait(B_SEL, 0);
#pragma unroll 1
        for (int kt = 0; kt < 16; kt += 2) {
          mbar_wait(B_EMPTY + 8 * s, ph);
          e_expect(B_FULL + 8 * s, 32768);
          e_tma3d(RING + s * SLOT, &mp.m_wqkv, kt * 64, c, B_FULL + 8 * s);
          e_tma3d(RING + s * SLOT + 16384, &mp.m_wqkv, kt * 64 + 64, c, B_FULL + 8 * s);
          if (++s == HST) { s = 0; ph ^= 1; }
        }
      }
    } else if (w < 4) {
      const uint32_t par = (ld_relaxed(&g_epoch) + 1) & 1u;
      sts32(S_ONES + tid * 4, 0x3f803f80u);
      fence_async_smem();
      nb_sync(NB_WG0, 128);
      int s = 0, ph = 0;
#pragma unroll 1
      for (int h = h0; h < h1; h += hs) {
        float c[4][4];
#pragma unroll
        for (int q = 0; q < 4; q++) reg_zero(c[q]);
        uint32_t prev = 0;
#pragma unroll 1
        for (int kt = 0; kt < 8; kt++) {
          mbar_wait(B_FULL + 8 * s, ph);
          const uint64_t dw = mkdesc(RING, 8192, 1024, 1) + s * (SLOT >> 4);
          wg_fence();
#pragma unroll
          for (int j = 0; j < 16; j++) wgmma_n8_ss<1, 0>(c[j & 3], dw + (j & 3) * 512 + (j >> 2) * 128, mkdesc(S_ONES, 128, 128, 0), 1);
          wg_commit();
          wg_wait<1>();
          if (prev && tid == 0) mbar_arrive(prev);
          prev = B_EMPTY + 8 * s;
          if (++s == HST) { s = 0; ph ^= 1; }
        }
        wg_wait<0>();
        if (tid == 0) mbar_arrive(prev);
#pragma unroll
        for (int q = 0; q < 4; q++) reg_fence(c[q]);
        const bool u2 = lane & 2, u1 = lane & 1;
        const float lo = u2 ? c[1][0] + c[3][0] : c[0][0] + c[2][0], hi = u2 ? c[1][2] + c[3][2] : c[0][2] + c[2][2];
        st_relaxed(g_csum + h * 128 + (lane & 2) * 32 + w * 16 + (lane & 1) * 8 + (lane >> 2), tagf(u1 ? hi : lo, par));
        STAMP_IF(tid == 0, h >= 8 ? 6 : 30);
      }
    } else if (w < 12 && bid == 128) {
      const int t = tid - 128, j = w - 4;
      const uint32_t ep = ld_relaxed(&g_epoch) + 1;
      uint32_t kk[16];
      poll_keys(kk, g_keys + t * 2, ep, 31u);
      STAMP_IF(t == 0, 42);
      const uint32_t m = __reduce_max_sync(0xffffffffu, max(max(max(kk[0], kk[2]), max(kk[4], kk[6])), max(max(kk[8], kk[10]), max(kk[12], kk[14]))));
      if (lane == 0) sts32(S_WMAX + j * 4, m);
      nb_sync(NB_WG1, 256);
      const uint32_t T = __reduce_min_sync(0xffffffffu, lds32(S_WMAX + (lane & 7) * 4));
      uint32_t cnt = 0;
#pragma unroll
      for (int i = 0; i < 8; i++) cnt += kk[2 * i] >= T;
      if (cnt) {
        uint32_t pos;
        asm volatile("atom.shared.add.u32 %0, [%1], %2;" : "=r"(pos) : "r"(S_NCAND), "r"(cnt * 8) : "memory");
#pragma unroll
        for (int i = 0; i < 8; i++)
          if (kk[2 * i] >= T) { sts64(AUX + pos, kk[2 * i], kk[2 * i + 1]); pos += 8; }
      }
      nb_sync(NB_WG1, 256);
      const uint32_t n8 = lds32(S_NCAND);
#pragma unroll 1
      for (uint32_t i0 = 0; i0 < n8; i0 += 256) {
        const uint32_t i = i0 + (t & ~7);
        const float2 c = lds64f(AUX + i);
        uint32_t rank = 0;
#pragma unroll 4
        for (uint32_t q = (t & 7) * 8; q < n8; q += 64) rank += lds32(AUX + q) > __float_as_uint(c.x);
        rank += __shfl_xor_sync(0xffffffffu, rank, 1);
        rank += __shfl_xor_sync(0xffffffffu, rank, 2);
        rank += __shfl_xor_sync(0xffffffffu, rank, 4);
        if (rank < 8 && i < n8) sts64(S_SEL + rank * 8, __float_as_uint(c.x), __float_as_uint(c.y));
      }
      nb_sync(NB_WG1, 256);
      if (j < 4) {
        const uint4 v = lds128(S_SEL + (lane & 3) * 16);
        asm volatile("{\n.reg .b64 x, y;\nmov.b64 x, {%1,%2};\nmov.b64 y, {%3,%4};\nst.relaxed.gpu.global.v2.b64 [%0], {x, y};\n}"
                     ::"l"(g_sel + (t >> 2) * 16 + (lane & 3) * 2), "r"(v.x), "r"(v.y), "r"(v.z), "r"(v.w) : "memory");
      } else if (j == 4) {
        fence_async_smem();
        e_arrive(B_SEL);
      }
      STAMP_IF(t == 0, 45);
    }
  } else if (w >= 12) {
    asm volatile("setmaxnreg.dec.sync.aligned.u32 32;");
    if (w == 12) {
      int s = 0, ph = 0;
#pragma unroll 1
      for (int it = NST; it < 48; it++) {
        const int c = (it < 32 ? (it & 16) + 16 : 0) + 2 * tn;
        const int k0 = ((it + (it >= 32 && tn < 4 ? 8 : 0)) & 15) * 64;
        const bool xr = (it >> 1) == 20 + (tn & 3);
        if (xr) { mbar_wait(B_SFREE, 0); e_expect(B_XRES + 8 * (it & 1), 16384); }
        refill_wx(B_EMPTY + 8 * s, ph, B_FULL + 8 * s, xr ? 16384 : 32768, RING + s * SLOT, &mp.m_wqkv, k0, c,
                  xr ? STG + (it & 1) * 16384 : RING + s * SLOT + 16384, &mp.m_x, tm * 128, xr ? B_XRES + 8 * (it & 1) : B_FULL + 8 * s);
        if (it >= NST) STAMP2(it - NST);
        if (++s == NST) { s = 0; ph ^= 1; }
      }
#pragma unroll 1
      for (int r = 0; r < 16; r++) {
        const int kb = out_kblock(r, tn);
        refill_w(B_EMPTY + 8 * s, ph, B_FULL + 8 * s, r < 2 ? 16384 : 32768, RING + s * SLOT, &mp.m_wo, kb * 64, 2 * tn);
        if (r < 2 || r == 4) {
          const uint32_t bar = B_DR + (r < 2 ? 16 : 8);
          const int k0 = (bid >> 4) * 448 + 128 + min(r, 2) * 128;
          if (r != 1) e_expect(bar, r ? 8192 : 32768);
          e_tma2d_ef(RING + s * SLOT + 16384, &mp.m_down, (bid & 15) * 64, k0, bar, EVICT_FIRST);
          if (r < 2) e_tma2d_ef(RING + s * SLOT + 24576, &mp.m_down, (bid & 15) * 64, k0 + 64, bar, EVICT_FIRST);
        }
        STAMP2(r + 48 - NST);
        if (++s == NST) { s = 0; ph ^= 1; }
      }
    } else if (w == 13) {
      mbar_wait(B_FULL, 0);
#pragma unroll 1
      for (int c = 0; c < 4; c++) {
        if (c >= XS_FLY) mbar_wait(B_XS + 8 * (c - XS_FLY), 0);
        if (c == (tm >> 2)) {
          e_expect(B_WK, 16384);
          e_tma3d(FR, &mp.m_wqkv, tm * 64, 16 + 2 * tn, B_WK);
        }
        e_expect(B_XS + 8 * c, 8192);
        e_tma2d(STG + c * 8192, &mp.m_xs, c * 256, tm * 128 + tn * 16, B_XS + 8 * c);
      }
      {
        const char* pd = mp.wd + (bid & 15) * 128 + ((bid >> 4) * 448 + lane) * 2048;
        mbar_wait(B_XS + 24, 0);
        __nanosleep(PF_WAIT);
#pragma unroll 1
        for (int i = 0; i < 14; i++, pd += 65536) {
          asm volatile("prefetch.global.L2 [%0];" ::"l"(pd));
          __nanosleep(PF_GAP);
        }
      }
      nb_sync(NB_Z, 160);
      const uint32_t ep = lds32(S_EPOCH);
      {
        float z[4] = {0.f, 0.f, 0.f, 0.f};
        e_signal(H_Z + tn, tm);
        await(H_Z + tn, 0xffffu, ep);
#pragma unroll 1
        for (int i = 0; i < 4; i++) {
          uint32_t p[16];
          poll_z(p, g_z + i * 4096 + tn * 128 + lane * 4, ep, 1u);
#pragma unroll
          for (int q = 0; q < 4; q++) z[q] += (__uint_as_float(p[q]) + __uint_as_float(p[4 + q])) + (__uint_as_float(p[8 + q]) + __uint_as_float(p[12 + q]));
        }
        const uint32_t z01 = pack(z[0], z[1]), z23 = pack(z[2], z[3]);
        if (bid < 112) mbar_wait(B_PFREE, 0);
#pragma unroll
        for (int n = 0; n < 8; n++) sts64(KVB + (lane >> 4) * 5120 + n * 128 + ((((lane >> 1) & 7) ^ n) << 4) + (lane & 1) * 8, z01, z23);
        fence_async_smem();
        nb_arrive(NB_KVB, 320);
        STAMP_IF(lane == 0, 46);
      }
      nb_sync(NB_Q0, 192);
      e_store2d(&mp.m_os, tn * 128, tm * 128, STG);
      nb_sync(NB_OWN0, 160);
      e_store2d(&mp.m_os, tn * 128, tm * 128 + 64, STG + 8192);
      if (!SIG_EARLY) bulk_wait_read(); else if (SIG_EARLY > 1) __nanosleep(SIG_EARLY);
      e_signal(H_O + tm, 2 * tn);
      STAMP_IF(lane == 0, 4);
      nb_sync(NB_H1, 160);
      e_store2d(&mp.m_os, tn * 128 + 64, tm * 128, STG + 16384);
      e_store2d(&mp.m_os, tn * 128 + 64, tm * 128 + 64, STG + 24576);
      bulk_wait_read();
      e_signal(H_O + tm, 2 * tn + 1);
      STAMP_IF(lane == 0, 5);
      nb_arrive(NB_ST, 288);
    } else if (w == 14) {
      e_pfmap(&mp.m_gu); e_pfmap(&mp.m_o); e_pfmap(&mp.m_os); e_pfmap(&mp.m_wo); e_pfmap(&mp.m_down); e_pfmap(&mp.m_out);
      const uint32_t ep = ld_relaxed(&g_epoch) + 1;
      nb_sync(NB_FDONE, 416);
      {
        uint32_t c[4];
        poll_quad(c, g_csum + tn * 128 + lane * 4, ep, 1u);
        sts128(S_CSQ + lane * 16, c[0], c[1], c[2], c[3]);
        nb_arrive(NB_CSQ, 160);
        poll_quad(c, g_csum + 1024 + tn * 128 + lane * 4, ep, 1u);
        sts128(S_CSV + lane * 16, c[0], c[1], c[2], c[3]);
        __syncwarp();
        e_arrive(B_CSV);
      }
      {
        mbar_wait(B_WK, 1);
        if (KV_SPEC) __nanosleep(KV_SPEC); else await(H_KV + tn, 0xffffu, ep);
        STAMP_IF(lane == 0, 7);
        if (bid < 112) mbar_wait(B_PFREE, 0);
        STAMP_IF(lane == 0, 23);
        uint32_t bad, ph = 0;
        do {
          e_expect(B_KVL, 8192);
          e_load(KVB + 1024, g_kv + tn * 512, 4096, B_KVL);
          e_load(KVB + 6144, g_kv + tn * 512 + 256, 4096, B_KVL);
          mbar_wait(B_KVL, ph & 1);
          bad = 0;
#pragma unroll
          for (int i = 0; i < 16; i++) bad |= __float_as_uint(lds32v(KVB + 1024 + (i & 8) * 128 + i * 512 + lane * 16)) ^ ep;
          bad = __any_sync(0xffffffffu, bad & 1u);
          if (bad) fence_async_smem();
        } while (bad && ++ph < 100000);
        nb_arrive(NB_KVB, 320);
        STAMP_IF(lane == 0, 24);
      }
      nb_sync(NB_Q0, 192);
      uint32_t ready = 0;
      int s = 0, ph = 1;
#pragma unroll 1
      for (int r = 2; r < 16; r++) {
        const int kb = out_kblock(r, tn);
        if (!((ready >> kb) & 1)) {
          uint32_t f[1];
          poll0(f, g_sig + (H_O + tm) * 32, 0u - (ep & 1u), 1u << kb);
          ready = f[0] ^ ((ep & 1u) - 1u);
        }
        if (r == 4) mbar_wait(B_DND, 0);
        refill_x(B_EMPTY + 8 * s, ph, B_FULL + 8 * s, RING + s * SLOT + 16384, &mp.m_o, kb * 64, tm * 128);
        STAMP_IF(lane == 0 && r == 2, 2);
        STAMP_IF(lane == 0 && r == 9, 3);
        if (++s == NST) { s = 0; ph ^= 1; }
      }
    } else {
      uint32_t nsm = 132;
      if (BY_SMID) asm volatile("mov.u32 %0, %%nsmid;" : "=r"(nsm));
      asm volatile("{\n.reg .pred q;\nsetp.eq.u32 q, %0, 1156;\n@q bra LOK;\ntrap;\nLOK:\n}" ::"r"((uint32_t)__cvta_generic_to_shared(smem_raw) + nsm));
      const uint32_t ep = ld_relaxed(&g_epoch) + 1;
      mbar_wait(B_CSDN, 0);
#pragma unroll 1
      for (int n = 0; n < 3 && bid < 112; n++) {
        __nanosleep(FFN_GAP);
        e_expect(B_FR + 8 * n, 8192);
        e_tma3d_ef(GR + n * 8192, &mp.m_gu, bid * 32, n * 64, B_FR + 8 * n, EVICT_FIRST);
      }
      if (bid < 112) {
        int s = 0, ph = 0;
#pragma unroll 1
        for (int n = 3; n < 16; n++) {
          refill_g(B_FE + 8 * s, ph, B_FR + 8 * s, GR + s * 8192, &mp.m_gu, bid * 32, n * 64);
          STAMP2(64 + n);
          if (++s == 3) { s = 0; ph ^= 1; }
        }
      }
      if (bid < 112) mbar_wait(B_FE, 1);
      e_expect(B_DR, 16384);
      e_tma2d_ef(AUX, &mp.m_down, (bid & 15) * 64, (bid >> 4) * 448, B_DR, EVICT_FIRST);
      e_tma2d_ef(AUX + 8192, &mp.m_down, (bid & 15) * 64, (bid >> 4) * 448 + 64, B_DR, EVICT_FIRST);
      {
        mbar_wait(B_WK, 1);
        if (bid < 112) mbar_wait(B_HGO, 0);
        await(H_H + (bid >> 4), 0x3fffu, ep);
        uint32_t bad, ph = 0;
        do {
          e_expect(B_HL, 7168);
          e_load(HOP, g_h + (bid >> 4) * 448, 6144, B_HL);
          e_load(S_CSK, g_h + (bid >> 4) * 448 + 384, 1024, B_HL);
          mbar_wait(B_HL, ph & 1);
          bad = 0;
#pragma unroll
          for (int i = 0; i < 14; i++) bad |= __float_as_uint(lds32v((i < 12 ? HOP : S_CSK - 6144) + i * 512 + lane * 16)) ^ ep;
          bad = __any_sync(0xffffffffu, bad & 1u);
          if (bad) fence_async_smem();
        } while (bad && ++ph < 100000);
        e_arrive(B_HOK);
      }
    }
  } else if (w >= 8) {
    asm volatile("setmaxnreg.dec.sync.aligned.u32 56;");
    const int t = tid - 256, ww = w - 8;
    const uint32_t ep = ld_relaxed(&g_epoch) + 1, par = ep & 1u;
    {
      const int r0 = (lane >> 3) + (lane & 4);
      const uint32_t a = FR + (ww >> 1) * 8192 + r0 * 128 + ((((ww & 1) * 4 + (lane & 3)) ^ r0) << 4);
      float c[8];
      reg_zero(c);
      mbar_wait(B_WK, 0);
#pragma unroll 2
      for (int i = 0; i < 8; i++) {
        const uint4 v = lds128(a + i * 1024);
        c[0] += bf_lo(v.x); c[1] += bf_hi(v.x); c[2] += bf_lo(v.y); c[3] += bf_hi(v.y);
        c[4] += bf_lo(v.z); c[5] += bf_hi(v.z); c[6] += bf_lo(v.w); c[7] += bf_hi(v.w);
      }
      const bool u16 = lane & 16, u8 = lane & 8, u4 = lane & 4;
      const float d0 = xred(c[0], c[4], u16, 16), d1 = xred(c[1], c[5], u16, 16), d2 = xred(c[2], c[6], u16, 16), d3 = xred(c[3], c[7], u16, 16);
      fence_async_smem();
      e_arrive(B_CSDN);
      const float sum = xred(xred(d0, d2, u8, 8), xred(d1, d3, u8, 8), u4, 4);
      st_relaxed(g_csum + (2 + tm) * 1024 + tn * 128 + ww * 32 + (lane & 3) * 8 + (lane >> 2), tagf(sum, par));
      STAMP_IF(t == 0, 8);
      nb_sync(NB_WG2, 128);
      if (ww == 0) { e_signal(H_CS + tn, tm); await(H_CS + tn, 0xffffu, ep); }
      nb_sync(NB_WG2, 128);
      uint32_t p[16];
      poll16(p, g_csum + 2048 + tn * 128 + t, par, 1u);
      float tot = 0.f;
#pragma unroll
      for (int i = 0; i < 16; i += 4) tot += (__uint_as_float(p[i]) + __uint_as_float(p[i + 1])) + (__uint_as_float(p[i + 2]) + __uint_as_float(p[i + 3]));
      sts32(S_CSK + t * 4, __float_as_uint(tot));
      nb_arrive(NB_FDONE, 416);
      STAMP_IF(t == 0, 9);
    }
    const int ks = bid >> 4, nt = bid & 15;
    uint32_t sel[2];
    poll_pair(sel, g_sel + (ks * 4 + ww) * 16 + (t >> 4), ep, 31u);
    if ((t & 15) == 0) sts64(S_SEL + (t >> 4) * 8, sel[0], sel[1]);
    if (bid >= 112) {
      nb_sync(NB_WG2, 128);
      if (t == 0) mbar_arrive(B_SEL);
    } else {
      const uint4* xs = reinterpret_cast<const uint4*>(mp.x + key_token(sel[0]) * 2048) + (t & 15);
      const uint32_t xd = AUX + (t & 8) * 128 + (t >> 4) * 128 + (((t ^ (t >> 4)) & 7) << 4), m2 = __byte_perm(sel[1], 0, 0x3232);
      uint4 v[4];
#pragma unroll
      for (int i = 0; i < 4; i++) v[i] = __ldg(xs + i * 16);
      float fg[4];
      reg_zero(fg);
      constexpr uint64_t DA0 = mkdesc(GR, 4096, 512, 2);
      uint64_t da = DA0;
      uint32_t bar = B_FR, ph = 0;
#pragma unroll 1
      for (int b = 0; b < 2; b++) {
        if (b) nb_sync(NB_WG2, 128);
#pragma unroll
        for (int i = 0; i < 4; i++) sts128(xd + i * 2048, sub2(v[i].x, m2), sub2(v[i].y, m2), sub2(v[i].z, m2), sub2(v[i].w, m2));
        fence_async_smem();
        nb_sync(NB_WG2, 128);
        if (!b) {
          if (t == 0) mbar_arrive(B_SEL);
#pragma unroll
          for (int i = 0; i < 4; i++) v[i] = __ldg(xs + 64 + i * 16);
        }
        uint64_t db = mkdesc(AUX, 16, 1024, 1);
#pragma unroll 1
        for (int n = 0; n < 8; n++) {
          mbar_wait(bar, ph);
          wg_fence();
#pragma unroll
          for (int q = 0; q < 4; q++) wgmma_n8_ss<1, 0>(fg, da + q * 64, db + q * 2, 1);
          wg_commit();
          const uint32_t rel = bar + (B_FE - B_FR);
          const bool wrap = bar == B_FR + 16;
          da = wrap ? DA0 : da + 512;
          db += 64;
          bar = wrap ? B_FR : bar + 8;
          ph ^= wrap;
          wg_wait<0>();
          if (t == 0) mbar_arrive(rel);
          if (t == 0 && b && n == 6) mbar_arrive(B_PFREE);
        }
      }
      const uint4 st = lds128(S_SEL + (lane & 3) * 16);
      const float r0 = rcp(bf_lo(st.y)), r1 = rcp(bf_lo(st.w));
      reg_fence(fg);
      const float fa[4] = {fg[0] * r0, fg[1] * r1, fg[2] * r0, fg[3] * r1};
      STAMP_IF(t == 0, 12);
      const bool isup = (ww >> 1) != (mp.wu < mp.wg);
      if (isup) sts128f(HOP + (t & 63) * 16, fa[0], fa[1], fa[2], fa[3]);
      nb_sync(NB_WG2, 128);
      if (!isup) {
        const float4 u = lds128f(HOP + (t & 63) * 16);
        const float uu[4] = {u.x, u.y, u.z, u.w};
        uint32_t hw[2];
#pragma unroll
        for (int i = 0; i < 2; i++)
          hw[i] = pack(fa[2 * i] * rcp(1.f + ex2(-fa[2 * i] * LOG2E)) * uu[2 * i], fa[2 * i + 1] * rcp(1.f + ex2(-fa[2 * i + 1] * LOG2E)) * uu[2 * i + 1]);
        const uint32_t ha = HOP + 1024 + (ww & 1) * 256 + (lane & 15) * 16;
        asm volatile("stmatrix.sync.aligned.m8n8.x2.trans.shared.b16 [%0], {%1,%2};" ::"r"(ha), "r"(hw[0]), "r"(hw[1]) : "memory");
        __syncwarp();
        const int tok = (lane >> 1) & 7, pc = (ww & 1) * 2 + (lane & 1);
        const uint4 hv = lds128(HOP + 1024 + pc * 128 + tok * 16);
        if (lane < 16) st_unit(g_h + bid * 32 + tok * 4 + (pc ^ (tok >> 1)), hv.x, hv.y, hv.z, hv.w, par);
      }
      fence_async_smem();
      nb_sync(NB_WG2, 128);
      if (ww == 0) { e_signal(H_H + bid / 14, bid % 14); e_arrive(B_HGO); }
    }
    mbar_wait(B_HOK, 0);
    STAMP_IF(t == 0, 13);
    float fa[4] = {0.f, 0.f, 0.f, 0.f};
    auto down = [&](uint32_t a, int k0, int nk) {
#pragma unroll
      for (int q = 0; q < nk; q++) wgmma_n8_ss<1, 0>(fa, mkdesc(a + q * 2048, 4096, 1024, 1), mkdesc((k0 < 24 ? HOP : S_CSK - 6144) + ((k0 + q) >> 1) * 512 + (q & 1) * 32, 16, 512, 2), 1);
    };
    mbar_wait(B_DR, 0);
    mbar_wait(B_DR + 16, 0);
    mbar_wait(B_DR + 8, 0);
    wg_fence();
    down(RING + 2 * SLOT + 16384, 24, 4);
    down(RING + 3 * SLOT + 16384, 8, 8);
    down(RING + 4 * SLOT + 16384, 16, 8);
    wg_commit();
    wg_fence();
    down(AUX, 0, 8);
    wg_commit();
    wg_wait<1>();
    if (t == 0) mbar_arrive(B_DND);
    wg_wait<0>();
    reg_fence(fa);
    STAMP_IF(t == 0, 14);
    {
      uint32_t* yp = g_yp + (nt * 8 + ks) * 512 + (lane & 3) * 128 + ww * 16 + (lane >> 2);
#pragma unroll
      for (int i = 0; i < 4; i++) st_relaxed(yp + (i & 1) * 64 + (i >> 1) * 8, tagf(fa[i], par));
    }
    nb_sync(NB_WG2, 128);
    if (ww == 0) e_signal(H_Y + (nt >> 1), (nt & 1) * 8 + ks);
    const uint32_t mykey = lds32(S_SEL + (lane & 7) * 8);
    const uint32_t inmask = __ballot_sync(0xffffffffu, (key_token(mykey) >> 7) == tm) & 0xffu;
    sts128(AUX + t * 16, 0u, 0u, 0u, 0u);
    if (inmask) {
      if (ww == 0) await(H_Y + tn, 0xffffu, ep);
      nb_sync(NB_WG2, 128);
      const float sg = rcp(1.f + ex2(-key_score(mykey) * LOG2E));
#pragma unroll 1
      for (uint32_t mine = __ballot_sync(0xffffffffu, ((inmask >> lane) & 1) && (__popc(inmask & ((1u << lane) - 1)) & 3) == ww); mine; mine &= mine - 1) {
        const int j = __ffs(mine) - 1;
        uint32_t p[32];
        poll8x4(p, g_yp + (tn * 2 + (lane >> 4)) * 4096 + j * 64 + (lane & 15) * 4, par, 1u);
        float y[4];
        const float sj = __shfl_sync(0xffffffffu, sg, j);
#pragma unroll
        for (int i = 0; i < 4; i++)
          y[i] = sj * (((__uint_as_float(p[i]) + __uint_as_float(p[4 + i])) + (__uint_as_float(p[8 + i]) + __uint_as_float(p[12 + i]))) +
                       ((__uint_as_float(p[16 + i]) + __uint_as_float(p[20 + i])) + (__uint_as_float(p[24 + i]) + __uint_as_float(p[28 + i]))));
        asm volatile("st.shared.v2.u32 [%0], {%1,%2};" ::"r"(AUX + (lane >> 4) * 1024 + j * 128 + ((((lane >> 1) & 7) ^ j) << 4) + (lane & 1) * 8),
                     "r"(pack(y[0], y[1])), "r"(pack(y[2], y[3])) : "memory");
      }
    }
    fence_async_smem();
    nb_arrive(NB_ST, 288);
    STAMP_IF(t == 0, 15);
  } else if (w >= 4) {
    asm volatile("setmaxnreg.inc.sync.aligned.u32 208;");
    const int t = tid - 128, ww = w - 4, g = lane >> 2, t4 = lane & 3;
    const bool leader = t == 0;
    const uint32_t ep = ld_relaxed(&g_epoch) + 1, par = ep & 1u;
    {
      const uint4* wp = reinterpret_cast<const uint4*>(mp.w_r) + lane;
      uint4 w0 = __ldg(wp), w1 = __ldg(wp + 32), w2 = __ldg(wp + 64), w3 = __ldg(wp + 96);
      if (leader) sts32(S_EPOCH, ep);
      if (KV_SPEC && t4 == 0) {
        const int grp = (tm & 1) * 2 + ((lane >> 3) & 1), row = ww * 2 + ((lane >> 2) & 1);
        st_unit(g_kv + tn * 512 + ((tm >> 3) * 4 + grp) * 64 + row * 8 + (((tm & 2) * 2 + ((tm >> 1) & 2) + (lane >> 4)) ^ row), 0u, 0u, 0u, 0u, par ^ 1u);
      }
      float s[4] = {0.f, 0.f, 0.f, 0.f}, q[4] = {0.f, 0.f, 0.f, 0.f}, d[4] = {0.f, 0.f, 0.f, 0.f}, wsum = 0.f;
#pragma unroll 1
      for (int c = 0; c < 4; c++) {
        const float wr[8] = {bf_lo(w0.x), bf_hi(w0.x), bf_lo(w0.y), bf_hi(w0.y), bf_lo(w0.z), bf_hi(w0.z), bf_lo(w0.w), bf_hi(w0.w)};
        w0 = w1; w1 = w2; w2 = w3;
        wsum += ((wr[0] + wr[1]) + (wr[2] + wr[3])) + ((wr[4] + wr[5]) + (wr[6] + wr[7]));
        mbar_wait(B_XS + 8 * c, 0);
#pragma unroll
        for (int r = 0; r < 4; r++) {
          const uint4 v = lds128(STG + c * 8192 + (ww * 4 + r) * 512 + lane * 16);
          const uint32_t xw[4] = {v.x, v.y, v.z, v.w};
#pragma unroll
          for (int i = 0; i < 4; i++) {
            const uint32_t dep = __float_as_uint(q[i ? r : (r + 3) & 3]);
            const float lo = __uint_as_float(prmt(xw[i], dep, 0x10ff)), hi = __uint_as_float(prmt(xw[i], dep, 0x32ff));
            s[r] += lo; q[r] = fmaf(lo, lo, q[r]); d[r] = fmaf(lo, wr[2 * i], d[r]);
            s[r] += hi; q[r] = fmaf(hi, hi, q[r]); d[r] = fmaf(hi, wr[2 * i + 1], d[r]);
          }
        }
      }
      STAMP_IF(leader, 16);
      const bool u16 = lane & 16, u8 = lane & 8, u4 = lane & 4, u2 = lane & 2;
      const float s1 = xred(xred(s[0], s[2], u16, 16), xred(s[1], s[3], u16, 16), u8, 8);
      const float q1 = xred(xred(q[0], q[2], u16, 16), xred(q[1], q[3], u16, 16), u8, 8);
      const float d1 = xred(xred(d[0], d[2], u16, 16), xred(d[1], d[3], u16, 16), u8, 8);
      wsum += __shfl_xor_sync(0xffffffffu, wsum, 16);
      wsum += __shfl_xor_sync(0xffffffffu, wsum, 8);
      float tot = xred(xred(s1, d1, u4, 4), xred(q1, wsum, u4, 4), u2, 2);
      tot += __shfl_xor_sync(0xffffffffu, tot, 1);
      const float qq = __shfl_down_sync(0xffffffffu, tot, 2), dd = __shfl_down_sync(0xffffffffu, tot, 4), ws = __shfl_down_sync(0xffffffffu, tot, 6);
      if ((lane & 7) == 0) {
        const float mean = tot * (1.f / 1024.f);
        const float var = fmaxf(fmaf(-mean, mean, qq * (1.f / 1024.f)), 0.f);
        float sd;
        asm("sqrt.approx.ftz.f32 %0, %1;" : "=f"(sd) : "f"(bf_round(bf_round(var) + 1e-5f)));
        const uint32_t ms = pack(sd, mean);
        const int row = tm * 128 + tn * 16 + ww * 4 + (lane >> 3);
        const uint32_t rbits = pack(0.f, fmaf(-bf_hi(ms), ws, dd) * rcp(bf_lo(ms)));
        const uint32_t key = (rbits ^ (((int)rbits >> 31 & 0x7fff0000u) | 0x80000000u)) | ((2047 - row) << 5) | (ep & 31u);
        asm volatile("{\n.reg .b64 x;\nmov.b64 x, {%1,%2};\nst.relaxed.gpu.global.b64 [%0], x;\n}" ::"l"(g_keys + row), "r"(key), "r"(ms) : "memory");
      }
      STAMP_IF(leader, 17);
      __nanosleep(400);
      uint32_t st[2];
      poll_pair(st, g_keys + tm * 128 + t, ep, 31u);
      asm volatile("st.shared.v2.f32 [%0], {%1,%2};" ::"r"(S_KSTAT + t * 8), "f"(bf_hi(st[1])), "f"(rcp(bf_lo(st[1])) * LOG2E) : "memory");
      nb_arrive(NB_FDONE, 416);
      STAMP_IF(leader, 10);
    }
    float a0[64], a1[64];
    reg_zero(a0); reg_zero(a1); reg_fence(a0); reg_fence(a1);
    STAMP_IF(leader, 18);
    nb_sync(NB_KV, 256);
    mainloop<true, 14>(a0, a1, 1, 1, 0, 0, leader);
    {
      auto half = [&](float (&a)[64], int s, int m) {
#pragma unroll
        for (int j = 0; j < 4; j++)
          wgmma_n128_ss<1, 0>(a, mkdesc(RING + s * SLOT + m * 8192 + j * 2048, 8192, 1024, 1), mkdesc(RING + s * SLOT + 16384 + j * 32, 16, 1024, 1), 1);
      };
      auto kvmma = [&](float (&a)[64], float (&c)[32], int m) {
        reg_fence(a);
        uint32_t f[32];
#pragma unroll
        for (int i = 0; i < 32; i++) f[i] = pack(a[2 * i], a[2 * i + 1]);
        reg_zero(c);
        wg_fence();
#pragma unroll
        for (int k = 0; k < 8; k++) {
          wgmma_n64_rs<0>(c, f[4 * k], f[4 * k + 1], f[4 * k + 2], f[4 * k + 3], mkdesc(STG + (k >> 2) * 16384 + m * 8192 + (k & 3) * 32, 16, 1024, 1), k != 0);
          if (m && k == HAND_K) nb_arrive(NB_VQ, 256);
        }
        wg_commit();
      };
      float c0[32], c1[32];
      mbar_wait(B_FULL, 0);
      wg_fence();
      half(a0, 0, 0);
      wg_commit();
      mbar_wait(B_FULL + 8, 0);
      wg_fence();
      half(a0, 1, 0);
      wg_commit();
      wg_wait<2>();
      if (leader) mbar_arrive(B_EMPTY + 32);
      wg_fence();
      half(a1, 0, 1);
      half(a1, 1, 1);
      wg_commit();
      nb_sync(NB_PK, 256);
      wg_wait<1>();
      kvmma(a0, c0, 0);
      wg_wait<1>();
      if (leader) { mbar_arrive(B_EMPTY); mbar_arrive(B_EMPTY + 8); }
      STAMP_IF(leader, 19);
      kvmma(a1, c1, 1);
      const bool hp = ww >> 1;
      float c[4];
      float2 tt[8];
#pragma unroll
      for (int i = 0; i < 8; i++) tt[i] = lds64f(S_CSK + ((i >> 2) * 64 + hp * 32 + (i & 3) * 8 + 2 * t4) * 4);
      mbar_wait(B_CSV, 0);
#pragma unroll
      for (int i = 0; i < 4; i++) c[i] = -__uint_as_float(lds32(S_CSV + ((i >> 1) * 64 + ww * 16 + (i & 1) * 8 + g) * 4));
      wg_wait<0>();
      reg_fence(c0);
      reg_fence(c1);
      if (leader) mbar_arrive(B_SFREE);
      STAMP_IF(leader, 20);
      uint4* pp = g_kvp + (tn * 16 + tm) * 512 + t;
      auto put = [&](int q, const float* d) {
        const float ca = c[q & 2], cb = c[q | 1];
        const float2 ta = tt[2 * q], tb = tt[2 * q + 1];
        st_unit(pp + q * 128, pack(fmaf(ca, ta.x, d[0]), fmaf(ca, ta.y, d[1])), pack(fmaf(cb, ta.x, d[2]), fmaf(cb, ta.y, d[3])),
                pack(fmaf(ca, tb.x, d[4]), fmaf(ca, tb.y, d[5])), pack(fmaf(cb, tb.x, d[6]), fmaf(cb, tb.y, d[7])), par);
      };
      if (!hp) { put(0, c0); put(1, c0 + 8); put(2, c1); put(3, c1 + 8); }
      else { put(0, c0 + 16); put(1, c0 + 24); put(2, c1 + 16); put(3, c1 + 24); }
      STAMP_IF(leader, 47);
      {
        uint32_t p[16];
        nb_sync(NB_WG1, 128);
        if (ww == 0) { e_signal(H_KVP + tn, tm); await(H_KVP + tn, 0xffffu, ep); }
        nb_sync(NB_WG1, 128);
        STAMP_IF(leader, 1);
        poll_kvp(p, g_kvp + (tn * 16 + (lane >> 3) * 4) * 512 + tm * 32 + ww * 8 + (lane & 7), par, 1u);
        float r[8];
#pragma unroll
        for (int i = 0; i < 4; i++) {
          r[2 * i] = (bf_lo(p[i]) + bf_lo(p[4 + i])) + (bf_lo(p[8 + i]) + bf_lo(p[12 + i]));
          r[2 * i + 1] = (bf_hi(p[i]) + bf_hi(p[4 + i])) + (bf_hi(p[8 + i]) + bf_hi(p[12 + i]));
        }
        const bool u16 = lane & 16, u8 = lane & 8;
        const uint32_t wd = pack(xred(xred(r[0], r[4], u16, 16), xred(r[2], r[6], u16, 16), u8, 8), xred(xred(r[1], r[5], u16, 16), xred(r[3], r[7], u16, 16), u8, 8));
        const uint32_t w1 = __shfl_down_sync(0xffffffffu, wd, 1), w2 = __shfl_down_sync(0xffffffffu, wd, 2), w3 = __shfl_down_sync(0xffffffffu, wd, 3);
        const int grp = (tm & 1) * 2 + ((lane >> 3) & 1), row = ww * 2 + ((lane >> 2) & 1);
        if (t4 == 0) st_unit(g_kv + tn * 512 + ((tm >> 3) * 4 + grp) * 64 + row * 8 + (((tm & 2) * 2 + ((tm >> 1) & 2) + (lane >> 4)) ^ row), wd, w1, w2, w3, par);
        nb_sync(NB_WG1, 128);
        if (ww == 0) { if (!KV_SPEC) e_signal(H_KV + tn, tm); e_arrive(B_WK); }
      }
      STAMP_IF(leader, 21);
    }
    const uint32_t sx = lane & 7, sc = lane >> 4;
    const uint32_t sa = STG + (ww * 16 + (lane & 15)) * 128;
    const uint32_t sw[4] = {sa + ((sc ^ sx) << 4), sa + (((2 + sc) ^ sx) << 4), sa + (((4 + sc) ^ sx) << 4), sa + (((6 + sc) ^ sx) << 4)};
    auto residual = [&]() {
      float ka[4], kb[4];
#pragma unroll
      for (int i = 0; i < 4; i++) {
        const float2 st = lds64f(S_KSTAT + ((i >> 1) * 64 + ww * 16 + (i & 1) * 8 + g) * 8);
        const float r = st.y * LN2;
        ka[i] = 1.f + r; kb[i] = -st.x * r;
      }
#pragma unroll
      for (int j = 0; j < 8; j++) {
        if ((j & 3) == 0) mbar_wait(B_XRES + 8 * (j >> 2), 0);
        const uint4 v = ldsm4(sw[j & 3] + (j >> 2) * 16384), u = ldsm4(sw[j & 3] + (j >> 2) * 16384 + 8192);
        const uint32_t vv[4] = {v.x, v.y, v.z, v.w}, uu[4] = {u.x, u.y, u.z, u.w};
#pragma unroll
        for (int i = 0; i < 4; i++) {
          a0[8 * j + 2 * i] = fmaf(bf_lo(vv[i]), ka[i & 1], kb[i & 1]);
          a0[8 * j + 2 * i + 1] = fmaf(bf_hi(vv[i]), ka[i & 1], kb[i & 1]);
          a1[8 * j + 2 * i] = fmaf(bf_lo(uu[i]), ka[2 + (i & 1)], kb[2 + (i & 1)]);
          a1[8 * j + 2 * i + 1] = fmaf(bf_hi(uu[i]), ka[2 + (i & 1)], kb[2 + (i & 1)]);
        }
      }
      reg_fence(a0);
      reg_fence(a1);
      STAMP_IF(leader, 22);
    };
    residual();
    nb_arrive(NB_KVB, 320);
    uint32_t oh[4];
    {
      mbar_wait(B_SEL, 0);
      const int r0 = key_token(lds32(S_SEL + t4 * 16)) - tm * 128, r1 = key_token(lds32(S_SEL + t4 * 16 + 8)) - tm * 128;
#pragma unroll
      for (int i = 0; i < 4; i++) {
        const int row = (i >> 1) * 64 + ww * 16 + (i & 1) * 8 + g;
        oh[i] = (r0 == row ? 0x3f00u : 0u) | (r1 == row ? 0x3f000000u : 0u);
      }
    }
    uint32_t va = RING + 16384 + sc * 8192 + (ww * 16 + (lane & 8)) * 128 + sx * 16 + (lane >> 3) * 4;
    asm volatile("" : "+r"(va));
    {
      auto own = [&](int r) {
        nb_sync(r ? NB_OWN1 : NB_Y, 256);
        mbar_wait(B_FULL + 8 * (3 + r), 1);
        STAMP_IF(leader, 25 + r);
        const uint64_t dw = mkdesc(RING + (3 + r) * SLOT, 8192, 1024, 1), dx = mkdesc(STG + r * 16384, 16, 1024, 1);
        wg_fence();
#pragma unroll
        for (int j = 0; j < 4; j++) {
          wgmma_n128_ss<0, 1>(a0, dx + j * 2, dw + j * 128, 1);
          wgmma_n128_ss<0, 1>(a1, dx + j * 2 + 512, dw + j * 128, 1);
        }
        wg_commit();
      };
      own(0);
      own(1);
      wg_wait<1>();
      if (leader) mbar_arrive(B_EMPTY + 24);
      auto check = [&](int r, int s) {
          uint32_t bad;
          asm volatile("{\n.reg .u32 a, b, c, d, e, f, g, h;\n.reg .pred p;\n"
                       "ld.shared.u32 a, [%1];\nld.shared.u32 b, [%1+128];\nld.shared.u32 c, [%1+256];\nld.shared.u32 d, [%1+384];\n"
                       "ld.shared.u32 e, [%1+512];\nld.shared.u32 f, [%1+640];\nld.shared.u32 g, [%1+768];\nld.shared.u32 h, [%1+896];\n"
                       "lop3.b32 a, a, b, %2, 0x7e;\nlop3.b32 c, c, d, %2, 0x7e;\nlop3.b32 e, e, f, %2, 0x7e;\nlop3.b32 g, g, h, %2, 0x7e;\n"
                       "lop3.b32 a, a, c, e, 0xfe;\nlop3.b32 a, a, g, 1, 0xa8;\nsetp.ne.u32 p, a, 0;\nvote.sync.any.pred p, p, 0xffffffff;\nselp.u32 %0, 1, 0, p;\n}"
                       : "=r"(bad) : "r"(va + s * SLOT), "r"(par) : "memory");
          if (__builtin_expect(bad, 0)) {
            const uint4* src = reinterpret_cast<const uint4*>(g_o + (tm * 128 + sc * 64 + ww * 16 + (lane & 15)) * 1024 + out_kblock(r, tn) * 64);
#pragma unroll 1
            for (int i = 0; i < 8; i++) {
              uint32_t v[4];
              asm volatile("{\n.reg .b64 x, y;\n.reg .b128 z;\n.reg .pred p, q, h;\n.reg .u32 c, b;\nmov.u32 c, 0;\nsetp.ne.u32 h, %6, 0;\nLW:\n"
                           "ld.relaxed.gpu.global.b128 z, [%4];\nmov.b128 {x, y}, z;\nmov.b64 {%0,%1}, x;\nmov.b64 {%2,%3}, y;\n"
                           "selp.b64 x, y, x, h;\nshr.b64 x, x, %7;\ncvt.u32.u64 b, x;\nand.b32 b, b, 1;\nsetp.eq.u32 p, b, %5;\n"
                           "vote.sync.all.pred p, p, 0xffffffff;\n@p bra.uni LD;\nadd.u32 c, c, 1;\nsetp.lt.u32 q, c, 1000000;\n@q bra.uni LW;\ntrap;\nLD:\n}"
                           : "=&r"(v[0]), "=&r"(v[1]), "=&r"(v[2]), "=&r"(v[3]) : "l"(src + i), "r"(par), "r"(sc), "r"((lane & 8) * 4) : "memory");
              sts128(RING + 16384 + s * SLOT + sc * 8192 + (ww * 16 + (lane & 15)) * 128 + ((i ^ sx) << 4), v[0], v[1], v[2], v[3]);
            }
            fence_async_smem();
            __syncwarp();
          }
      };
      int s = 0, ph = 0;
      uint32_t prev = B_EMPTY + 32;
#pragma unroll 1
      for (int r = 2; r < 12; r++) {
        mbar_wait(B_FULL + 8 * s, ph);
        check(r, s);
        if (!LITE || ((LITE_MASK >> 27) & 1)) STAMP_IF(leader && r == 2, 27);
        const uint64_t dw = mkdesc(RING, 8192, 1024, 1) + s * (SLOT >> 4), dx = mkdesc(RING + 16384, 16, 1024, 1) + s * (SLOT >> 4);
        wg_fence();
#pragma unroll
        for (int j = 0; j < 4; j++) {
          wgmma_n128_ss<0, 1>(a0, dx + j * 2, dw + j * 128, 1);
          wgmma_n128_ss<0, 1>(a1, dx + j * 2 + 512, dw + j * 128, 1);
        }
        wg_commit();
        wg_wait<1>();
        if (leader) mbar_arrive(prev);
        prev = B_EMPTY + 8 * s;
        if (++s == NST) { s = 0; ph ^= 1; }
      }
      auto half = [&](float (&a)[64], int s, int m) {
        const uint64_t dw = mkdesc(RING, 8192, 1024, 1) + s * (SLOT >> 4), dx = mkdesc(RING + 16384 + m * 8192, 16, 1024, 1) + s * (SLOT >> 4);
#pragma unroll
        for (int j = 0; j < 4; j++) wgmma_n128_ss<0, 1>(a, dx + j * 2, dw + j * 128, 1);
      };
      auto store = [&](float (&a)[64], int m, int c) {
#pragma unroll
        for (int i = 0; i < 32; i++) asm volatile("" : "+f"(a[32 * c + i])::"memory");
#pragma unroll
        for (int j = 4 * c; j < 4 * c + 4; j++)
          stsm4(sw[j & 3] + c * 16384 + m * 8192, pack(a[8 * j], a[8 * j + 1]), pack(a[8 * j + 2], a[8 * j + 3]), pack(a[8 * j + 4], a[8 * j + 5]), pack(a[8 * j + 6], a[8 * j + 7]));
        fence_async_smem();
        e_store2d(&mp.m_out, tn * 128 + c * 64, tm * 128 + m * 64 + ww * 16, STG + c * 16384 + m * 8192 + ww * 2048);
      };
#pragma unroll 1
      for (int q = 0; q < 4; q++) {
        mbar_wait(B_FULL + 8 * q, 0);
        check(12 + q, q);
        wg_fence();
        half(a0, q, 0);
        wg_commit();
      }
      nb_sync(NB_ST, 288);
      wg_fence();
      wgmma_n128_rs<1>(a0, oh[0], oh[1], oh[0], oh[1], mkdesc(AUX, 1024, 0, 1), 1);
      wg_commit();
      wg_fence();
      half(a1, 0, 1);
      half(a1, 1, 1);
      wg_commit();
      wg_wait<1>();
      store(a0, 0, 0);
      store(a0, 0, 1);
      wg_fence();
      half(a1, 2, 1);
      half(a1, 3, 1);
      wgmma_n128_rs<1>(a1, oh[2], oh[3], oh[2], oh[3], mkdesc(AUX, 1024, 0, 1), 1);
      wg_commit();
      wg_wait<0>();
      STAMP_IF(leader, 28);
      store(a1, 1, 0);
      store(a1, 1, 1);
    }
    bulk_wait_read();
    if (bid == 0 && leader) st_relaxed(&g_epoch, ep);
    STAMP_IF(leader, 29);
  } else {
    asm volatile("setmaxnreg.inc.sync.aligned.u32 216;");
    const int g = lane >> 2, t4 = lane & 3;
    const bool leader = tid == 0;
    const uint32_t sx = lane & 7, sc = lane >> 4;
    const uint32_t sa = STG + (w * 16 + (lane & 15)) * 128;
    const uint32_t sw[4] = {sa + ((sc ^ sx) << 4), sa + (((2 + sc) ^ sx) << 4), sa + (((4 + sc) ^ sx) << 4), sa + (((6 + sc) ^ sx) << 4)};
    float a0[64], a1[64];
    reg_zero(a0); reg_zero(a1); reg_fence(a0); reg_fence(a1);
    mainloop<true>(a0, a1, 0, 0, NB_KV, 0, leader);
    STAMP_IF(leader, 33);
    {
      nb_sync(NB_FDONE, 416);
      STAMP_IF(leader, 34);
      const uint32_t par = lds32(S_EPOCH) & 1u;
#pragma unroll 1
      for (int m = 0;; m++) {
        const uint32_t ca = S_CSK + (m * 64 + w * 16 + g) * 4;
        const float c[2] = {-lds32v(ca), -lds32v(ca + 32)};
        float z[2] = {0.f, 0.f}, tt[2] = {0.f, 0.f};
#pragma unroll
        for (int j = 0; j < 8; j++) {
          const float4 s0 = lds128v(S_KSTAT + (j * 16 + 2 * t4) * 8), s1 = lds128v(S_KSTAT + (j * 16 + 8 + 2 * t4) * 8);
          const float mu[4] = {s0.x, s0.z, s1.x, s1.z}, rl[4] = {s0.y, s0.w, s1.y, s1.w};
          float p[8];
#pragma unroll
          for (int i = 0; i < 8; i++) {
            const int r = (i >> 1) & 1, cc = (i >> 2) * 2 + (i & 1);
            p[i] = phi2(fmaf(c[r], mu[cc], a0[8 * j + i]) * rl[cc]);
            a0[8 * j + i] = a1[8 * j + i];
            z[r] += p[i];
            p[i] *= rl[cc];
            tt[r] = fmaf(p[i], mu[cc], tt[r]);
          }
          stsm4(sw[j & 3] + (j >> 2) * 16384 + m * 8192, pack(p[0], p[1]), pack(p[2], p[3]), pack(p[4], p[5]), pack(p[6], p[7]));
        }
        const bool u2 = lane & 2, u1 = lane & 1;
        const float v = xred(xred(z[0], tt[0], u2, 2), xred(z[1], tt[1], u2, 2), u1, 1);
        if (u2) sts32(ca + (t4 & 1) * 32, __float_as_uint(v));
        else st_relaxed(g_z + tm * 1024 + tn * 128 + m * 64 + w * 16 + t4 * 8 + g, tagf(v * LOG2E, par));
        if (m) break;
      }
      fence_async_smem();
      nb_arrive(NB_PK, 256);
      nb_arrive(NB_Z, 160);
    }
    STAMP_IF(leader, 35);
    const uint32_t ep = lds32(S_EPOCH);
    uint32_t sd2[4];
    float es[4];
    {
      nb_sync(NB_CSQ, 160);
      float mu[4];
#pragma unroll
      for (int i = 0; i < 4; i++) {
        const float2 st = lds64f(S_KSTAT + ((i >> 1) * 64 + w * 16 + (i & 1) * 8 + g) * 8);
        mu[i] = -st.x;
        const float sd = LOG2E * rcp(st.y);
        sd2[i] = pack(sd, sd);
        es[i] = sd * (1e-6f * LOG2E);
      }
#pragma unroll
      for (int j = 0; j < 16; j++) {
        const float2 c = lds64f(S_CSQ + (j * 8 + 2 * t4) * 4);
        a0[4 * j] = mu[0] * c.x; a0[4 * j + 1] = mu[0] * c.y; a0[4 * j + 2] = mu[1] * c.x; a0[4 * j + 3] = mu[1] * c.y;
        a1[4 * j] = mu[2] * c.x; a1[4 * j + 1] = mu[2] * c.y; a1[4 * j + 2] = mu[3] * c.x; a1[4 * j + 3] = mu[3] * c.y;
      }
      reg_fence(a0); reg_fence(a1);
    }
    STAMP_IF(leader, 40);
    nb_sync(NB_VQ, 256);
    mainloop<false, 13>(a0, a1, 2, 0, 0, 4 + (tn & 3), leader);
    {
      uint32_t f[2][16];
      const uint32_t ra = S_KSTAT + (w * 16 + g) * 8 + 4;
      auto phi = [&](const float (&a)[64], int off, int m, int i0, int i1, uint32_t (&o)[16]) {
        const float r0 = lds32v(ra + m * 512), r1 = lds32v(ra + m * 512 + 64);
#pragma unroll
        for (int i = i0; i < i1; i++) o[i] = phi_pack(a[off + 2 * i], a[off + 2 * i + 1], i & 1 ? r1 : r0, sd2[2 * m + (i & 1)]);
      };
      auto half = [&](float (&a)[64], int s, int m) {
        const bool xr = ((13 + s) >> 1) == 4 + (tn & 3);
        if (!m) {
          mbar_wait(B_FULL + 8 * s, 1);
          if (xr) mbar_wait(B_XRES + 8 * (~s & 1), 0);
          wg_fence();
        }
        const uint64_t dx = mkdesc(m * 8192, 16, 1024, 1) + ((xr ? STG + (~s & 1) * 16384 : RING + s * SLOT + 16384) >> 4);
#pragma unroll
        for (int j = 0; j < 4; j++) wgmma_n128_ss<0, 1>(a, dx + j * 2, mkdesc(RING + s * SLOT + j * 2048, 8192, 1024, 1), 1);
      };
      half(a0, 0, 0);
      wg_commit();
      half(a0, 1, 0);
      wg_commit();
      wg_wait<2>();
      if (leader) mbar_arrive(B_EMPTY + 32);
      half(a0, 2, 0);
      wg_commit();
      wg_fence();
      half(a1, 0, 1);
      half(a1, 1, 1);
      wg_commit();
      wg_wait<1>();
      reg_fence(a0);
      phi(a0, 0, 0, 0, PHI_CUT, f[0]);
      wg_fence();
      half(a1, 2, 1);
      wg_commit();
      phi(a0, 0, 0, PHI_CUT, 16, f[0]);
      nb_sync(NB_KVB, 320);
      wg_wait<0>();
      if (leader) { mbar_arrive(B_EMPTY); mbar_arrive(B_EMPTY + 8); mbar_arrive(B_EMPTY + 16); }
      reg_fence(a1);
      STAMP_IF(leader, 36);
      const uint32_t mk[4] = {t4 == 0, t4 == 1, t4 == 2, t4 == 3};
      uint64_t db = mkdesc(KVB, 16, 1024, 1);
      uint32_t so = 0;
#pragma unroll 1
      for (int j = 0;; j++) {
        float oc[2][2][20];
        auto mma = [&](const uint32_t (&a)[16], float (&o)[2][20]) {
          reg_zero(o[0]); reg_zero(o[1]);
          wg_fence();
          wgmma_n40_rs<0>(o[0], a[0], a[1], a[2], a[3], db, 0);
          wgmma_n40_rs<0>(o[1], a[8], a[9], a[10], a[11], db + 4, 0);
          wgmma_n40_rs<0>(o[0], a[4], a[5], a[6], a[7], db + 2, 1);
          wgmma_n40_rs<0>(o[1], a[12], a[13], a[14], a[15], db + 6, 1);
          wg_commit();
        };
        auto fin = [&](int m, float (&o)[2][20]) {
          const uint32_t m0 = mk[2 * m], m1 = mk[2 * m + 1];
#pragma unroll
          for (int h = 0; h < 2; h++) {
            const float r0 = rcp(o[h][0] + es[2 * m]), r1 = rcp(o[h][2] + es[2 * m + 1]);
            {
#pragma unroll
              for (int q = 0; q < 2; q++)
                stsm4(sw[h * 2 + q] + so + m * 8192,
                      bsel(pack(o[h][4 + 8 * q] * r0, o[h][5 + 8 * q] * r0), ep, m0), bsel(pack(o[h][6 + 8 * q] * r1, o[h][7 + 8 * q] * r1), ep, m1),
                      bsel(pack(o[h][8 + 8 * q] * r0, o[h][9 + 8 * q] * r0), ep, m0), bsel(pack(o[h][10 + 8 * q] * r1, o[h][11 + 8 * q] * r1), ep, m1));
            }
          }
        };
        mma(f[0], oc[0]);
        if (j) nb_arrive(NB_Y, 256);
        phi(a1, 0, 1, 0, 16, f[1]);
        wg_wait<0>();
        reg_fence(oc[0][0]); reg_fence(oc[0][1]);
        mma(f[1], oc[1]);
        fin(0, oc[0]);
        if (j == 0) { fence_async_smem(); nb_arrive(NB_Q0, 192); }
        wg_wait<0>();
        reg_fence(oc[1][0]); reg_fence(oc[1][1]);
        fin(1, oc[1]);
        fence_async_smem();
        if (j) break;
        nb_arrive(NB_OWN0, 160);
        STAMP_IF(leader, 38);
#pragma unroll
        for (int i = 0; i < 32; i++) a1[i] = a1[32 + i];
        phi(a0, 32, 0, 0, 16, f[0]);
        db = mkdesc(KVB + 5120, 16, 1024, 1);
        so = 16384;
      }
      nb_arrive(NB_OWN1, 256);
      nb_arrive(NB_H1, 160);
      STAMP_IF(leader, 39);
    }
  }
}

#undef CK
typedef CUresult (*EncodeFn)(CUtensorMap*, CUtensorMapDataType, cuuint32_t, void*, const cuuint64_t*, const cuuint64_t*, const cuuint32_t*,
                             const cuuint32_t*, CUtensorMapInterleave, CUtensorMapSwizzle, CUtensorMapL2promotion, CUtensorMapFloatOOBfill);

void make_map(EncodeFn enc, CUtensorMap* m, const void* p, int rank, uint64_t d0, uint64_t d1, uint64_t d2, uint64_t s1, uint64_t s2,
              uint32_t b0, uint32_t b1, uint32_t b2, CUtensorMapSwizzle sw) {
  cuuint64_t gd[3] = {d0, d1, d2}, gs[2] = {s1, s2};
  cuuint32_t bd[3] = {b0, b1, b2}, es[3] = {1, 1, 1};
  enc(m, CU_TENSOR_MAP_DATA_TYPE_BFLOAT16, rank, const_cast<void*>(p), gd, gs, bd, es, CU_TENSOR_MAP_INTERLEAVE_NONE, sw,
      CU_TENSOR_MAP_L2_PROMOTION_L2_128B, CU_TENSOR_MAP_FLOAT_OOB_FILL_NONE);
}

}

extern "C" void kernel_launch(void* const* d_in, const int* in_sizes, int n_in, void* d_out, int out_size) {
  (void)in_sizes; (void)n_in; (void)out_size;
  void* fn = nullptr;
  cudaDriverEntryPointQueryResult qr;
  cudaGetDriverEntryPoint("cuTensorMapEncodeTiled", &fn, cudaEnableDefault, &qr);
  EncodeFn enc = (EncodeFn)fn;
  void* o;
  cudaGetSymbolAddress(&o, g_o);
  const CUtensorMapSwizzle S128 = CU_TENSOR_MAP_SWIZZLE_128B, S64 = CU_TENSOR_MAP_SWIZZLE_64B, S0 = CU_TENSOR_MAP_SWIZZLE_NONE;
  Params mp;
  mp.x = (const char*)d_in[0]; mp.w_r = (const char*)d_in[4];
  mp.wg = (const char*)d_in[5]; mp.wu = (const char*)d_in[6]; mp.wd = (const char*)d_in[7];
  make_map(enc, &mp.m_wqkv, d_in[1], 3, 64, 1024, 48, 6144, 128, 64, 64, 2, S128);
  make_map(enc, &mp.m_x, d_in[0], 2, 1024, 2048, 1, 2048, 0, 64, 128, 1, S128);
  make_map(enc, &mp.m_os, o, 2, 1024, 2048, 1, 2048, 0, 64, 64, 1, S128);
  make_map(enc, &mp.m_o, o, 2, 1024, 2048, 1, 2048, 0, 64, 128, 1, S128);
  make_map(enc, &mp.m_wo, d_in[2], 3, 64, 1024, 16, 2048, 128, 64, 64, 2, S128);
  make_map(enc, &mp.m_xs, d_in[0], 2, 1024, 2048, 1, 2048, 0, 256, 16, 1, S0);
  const char *wg = (const char*)d_in[5], *wu = (const char*)d_in[6];
  make_map(enc, &mp.m_gu, wu < wg ? wu : wg, 3, 3584, 1024, 2, 7168, (uint64_t)(wu < wg ? wg - wu : wu - wg), 32, 64, 2, S64);
  make_map(enc, &mp.m_down, d_in[7], 2, 1024, 3584, 1, 2048, 0, 64, 64, 1, S128);
  make_map(enc, &mp.m_out, d_out, 2, 1024, 2048, 1, 2048, 0, 64, 16, 1, S128);
  int dev = 0, sms = 0;
  cudaGetDevice(&dev);
  cudaDeviceGetAttribute(&sms, cudaDevAttrMultiProcessorCount, dev);
  auto kern = sms == 132 ? fused_kernel<true> : fused_kernel<false>;
  cudaFuncSetAttribute(kern, cudaFuncAttributeMaxDynamicSharedMemorySize, SMEM_BYTES);
  kern<<<132, 512, SMEM_BYTES>>>(mp);
}
```

```cpp
#include <cuda_runtime.h>
#include <cuda.h>
#include <cuda_bf16.h>
#include <stdint.h>

namespace {

template <int TA, int TB>
__device__ __forceinline__ void wgmma_n8_ss(float (&d)[4], uint64_t da, uint64_t db, int sc) {
  asm volatile("{\n.reg .pred p;\nsetp.ne.b32 p, %6, 0;\n"
    "wgmma.mma_async.sync.aligned.m64n8k16.f32.bf16.bf16 {%0, %1, %2, %3}, %4, %5, p, 1, 1, %7, %8;\n}\n"
    : "+f"(d[0]), "+f"(d[1]), "+f"(d[2]), "+f"(d[3])
    : "l"(da), "l"(db), "r"(sc), "n"(TA), "n"(TB));
}
template <int TB>
__device__ __forceinline__ void wgmma_n40_rs(float (&d)[20], uint32_t a0, uint32_t a1, uint32_t a2, uint32_t a3, uint64_t db, int sc) {
  asm volatile("{\n.reg .pred p;\nsetp.ne.b32 p, %25, 0;\n"
    "wgmma.mma_async.sync.aligned.m64n40k16.f32.bf16.bf16 {%0, %1, %2, %3, %4, %5, %6, %7, %8, %9, %10, %11, %12, %13, %14, %15, %16, %17, %18, %19}, {%20,%21,%22,%23}, %24, p, 1, 1, %26;\n}\n"
    : "+f"(d[0]), "+f"(d[1]), "+f"(d[2]), "+f"(d[3]), "+f"(d[4]), "+f"(d[5]), "+f"(d[6]), "+f"(d[7]),
      "+f"(d[8]), "+f"(d[9]), "+f"(d[10]), "+f"(d[11]), "+f"(d[12]), "+f"(d[13]), "+f"(d[14]), "+f"(d[15]),
      "+f"(d[16]), "+f"(d[17]), "+f"(d[18]), "+f"(d[19])
    : "r"(a0), "r"(a1), "r"(a2), "r"(a3), "l"(db), "r"(sc), "n"(TB));
}
template <int TB>
__device__ __forceinline__ void wgmma_n64_rs(float (&d)[32], uint32_t a0, uint32_t a1, uint32_t a2, uint32_t a3, uint64_t db, int sc) {
  asm volatile("{\n.reg .pred p;\nsetp.ne.b32 p, %37, 0;\n"
    "wgmma.mma_async.sync.aligned.m64n64k16.f32.bf16.bf16 {%0, %1, %2, %3, %4, %5, %6, %7, %8, %9, %10, %11, %12, %13, %14, %15, %16, %17, %18, %19, %20, %21, %22, %23, %24, %25, %26, %27, %28, %29, %30, %31}, {%32,%33,%34,%35}, %36, p, 1, 1, %38;\n}\n"
    : "+f"(d[0]), "+f"(d[1]), "+f"(d[2]), "+f"(d[3]), "+f"(d[4]), "+f"(d[5]), "+f"(d[6]), "+f"(d[7]),
      "+f"(d[8]), "+f"(d[9]), "+f"(d[10]), "+f"(d[11]), "+f"(d[12]), "+f"(d[13]), "+f"(d[14]), "+f"(d[15]),
      "+f"(d[16]), "+f"(d[17]), "+f"(d[18]), "+f"(d[19]), "+f"(d[20]), "+f"(d[21]), "+f"(d[22]), "+f"(d[23]),
      "+f"(d[24]), "+f"(d[25]), "+f"(d[26]), "+f"(d[27]), "+f"(d[28]), "+f"(d[29]), "+f"(d[30]), "+f"(d[31])
    : "r"(a0), "r"(a1), "r"(a2), "r"(a3), "l"(db), "r"(sc), "n"(TB));
}
template <int TA, int TB>
__device__ __forceinline__ void wgmma_n128_ss(float (&d)[64], uint64_t da, uint64_t db, int sc) {
  asm volatile("{\n.reg .pred p;\nsetp.ne.b32 p, %66, 0;\n"
    "wgmma.mma_async.sync.aligned.m64n128k16.f32.bf16.bf16 {%0, %1, %2, %3, %4, %5, %6, %7, %8, %9, %10, %11, %12, %13, %14, %15, %16, %17, %18, %19, %20, %21, %22, %23, %24, %25, %26, %27, %28, %29, %30, %31, %32, %33, %34, %35, %36, %37, %38, %39, %40, %41, %42, %43, %44, %45, %46, %47, %48, %49, %50, %51, %52, %53, %54, %55, %56, %57, %58, %59, %60, %61, %62, %63}, %64, %65, p, 1, 1, %67, %68;\n}\n"
    : "+f"(d[0]), "+f"(d[1]), "+f"(d[2]), "+f"(d[3]), "+f"(d[4]), "+f"(d[5]), "+f"(d[6]), "+f"(d[7]),
      "+f"(d[8]), "+f"(d[9]), "+f"(d[10]), "+f"(d[11]), "+f"(d[12]), "+f"(d[13]), "+f"(d[14]), "+f"(d[15]),
      "+f"(d[16]), "+f"(d[17]), "+f"(d[18]), "+f"(d[19]), "+f"(d[20]), "+f"(d[21]), "+f"(d[22]), "+f"(d[23]),
      "+f"(d[24]), "+f"(d[25]), "+f"(d[26]), "+f"(d[27]), "+f"(d[28]), "+f"(d[29]), "+f"(d[30]), "+f"(d[31]),
      "+f"(d[32]), "+f"(d[33]), "+f"(d[34]), "+f"(d[35]), "+f"(d[36]), "+f"(d[37]), "+f"(d[38]), "+f"(d[39]),
      "+f"(d[40]), "+f"(d[41]), "+f"(d[42]), "+f"(d[43]), "+f"(d[44]), "+f"(d[45]), "+f"(d[46]), "+f"(d[47]),
      "+f"(d[48]), "+f"(d[49]), "+f"(d[50]), "+f"(d[51]), "+f"(d[52]), "+f"(d[53]), "+f"(d[54]), "+f"(d[55]),
      "+f"(d[56]), "+f"(d[57]), "+f"(d[58]), "+f"(d[59]), "+f"(d[60]), "+f"(d[61]), "+f"(d[62]), "+f"(d[63])
    : "l"(da), "l"(db), "r"(sc), "n"(TA), "n"(TB));
}
template <int TB>
__device__ __forceinline__ void wgmma_n128_rs(float (&d)[64], uint32_t a0, uint32_t a1, uint32_t a2, uint32_t a3, uint64_t db, int sc) {
  asm volatile("{\n.reg .pred p;\nsetp.ne.b32 p, %69, 0;\n"
    "wgmma.mma_async.sync.aligned.m64n128k16.f32.bf16.bf16 {%0, %1, %2, %3, %4, %5, %6, %7, %8, %9, %10, %11, %12, %13, %14, %15, %16, %17, %18, %19, %20, %21, %22, %23, %24, %25, %26, %27, %28, %29, %30, %31, %32, %33, %34, %35, %36, %37, %38, %39, %40, %41, %42, %43, %44, %45, %46, %47, %48, %49, %50, %51, %52, %53, %54, %55, %56, %57, %58, %59, %60, %61, %62, %63}, {%64,%65,%66,%67}, %68, p, 1, 1, %70;\n}\n"
    : "+f"(d[0]), "+f"(d[1]), "+f"(d[2]), "+f"(d[3]), "+f"(d[4]), "+f"(d[5]), "+f"(d[6]), "+f"(d[7]),
      "+f"(d[8]), "+f"(d[9]), "+f"(d[10]), "+f"(d[11]), "+f"(d[12]), "+f"(d[13]), "+f"(d[14]), "+f"(d[15]),
      "+f"(d[16]), "+f"(d[17]), "+f"(d[18]), "+f"(d[19]), "+f"(d[20]), "+f"(d[21]), "+f"(d[22]), "+f"(d[23]),
      "+f"(d[24]), "+f"(d[25]), "+f"(d[26]), "+f"(d[27]), "+f"(d[28]), "+f"(d[29]), "+f"(d[30]), "+f"(d[31]),
      "+f"(d[32]), "+f"(d[33]), "+f"(d[34]), "+f"(d[35]), "+f"(d[36]), "+f"(d[37]), "+f"(d[38]), "+f"(d[39]),
      "+f"(d[40]), "+f"(d[41]), "+f"(d[42]), "+f"(d[43]), "+f"(d[44]), "+f"(d[45]), "+f"(d[46]), "+f"(d[47]),
      "+f"(d[48]), "+f"(d[49]), "+f"(d[50]), "+f"(d[51]), "+f"(d[52]), "+f"(d[53]), "+f"(d[54]), "+f"(d[55]),
      "+f"(d[56]), "+f"(d[57]), "+f"(d[58]), "+f"(d[59]), "+f"(d[60]), "+f"(d[61]), "+f"(d[62]), "+f"(d[63])
    : "r"(a0), "r"(a1), "r"(a2), "r"(a3), "l"(db), "r"(sc), "n"(TB));
}

__device__ __forceinline__ void poll1f(uint32_t (&v)[1], const void* p, uint32_t tag, uint32_t mask) {
  asm volatile("{\n.reg .pred p, q;\n.reg .u32 c, b;\n.reg .b64 x, y;\n.reg .b128 z;\nmov.u32 c, 0;\nLW:\n"
               "ld.relaxed.gpu.global.u32 %0, [%1+0];\n"
               "xor.b32 b, %0, %2;\n"
               "and.b32 b, b, %3;\nsetp.eq.u32 p, b, 0;\nvote.sync.all.pred p, p, 0xffffffff;\n@p bra.uni LD;\n"
               "nanosleep.u32 50;\nadd.u32 c, c, 1;\nsetp.lt.u32 q, c, 1000000;\n@q bra.uni LW;\ntrap;\nLD:\n}"
               : "=&r"(v[0])
               : "l"(p), "r"(tag), "r"(mask) : "memory");
}
__device__ __forceinline__ void poll0(uint32_t (&v)[1], const void* p, uint32_t tag, uint32_t mask) {
  asm volatile("{\n.reg .pred p, q;\n.reg .u32 c, b;\n.reg .b64 x, y;\n.reg .b128 z;\nmov.u32 c, 0;\nLW:\n"
               "ld.relaxed.gpu.global.u32 %0, [%1+0];\n"
               "xor.b32 b, %0, %2;\n"
               "and.b32 b, b, %3;\nsetp.eq.u32 p, b, 0;\nvote.sync.all.pred p, p, 0xffffffff;\n@p bra.uni LD;\n"
               "add.u32 c, c, 1;\nsetp.lt.u32 q, c, 1000000;\n@q bra.uni LW;\ntrap;\nLD:\n}"
               : "=&r"(v[0])
               : "l"(p), "r"(tag), "r"(mask) : "memory");
}
__device__ __forceinline__ void poll_pair(uint32_t (&v)[2], const void* p, uint32_t tag, uint32_t mask) {
  asm volatile("{\n.reg .pred p, q;\n.reg .u32 c, b;\n.reg .b64 x, y;\n.reg .b128 z;\nmov.u32 c, 0;\nLW:\n"
               "ld.relaxed.gpu.global.b64 x, [%2+0];\nmov.b64 {%0,%1}, x;\n"
               "xor.b32 b, %0, %3;\n"
               "and.b32 b, b, %4;\nsetp.eq.u32 p, b, 0;\nvote.sync.all.pred p, p, 0xffffffff;\n@p bra.uni LD;\n"
               "nanosleep.u32 100;\nadd.u32 c, c, 1;\nsetp.lt.u32 q, c, 1000000;\n@q bra.uni LW;\ntrap;\nLD:\n}"
               : "=&r"(v[0]), "=&r"(v[1])
               : "l"(p), "r"(tag), "r"(mask) : "memory");
}
__device__ __forceinline__ void poll_quad(uint32_t (&v)[4], const void* p, uint32_t tag, uint32_t mask) {
  asm volatile("{\n.reg .pred p, q;\n.reg .u32 c, b;\n.reg .b64 x, y;\n.reg .b128 z;\nmov.u32 c, 0;\nLW:\n"
               "ld.relaxed.gpu.global.v4.u32 {%0,%1,%2,%3}, [%4+0];\n"
               "xor.b32 b, %0, %5;\n"
               "lop3.b32 b, b, %1, %5, 0xf6;\nlop3.b32 b, b, %2, %5, 0xf6;\nlop3.b32 b, b, %3, %5, 0xf6;\n"
               "and.b32 b, b, %6;\nsetp.eq.u32 p, b, 0;\nvote.sync.all.pred p, p, 0xffffffff;\n@p bra.uni LD;\n"
               "nanosleep.u32 200;\nadd.u32 c, c, 1;\nsetp.lt.u32 q, c, 1000000;\n@q bra.uni LW;\ntrap;\nLD:\n}"
               : "=&r"(v[0]), "=&r"(v[1]), "=&r"(v[2]), "=&r"(v[3])
               : "l"(p), "r"(tag), "r"(mask) : "memory");
}
__device__ __forceinline__ void poll8x4(uint32_t (&v)[32], const void* p, uint32_t tag, uint32_t mask) {
  asm volatile("{\n.reg .pred p, q;\n.reg .u32 c, b;\n.reg .b64 x, y;\n.reg .b128 z;\nmov.u32 c, 0;\nLW:\n"
               "ld.relaxed.gpu.global.v4.u32 {%0,%1,%2,%3}, [%32+0];\n"
               "ld.relaxed.gpu.global.v4.u32 {%4,%5,%6,%7}, [%32+2048];\n"
               "ld.relaxed.gpu.global.v4.u32 {%8,%9,%10,%11}, [%32+4096];\n"
               "ld.relaxed.gpu.global.v4.u32 {%12,%13,%14,%15}, [%32+6144];\n"
               "ld.relaxed.gpu.global.v4.u32 {%16,%17,%18,%19}, [%32+8192];\n"
               "ld.relaxed.gpu.global.v4.u32 {%20,%21,%22,%23}, [%32+10240];\n"
               "ld.relaxed.gpu.global.v4.u32 {%24,%25,%26,%27}, [%32+12288];\n"
               "ld.relaxed.gpu.global.v4.u32 {%28,%29,%30,%31}, [%32+14336];\n"
               "xor.b32 b, %0, %33;\n"
               "lop3.b32 b, b, %1, %33, 0xf6;\nlop3.b32 b, b, %2, %33, 0xf6;\nlop3.b32 b, b, %3, %33, 0xf6;\nlop3.b32 b, b, %4, %33, 0xf6;\n"
               "lop3.b32 b, b, %5, %33, 0xf6;\nlop3.b32 b, b, %6, %33, 0xf6;\nlop3.b32 b, b, %7, %33, 0xf6;\nlop3.b32 b, b, %8, %33, 0xf6;\n"
               "lop3.b32 b, b, %9, %33, 0xf6;\nlop3.b32 b, b, %10, %33, 0xf6;\nlop3.b32 b, b, %11, %33, 0xf6;\nlop3.b32 b, b, %12, %33, 0xf6;\n"
               "lop3.b32 b, b, %13, %33, 0xf6;\nlop3.b32 b, b, %14, %33, 0xf6;\nlop3.b32 b, b, %15, %33, 0xf6;\nlop3.b32 b, b, %16, %33, 0xf6;\n"
               "lop3.b32 b, b, %17, %33, 0xf6;\nlop3.b32 b, b, %18, %33, 0xf6;\nlop3.b32 b, b, %19, %33, 0xf6;\nlop3.b32 b, b, %20, %33, 0xf6;\n"
               "lop3.b32 b, b, %21, %33, 0xf6;\nlop3.b32 b, b, %22, %33, 0xf6;\nlop3.b32 b, b, %23, %33, 0xf6;\nlop3.b32 b, b, %24, %33, 0xf6;\n"
               "lop3.b32 b, b, %25, %33, 0xf6;\nlop3.b32 b, b, %26, %33, 0xf6;\nlop3.b32 b, b, %27, %33, 0xf6;\nlop3.b32 b, b, %28, %33, 0xf6;\n"
               "lop3.b32 b, b, %29, %33, 0xf6;\nlop3.b32 b, b, %30, %33, 0xf6;\nlop3.b32 b, b, %31, %33, 0xf6;\n"
               "and.b32 b, b, %34;\nsetp.eq.u32 p, b, 0;\nvote.sync.all.pred p, p, 0xffffffff;\n@p bra.uni LD;\n"
               "nanosleep.u32 50;\nadd.u32 c, c, 1;\nsetp.lt.u32 q, c, 1000000;\n@q bra.uni LW;\ntrap;\nLD:\n}"
               : "=&r"(v[0]), "=&r"(v[1]), "=&r"(v[2]), "=&r"(v[3]), "=&r"(v[4]), "=&r"(v[5]), "=&r"(v[6]), "=&r"(v[7]), "=&r"(v[8]), "=&r"(v[9]), "=&r"(v[10]), "=&r"(v[11]), "=&r"(v[12]), "=&r"(v[13]), "=&r"(v[14]), "=&r"(v[15]), "=&r"(v[16]), "=&r"(v[17]), "=&r"(v[18]), "=&r"(v[19]), "=&r"(v[20]), "=&r"(v[21]), "=&r"(v[22]), "=&r"(v[23]), "=&r"(v[24]), "=&r"(v[25]), "=&r"(v[26]), "=&r"(v[27]), "=&r"(v[28]), "=&r"(v[29]), "=&r"(v[30]), "=&r"(v[31])
               : "l"(p), "r"(tag), "r"(mask) : "memory");
}
__device__ __forceinline__ void poll16(uint32_t (&v)[16], const void* p, uint32_t tag, uint32_t mask) {
  asm volatile("{\n.reg .pred p, q;\n.reg .u32 c, b;\n.reg .b64 x, y;\n.reg .b128 z;\nmov.u32 c, 0;\nLW:\n"
               "ld.relaxed.gpu.global.u32 %0, [%16+0];\n"
               "ld.relaxed.gpu.global.u32 %1, [%16+4096];\n"
               "ld.relaxed.gpu.global.u32 %2, [%16+8192];\n"
               "ld.relaxed.gpu.global.u32 %3, [%16+12288];\n"
               "ld.relaxed.gpu.global.u32 %4, [%16+16384];\n"
               "ld.relaxed.gpu.global.u32 %5, [%16+20480];\n"
               "ld.relaxed.gpu.global.u32 %6, [%16+24576];\n"
               "ld.relaxed.gpu.global.u32 %7, [%16+28672];\n"
               "ld.relaxed.gpu.global.u32 %8, [%16+32768];\n"
               "ld.relaxed.gpu.global.u32 %9, [%16+36864];\n"
               "ld.relaxed.gpu.global.u32 %10, [%16+40960];\n"
               "ld.relaxed.gpu.global.u32 %11, [%16+45056];\n"
               "ld.relaxed.gpu.global.u32 %12, [%16+49152];\n"
               "ld.relaxed.gpu.global.u32 %13, [%16+53248];\n"
               "ld.relaxed.gpu.global.u32 %14, [%16+57344];\n"
               "ld.relaxed.gpu.global.u32 %15, [%16+61440];\n"
               "xor.b32 b, %0, %17;\n"
               "lop3.b32 b, b, %1, %17, 0xf6;\nlop3.b32 b, b, %2, %17, 0xf6;\nlop3.b32 b, b, %3, %17, 0xf6;\nlop3.b32 b, b, %4, %17, 0xf6;\n"
               "lop3.b32 b, b, %5, %17, 0xf6;\nlop3.b32 b, b, %6, %17, 0xf6;\nlop3.b32 b, b, %7, %17, 0xf6;\nlop3.b32 b, b, %8, %17, 0xf6;\n"
               "lop3.b32 b, b, %9, %17, 0xf6;\nlop3.b32 b, b, %10, %17, 0xf6;\nlop3.b32 b, b, %11, %17, 0xf6;\nlop3.b32 b, b, %12, %17, 0xf6;\n"
               "lop3.b32 b, b, %13, %17, 0xf6;\nlop3.b32 b, b, %14, %17, 0xf6;\nlop3.b32 b, b, %15, %17, 0xf6;\n"
               "and.b32 b, b, %18;\nsetp.eq.u32 p, b, 0;\nvote.sync.all.pred p, p, 0xffffffff;\n@p bra.uni LD;\n"
               "nanosleep.u32 200;\nadd.u32 c, c, 1;\nsetp.lt.u32 q, c, 1000000;\n@q bra.uni LW;\ntrap;\nLD:\n}"
               : "=&r"(v[0]), "=&r"(v[1]), "=&r"(v[2]), "=&r"(v[3]), "=&r"(v[4]), "=&r"(v[5]), "=&r"(v[6]), "=&r"(v[7]), "=&r"(v[8]), "=&r"(v[9]), "=&r"(v[10]), "=&r"(v[11]), "=&r"(v[12]), "=&r"(v[13]), "=&r"(v[14]), "=&r"(v[15])
               : "l"(p), "r"(tag), "r"(mask) : "memory");
}
__device__ __forceinline__ void poll_keys(uint32_t (&v)[16], const void* p, uint32_t tag, uint32_t mask) {
  asm volatile("{\n.reg .pred p, q;\n.reg .u32 c, b;\n.reg .b64 x, y;\n.reg .b128 z;\nmov.u32 c, 0;\nLW:\n"
               "ld.relaxed.gpu.global.v2.b64 {x, y}, [%16+0];\nmov.b64 {%0,%1}, x;\nmov.b64 {%2,%3}, y;\n"
               "ld.relaxed.gpu.global.v2.b64 {x, y}, [%16+4096];\nmov.b64 {%4,%5}, x;\nmov.b64 {%6,%7}, y;\n"
               "ld.relaxed.gpu.global.v2.b64 {x, y}, [%16+8192];\nmov.b64 {%8,%9}, x;\nmov.b64 {%10,%11}, y;\n"
               "ld.relaxed.gpu.global.v2.b64 {x, y}, [%16+12288];\nmov.b64 {%12,%13}, x;\nmov.b64 {%14,%15}, y;\n"
               "xor.b32 b, %0, %17;\n"
               "lop3.b32 b, b, %2, %17, 0xf6;\nlop3.b32 b, b, %4, %17, 0xf6;\nlop3.b32 b, b, %6, %17, 0xf6;\nlop3.b32 b, b, %8, %17, 0xf6;\n"
               "lop3.b32 b, b, %10, %17, 0xf6;\nlop3.b32 b, b, %12, %17, 0xf6;\nlop3.b32 b, b, %14, %17, 0xf6;\n"
               "and.b32 b, b, %18;\nsetp.eq.u32 p, b, 0;\nvote.sync.all.pred p, p, 0xffffffff;\n@p bra.uni LD;\n"
               "nanosleep.u32 20;\nadd.u32 c, c, 1;\nsetp.lt.u32 q, c, 1000000;\n@q bra.uni LW;\ntrap;\nLD:\n}"
               : "=&r"(v[0]), "=&r"(v[1]), "=&r"(v[2]), "=&r"(v[3]), "=&r"(v[4]), "=&r"(v[5]), "=&r"(v[6]), "=&r"(v[7]), "=&r"(v[8]), "=&r"(v[9]), "=&r"(v[10]), "=&r"(v[11]), "=&r"(v[12]), "=&r"(v[13]), "=&r"(v[14]), "=&r"(v[15])
               : "l"(p), "r"(tag), "r"(mask) : "memory");
}
__device__ __forceinline__ void poll_z(uint32_t (&v)[16], const void* p, uint32_t tag, uint32_t mask) {
  asm volatile("{\n.reg .pred p, q;\n.reg .u32 c, b;\n.reg .b64 x, y;\n.reg .b128 z;\nmov.u32 c, 0;\nLW:\n"
               "ld.relaxed.gpu.global.v4.u32 {%0,%1,%2,%3}, [%16+0];\n"
               "ld.relaxed.gpu.global.v4.u32 {%4,%5,%6,%7}, [%16+4096];\n"
               "ld.relaxed.gpu.global.v4.u32 {%8,%9,%10,%11}, [%16+8192];\n"
               "ld.relaxed.gpu.global.v4.u32 {%12,%13,%14,%15}, [%16+12288];\n"
               "xor.b32 b, %0, %17;\n"
               "lop3.b32 b, b, %1, %17, 0xf6;\nlop3.b32 b, b, %2, %17, 0xf6;\nlop3.b32 b, b, %3, %17, 0xf6;\nlop3.b32 b, b, %4, %17, 0xf6;\n"
               "lop3.b32 b, b, %5, %17, 0xf6;\nlop3.b32 b, b, %6, %17, 0xf6;\nlop3.b32 b, b, %7, %17, 0xf6;\nlop3.b32 b, b, %8, %17, 0xf6;\n"
               "lop3.b32 b, b, %9, %17, 0xf6;\nlop3.b32 b, b, %10, %17, 0xf6;\nlop3.b32 b, b, %11, %17, 0xf6;\nlop3.b32 b, b, %12, %17, 0xf6;\n"
               "lop3.b32 b, b, %13, %17, 0xf6;\nlop3.b32 b, b, %14, %17, 0xf6;\nlop3.b32 b, b, %15, %17, 0xf6;\n"
               "and.b32 b, b, %18;\nsetp.eq.u32 p, b, 0;\nvote.sync.all.pred p, p, 0xffffffff;\n@p bra.uni LD;\n"
               "nanosleep.u32 300;\nadd.u32 c, c, 1;\nsetp.lt.u32 q, c, 1000000;\n@q bra.uni LW;\ntrap;\nLD:\n}"
               : "=&r"(v[0]), "=&r"(v[1]), "=&r"(v[2]), "=&r"(v[3]), "=&r"(v[4]), "=&r"(v[5]), "=&r"(v[6]), "=&r"(v[7]), "=&r"(v[8]), "=&r"(v[9]), "=&r"(v[10]), "=&r"(v[11]), "=&r"(v[12]), "=&r"(v[13]), "=&r"(v[14]), "=&r"(v[15])
               : "l"(p), "r"(tag), "r"(mask) : "memory");
}
__device__ __forceinline__ void poll_kvp(uint32_t (&v)[16], const void* p, uint32_t tag, uint32_t mask) {
  asm volatile("{\n.reg .pred p, q;\n.reg .u32 c, b;\n.reg .b64 x, y;\n.reg .b128 z;\nmov.u32 c, 0;\nLW:\n"
               "ld.relaxed.gpu.global.b128 z, [%16+0];\nmov.b128 {x, y}, z;\nmov.b64 {%0,%1}, x;\nmov.b64 {%2,%3}, y;\n"
               "ld.relaxed.gpu.global.b128 z, [%16+8192];\nmov.b128 {x, y}, z;\nmov.b64 {%4,%5}, x;\nmov.b64 {%6,%7}, y;\n"
               "ld.relaxed.gpu.global.b128 z, [%16+16384];\nmov.b128 {x, y}, z;\nmov.b64 {%8,%9}, x;\nmov.b64 {%10,%11}, y;\n"
               "ld.relaxed.gpu.global.b128 z, [%16+24576];\nmov.b128 {x, y}, z;\nmov.b64 {%12,%13}, x;\nmov.b64 {%14,%15}, y;\n"
               "xor.b32 b, %0, %17;\n"
               "lop3.b32 b, b, %4, %17, 0xf6;\nlop3.b32 b, b, %8, %17, 0xf6;\nlop3.b32 b, b, %12, %17, 0xf6;\n"
               "and.b32 b, b, %18;\nsetp.eq.u32 p, b, 0;\nvote.sync.all.pred p, p, 0xffffffff;\n@p bra.uni LD;\n"
               "nanosleep.u32 50;\nadd.u32 c, c, 1;\nsetp.lt.u32 q, c, 1000000;\n@q bra.uni LW;\ntrap;\nLD:\n}"
               : "=&r"(v[0]), "=&r"(v[1]), "=&r"(v[2]), "=&r"(v[3]), "=&r"(v[4]), "=&r"(v[5]), "=&r"(v[6]), "=&r"(v[7]), "=&r"(v[8]), "=&r"(v[9]), "=&r"(v[10]), "=&r"(v[11]), "=&r"(v[12]), "=&r"(v[13]), "=&r"(v[14]), "=&r"(v[15])
               : "l"(p), "r"(tag), "r"(mask) : "memory");
}

__device__ __align__(1024) __nv_bfloat16 g_o[2048 * 1024];
__device__ __align__(128) uint2 g_keys[2048];
__device__ __align__(128) uint32_t g_csum[18 * 1024];
__device__ __align__(128) uint32_t g_z[16 * 1024];
__device__ __align__(128) uint4 g_kvp[128 * 512];
__device__ __align__(128) uint4 g_kv[8 * 512];
__device__ __align__(128) uint4 g_h[112 * 32];
__device__ __align__(128) uint32_t g_yp[128 * 512];
__device__ __align__(128) uint2 g_sel[32 * 16];
enum { H_CS = 0, H_KVP = 8, H_KV = 16, H_H = 24, H_Y = 32, H_O = 40, H_Z = 56 };
__device__ __align__(128) uint32_t g_sig[64 * 32];
__device__ uint32_t g_epoch;

constexpr uint32_t RING = 1024, SLOT = 32768, SMEM_BYTES = 232448;
constexpr int NST = 5, HST = 7;
constexpr uint32_t STG = RING + 163840, AUX = RING + 196608, FR = RING + 212992, MISC = RING + 229376;
constexpr uint32_t B_FULL = MISC, B_EMPTY = MISC + 56, B_XS = MISC + 112, B_SEL = MISC + 144, B_WK = MISC + 160, B_CSDN = MISC + 168,
                   B_FR = MISC + 176, B_FE = MISC + 200, B_DR = MISC + 224, B_CSV = MISC + 248,
                   B_DND = MISC + 256, B_XRES = MISC + 264, B_PFREE = MISC + 280, B_SFREE = MISC + 288, B_KVL = MISC + 296, B_HL = MISC + 304, B_HOK = MISC + 312, B_HGO = MISC + 320, NBAR = 41;
constexpr uint32_t S_EPOCH = MISC + 352, S_NCAND = MISC + 356, S_SEL = MISC + 368, S_WMAX = MISC + 432,
                   S_KSTAT = MISC + 512, S_CSK = MISC + 1536, S_CSV = MISC + 2048, S_CSQ = MISC + 2560, S_ONES = MISC + 512;
constexpr uint32_t KVB = FR, HOP = FR + 10240, GR = FR - 8192;
enum { NB_Z = 0, NB_KV = 1, NB_VQ = 2, NB_WG0 = 3, NB_FDONE = 4, NB_PK = 5, NB_KVB = 6, NB_WG1 = 7, NB_WG2 = 8, NB_CSQ = 9,
       NB_Y = 10, NB_ST = 11, NB_OWN0 = 12, NB_OWN1 = 13, NB_Q0 = 14, NB_H1 = 15 };

#define XS_FLY 2
#define FFN_GAP 400
#define PF_GAP 200
#define PF_WAIT 1000
#define GPCMAP 0x75143620u
#define KV_SPEC 200
#define HAND_K 5
#define PHI_CUT 11
#define SIG_EARLY 50
#define WK_AT 0x3210
#define XS_AT 0
#define XS_GAP 0
#define H_DELAY 0
#define KPF 1
constexpr uint64_t EVICT_FIRST = 0x12f0000000000000ull;
constexpr float LOG2E = 1.4426950408889634f, LN2 = 0.6931471805599453f;

#define ELECT "{\n.reg .pred p;\nelect.sync _|p, 0xffffffff;\n"
#define TMA2D "cp.async.bulk.tensor.2d.shared::cluster.global.mbarrier::complete_tx::bytes"
#define TMA3D "cp.async.bulk.tensor.3d.shared::cluster.global.mbarrier::complete_tx::bytes"
__device__ __forceinline__ void e_expect(uint32_t b, uint32_t n) {
  asm volatile(ELECT "@p mbarrier.arrive.expect_tx.shared::cta.b64 _, [%0], %1;\n}" ::"r"(b), "r"(n) : "memory");
}
__device__ __forceinline__ void e_arrive(uint32_t b) { asm volatile(ELECT "@p mbarrier.arrive.shared::cta.b64 _, [%0];\n}" ::"r"(b) : "memory"); }
__device__ __forceinline__ void e_tma2d(uint32_t dst, const CUtensorMap* m, int c0, int c1, uint32_t bar) {
  asm volatile(ELECT "@p " TMA2D " [%0], [%1, {%3, %4}], [%2];\n}" ::"r"(dst), "l"(m), "r"(bar), "r"(c0), "r"(c1) : "memory");
}
__device__ __forceinline__ void e_tma2d_ef(uint32_t dst, const CUtensorMap* m, int c0, int c1, uint32_t bar, uint64_t pol) {
  asm volatile(ELECT "@p " TMA2D ".L2::cache_hint [%0], [%1, {%3, %4}], [%2], %5;\n}" ::"r"(dst), "l"(m), "r"(bar), "r"(c0), "r"(c1), "l"(pol) : "memory");
}
__device__ __forceinline__ void e_tma3d(uint32_t dst, const CUtensorMap* m, int c1, int c2, uint32_t bar) {
  asm volatile(ELECT "@p " TMA3D " [%0], [%1, {0, %3, %4}], [%2];\n}" ::"r"(dst), "l"(m), "r"(bar), "r"(c1), "r"(c2) : "memory");
}
__device__ __forceinline__ void e_store2d(const CUtensorMap* m, int c0, int c1, uint32_t src) {
  asm volatile(ELECT "@p cp.async.bulk.tensor.2d.global.shared::cta.bulk_group [%0, {%2, %3}], [%1];\n}" ::"l"(m), "r"(src), "r"(c0), "r"(c1) : "memory");
}
__device__ __forceinline__ void e_tma3d_ef(uint32_t dst, const CUtensorMap* m, int c0, int c1, uint32_t bar, uint64_t pol) {
  asm volatile(ELECT "@p " TMA3D ".L2::cache_hint [%0], [%1, {%3, %4, 0}], [%2], %5;\n}" ::"r"(dst), "l"(m), "r"(bar), "r"(c0), "r"(c1), "l"(pol) : "memory");
}
__device__ __forceinline__ void e_load(uint32_t dst, const void* src, uint32_t n, uint32_t bar) {
  asm volatile(ELECT "@p cp.async.bulk.shared::cluster.global.mbarrier::complete_tx::bytes [%0], [%1], %2, [%3];\n}" ::"r"(dst), "l"(src), "r"(n), "r"(bar) : "memory");
}
__device__ __forceinline__ void e_pfmap(const CUtensorMap* m) { asm volatile(ELECT "@p prefetch.tensormap [%0];\n}" ::"l"(m) : "memory"); }
__device__ __forceinline__ void bulk_wait_read() { asm volatile("cp.async.bulk.commit_group;\ncp.async.bulk.wait_group.read 0;" ::: "memory"); }
__device__ __forceinline__ void e_signal(int word, int bit) {
  asm volatile(ELECT "@p red.relaxed.gpu.global.xor.b32 [%0], %1;\n}" ::"l"(g_sig + word * 32), "r"(1u << bit) : "memory");
}
__device__ __forceinline__ void await(int word, uint32_t mask, uint32_t ep) {
  uint32_t f[1];
  poll1f(f, g_sig + word * 32, 0u - (ep & 1u), mask);
}

__device__ __forceinline__ void mbar_arrive(uint32_t b) { asm volatile("mbarrier.arrive.shared::cta.b64 _, [%0];" ::"r"(b) : "memory"); }
__device__ __forceinline__ void mbar_wait(uint32_t b, uint32_t ph) {
  asm volatile("{\n.reg .pred p, q;\n.reg .u32 c;\nmov.u32 c, 0;\nLW:\nmbarrier.try_wait.parity.shared::cta.b64 p, [%0], %1;\n@p bra LD;\n"
               "add.u32 c, c, 1;\nsetp.lt.u32 q, c, 100000;\n@q bra LW;\ntrap;\nLD:\n}" ::"r"(b), "r"(ph) : "memory");
}
#define WAIT01 "{\n.reg .pred p, q;\n.reg .u32 c;\nmov.u32 c, 0;\nLW:\nmbarrier.try_wait.parity.shared::cta.b64 p, [%0], %1;\n@p bra LD;\n" \
               "add.u32 c, c, 1;\nsetp.lt.u32 q, c, 100000;\n@q bra LW;\ntrap;\nLD:\nelect.sync _|p, 0xffffffff;\n"
__device__ __forceinline__ void refill_wx(uint32_t eb, uint32_t ph, uint32_t fb, uint32_t bytes, uint32_t dw, const CUtensorMap* mw, int k0, int c,
                                          uint32_t dx, const CUtensorMap* mx, int row, uint32_t xb) {
  asm volatile(WAIT01 "@p " TMA3D " [%4], [%5, {0, %6, %7}], [%2];\n@p " TMA2D " [%8], [%9, {%6, %10}], [%11];\n"
               "@p mbarrier.arrive.expect_tx.shared::cta.b64 _, [%2], %3;\n}"
               ::"r"(eb), "r"(ph), "r"(fb), "r"(bytes), "r"(dw), "l"(mw), "r"(k0), "r"(c), "r"(dx), "l"(mx), "r"(row), "r"(xb) : "memory");
}
__device__ __forceinline__ void refill_w(uint32_t eb, uint32_t ph, uint32_t fb, uint32_t bytes, uint32_t dw, const CUtensorMap* mw, int k0, int c) {
  asm volatile(WAIT01 "@p " TMA3D " [%4], [%5, {0, %6, %7}], [%2];\n@p mbarrier.arrive.expect_tx.shared::cta.b64 _, [%2], %3;\n}"
               ::"r"(eb), "r"(ph), "r"(fb), "r"(bytes), "r"(dw), "l"(mw), "r"(k0), "r"(c) : "memory");
}
__device__ __forceinline__ void refill_x(uint32_t eb, uint32_t ph, uint32_t fb, uint32_t dx, const CUtensorMap* mx, int k0, int row) {
  asm volatile(WAIT01 "@p " TMA2D " [%3], [%4, {%5, %6}], [%2];\n}" ::"r"(eb), "r"(ph), "r"(fb), "r"(dx), "l"(mx), "r"(k0), "r"(row) : "memory");
}
__device__ __forceinline__ void refill_g(uint32_t eb, uint32_t ph, uint32_t fb, uint32_t dw, const CUtensorMap* mw, int c0, int k0) {
  asm volatile(WAIT01 "@p " TMA3D ".L2::cache_hint [%3], [%4, {%5, %6, 0}], [%2], %7;\n@p mbarrier.arrive.expect_tx.shared::cta.b64 _, [%2], 8192;\n}"
               ::"r"(eb), "r"(ph), "r"(fb), "r"(dw), "l"(mw), "r"(c0), "r"(k0), "l"(EVICT_FIRST) : "memory");
}
__device__ __forceinline__ void nb_sync(int id, int n) { asm volatile("bar.sync %0, %1;" ::"r"(id), "r"(n) : "memory"); }
__device__ __forceinline__ void nb_arrive(int id, int n) { asm volatile("bar.arrive %0, %1;" ::"r"(id), "r"(n) : "memory"); }
__device__ __forceinline__ void wg_fence() { asm volatile("wgmma.fence.sync.aligned;" ::: "memory"); }
__device__ __forceinline__ void wg_commit() { asm volatile("wgmma.commit_group.sync.aligned;" ::: "memory"); }
template <int N> __device__ __forceinline__ void wg_wait() { asm volatile("wgmma.wait_group.sync.aligned %0;" ::"n"(N) : "memory"); }
template <int N> __device__ __forceinline__ void reg_fence(float (&a)[N]) {
#pragma unroll
  for (int i = 0; i < N; i++) asm volatile("" : "+f"(a[i])::"memory");
}
template <int N> __device__ __forceinline__ void reg_zero(float (&a)[N]) {
#pragma unroll
  for (int i = 0; i < N; i++) a[i] = 0.f;
}
__device__ __forceinline__ constexpr uint64_t mkdesc(uint32_t addr, uint32_t lbo, uint32_t sbo, uint32_t swz) {
  return (uint64_t)(addr >> 4) | ((uint64_t)(lbo >> 4) << 16) | ((uint64_t)(sbo >> 4) << 32) | ((uint64_t)swz << 62);
}
__device__ __forceinline__ void fence_async_smem() { asm volatile("fence.proxy.async.shared::cta;" ::: "memory"); }
__device__ __forceinline__ void st_relaxed(uint32_t* p, uint32_t v) { asm volatile("st.relaxed.gpu.global.u32 [%0], %1;" ::"l"(p), "r"(v) : "memory"); }
__device__ __forceinline__ uint32_t ld_relaxed(const uint32_t* p) { uint32_t v; asm volatile("ld.relaxed.gpu.global.u32 %0, [%1];" : "=r"(v) : "l"(p) : "memory"); return v; }
__device__ __forceinline__ void st_unit(uint4* p, uint32_t a, uint32_t b, uint32_t c, uint32_t d, uint32_t par) {
  asm volatile("{\n.reg .b64 x, y;\n.reg .b128 z;\nmov.b64 x, {%1,%2};\nmov.b64 y, {%3,%4};\nmov.b128 z, {x, y};\nst.relaxed.gpu.global.b128 [%0], z;\n}"
               ::"l"(p), "r"((a & ~1u) | par), "r"(b), "r"(c), "r"(d) : "memory");
}
__device__ __forceinline__ uint4 lds128(uint32_t a) { uint4 v; asm volatile("ld.shared.v4.u32 {%0,%1,%2,%3}, [%4];" : "=r"(v.x), "=r"(v.y), "=r"(v.z), "=r"(v.w) : "r"(a)); return v; }
__device__ __forceinline__ float4 lds128f(uint32_t a) { float4 v; asm volatile("ld.shared.v4.f32 {%0,%1,%2,%3}, [%4];" : "=f"(v.x), "=f"(v.y), "=f"(v.z), "=f"(v.w) : "r"(a)); return v; }
__device__ __forceinline__ float4 lds128v(uint32_t a) { float4 v; asm volatile("ld.volatile.shared.v4.f32 {%0,%1,%2,%3}, [%4];" : "=f"(v.x), "=f"(v.y), "=f"(v.z), "=f"(v.w) : "r"(a) : "memory"); return v; }
__device__ __forceinline__ float lds32v(uint32_t a) { float v; asm volatile("ld.volatile.shared.f32 %0, [%1];" : "=f"(v) : "r"(a) : "memory"); return v; }
__device__ __forceinline__ float2 lds64f(uint32_t a) { float2 v; asm volatile("ld.shared.v2.f32 {%0,%1}, [%2];" : "=f"(v.x), "=f"(v.y) : "r"(a)); return v; }
__device__ __forceinline__ uint32_t lds32(uint32_t a) { uint32_t v; asm volatile("ld.shared.u32 %0, [%1];" : "=r"(v) : "r"(a)); return v; }
__device__ __forceinline__ void sts128(uint32_t a, uint32_t x, uint32_t y, uint32_t z, uint32_t w) { asm volatile("st.shared.v4.u32 [%0], {%1,%2,%3,%4};" ::"r"(a), "r"(x), "r"(y), "r"(z), "r"(w) : "memory"); }
__device__ __forceinline__ void sts128f(uint32_t a, float x, float y, float z, float w) { asm volatile("st.shared.v4.f32 [%0], {%1,%2,%3,%4};" ::"r"(a), "f"(x), "f"(y), "f"(z), "f"(w) : "memory"); }
__device__ __forceinline__ void sts64(uint32_t a, uint32_t x, uint32_t y) { asm volatile("st.shared.v2.u32 [%0], {%1,%2};" ::"r"(a), "r"(x), "r"(y) : "memory"); }
__device__ __forceinline__ void sts32(uint32_t a, uint32_t x) { asm volatile("st.shared.u32 [%0], %1;" ::"r"(a), "r"(x) : "memory"); }
__device__ __forceinline__ void stsm4(uint32_t a, uint32_t r0, uint32_t r1, uint32_t r2, uint32_t r3) {
  asm volatile("stmatrix.sync.aligned.m8n8.x4.shared.b16 [%0], {%1,%2,%3,%4};" ::"r"(a), "r"(r0), "r"(r1), "r"(r2), "r"(r3) : "memory");
}
__device__ __forceinline__ uint4 ldsm4(uint32_t a) {
  uint4 v; asm volatile("ldmatrix.sync.aligned.m8n8.x4.shared.b16 {%0,%1,%2,%3}, [%4];" : "=r"(v.x), "=r"(v.y), "=r"(v.z), "=r"(v.w) : "r"(a) : "memory"); return v;
}
__device__ __forceinline__ uint32_t pack(float lo, float hi) { uint32_t r; asm("cvt.rn.bf16x2.f32 %0, %1, %2;" : "=r"(r) : "f"(hi), "f"(lo)); return r; }
__device__ __forceinline__ float bf_lo(uint32_t w) { return __uint_as_float(w << 16); }
__device__ __forceinline__ float bf_hi(uint32_t w) { return __uint_as_float(w & 0xffff0000u); }
__device__ __forceinline__ float bf_round(float x) { return bf_lo(pack(x, x)); }
__device__ __forceinline__ float ex2(float x) { float v; asm("ex2.approx.ftz.f32 %0, %1;" : "=f"(v) : "f"(x)); return v; }
__device__ __forceinline__ float rcp(float x) { float v; asm("rcp.approx.ftz.f32 %0, %1;" : "=f"(v) : "f"(x)); return v; }
__device__ __forceinline__ float addsat(float a, float b) { float v; asm("add.sat.f32 %0, %1, %2;" : "=f"(v) : "f"(a), "f"(b)); return v; }
__device__ __forceinline__ float phi2(float a) { return fmaf(fmaxf(a, 0.f), LN2, addsat(ex2(a), 1e-6f)); }
__device__ __forceinline__ uint32_t phi_pack(float u0, float u1, float rl, uint32_t sd2) {
  uint32_t r;
  asm("{\n.reg .b32 m;\ncvt.rn.relu.bf16x2.f32 m, %2, %1;\nfma.rn.bf16x2 %0, %3, %4, m;\n}"
      : "=r"(r) : "f"(u0), "f"(u1), "r"(pack(addsat(ex2(u0 * rl), 1e-6f), addsat(ex2(u1 * rl), 1e-6f))), "r"(sd2));
  return r;
}
__device__ __forceinline__ uint32_t sub2(uint32_t a, uint32_t b) { uint32_t r; asm("sub.rn.bf16x2 %0, %1, %2;" : "=r"(r) : "r"(a), "r"(b)); return r; }
__device__ __forceinline__ float key_score(uint32_t key) { uint32_t u = key >> 16; u = (u & 0x8000u) ? (u & 0x7fffu) : (~u & 0xffffu); return __uint_as_float(u << 16); }
__device__ __forceinline__ int key_token(uint32_t key) { return 2047 - (int)((key >> 5) & 2047u); }
__device__ __forceinline__ uint32_t bsel(uint32_t a, uint32_t b, uint32_t m) { uint32_t r; asm("lop3.b32 %0, %1, %2, %3, 0xd8;" : "=r"(r) : "r"(a), "r"(b), "r"(m)); return r; }
__device__ __forceinline__ uint32_t prmt(uint32_t a, uint32_t b, uint32_t c) { uint32_t r; asm("prmt.b32 %0, %1, %2, %3;" : "=r"(r) : "r"(a), "r"(b), "r"(c)); return r; }
__device__ __forceinline__ uint32_t tagf(float v, uint32_t par) { return (__float_as_uint(v) & ~1u) | par; }
__device__ __forceinline__ float xred(float a, float b, bool up, int o) { return (up ? b : a) + __shfl_xor_sync(0xffffffffu, up ? a : b, o); }

#define STAMP(id)
#define STAMP_IF(c, id)
#define STAMP2(i)
#define LITE 1
#define LITE_MASK 0ull

template <bool TRANS, int NK = 16>
__device__ __forceinline__ void mainloop(float (&a0)[64], float (&a1)[64], int s, int ph, int handoff, int xpair, bool leader) {
  uint32_t prev = 0;
#pragma unroll 1
  for (int kt = 0; kt < NK; kt++) {
    const bool xr = !TRANS && (kt >> 1) == xpair;
    mbar_wait(B_FULL + 8 * s, ph);
    const uint64_t dw = mkdesc(RING, 8192, 1024, 1) + s * (SLOT >> 4), dx = mkdesc(0, 16, 1024, 1) + (xr ? (STG >> 4) + (kt & 1) * 1024 : ((RING + 16384) >> 4) + s * (SLOT >> 4));
    if (xr) mbar_wait(B_XRES + 8 * (kt & 1), 0);
    wg_fence();
#pragma unroll
    for (int j = 0; j < 4; j++) {
      if (TRANS) {
        wgmma_n128_ss<1, 0>(a0, dw + j * 128, dx + j * 2, 1);
        wgmma_n128_ss<1, 0>(a1, dw + j * 128 + 512, dx + j * 2, 1);
      } else {
        wgmma_n128_ss<0, 1>(a0, dx + j * 2, dw + j * 128, 1);
        wgmma_n128_ss<0, 1>(a1, dx + j * 2 + 512, dw + j * 128, 1);
      }
    }
    wg_commit();
    if (handoff && kt == 15) nb_arrive(handoff, 256);
    wg_wait<1>();
    if (prev && leader) mbar_arrive(prev);
    prev = B_EMPTY + 8 * s;
    if (++s == NST) { s = 0; ph ^= 1; }
  }
  if (NK < 16) return;
  wg_wait<0>();
  if (leader) mbar_arrive(prev);
  reg_fence(a0);
  reg_fence(a1);
}

__device__ __forceinline__ int out_kblock(int r, int tn) {
  const int q = r - 2, half = q >= 7, pi = q - 7 * half;
  return r < 2 ? 2 * tn + r : 2 * ((pi + (pi >= (tn & 3))) ^ (tn & 4)) + half;
}

struct Params {
  const char *x, *w_r, *wg, *wu, *wd;
  CUtensorMap m_wqkv, m_x, m_xs, m_o, m_os, m_wo, m_gu, m_down, m_out;
};

template <bool BY_SMID>
__global__ void __launch_bounds__(512, 1) fused_kernel(const __grid_constant__ Params mp) {
  extern __shared__ __align__(1024) uint8_t smem_raw[];
#define CK(i)
  CK(0);
  const int tid = threadIdx.x, lane = tid & 31;
  const int w = __shfl_sync(0xffffffffu, tid >> 5, 0);
  int bid = blockIdx.x;
  if (BY_SMID) {
    uint32_t sm;
    asm volatile("mov.u32 %0, %%smid;" : "=r"(sm));
    const uint32_t p = sm >> 1, q = ((p - 32) * 37) >> 8;
    const uint32_t gpc = p < 32 ? p & 7 : p < 60 ? p - 31 - 7 * q : 0, tpc = p < 32 ? p >> 3 : p < 60 ? 4 + q : p - 58;
    bid = (p >> 1) == 30 ? 128 + ((0x9cu >> (2 * (sm & 3))) & 3) : ((GPCMAP >> (4 * gpc)) & 7) * 16 + tpc * 2 + (sm & 1);
  }
  const int tn = (bid & 3) + 4 * (bid >> 6), tm = (bid >> 2) & 15;

  CK(1);
  if (w == 0) {
#pragma unroll 1
    for (int s = 0; s < NST; s++) {
      asm volatile(ELECT "@p mbarrier.init.shared::cta.b64 [%0], 1;\n}" ::"r"(B_FULL + 8 * s) : "memory");
      if (bid < 128) {
        e_expect(B_FULL + 8 * s, 32768);
        e_tma2d(RING + s * SLOT + 16384, &mp.m_x, s * 64, tm * 128, B_FULL + 8 * s);
        e_tma3d(RING + s * SLOT, &mp.m_wqkv, s * 64, 16 + 2 * tn, B_FULL + 8 * s);
      }
      if (s == 0) CK(2);
    }
  }
  if (w == 1) e_pfmap(&mp.m_wqkv);
  if (w == 2) e_pfmap(&mp.m_xs);
  if (w >= 4) {
#pragma unroll 1
    for (uint32_t b = MISC + 8 * (w + 1); b < MISC + 8 * NBAR; b += 96)
      asm volatile(ELECT "@p mbarrier.init.shared::cta.b64 [%0], %1;\n}" ::"r"(b), "r"(b == B_CSDN ? 4 : 1) : "memory");
    if (w == 15) sts32(S_NCAND, 0);
  }
  CK(3);
  asm volatile("fence.mbarrier_init.release.cluster;" ::: "memory");
  __syncthreads();

  if (bid >= 128) {
    const int h0 = bid == 128 ? 14 : bid - 129, hs = bid == 128 ? 1 : 3, h1 = bid == 128 ? 16 : 14;
    if (w == 12) {
      int s = 0, ph = 1;
#pragma unroll 1
      for (int h = h0; h < h1; h += hs) {
        const int c = 2 * h + (h & 8) * 2;
        if (h == 14) mbar_wait(B_SEL, 0);
        if (H_DELAY && h < 3) __nanosleep(H_DELAY);
#pragma unroll 1
        for (int kt = 0; kt < 16; kt += 2) {
          mbar_wait(B_EMPTY + 8 * s, ph);
          e_expect(B_FULL + 8 * s, 32768);
          e_tma3d(RING + s * SLOT, &mp.m_wqkv, kt * 64, c, B_FULL + 8 * s);
          e_tma3d(RING + s * SLOT + 16384, &mp.m_wqkv, kt * 64 + 64, c, B_FULL + 8 * s);
          if (++s == HST) { s = 0; ph ^= 1; }
        }
      }
    } else if (w < 4) {
      const uint32_t par = (ld_relaxed(&g_epoch) + 1) & 1u;
      sts32(S_ONES + tid * 4, 0x3f803f80u);
      fence_async_smem();
      nb_sync(NB_WG0, 128);
      int s = 0, ph = 0;
#pragma unroll 1
      for (int h = h0; h < h1; h += hs) {
        float c[4][4];
#pragma unroll
        for (int q = 0; q < 4; q++) reg_zero(c[q]);
        uint32_t prev = 0;
#pragma unroll 1
        for (int kt = 0; kt < 8; kt++) {
          mbar_wait(B_FULL + 8 * s, ph);
          const uint64_t dw = mkdesc(RING, 8192, 1024, 1) + s * (SLOT >> 4);
          wg_fence();
#pragma unroll
          for (int j = 0; j < 16; j++) wgmma_n8_ss<1, 0>(c[j & 3], dw + (j & 3) * 512 + (j >> 2) * 128, mkdesc(S_ONES, 128, 128, 0), 1);
          wg_commit();
          wg_wait<1>();
          if (prev && tid == 0) mbar_arrive(prev);
          prev = B_EMPTY + 8 * s;
          if (++s == HST) { s = 0; ph ^= 1; }
        }
        wg_wait<0>();
        if (tid == 0) mbar_arrive(prev);
#pragma unroll
        for (int q = 0; q < 4; q++) reg_fence(c[q]);
        const bool u2 = lane & 2, u1 = lane & 1;
        const float lo = u2 ? c[1][0] + c[3][0] : c[0][0] + c[2][0], hi = u2 ? c[1][2] + c[3][2] : c[0][2] + c[2][2];
        st_relaxed(g_csum + h * 128 + (lane & 2) * 32 + w * 16 + (lane & 1) * 8 + (lane >> 2), tagf(u1 ? hi : lo, par));
        STAMP_IF(tid == 0, h >= 8 ? 6 : 30);
      }
    } else if (w < 12 && bid == 128) {
      const int t = tid - 128, j = w - 4;
      const uint32_t ep = ld_relaxed(&g_epoch) + 1;
      uint32_t kk[16];
      poll_keys(kk, g_keys + t * 2, ep, 31u);
      STAMP_IF(t == 0, 42);
      const uint32_t m = __reduce_max_sync(0xffffffffu, max(max(max(kk[0], kk[2]), max(kk[4], kk[6])), max(max(kk[8], kk[10]), max(kk[12], kk[14]))));
      if (lane == 0) sts32(S_WMAX + j * 4, m);
      nb_sync(NB_WG1, 256);
      const uint32_t T = __reduce_min_sync(0xffffffffu, lds32(S_WMAX + (lane & 7) * 4));
      uint32_t cnt = 0;
#pragma unroll
      for (int i = 0; i < 8; i++) cnt += kk[2 * i] >= T;
      if (cnt) {
        uint32_t pos;
        asm volatile("atom.shared.add.u32 %0, [%1], %2;" : "=r"(pos) : "r"(S_NCAND), "r"(cnt * 8) : "memory");
#pragma unroll
        for (int i = 0; i < 8; i++)
          if (kk[2 * i] >= T) { sts64(AUX + pos, kk[2 * i], kk[2 * i + 1]); pos += 8; }
      }
      nb_sync(NB_WG1, 256);
      const uint32_t n8 = lds32(S_NCAND);
#pragma unroll 1
      for (uint32_t i0 = 0; i0 < n8; i0 += 256) {
        const uint32_t i = i0 + (t & ~7);
        const float2 c = lds64f(AUX + i);
        uint32_t rank = 0;
#pragma unroll 4
        for (uint32_t q = (t & 7) * 8; q < n8; q += 64) rank += lds32(AUX + q) > __float_as_uint(c.x);
        rank += __shfl_xor_sync(0xffffffffu, rank, 1);
        rank += __shfl_xor_sync(0xffffffffu, rank, 2);
        rank += __shfl_xor_sync(0xffffffffu, rank, 4);
        if (rank < 8 && i < n8) sts64(S_SEL + rank * 8, __float_as_uint(c.x), __float_as_uint(c.y));
      }
      nb_sync(NB_WG1, 256);
      if (j < 4) {
        const uint4 v = lds128(S_SEL + (lane & 3) * 16);
        asm volatile("{\n.reg .b64 x, y;\nmov.b64 x, {%1,%2};\nmov.b64 y, {%3,%4};\nst.relaxed.gpu.global.v2.b64 [%0], {x, y};\n}"
                     ::"l"(g_sel + (t >> 2) * 16 + (lane & 3) * 2), "r"(v.x), "r"(v.y), "r"(v.z), "r"(v.w) : "memory");
      } else if (j == 4) {
        fence_async_smem();
        e_arrive(B_SEL);
      }
      STAMP_IF(t == 0, 45);
    }
  } else if (w >= 12) {
    asm volatile("setmaxnreg.dec.sync.aligned.u32 32;");
    if (w == 12) {
      int s = 0, ph = 0;
#pragma unroll 1
      for (int it = NST; it < 48; it++) {
        const int c = (it < 32 ? (it & 16) + 16 : 0) + 2 * tn;
        const int k0 = ((it + (it >= 32 && tn < 4 ? 8 : 0)) & 15) * 64;
        const bool xr = (it >> 1) == 20 + (tn & 3);
        if (xr) { mbar_wait(B_SFREE, 0); e_expect(B_XRES + 8 * (it & 1), 16384); }
        refill_wx(B_EMPTY + 8 * s, ph, B_FULL + 8 * s, xr ? 16384 : 32768, RING + s * SLOT, &mp.m_wqkv, k0, c,
                  xr ? STG + (it & 1) * 16384 : RING + s * SLOT + 16384, &mp.m_x, tm * 128, xr ? B_XRES + 8 * (it & 1) : B_FULL + 8 * s);
        if (it >= NST) STAMP2(it - NST);
        if (++s == NST) { s = 0; ph ^= 1; }
      }
#pragma unroll 1
      for (int r = 0; r < 16; r++) {
        const int kb = out_kblock(r, tn);
        refill_w(B_EMPTY + 8 * s, ph, B_FULL + 8 * s, r < 2 ? 16384 : 32768, RING + s * SLOT, &mp.m_wo, kb * 64, 2 * tn);
        if (r < 2 || r == 4) {
          const uint32_t bar = B_DR + (r < 2 ? 16 : 8);
          const int k0 = (bid >> 4) * 448 + 128 + min(r, 2) * 128;
          if (r != 1) e_expect(bar, r ? 8192 : 32768);
          e_tma2d_ef(RING + s * SLOT + 16384, &mp.m_down, (bid & 15) * 64, k0, bar, EVICT_FIRST);
          if (r < 2) e_tma2d_ef(RING + s * SLOT + 24576, &mp.m_down, (bid & 15) * 64, k0 + 64, bar, EVICT_FIRST);
        }
        STAMP2(r + 48 - NST);
        if (++s == NST) { s = 0; ph ^= 1; }
      }
    } else if (w == 13) {
      mbar_wait(B_FULL + 8 * XS_AT, 0);
#pragma unroll 1
      for (int c = 0; c < 5; c++) {
        if (c >= XS_FLY) mbar_wait(B_XS + 8 * (c - XS_FLY), 0);
        if (c == ((WK_AT >> (4 * (tm >> 2))) & 7)) {
          e_expect(B_WK, 16384);
          e_tma3d(FR, &mp.m_wqkv, tm * 64, 16 + 2 * tn, B_WK);
        }
        if (c == 4) break;
        e_expect(B_XS + 8 * c, 8192);
        e_tma2d(STG + c * 8192, &mp.m_xs, c * 256, tm * 128 + tn * 16, B_XS + 8 * c);
        if (XS_GAP && c == 0) __nanosleep(XS_GAP);
      }
      {
        const char* pd = mp.wd + (bid & 15) * 128 + ((bid >> 4) * 448 + lane) * 2048;
        mbar_wait(B_XS + 24, 0);
        __nanosleep(PF_WAIT);
#pragma unroll 1
        for (int i = 0; i < 14; i++, pd += 65536) {
          asm volatile("prefetch.global.L2 [%0];" ::"l"(pd));
          __nanosleep(PF_GAP);
        }
      }
      nb_sync(NB_Z, 160);
      const uint32_t ep = lds32(S_EPOCH);
      {
        float z[4] = {0.f, 0.f, 0.f, 0.f};
        e_signal(H_Z + tn, tm);
        await(H_Z + tn, 0xffffu, ep);
#pragma unroll 1
        for (int i = 0; i < 4; i++) {
          uint32_t p[16];
          poll_z(p, g_z + i * 4096 + tn * 128 + lane * 4, ep, 1u);
#pragma unroll
          for (int q = 0; q < 4; q++) z[q] += (__uint_as_float(p[q]) + __uint_as_float(p[4 + q])) + (__uint_as_float(p[8 + q]) + __uint_as_float(p[12 + q]));
        }
        const uint32_t z01 = pack(z[0], z[1]), z23 = pack(z[2], z[3]);
        if (bid < 112) mbar_wait(B_PFREE, 0);
#pragma unroll
        for (int n = 0; n < 8; n++) sts64(KVB + (lane >> 4) * 5120 + n * 128 + ((((lane >> 1) & 7) ^ n) << 4) + (lane & 1) * 8, z01, z23);
        fence_async_smem();
        nb_arrive(NB_KVB, 320);
        STAMP_IF(lane == 0, 46);
      }
      nb_sync(NB_Q0, 192);
      e_store2d(&mp.m_os, tn * 128, tm * 128, STG);
      nb_sync(NB_OWN0, 160);
      e_store2d(&mp.m_os, tn * 128, tm * 128 + 64, STG + 8192);
      if (!SIG_EARLY) bulk_wait_read(); else if (SIG_EARLY > 1) __nanosleep(SIG_EARLY);
      e_signal(H_O + tm, 2 * tn);
      STAMP_IF(lane == 0, 4);
      nb_sync(NB_H1, 160);
      e_store2d(&mp.m_os, tn * 128 + 64, tm * 128, STG + 16384);
      e_store2d(&mp.m_os, tn * 128 + 64, tm * 128 + 64, STG + 24576);
      bulk_wait_read();
      e_signal(H_O + tm, 2 * tn + 1);
      STAMP_IF(lane == 0, 5);
      nb_arrive(NB_ST, 288);
    } else if (w == 14) {
      e_pfmap(&mp.m_gu); e_pfmap(&mp.m_o); e_pfmap(&mp.m_os); e_pfmap(&mp.m_wo); e_pfmap(&mp.m_down); e_pfmap(&mp.m_out);
      const uint32_t ep = ld_relaxed(&g_epoch) + 1;
      nb_sync(NB_FDONE, 416);
      {
        uint32_t c[4];
        poll_quad(c, g_csum + tn * 128 + lane * 4, ep, 1u);
        sts128(S_CSQ + lane * 16, c[0], c[1], c[2], c[3]);
        nb_arrive(NB_CSQ, 160);
        poll_quad(c, g_csum + 1024 + tn * 128 + lane * 4, ep, 1u);
        sts128(S_CSV + lane * 16, c[0], c[1], c[2], c[3]);
        __syncwarp();
        e_arrive(B_CSV);
      }
      {
        mbar_wait(B_WK, 1);
        if (KV_SPEC) __nanosleep(KV_SPEC); else await(H_KV + tn, 0xffffu, ep);
        STAMP_IF(lane == 0, 7);
        if (bid < 112) mbar_wait(B_PFREE, 0);
        STAMP_IF(lane == 0, 23);
        uint32_t bad, ph = 0;
        do {
          e_expect(B_KVL, 8192);
          e_load(KVB + 1024, g_kv + tn * 512, 4096, B_KVL);
          e_load(KVB + 6144, g_kv + tn * 512 + 256, 4096, B_KVL);
          mbar_wait(B_KVL, ph & 1);
          bad = 0;
#pragma unroll
          for (int i = 0; i < 16; i++) bad |= __float_as_uint(lds32v(KVB + 1024 + (i & 8) * 128 + i * 512 + lane * 16)) ^ ep;
          bad = __any_sync(0xffffffffu, bad & 1u);
          if (bad) fence_async_smem();
        } while (bad && ++ph < 100000);
        nb_arrive(NB_KVB, 320);
        STAMP_IF(lane == 0, 24);
      }
      nb_sync(NB_Q0, 192);
      uint32_t ready = 0;
      int s = 0, ph = 1;
#pragma unroll 1
      for (int r = 2; r < 16; r++) {
        const int kb = out_kblock(r, tn);
        if (!((ready >> kb) & 1)) {
          uint32_t f[1];
          poll0(f, g_sig + (H_O + tm) * 32, 0u - (ep & 1u), 1u << kb);
          ready = f[0] ^ ((ep & 1u) - 1u);
        }
        if (r == 4) mbar_wait(B_DND, 0);
        refill_x(B_EMPTY + 8 * s, ph, B_FULL + 8 * s, RING + s * SLOT + 16384, &mp.m_o, kb * 64, tm * 128);
        STAMP_IF(lane == 0 && r == 2, 2);
        STAMP_IF(lane == 0 && r == 9, 3);
        if (++s == NST) { s = 0; ph ^= 1; }
      }
    } else {
      uint32_t nsm = 132;
      if (BY_SMID) asm volatile("mov.u32 %0, %%nsmid;" : "=r"(nsm));
      asm volatile("{\n.reg .pred q;\nsetp.eq.u32 q, %0, 1156;\n@q bra LOK;\ntrap;\nLOK:\n}" ::"r"((uint32_t)__cvta_generic_to_shared(smem_raw) + nsm));
      const uint32_t ep = ld_relaxed(&g_epoch) + 1;
      mbar_wait(B_CSDN, 0);
#pragma unroll 1
      for (int n = 0; n < 3 && bid < 112; n++) {
        __nanosleep(FFN_GAP);
        e_expect(B_FR + 8 * n, 8192);
        e_tma3d_ef(GR + n * 8192, &mp.m_gu, bid * 32, n * 64, B_FR + 8 * n, EVICT_FIRST);
      }
      if (bid < 112) {
        int s = 0, ph = 0;
#pragma unroll 1
        for (int n = 3; n < 16; n++) {
          refill_g(B_FE + 8 * s, ph, B_FR + 8 * s, GR + s * 8192, &mp.m_gu, bid * 32, n * 64);
          STAMP2(64 + n);
          if (++s == 3) { s = 0; ph ^= 1; }
        }
      }
      if (bid < 112) mbar_wait(B_FE, 1);
      e_expect(B_DR, 16384);
      e_tma2d_ef(AUX, &mp.m_down, (bid & 15) * 64, (bid >> 4) * 448, B_DR, EVICT_FIRST);
      e_tma2d_ef(AUX + 8192, &mp.m_down, (bid & 15) * 64, (bid >> 4) * 448 + 64, B_DR, EVICT_FIRST);
      {
        mbar_wait(B_WK, 1);
        if (bid < 112) mbar_wait(B_HGO, 0);
        await(H_H + (bid >> 4), 0x3fffu, ep);
        uint32_t bad, ph = 0;
        do {
          e_expect(B_HL, 7168);
          e_load(HOP, g_h + (bid >> 4) * 448, 6144, B_HL);
          e_load(S_CSK, g_h + (bid >> 4) * 448 + 384, 1024, B_HL);
          mbar_wait(B_HL, ph & 1);
          bad = 0;
#pragma unroll
          for (int i = 0; i < 14; i++) bad |= __float_as_uint(lds32v((i < 12 ? HOP : S_CSK - 6144) + i * 512 + lane * 16)) ^ ep;
          bad = __any_sync(0xffffffffu, bad & 1u);
          if (bad) fence_async_smem();
        } while (bad && ++ph < 100000);
        e_arrive(B_HOK);
      }
    }
  } else if (w >= 8) {
    asm volatile("setmaxnreg.dec.sync.aligned.u32 56;");
    const int t = tid - 256, ww = w - 8;
    const uint32_t ep = ld_relaxed(&g_epoch) + 1, par = ep & 1u;
    {
      const int r0 = (lane >> 3) + (lane & 4);
      const uint32_t a = FR + (ww >> 1) * 8192 + r0 * 128 + ((((ww & 1) * 4 + (lane & 3)) ^ r0) << 4);
      float c[8];
      reg_zero(c);
      mbar_wait(B_WK, 0);
#pragma unroll 2
      for (int i = 0; i < 8; i++) {
        const uint4 v = lds128(a + i * 1024);
        c[0] += bf_lo(v.x); c[1] += bf_hi(v.x); c[2] += bf_lo(v.y); c[3] += bf_hi(v.y);
        c[4] += bf_lo(v.z); c[5] += bf_hi(v.z); c[6] += bf_lo(v.w); c[7] += bf_hi(v.w);
      }
      const bool u16 = lane & 16, u8 = lane & 8, u4 = lane & 4;
      const float d0 = xred(c[0], c[4], u16, 16), d1 = xred(c[1], c[5], u16, 16), d2 = xred(c[2], c[6], u16, 16), d3 = xred(c[3], c[7], u16, 16);
      fence_async_smem();
      e_arrive(B_CSDN);
      const float sum = xred(xred(d0, d2, u8, 8), xred(d1, d3, u8, 8), u4, 4);
      st_relaxed(g_csum + (2 + tm) * 1024 + tn * 128 + ww * 32 + (lane & 3) * 8 + (lane >> 2), tagf(sum, par));
      STAMP_IF(t == 0, 8);
      nb_sync(NB_WG2, 128);
      if (ww == 0) { e_signal(H_CS + tn, tm); await(H_CS + tn, 0xffffu, ep); }
      nb_sync(NB_WG2, 128);
      uint32_t p[16];
      poll16(p, g_csum + 2048 + tn * 128 + t, par, 1u);
      float tot = 0.f;
#pragma unroll
      for (int i = 0; i < 16; i += 4) tot += (__uint_as_float(p[i]) + __uint_as_float(p[i + 1])) + (__uint_as_float(p[i + 2]) + __uint_as_float(p[i + 3]));
      sts32(S_CSK + t * 4, __float_as_uint(tot));
      nb_arrive(NB_FDONE, 416);
      STAMP_IF(t == 0, 9);
    }
    const int ks = bid >> 4, nt = bid & 15;
    uint32_t sel[2];
    poll_pair(sel, g_sel + (ks * 4 + ww) * 16 + (t >> 4), ep, 31u);
    if ((t & 15) == 0) sts64(S_SEL + (t >> 4) * 8, sel[0], sel[1]);
    if (bid >= 112) {
      nb_sync(NB_WG2, 128);
      if (t == 0) mbar_arrive(B_SEL);
    } else {
      const uint4* xs = reinterpret_cast<const uint4*>(mp.x + key_token(sel[0]) * 2048) + (t & 15);
      const uint32_t xd = AUX + (t & 8) * 128 + (t >> 4) * 128 + (((t ^ (t >> 4)) & 7) << 4), m2 = __byte_perm(sel[1], 0, 0x3232);
      uint4 v[4];
#pragma unroll
      for (int i = 0; i < 4; i++) v[i] = __ldg(xs + i * 16);
      float fg[4];
      reg_zero(fg);
      constexpr uint64_t DA0 = mkdesc(GR, 4096, 512, 2);
      uint64_t da = DA0;
      uint32_t bar = B_FR, ph = 0;
#pragma unroll 1
      for (int b = 0; b < 2; b++) {
        if (b) nb_sync(NB_WG2, 128);
#pragma unroll
        for (int i = 0; i < 4; i++) sts128(xd + i * 2048, sub2(v[i].x, m2), sub2(v[i].y, m2), sub2(v[i].z, m2), sub2(v[i].w, m2));
        fence_async_smem();
        nb_sync(NB_WG2, 128);
        if (!b) {
          if (t == 0) mbar_arrive(B_SEL);
#pragma unroll
          for (int i = 0; i < 4; i++) v[i] = __ldg(xs + 64 + i * 16);
        }
        uint64_t db = mkdesc(AUX, 16, 1024, 1);
#pragma unroll 1
        for (int n = 0; n < 8; n++) {
          mbar_wait(bar, ph);
          wg_fence();
#pragma unroll
          for (int q = 0; q < 4; q++) wgmma_n8_ss<1, 0>(fg, da + q * 64, db + q * 2, 1);
          wg_commit();
          const uint32_t rel = bar + (B_FE - B_FR);
          const bool wrap = bar == B_FR + 16;
          da = wrap ? DA0 : da + 512;
          db += 64;
          bar = wrap ? B_FR : bar + 8;
          ph ^= wrap;
          wg_wait<0>();
          if (t == 0) mbar_arrive(rel);
          if (t == 0 && b && n == 6) mbar_arrive(B_PFREE);
        }
      }
      const uint4 st = lds128(S_SEL + (lane & 3) * 16);
      const float r0 = rcp(bf_lo(st.y)), r1 = rcp(bf_lo(st.w));
      reg_fence(fg);
      const float fa[4] = {fg[0] * r0, fg[1] * r1, fg[2] * r0, fg[3] * r1};
      STAMP_IF(t == 0, 12);
      const bool isup = (ww >> 1) != (mp.wu < mp.wg);
      if (isup) sts128f(HOP + (t & 63) * 16, fa[0], fa[1], fa[2], fa[3]);
      nb_sync(NB_WG2, 128);
      if (!isup) {
        const float4 u = lds128f(HOP + (t & 63) * 16);
        const float uu[4] = {u.x, u.y, u.z, u.w};
        uint32_t hw[2];
#pragma unroll
        for (int i = 0; i < 2; i++)
          hw[i] = pack(fa[2 * i] * rcp(1.f + ex2(-fa[2 * i] * LOG2E)) * uu[2 * i], fa[2 * i + 1] * rcp(1.f + ex2(-fa[2 * i + 1] * LOG2E)) * uu[2 * i + 1]);
        const uint32_t ha = HOP + 1024 + (ww & 1) * 256 + (lane & 15) * 16;
        asm volatile("stmatrix.sync.aligned.m8n8.x2.trans.shared.b16 [%0], {%1,%2};" ::"r"(ha), "r"(hw[0]), "r"(hw[1]) : "memory");
        __syncwarp();
        const int tok = (lane >> 1) & 7, pc = (ww & 1) * 2 + (lane & 1);
        const uint4 hv = lds128(HOP + 1024 + pc * 128 + tok * 16);
        if (lane < 16) st_unit(g_h + bid * 32 + tok * 4 + (pc ^ (tok >> 1)), hv.x, hv.y, hv.z, hv.w, par);
      }
      fence_async_smem();
      nb_sync(NB_WG2, 128);
      if (ww == 0) { e_signal(H_H + bid / 14, bid % 14); e_arrive(B_HGO); }
    }
    mbar_wait(B_HOK, 0);
    STAMP_IF(t == 0, 13);
    float fa[4] = {0.f, 0.f, 0.f, 0.f};
    auto down = [&](uint32_t a, int k0, int nk) {
#pragma unroll
      for (int q = 0; q < nk; q++) wgmma_n8_ss<1, 0>(fa, mkdesc(a + q * 2048, 4096, 1024, 1), mkdesc((k0 < 24 ? HOP : S_CSK - 6144) + ((k0 + q) >> 1) * 512 + (q & 1) * 32, 16, 512, 2), 1);
    };
    mbar_wait(B_DR, 0);
    mbar_wait(B_DR + 16, 0);
    mbar_wait(B_DR + 8, 0);
    wg_fence();
    down(RING + 2 * SLOT + 16384, 24, 4);
    down(RING + 3 * SLOT + 16384, 8, 8);
    down(RING + 4 * SLOT + 16384, 16, 8);
    wg_commit();
    wg_fence();
    down(AUX, 0, 8);
    wg_commit();
    wg_wait<1>();
    if (t == 0) mbar_arrive(B_DND);
    wg_wait<0>();
    reg_fence(fa);
    STAMP_IF(t == 0, 14);
    {
      uint32_t* yp = g_yp + (nt * 8 + ks) * 512 + (lane & 3) * 128 + ww * 16 + (lane >> 2);
#pragma unroll
      for (int i = 0; i < 4; i++) st_relaxed(yp + (i & 1) * 64 + (i >> 1) * 8, tagf(fa[i], par));
    }
    nb_sync(NB_WG2, 128);
    if (ww == 0) e_signal(H_Y + (nt >> 1), (nt & 1) * 8 + ks);
    const uint32_t mykey = lds32(S_SEL + (lane & 7) * 8);
    const uint32_t inmask = __ballot_sync(0xffffffffu, (key_token(mykey) >> 7) == tm) & 0xffu;
    sts128(AUX + t * 16, 0u, 0u, 0u, 0u);
    if (inmask) {
      if (ww == 0) await(H_Y + tn, 0xffffu, ep);
      nb_sync(NB_WG2, 128);
      const float sg = rcp(1.f + ex2(-key_score(mykey) * LOG2E));
#pragma unroll 1
      for (uint32_t mine = __ballot_sync(0xffffffffu, ((inmask >> lane) & 1) && (__popc(inmask & ((1u << lane) - 1)) & 3) == ww); mine; mine &= mine - 1) {
        const int j = __ffs(mine) - 1;
        uint32_t p[32];
        poll8x4(p, g_yp + (tn * 2 + (lane >> 4)) * 4096 + j * 64 + (lane & 15) * 4, par, 1u);
        float y[4];
        const float sj = __shfl_sync(0xffffffffu, sg, j);
#pragma unroll
        for (int i = 0; i < 4; i++)
          y[i] = sj * (((__uint_as_float(p[i]) + __uint_as_float(p[4 + i])) + (__uint_as_float(p[8 + i]) + __uint_as_float(p[12 + i]))) +
                       ((__uint_as_float(p[16 + i]) + __uint_as_float(p[20 + i])) + (__uint_as_float(p[24 + i]) + __uint_as_float(p[28 + i]))));
        asm volatile("st.shared.v2.u32 [%0], {%1,%2};" ::"r"(AUX + (lane >> 4) * 1024 + j * 128 + ((((lane >> 1) & 7) ^ j) << 4) + (lane & 1) * 8),
                     "r"(pack(y[0], y[1])), "r"(pack(y[2], y[3])) : "memory");
      }
    }
    fence_async_smem();
    nb_arrive(NB_ST, 288);
    STAMP_IF(t == 0, 15);
  } else if (w >= 4) {
    asm volatile("setmaxnreg.inc.sync.aligned.u32 208;");
    const int t = tid - 128, ww = w - 4, g = lane >> 2, t4 = lane & 3;
    const bool leader = t == 0;
    const uint32_t ep = ld_relaxed(&g_epoch) + 1, par = ep & 1u;
    {
      const uint4* wp = reinterpret_cast<const uint4*>(mp.w_r) + lane;
      uint4 w0 = __ldg(wp), w1 = __ldg(wp + 32), w2 = __ldg(wp + 64), w3 = __ldg(wp + 96);
      if (leader) sts32(S_EPOCH, ep);
      if (KV_SPEC && t4 == 0) {
        const int grp = (tm & 1) * 2 + ((lane >> 3) & 1), row = ww * 2 + ((lane >> 2) & 1);
        st_unit(g_kv + tn * 512 + ((tm >> 3) * 4 + grp) * 64 + row * 8 + (((tm & 2) * 2 + ((tm >> 1) & 2) + (lane >> 4)) ^ row), 0u, 0u, 0u, 0u, par ^ 1u);
      }
      float s[4] = {0.f, 0.f, 0.f, 0.f}, q[4] = {0.f, 0.f, 0.f, 0.f}, d[4] = {0.f, 0.f, 0.f, 0.f}, wsum = 0.f;
#pragma unroll 1
      for (int c = 0; c < 4; c++) {
        const float wr[8] = {bf_lo(w0.x), bf_hi(w0.x), bf_lo(w0.y), bf_hi(w0.y), bf_lo(w0.z), bf_hi(w0.z), bf_lo(w0.w), bf_hi(w0.w)};
        w0 = w1; w1 = w2; w2 = w3;
        wsum += ((wr[0] + wr[1]) + (wr[2] + wr[3])) + ((wr[4] + wr[5]) + (wr[6] + wr[7]));
        mbar_wait(B_XS + 8 * c, 0);
#pragma unroll
        for (int r = 0; r < 4; r++) {
          const uint4 v = lds128(STG + c * 8192 + (ww * 4 + r) * 512 + lane * 16);
          const uint32_t xw[4] = {v.x, v.y, v.z, v.w};
#pragma unroll
          for (int i = 0; i < 4; i++) {
            const uint32_t dep = __float_as_uint(q[i ? r : (r + 3) & 3]);
            const float lo = __uint_as_float(prmt(xw[i], dep, 0x10ff)), hi = __uint_as_float(prmt(xw[i], dep, 0x32ff));
            s[r] += lo; q[r] = fmaf(lo, lo, q[r]); d[r] = fmaf(lo, wr[2 * i], d[r]);
            s[r] += hi; q[r] = fmaf(hi, hi, q[r]); d[r] = fmaf(hi, wr[2 * i + 1], d[r]);
          }
        }
      }
      STAMP_IF(leader, 16);
      const bool u16 = lane & 16, u8 = lane & 8, u4 = lane & 4, u2 = lane & 2;
      const float s1 = xred(xred(s[0], s[2], u16, 16), xred(s[1], s[3], u16, 16), u8, 8);
      const float q1 = xred(xred(q[0], q[2], u16, 16), xred(q[1], q[3], u16, 16), u8, 8);
      const float d1 = xred(xred(d[0], d[2], u16, 16), xred(d[1], d[3], u16, 16), u8, 8);
      wsum += __shfl_xor_sync(0xffffffffu, wsum, 16);
      wsum += __shfl_xor_sync(0xffffffffu, wsum, 8);
      float tot = xred(xred(s1, d1, u4, 4), xred(q1, wsum, u4, 4), u2, 2);
      tot += __shfl_xor_sync(0xffffffffu, tot, 1);
      const float qq = __shfl_down_sync(0xffffffffu, tot, 2), dd = __shfl_down_sync(0xffffffffu, tot, 4), ws = __shfl_down_sync(0xffffffffu, tot, 6);
      if ((lane & 7) == 0) {
        const float mean = tot * (1.f / 1024.f);
        const float var = fmaxf(fmaf(-mean, mean, qq * (1.f / 1024.f)), 0.f);
        float sd;
        asm("sqrt.approx.ftz.f32 %0, %1;" : "=f"(sd) : "f"(bf_round(bf_round(var) + 1e-5f)));
        const uint32_t ms = pack(sd, mean);
        const int row = tm * 128 + tn * 16 + ww * 4 + (lane >> 3);
        const uint32_t rbits = pack(0.f, fmaf(-bf_hi(ms), ws, dd) * rcp(bf_lo(ms)));
        const uint32_t key = (rbits ^ (((int)rbits >> 31 & 0x7fff0000u) | 0x80000000u)) | ((2047 - row) << 5) | (ep & 31u);
        asm volatile("{\n.reg .b64 x;\nmov.b64 x, {%1,%2};\nst.relaxed.gpu.global.b64 [%0], x;\n}" ::"l"(g_keys + row), "r"(key), "r"(ms) : "memory");
      }
      STAMP_IF(leader, 17);
      __nanosleep(400);
      uint32_t st[2];
      poll_pair(st, g_keys + tm * 128 + t, ep, 31u);
      asm volatile("st.shared.v2.f32 [%0], {%1,%2};" ::"r"(S_KSTAT + t * 8), "f"(bf_hi(st[1])), "f"(rcp(bf_lo(st[1])) * LOG2E) : "memory");
      nb_arrive(NB_FDONE, 416);
      STAMP_IF(leader, 10);
    }
    float a0[64], a1[64];
    reg_zero(a0); reg_zero(a1); reg_fence(a0); reg_fence(a1);
    STAMP_IF(leader, 18);
    nb_sync(NB_KV, 256);
    mainloop<true, 14>(a0, a1, 1, 1, 0, 0, leader);
    {
      auto half = [&](float (&a)[64], int s, int m) {
#pragma unroll
        for (int j = 0; j < 4; j++)
          wgmma_n128_ss<1, 0>(a, mkdesc(RING + s * SLOT + m * 8192 + j * 2048, 8192, 1024, 1), mkdesc(RING + s * SLOT + 16384 + j * 32, 16, 1024, 1), 1);
      };
      auto kvmma = [&](float (&a)[64], float (&c)[32], int m) {
        reg_fence(a);
        uint32_t f[32];
#pragma unroll
        for (int i = 0; i < 32; i++) f[i] = pack(a[2 * i], a[2 * i + 1]);
        reg_zero(c);
        wg_fence();
#pragma unroll
        for (int k = 0; k < 8; k++) {
          wgmma_n64_rs<0>(c, f[4 * k], f[4 * k + 1], f[4 * k + 2], f[4 * k + 3], mkdesc(STG + (k >> 2) * 16384 + m * 8192 + (k & 3) * 32, 16, 1024, 1), k != 0);
          if (m && k == HAND_K) nb_arrive(NB_VQ, 256);
        }
        wg_commit();
      };
      float c0[32], c1[32];
      mbar_wait(B_FULL, 0);
      wg_fence();
      half(a0, 0, 0);
      wg_commit();
      mbar_wait(B_FULL + 8, 0);
      wg_fence();
      half(a0, 1, 0);
      wg_commit();
      wg_wait<2>();
      if (leader) mbar_arrive(B_EMPTY + 32);
      wg_fence();
      half(a1, 0, 1);
      half(a1, 1, 1);
      wg_commit();
      nb_sync(NB_WG0, 256);
      wg_wait<1>();
      kvmma(a0, c0, 0);
      nb_sync(NB_PK, 256);
      wg_wait<1>();
      if (leader) { mbar_arrive(B_EMPTY); mbar_arrive(B_EMPTY + 8); }
      STAMP_IF(leader, 19);
      kvmma(a1, c1, 1);
      const bool hp = ww >> 1;
      float c[4];
      float2 tt[8];
#pragma unroll
      for (int i = 0; i < 8; i++) tt[i] = lds64f(S_CSK + ((i >> 2) * 64 + hp * 32 + (i & 3) * 8 + 2 * t4) * 4);
      mbar_wait(B_CSV, 0);
#pragma unroll
      for (int i = 0; i < 4; i++) c[i] = -__uint_as_float(lds32(S_CSV + ((i >> 1) * 64 + ww * 16 + (i & 1) * 8 + g) * 4));
      wg_wait<0>();
      reg_fence(c0);
      reg_fence(c1);
      if (leader) mbar_arrive(B_SFREE);
      STAMP_IF(leader, 20);
      uint4* pp = g_kvp + (tn * 16 + tm) * 512 + t;
      auto put = [&](int q, const float* d) {
        const float ca = c[q & 2], cb = c[q | 1];
        const float2 ta = tt[2 * q], tb = tt[2 * q + 1];
        st_unit(pp + q * 128, pack(fmaf(ca, ta.x, d[0]), fmaf(ca, ta.y, d[1])), pack(fmaf(cb, ta.x, d[2]), fmaf(cb, ta.y, d[3])),
                pack(fmaf(ca, tb.x, d[4]), fmaf(ca, tb.y, d[5])), pack(fmaf(cb, tb.x, d[6]), fmaf(cb, tb.y, d[7])), par);
      };
      if (!hp) { put(0, c0); put(1, c0 + 8); put(2, c1); put(3, c1 + 8); }
      else { put(0, c0 + 16); put(1, c0 + 24); put(2, c1 + 16); put(3, c1 + 24); }
      STAMP_IF(leader, 47);
      {
        uint32_t p[16];
        nb_sync(NB_WG1, 128);
        if (ww == 0) { e_signal(H_KVP + tn, tm); await(H_KVP + tn, 0xffffu, ep); }
        nb_sync(NB_WG1, 128);
        STAMP_IF(leader, 1);
        poll_kvp(p, g_kvp + (tn * 16 + (lane >> 3) * 4) * 512 + tm * 32 + ww * 8 + (lane & 7), par, 1u);
        float r[8];
#pragma unroll
        for (int i = 0; i < 4; i++) {
          r[2 * i] = (bf_lo(p[i]) + bf_lo(p[4 + i])) + (bf_lo(p[8 + i]) + bf_lo(p[12 + i]));
          r[2 * i + 1] = (bf_hi(p[i]) + bf_hi(p[4 + i])) + (bf_hi(p[8 + i]) + bf_hi(p[12 + i]));
        }
        const bool u16 = lane & 16, u8 = lane & 8;
        const uint32_t wd = pack(xred(xred(r[0], r[4], u16, 16), xred(r[2], r[6], u16, 16), u8, 8), xred(xred(r[1], r[5], u16, 16), xred(r[3], r[7], u16, 16), u8, 8));
        const uint32_t w1 = __shfl_down_sync(0xffffffffu, wd, 1), w2 = __shfl_down_sync(0xffffffffu, wd, 2), w3 = __shfl_down_sync(0xffffffffu, wd, 3);
        const int grp = (tm & 1) * 2 + ((lane >> 3) & 1), row = ww * 2 + ((lane >> 2) & 1);
        if (t4 == 0) st_unit(g_kv + tn * 512 + ((tm >> 3) * 4 + grp) * 64 + row * 8 + (((tm & 2) * 2 + ((tm >> 1) & 2) + (lane >> 4)) ^ row), wd, w1, w2, w3, par);
        nb_sync(NB_WG1, 128);
        if (ww == 0) { if (!KV_SPEC) e_signal(H_KV + tn, tm); e_arrive(B_WK); }
      }
      STAMP_IF(leader, 21);
    }
    const uint32_t sx = lane & 7, sc = lane >> 4;
    const uint32_t sa = STG + (ww * 16 + (lane & 15)) * 128;
    const uint32_t sw[4] = {sa + ((sc ^ sx) << 4), sa + (((2 + sc) ^ sx) << 4), sa + (((4 + sc) ^ sx) << 4), sa + (((6 + sc) ^ sx) << 4)};
    auto residual = [&]() {
      float ka[4], kb[4];
#pragma unroll
      for (int i = 0; i < 4; i++) {
        const float2 st = lds64f(S_KSTAT + ((i >> 1) * 64 + ww * 16 + (i & 1) * 8 + g) * 8);
        const float r = st.y * LN2;
        ka[i] = 1.f + r; kb[i] = -st.x * r;
      }
#pragma unroll
      for (int j = 0; j < 8; j++) {
        if ((j & 3) == 0) mbar_wait(B_XRES + 8 * (j >> 2), 0);
        const uint4 v = ldsm4(sw[j & 3] + (j >> 2) * 16384), u = ldsm4(sw[j & 3] + (j >> 2) * 16384 + 8192);
        const uint32_t vv[4] = {v.x, v.y, v.z, v.w}, uu[4] = {u.x, u.y, u.z, u.w};
#pragma unroll
        for (int i = 0; i < 4; i++) {
          a0[8 * j + 2 * i] = fmaf(bf_lo(vv[i]), ka[i & 1], kb[i & 1]);
          a0[8 * j + 2 * i + 1] = fmaf(bf_hi(vv[i]), ka[i & 1], kb[i & 1]);
          a1[8 * j + 2 * i] = fmaf(bf_lo(uu[i]), ka[2 + (i & 1)], kb[2 + (i & 1)]);
          a1[8 * j + 2 * i + 1] = fmaf(bf_hi(uu[i]), ka[2 + (i & 1)], kb[2 + (i & 1)]);
        }
      }
      reg_fence(a0);
      reg_fence(a1);
      STAMP_IF(leader, 22);
    };
    residual();
    nb_arrive(NB_KVB, 320);
    uint32_t oh[4];
    {
      mbar_wait(B_SEL, 0);
      const int r0 = key_token(lds32(S_SEL + t4 * 16)) - tm * 128, r1 = key_token(lds32(S_SEL + t4 * 16 + 8)) - tm * 128;
#pragma unroll
      for (int i = 0; i < 4; i++) {
        const int row = (i >> 1) * 64 + ww * 16 + (i & 1) * 8 + g;
        oh[i] = (r0 == row ? 0x3f00u : 0u) | (r1 == row ? 0x3f000000u : 0u);
      }
    }
    uint32_t va = RING + 16384 + sc * 8192 + (ww * 16 + (lane & 8)) * 128 + sx * 16 + (lane >> 3) * 4;
    asm volatile("" : "+r"(va));
    {
      auto own = [&](int r) {
        nb_sync(r ? NB_OWN1 : NB_Y, 256);
        mbar_wait(B_FULL + 8 * (3 + r), 1);
        STAMP_IF(leader, 25 + r);
        const uint64_t dw = mkdesc(RING + (3 + r) * SLOT, 8192, 1024, 1), dx = mkdesc(STG + r * 16384, 16, 1024, 1);
        wg_fence();
#pragma unroll
        for (int j = 0; j < 4; j++) {
          wgmma_n128_ss<0, 1>(a0, dx + j * 2, dw + j * 128, 1);
          wgmma_n128_ss<0, 1>(a1, dx + j * 2 + 512, dw + j * 128, 1);
        }
        wg_commit();
      };
      own(0);
      own(1);
      wg_wait<1>();
      if (leader) mbar_arrive(B_EMPTY + 24);
      auto check = [&](int r, int s) {
          uint32_t bad;
          asm volatile("{\n.reg .u32 a, b, c, d, e, f, g, h;\n.reg .pred p;\n"
                       "ld.shared.u32 a, [%1];\nld.shared.u32 b, [%1+128];\nld.shared.u32 c, [%1+256];\nld.shared.u32 d, [%1+384];\n"
                       "ld.shared.u32 e, [%1+512];\nld.shared.u32 f, [%1+640];\nld.shared.u32 g, [%1+768];\nld.shared.u32 h, [%1+896];\n"
                       "lop3.b32 a, a, b, %2, 0x7e;\nlop3.b32 c, c, d, %2, 0x7e;\nlop3.b32 e, e, f, %2, 0x7e;\nlop3.b32 g, g, h, %2, 0x7e;\n"
                       "lop3.b32 a, a, c, e, 0xfe;\nlop3.b32 a, a, g, 1, 0xa8;\nsetp.ne.u32 p, a, 0;\nvote.sync.any.pred p, p, 0xffffffff;\nselp.u32 %0, 1, 0, p;\n}"
                       : "=r"(bad) : "r"(va + s * SLOT), "r"(par) : "memory");
          if (__builtin_expect(bad, 0)) {
            const uint4* src = reinterpret_cast<const uint4*>(g_o + (tm * 128 + sc * 64 + ww * 16 + (lane & 15)) * 1024 + out_kblock(r, tn) * 64);
#pragma unroll 1
            for (int i = 0; i < 8; i++) {
              uint32_t v[4];
              asm volatile("{\n.reg .b64 x, y;\n.reg .b128 z;\n.reg .pred p, q, h;\n.reg .u32 c, b;\nmov.u32 c, 0;\nsetp.ne.u32 h, %6, 0;\nLW:\n"
                           "ld.relaxed.gpu.global.b128 z, [%4];\nmov.b128 {x, y}, z;\nmov.b64 {%0,%1}, x;\nmov.b64 {%2,%3}, y;\n"
                           "selp.b64 x, y, x, h;\nshr.b64 x, x, %7;\ncvt.u32.u64 b, x;\nand.b32 b, b, 1;\nsetp.eq.u32 p, b, %5;\n"
                           "vote.sync.all.pred p, p, 0xffffffff;\n@p bra.uni LD;\nadd.u32 c, c, 1;\nsetp.lt.u32 q, c, 1000000;\n@q bra.uni LW;\ntrap;\nLD:\n}"
                           : "=&r"(v[0]), "=&r"(v[1]), "=&r"(v[2]), "=&r"(v[3]) : "l"(src + i), "r"(par), "r"(sc), "r"((lane & 8) * 4) : "memory");
              sts128(RING + 16384 + s * SLOT + sc * 8192 + (ww * 16 + (lane & 15)) * 128 + ((i ^ sx) << 4), v[0], v[1], v[2], v[3]);
            }
            fence_async_smem();
            __syncwarp();
          }
      };
      int s = 0, ph = 0;
      uint32_t prev = B_EMPTY + 32;
#pragma unroll 1
      for (int r = 2; r < 12; r++) {
        mbar_wait(B_FULL + 8 * s, ph);
        check(r, s);
        if (!LITE || ((LITE_MASK >> 27) & 1)) STAMP_IF(leader && r == 2, 27);
        const uint64_t dw = mkdesc(RING, 8192, 1024, 1) + s * (SLOT >> 4), dx = mkdesc(RING + 16384, 16, 1024, 1) + s * (SLOT >> 4);
        wg_fence();
#pragma unroll
        for (int j = 0; j < 4; j++) {
          wgmma_n128_ss<0, 1>(a0, dx + j * 2, dw + j * 128, 1);
          wgmma_n128_ss<0, 1>(a1, dx + j * 2 + 512, dw + j * 128, 1);
        }
        wg_commit();
        wg_wait<1>();
        if (leader) mbar_arrive(prev);
        prev = B_EMPTY + 8 * s;
        if (++s == NST) { s = 0; ph ^= 1; }
      }
      auto half = [&](float (&a)[64], int s, int m) {
        const uint64_t dw = mkdesc(RING, 8192, 1024, 1) + s * (SLOT >> 4), dx = mkdesc(RING + 16384 + m * 8192, 16, 1024, 1) + s * (SLOT >> 4);
#pragma unroll
        for (int j = 0; j < 4; j++) wgmma_n128_ss<0, 1>(a, dx + j * 2, dw + j * 128, 1);
      };
      auto store = [&](float (&a)[64], int m, int c) {
#pragma unroll
        for (int i = 0; i < 32; i++) asm volatile("" : "+f"(a[32 * c + i])::"memory");
#pragma unroll
        for (int j = 4 * c; j < 4 * c + 4; j++)
          stsm4(sw[j & 3] + c * 16384 + m * 8192, pack(a[8 * j], a[8 * j + 1]), pack(a[8 * j + 2], a[8 * j + 3]), pack(a[8 * j + 4], a[8 * j + 5]), pack(a[8 * j + 6], a[8 * j + 7]));
        fence_async_smem();
        e_store2d(&mp.m_out, tn * 128 + c * 64, tm * 128 + m * 64 + ww * 16, STG + c * 16384 + m * 8192 + ww * 2048);
      };
#pragma unroll 1
      for (int q = 0; q < 4; q++) {
        mbar_wait(B_FULL + 8 * q, 0);
        check(12 + q, q);
        wg_fence();
        half(a0, q, 0);
        wg_commit();
      }
      nb_sync(NB_ST, 288);
      wg_fence();
      wgmma_n128_rs<1>(a0, oh[0], oh[1], oh[0], oh[1], mkdesc(AUX, 1024, 0, 1), 1);
      wg_commit();
      wg_fence();
      half(a1, 0, 1);
      half(a1, 1, 1);
      wg_commit();
      wg_wait<1>();
      store(a0, 0, 0);
      store(a0, 0, 1);
      wg_fence();
      half(a1, 2, 1);
      half(a1, 3, 1);
      wgmma_n128_rs<1>(a1, oh[2], oh[3], oh[2], oh[3], mkdesc(AUX, 1024, 0, 1), 1);
      wg_commit();
      wg_wait<0>();
      STAMP_IF(leader, 28);
      store(a1, 1, 0);
      store(a1, 1, 1);
    }
    bulk_wait_read();
    if (bid == 0 && leader) st_relaxed(&g_epoch, ep);
    STAMP_IF(leader, 29);
  } else {
    asm volatile("setmaxnreg.inc.sync.aligned.u32 216;");
    const int g = lane >> 2, t4 = lane & 3;
    const bool leader = tid == 0;
    const uint32_t sx = lane & 7, sc = lane >> 4;
    const uint32_t sa = STG + (w * 16 + (lane & 15)) * 128;
    const uint32_t sw[4] = {sa + ((sc ^ sx) << 4), sa + (((2 + sc) ^ sx) << 4), sa + (((4 + sc) ^ sx) << 4), sa + (((6 + sc) ^ sx) << 4)};
    float a0[64], a1[64];
    reg_zero(a0); reg_zero(a1); reg_fence(a0); reg_fence(a1);
    mainloop<true>(a0, a1, 0, 0, NB_KV, 0, leader);
    STAMP_IF(leader, 33);
    {
      nb_sync(NB_FDONE, 416);
      STAMP_IF(leader, 34);
      const uint32_t par = lds32(S_EPOCH) & 1u;
#pragma unroll 1
      for (int m = 0;; m++) {
        const uint32_t ca = S_CSK + (m * 64 + w * 16 + g) * 4;
        const float c[2] = {-lds32v(ca), -lds32v(ca + 32)};
        float z[2] = {0.f, 0.f}, tt[2] = {0.f, 0.f};
        float4 n0, n1;
        if (KPF) { n0 = lds128v(S_KSTAT + 2 * t4 * 8); n1 = lds128v(S_KSTAT + (8 + 2 * t4) * 8); }
#pragma unroll
        for (int j = 0; j < 8; j++) {
          if (!KPF) { n0 = lds128v(S_KSTAT + (j * 16 + 2 * t4) * 8); n1 = lds128v(S_KSTAT + (j * 16 + 8 + 2 * t4) * 8); }
          const float mu[4] = {n0.x, n0.z, n1.x, n1.z}, rl[4] = {n0.y, n0.w, n1.y, n1.w};
          if (KPF && j < 7) { n0 = lds128v(S_KSTAT + (j * 16 + 16 + 2 * t4) * 8); n1 = lds128v(S_KSTAT + (j * 16 + 24 + 2 * t4) * 8); }
          float p[8];
#pragma unroll
          for (int i = 0; i < 8; i++) {
            const int r = (i >> 1) & 1, cc = (i >> 2) * 2 + (i & 1);
            p[i] = phi2(fmaf(c[r], mu[cc], a0[8 * j + i]) * rl[cc]);
            z[r] += p[i];
            p[i] *= rl[cc];
            tt[r] = fmaf(p[i], mu[cc], tt[r]);
          }
          stsm4(sw[j & 3] + (j >> 2) * 16384 + m * 8192, pack(p[0], p[1]), pack(p[2], p[3]), pack(p[4], p[5]), pack(p[6], p[7]));
        }
        const bool u2 = lane & 2, u1 = lane & 1;
        const float v = xred(xred(z[0], tt[0], u2, 2), xred(z[1], tt[1], u2, 2), u1, 1);
        if (u2) sts32(ca + (t4 & 1) * 32, __float_as_uint(v));
        else st_relaxed(g_z + tm * 1024 + tn * 128 + m * 64 + w * 16 + t4 * 8 + g, tagf(v * LOG2E, par));
        if (m) break;
        fence_async_smem();
        nb_arrive(NB_WG0, 256);
#pragma unroll
        for (int i = 0; i < 64; i++) a0[i] = a1[i];
      }
      fence_async_smem();
      nb_arrive(NB_PK, 256);
      nb_arrive(NB_Z, 160);
    }
    STAMP_IF(leader, 35);
    const uint32_t ep = lds32(S_EPOCH);
    uint32_t sd2[4];
    float es[4];
    {
      nb_sync(NB_CSQ, 160);
      float mu[4];
#pragma unroll
      for (int i = 0; i < 4; i++) {
        const float2 st = lds64f(S_KSTAT + ((i >> 1) * 64 + w * 16 + (i & 1) * 8 + g) * 8);
        mu[i] = -st.x;
        const float sd = LOG2E * rcp(st.y);
        sd2[i] = pack(sd, sd);
        es[i] = sd * (1e-6f * LOG2E);
      }
#pragma unroll
      for (int j = 0; j < 16; j++) {
        const float2 c = lds64f(S_CSQ + (j * 8 + 2 * t4) * 4);
        a0[4 * j] = mu[0] * c.x; a0[4 * j + 1] = mu[0] * c.y; a0[4 * j + 2] = mu[1] * c.x; a0[4 * j + 3] = mu[1] * c.y;
        a1[4 * j] = mu[2] * c.x; a1[4 * j + 1] = mu[2] * c.y; a1[4 * j + 2] = mu[3] * c.x; a1[4 * j + 3] = mu[3] * c.y;
      }
      reg_fence(a0); reg_fence(a1);
    }
    STAMP_IF(leader, 40);
    nb_sync(NB_VQ, 256);
    mainloop<false, 13>(a0, a1, 2, 0, 0, 4 + (tn & 3), leader);
    {
      uint32_t f[2][16];
      const uint32_t ra = S_KSTAT + (w * 16 + g) * 8 + 4;
      auto phi = [&](const float (&a)[64], int off, int m, int i0, int i1, uint32_t (&o)[16]) {
        const float r0 = lds32v(ra + m * 512), r1 = lds32v(ra + m * 512 + 64);
#pragma unroll
        for (int i = i0; i < i1; i++) o[i] = phi_pack(a[off + 2 * i], a[off + 2 * i + 1], i & 1 ? r1 : r0, sd2[2 * m + (i & 1)]);
      };
      auto half = [&](float (&a)[64], int s, int m) {
        const bool xr = ((13 + s) >> 1) == 4 + (tn & 3);
        if (!m) {
          mbar_wait(B_FULL + 8 * s, 1);
          if (xr) mbar_wait(B_XRES + 8 * (~s & 1), 0);
          wg_fence();
        }
        const uint64_t dx = mkdesc(m * 8192, 16, 1024, 1) + ((xr ? STG + (~s & 1) * 16384 : RING + s * SLOT + 16384) >> 4);
#pragma unroll
        for (int j = 0; j < 4; j++) wgmma_n128_ss<0, 1>(a, dx + j * 2, mkdesc(RING + s * SLOT + j * 2048, 8192, 1024, 1), 1);
      };
      half(a0, 0, 0);
      wg_commit();
      half(a0, 1, 0);
      wg_commit();
      wg_wait<2>();
      if (leader) mbar_arrive(B_EMPTY + 32);
      half(a0, 2, 0);
      wg_commit();
      wg_fence();
      half(a1, 0, 1);
      half(a1, 1, 1);
      wg_commit();
      wg_wait<1>();
      reg_fence(a0);
      phi(a0, 0, 0, 0, PHI_CUT, f[0]);
      wg_fence();
      half(a1, 2, 1);
      wg_commit();
      phi(a0, 0, 0, PHI_CUT, 16, f[0]);
      nb_sync(NB_KVB, 320);
      wg_wait<0>();
      if (leader) { mbar_arrive(B_EMPTY); mbar_arrive(B_EMPTY + 8); mbar_arrive(B_EMPTY + 16); }
      reg_fence(a1);
      STAMP_IF(leader, 36);
      const uint32_t mk[4] = {t4 == 0, t4 == 1, t4 == 2, t4 == 3};
      uint64_t db = mkdesc(KVB, 16, 1024, 1);
      uint32_t so = 0;
#pragma unroll 1
      for (int j = 0;; j++) {
        float oc[2][2][20];
        auto mma = [&](const uint32_t (&a)[16], float (&o)[2][20]) {
          reg_zero(o[0]); reg_zero(o[1]);
          wg_fence();
          wgmma_n40_rs<0>(o[0], a[0], a[1], a[2], a[3], db, 0);
          wgmma_n40_rs<0>(o[1], a[8], a[9], a[10], a[11], db + 4, 0);
          wgmma_n40_rs<0>(o[0], a[4], a[5], a[6], a[7], db + 2, 1);
          wgmma_n40_rs<0>(o[1], a[12], a[13], a[14], a[15], db + 6, 1);
          wg_commit();
        };
        auto fin = [&](int m, float (&o)[2][20]) {
          const uint32_t m0 = mk[2 * m], m1 = mk[2 * m + 1];
#pragma unroll
          for (int h = 0; h < 2; h++) {
            const float r0 = rcp(o[h][0] + es[2 * m]), r1 = rcp(o[h][2] + es[2 * m + 1]);
            {
#pragma unroll
              for (int q = 0; q < 2; q++)
                stsm4(sw[h * 2 + q] + so + m * 8192,
                      bsel(pack(o[h][4 + 8 * q] * r0, o[h][5 + 8 * q] * r0), ep, m0), bsel(pack(o[h][6 + 8 * q] * r1, o[h][7 + 8 * q] * r1), ep, m1),
                      bsel(pack(o[h][8 + 8 * q] * r0, o[h][9 + 8 * q] * r0), ep, m0), bsel(pack(o[h][10 + 8 * q] * r1, o[h][11 + 8 * q] * r1), ep, m1));
            }
          }
        };
        mma(f[0], oc[0]);
        if (j) nb_arrive(NB_Y, 256);
        phi(a1, 0, 1, 0, 16, f[1]);
        wg_wait<0>();
        reg_fence(oc[0][0]); reg_fence(oc[0][1]);
        mma(f[1], oc[1]);
        fin(0, oc[0]);
        if (j == 0) { fence_async_smem(); nb_arrive(NB_Q0, 192); }
        wg_wait<0>();
        reg_fence(oc[1][0]); reg_fence(oc[1][1]);
        fin(1, oc[1]);
        fence_async_smem();
        if (j) break;
        nb_arrive(NB_OWN0, 160);
        STAMP_IF(leader, 38);
#pragma unroll
        for (int i = 0; i < 32; i++) a1[i] = a1[32 + i];
        phi(a0, 32, 0, 0, 16, f[0]);
        db = mkdesc(KVB + 5120, 16, 1024, 1);
        so = 16384;
      }
      nb_arrive(NB_OWN1, 256);
      nb_arrive(NB_H1, 160);
      STAMP_IF(leader, 39);
    }
  }
}

#undef CK
typedef CUresult (*EncodeFn)(CUtensorMap*, CUtensorMapDataType, cuuint32_t, void*, const cuuint64_t*, const cuuint64_t*, const cuuint32_t*,
                             const cuuint32_t*, CUtensorMapInterleave, CUtensorMapSwizzle, CUtensorMapL2promotion, CUtensorMapFloatOOBfill);

void make_map(EncodeFn enc, CUtensorMap* m, const void* p, int rank, uint64_t d0, uint64_t d1, uint64_t d2, uint64_t s1, uint64_t s2,
              uint32_t b0, uint32_t b1, uint32_t b2, CUtensorMapSwizzle sw) {
  cuuint64_t gd[3] = {d0, d1, d2}, gs[2] = {s1, s2};
  cuuint32_t bd[3] = {b0, b1, b2}, es[3] = {1, 1, 1};
  enc(m, CU_TENSOR_MAP_DATA_TYPE_BFLOAT16, rank, const_cast<void*>(p), gd, gs, bd, es, CU_TENSOR_MAP_INTERLEAVE_NONE, sw,
      CU_TENSOR_MAP_L2_PROMOTION_L2_128B, CU_TENSOR_MAP_FLOAT_OOB_FILL_NONE);
}

}

extern "C" void kernel_launch(void* const* d_in, const int* in_sizes, int n_in, void* d_out, int out_size) {
  (void)in_sizes; (void)n_in; (void)out_size;
  void* fn = nullptr;
  cudaDriverEntryPointQueryResult qr;
  cudaGetDriverEntryPoint("cuTensorMapEncodeTiled", &fn, cudaEnableDefault, &qr);
  EncodeFn enc = (EncodeFn)fn;
  void* o;
  cudaGetSymbolAddress(&o, g_o);
  const CUtensorMapSwizzle S128 = CU_TENSOR_MAP_SWIZZLE_128B, S64 = CU_TENSOR_MAP_SWIZZLE_64B, S0 = CU_TENSOR_MAP_SWIZZLE_NONE;
  Params mp;
  mp.x = (const char*)d_in[0]; mp.w_r = (const char*)d_in[4];
  mp.wg = (const char*)d_in[5]; mp.wu = (const char*)d_in[6]; mp.wd = (const char*)d_in[7];
  make_map(enc, &mp.m_wqkv, d_in[1], 3, 64, 1024, 48, 6144, 128, 64, 64, 2, S128);
  make_map(enc, &mp.m_x, d_in[0], 2, 1024, 2048, 1, 2048, 0, 64, 128, 1, S128);
  make_map(enc, &mp.m_os, o, 2, 1024, 2048, 1, 2048, 0, 64, 64, 1, S128);
  make_map(enc, &mp.m_o, o, 2, 1024, 2048, 1, 2048, 0, 64, 128, 1, S128);
  make_map(enc, &mp.m_wo, d_in[2], 3, 64, 1024, 16, 2048, 128, 64, 64, 2, S128);
  make_map(enc, &mp.m_xs, d_in[0], 2, 1024, 2048, 1, 2048, 0, 256, 16, 1, S0);
  const char *wg = (const char*)d_in[5], *wu = (const char*)d_in[6];
  make_map(enc, &mp.m_gu, wu < wg ? wu : wg, 3, 3584, 1024, 2, 7168, (uint64_t)(wu < wg ? wg - wu : wu - wg), 32, 64, 2, S64);
  make_map(enc, &mp.m_down, d_in[7], 2, 1024, 3584, 1, 2048, 0, 64, 64, 1, S128);
  make_map(enc, &mp.m_out, d_out, 2, 1024, 2048, 1, 2048, 0, 64, 16, 1, S128);
  int dev = 0, sms = 0;
  cudaGetDevice(&dev);
  cudaDeviceGetAttribute(&sms, cudaDevAttrMultiProcessorCount, dev);
  auto kern = sms == 132 ? fused_kernel<true> : fused_kernel<false>;
  cudaFuncSetAttribute(kern, cudaFuncAttributeMaxDynamicSharedMemorySize, SMEM_BYTES);
  kern<<<132, 512, SMEM_BYTES>>>(mp);
}
```

```cpp
#include <cuda_runtime.h>
#include <cuda.h>
#include <cuda_bf16.h>
#include <stdint.h>

namespace {

template <int TA, int TB>
__device__ __forceinline__ void wgmma_n8_ss(float (&d)[4], uint64_t da, uint64_t db, int sc) {
  asm volatile("{\n.reg .pred p;\nsetp.ne.b32 p, %6, 0;\n"
    "wgmma.mma_async.sync.aligned.m64n8k16.f32.bf16.bf16 {%0, %1, %2, %3}, %4, %5, p, 1, 1, %7, %8;\n}\n"
    : "+f"(d[0]), "+f"(d[1]), "+f"(d[2]), "+f"(d[3])
    : "l"(da), "l"(db), "r"(sc), "n"(TA), "n"(TB));
}
template <int TB>
__device__ __forceinline__ void wgmma_n40_rs(float (&d)[20], uint32_t a0, uint32_t a1, uint32_t a2, uint32_t a3, uint64_t db, int sc) {
  asm volatile("{\n.reg .pred p;\nsetp.ne.b32 p, %25, 0;\n"
    "wgmma.mma_async.sync.aligned.m64n40k16.f32.bf16.bf16 {%0, %1, %2, %3, %4, %5, %6, %7, %8, %9, %10, %11, %12, %13, %14, %15, %16, %17, %18, %19}, {%20,%21,%22,%23}, %24, p, 1, 1, %26;\n}\n"
    : "+f"(d[0]), "+f"(d[1]), "+f"(d[2]), "+f"(d[3]), "+f"(d[4]), "+f"(d[5]), "+f"(d[6]), "+f"(d[7]),
      "+f"(d[8]), "+f"(d[9]), "+f"(d[10]), "+f"(d[11]), "+f"(d[12]), "+f"(d[13]), "+f"(d[14]), "+f"(d[15]),
      "+f"(d[16]), "+f"(d[17]), "+f"(d[18]), "+f"(d[19])
    : "r"(a0), "r"(a1), "r"(a2), "r"(a3), "l"(db), "r"(sc), "n"(TB));
}
template <int TB>
__device__ __forceinline__ void wgmma_n64_rs(float (&d)[32], uint32_t a0, uint32_t a1, uint32_t a2, uint32_t a3, uint64_t db, int sc) {
  asm volatile("{\n.reg .pred p;\nsetp.ne.b32 p, %37, 0;\n"
    "wgmma.mma_async.sync.aligned.m64n64k16.f32.bf16.bf16 {%0, %1, %2, %3, %4, %5, %6, %7, %8, %9, %10, %11, %12, %13, %14, %15, %16, %17, %18, %19, %20, %21, %22, %23, %24, %25, %26, %27, %28, %29, %30, %31}, {%32,%33,%34,%35}, %36, p, 1, 1, %38;\n}\n"
    : "+f"(d[0]), "+f"(d[1]), "+f"(d[2]), "+f"(d[3]), "+f"(d[4]), "+f"(d[5]), "+f"(d[6]), "+f"(d[7]),
      "+f"(d[8]), "+f"(d[9]), "+f"(d[10]), "+f"(d[11]), "+f"(d[12]), "+f"(d[13]), "+f"(d[14]), "+f"(d[15]),
      "+f"(d[16]), "+f"(d[17]), "+f"(d[18]), "+f"(d[19]), "+f"(d[20]), "+f"(d[21]), "+f"(d[22]), "+f"(d[23]),
      "+f"(d[24]), "+f"(d[25]), "+f"(d[26]), "+f"(d[27]), "+f"(d[28]), "+f"(d[29]), "+f"(d[30]), "+f"(d[31])
    : "r"(a0), "r"(a1), "r"(a2), "r"(a3), "l"(db), "r"(sc), "n"(TB));
}
template <int TA, int TB>
__device__ __forceinline__ void wgmma_n128_ss(float (&d)[64], uint64_t da, uint64_t db, int sc) {
  asm volatile("{\n.reg .pred p;\nsetp.ne.b32 p, %66, 0;\n"
    "wgmma.mma_async.sync.aligned.m64n128k16.f32.bf16.bf16 {%0, %1, %2, %3, %4, %5, %6, %7, %8, %9, %10, %11, %12, %13, %14, %15, %16, %17, %18, %19, %20, %21, %22, %23, %24, %25, %26, %27, %28, %29, %30, %31, %32, %33, %34, %35, %36, %37, %38, %39, %40, %41, %42, %43, %44, %45, %46, %47, %48, %49, %50, %51, %52, %53, %54, %55, %56, %57, %58, %59, %60, %61, %62, %63}, %64, %65, p, 1, 1, %67, %68;\n}\n"
    : "+f"(d[0]), "+f"(d[1]), "+f"(d[2]), "+f"(d[3]), "+f"(d[4]), "+f"(d[5]), "+f"(d[6]), "+f"(d[7]),
      "+f"(d[8]), "+f"(d[9]), "+f"(d[10]), "+f"(d[11]), "+f"(d[12]), "+f"(d[13]), "+f"(d[14]), "+f"(d[15]),
      "+f"(d[16]), "+f"(d[17]), "+f"(d[18]), "+f"(d[19]), "+f"(d[20]), "+f"(d[21]), "+f"(d[22]), "+f"(d[23]),
      "+f"(d[24]), "+f"(d[25]), "+f"(d[26]), "+f"(d[27]), "+f"(d[28]), "+f"(d[29]), "+f"(d[30]), "+f"(d[31]),
      "+f"(d[32]), "+f"(d[33]), "+f"(d[34]), "+f"(d[35]), "+f"(d[36]), "+f"(d[37]), "+f"(d[38]), "+f"(d[39]),
      "+f"(d[40]), "+f"(d[41]), "+f"(d[42]), "+f"(d[43]), "+f"(d[44]), "+f"(d[45]), "+f"(d[46]), "+f"(d[47]),
      "+f"(d[48]), "+f"(d[49]), "+f"(d[50]), "+f"(d[51]), "+f"(d[52]), "+f"(d[53]), "+f"(d[54]), "+f"(d[55]),
      "+f"(d[56]), "+f"(d[57]), "+f"(d[58]), "+f"(d[59]), "+f"(d[60]), "+f"(d[61]), "+f"(d[62]), "+f"(d[63])
    : "l"(da), "l"(db), "r"(sc), "n"(TA), "n"(TB));
}
template <int TB>
__device__ __forceinline__ void wgmma_n128_rs(float (&d)[64], uint32_t a0, uint32_t a1, uint32_t a2, uint32_t a3, uint64_t db, int sc) {
  asm volatile("{\n.reg .pred p;\nsetp.ne.b32 p, %69, 0;\n"
    "wgmma.mma_async.sync.aligned.m64n128k16.f32.bf16.bf16 {%0, %1, %2, %3, %4, %5, %6, %7, %8, %9, %10, %11, %12, %13, %14, %15, %16, %17, %18, %19, %20, %21, %22, %23, %24, %25, %26, %27, %28, %29, %30, %31, %32, %33, %34, %35, %36, %37, %38, %39, %40, %41, %42, %43, %44, %45, %46, %47, %48, %49, %50, %51, %52, %53, %54, %55, %56, %57, %58, %59, %60, %61, %62, %63}, {%64,%65,%66,%67}, %68, p, 1, 1, %70;\n}\n"
    : "+f"(d[0]), "+f"(d[1]), "+f"(d[2]), "+f"(d[3]), "+f"(d[4]), "+f"(d[5]), "+f"(d[6]), "+f"(d[7]),
      "+f"(d[8]), "+f"(d[9]), "+f"(d[10]), "+f"(d[11]), "+f"(d[12]), "+f"(d[13]), "+f"(d[14]), "+f"(d[15]),
      "+f"(d[16]), "+f"(d[17]), "+f"(d[18]), "+f"(d[19]), "+f"(d[20]), "+f"(d[21]), "+f"(d[22]), "+f"(d[23]),
      "+f"(d[24]), "+f"(d[25]), "+f"(d[26]), "+f"(d[27]), "+f"(d[28]), "+f"(d[29]), "+f"(d[30]), "+f"(d[31]),
      "+f"(d[32]), "+f"(d[33]), "+f"(d[34]), "+f"(d[35]), "+f"(d[36]), "+f"(d[37]), "+f"(d[38]), "+f"(d[39]),
      "+f"(d[40]), "+f"(d[41]), "+f"(d[42]), "+f"(d[43]), "+f"(d[44]), "+f"(d[45]), "+f"(d[46]), "+f"(d[47]),
      "+f"(d[48]), "+f"(d[49]), "+f"(d[50]), "+f"(d[51]), "+f"(d[52]), "+f"(d[53]), "+f"(d[54]), "+f"(d[55]),
      "+f"(d[56]), "+f"(d[57]), "+f"(d[58]), "+f"(d[59]), "+f"(d[60]), "+f"(d[61]), "+f"(d[62]), "+f"(d[63])
    : "r"(a0), "r"(a1), "r"(a2), "r"(a3), "l"(db), "r"(sc), "n"(TB));
}

__device__ __forceinline__ void poll1f(uint32_t (&v)[1], const void* p, uint32_t tag, uint32_t mask) {
  asm volatile("{\n.reg .pred p, q;\n.reg .u32 c, b;\n.reg .b64 x, y;\n.reg .b128 z;\nmov.u32 c, 0;\nLW:\n"
               "ld.relaxed.gpu.global.u32 %0, [%1+0];\n"
               "xor.b32 b, %0, %2;\n"
               "and.b32 b, b, %3;\nsetp.eq.u32 p, b, 0;\nvote.sync.all.pred p, p, 0xffffffff;\n@p bra.uni LD;\n"
               "nanosleep.u32 50;\nadd.u32 c, c, 1;\nsetp.lt.u32 q, c, 1000000;\n@q bra.uni LW;\ntrap;\nLD:\n}"
               : "=&r"(v[0])
               : "l"(p), "r"(tag), "r"(mask) : "memory");
}
__device__ __forceinline__ void poll0(uint32_t (&v)[1], const void* p, uint32_t tag, uint32_t mask) {
  asm volatile("{\n.reg .pred p, q;\n.reg .u32 c, b;\n.reg .b64 x, y;\n.reg .b128 z;\nmov.u32 c, 0;\nLW:\n"
               "ld.relaxed.gpu.global.u32 %0, [%1+0];\n"
               "xor.b32 b, %0, %2;\n"
               "and.b32 b, b, %3;\nsetp.eq.u32 p, b, 0;\nvote.sync.all.pred p, p, 0xffffffff;\n@p bra.uni LD;\n"
               "add.u32 c, c, 1;\nsetp.lt.u32 q, c, 1000000;\n@q bra.uni LW;\ntrap;\nLD:\n}"
               : "=&r"(v[0])
               : "l"(p), "r"(tag), "r"(mask) : "memory");
}
__device__ __forceinline__ void poll_pair(uint32_t (&v)[2], const void* p, uint32_t tag, uint32_t mask) {
  asm volatile("{\n.reg .pred p, q;\n.reg .u32 c, b;\n.reg .b64 x, y;\n.reg .b128 z;\nmov.u32 c, 0;\nLW:\n"
               "ld.relaxed.gpu.global.b64 x, [%2+0];\nmov.b64 {%0,%1}, x;\n"
               "xor.b32 b, %0, %3;\n"
               "and.b32 b, b, %4;\nsetp.eq.u32 p, b, 0;\nvote.sync.all.pred p, p, 0xffffffff;\n@p bra.uni LD;\n"
               "nanosleep.u32 100;\nadd.u32 c, c, 1;\nsetp.lt.u32 q, c, 1000000;\n@q bra.uni LW;\ntrap;\nLD:\n}"
               : "=&r"(v[0]), "=&r"(v[1])
               : "l"(p), "r"(tag), "r"(mask) : "memory");
}
__device__ __forceinline__ void poll_quad(uint32_t (&v)[4], const void* p, uint32_t tag, uint32_t mask) {
  asm volatile("{\n.reg .pred p, q;\n.reg .u32 c, b;\n.reg .b64 x, y;\n.reg .b128 z;\nmov.u32 c, 0;\nLW:\n"
               "ld.relaxed.gpu.global.v4.u32 {%0,%1,%2,%3}, [%4+0];\n"
               "xor.b32 b, %0, %5;\n"
               "lop3.b32 b, b, %1, %5, 0xf6;\nlop3.b32 b, b, %2, %5, 0xf6;\nlop3.b32 b, b, %3, %5, 0xf6;\n"
               "and.b32 b, b, %6;\nsetp.eq.u32 p, b, 0;\nvote.sync.all.pred p, p, 0xffffffff;\n@p bra.uni LD;\n"
               "nanosleep.u32 200;\nadd.u32 c, c, 1;\nsetp.lt.u32 q, c, 1000000;\n@q bra.uni LW;\ntrap;\nLD:\n}"
               : "=&r"(v[0]), "=&r"(v[1]), "=&r"(v[2]), "=&r"(v[3])
               : "l"(p), "r"(tag), "r"(mask) : "memory");
}
__device__ __forceinline__ void poll8x4(uint32_t (&v)[32], const void* p, uint32_t tag, uint32_t mask) {
  asm volatile("{\n.reg .pred p, q;\n.reg .u32 c, b;\n.reg .b64 x, y;\n.reg .b128 z;\nmov.u32 c, 0;\nLW:\n"
               "ld.relaxed.gpu.global.v4.u32 {%0,%1,%2,%3}, [%32+0];\n"
               "ld.relaxed.gpu.global.v4.u32 {%4,%5,%6,%7}, [%32+2048];\n"
               "ld.relaxed.gpu.global.v4.u32 {%8,%9,%10,%11}, [%32+4096];\n"
               "ld.relaxed.gpu.global.v4.u32 {%12,%13,%14,%15}, [%32+6144];\n"
               "ld.relaxed.gpu.global.v4.u32 {%16,%17,%18,%19}, [%32+8192];\n"
               "ld.relaxed.gpu.global.v4.u32 {%20,%21,%22,%23}, [%32+10240];\n"
               "ld.relaxed.gpu.global.v4.u32 {%24,%25,%26,%27}, [%32+12288];\n"
               "ld.relaxed.gpu.global.v4.u32 {%28,%29,%30,%31}, [%32+14336];\n"
               "xor.b32 b, %0, %33;\n"
               "lop3.b32 b, b, %1, %33, 0xf6;\nlop3.b32 b, b, %2, %33, 0xf6;\nlop3.b32 b, b, %3, %33, 0xf6;\nlop3.b32 b, b, %4, %33, 0xf6;\n"
               "lop3.b32 b, b, %5, %33, 0xf6;\nlop3.b32 b, b, %6, %33, 0xf6;\nlop3.b32 b, b, %7, %33, 0xf6;\nlop3.b32 b, b, %8, %33, 0xf6;\n"
               "lop3.b32 b, b, %9, %33, 0xf6;\nlop3.b32 b, b, %10, %33, 0xf6;\nlop3.b32 b, b, %11, %33, 0xf6;\nlop3.b32 b, b, %12, %33, 0xf6;\n"
               "lop3.b32 b, b, %13, %33, 0xf6;\nlop3.b32 b, b, %14, %33, 0xf6;\nlop3.b32 b, b, %15, %33, 0xf6;\nlop3.b32 b, b, %16, %33, 0xf6;\n"
               "lop3.b32 b, b, %17, %33, 0xf6;\nlop3.b32 b, b, %18, %33, 0xf6;\nlop3.b32 b, b, %19, %33, 0xf6;\nlop3.b32 b, b, %20, %33, 0xf6;\n"
               "lop3.b32 b, b, %21, %33, 0xf6;\nlop3.b32 b, b, %22, %33, 0xf6;\nlop3.b32 b, b, %23, %33, 0xf6;\nlop3.b32 b, b, %24, %33, 0xf6;\n"
               "lop3.b32 b, b, %25, %33, 0xf6;\nlop3.b32 b, b, %26, %33, 0xf6;\nlop3.b32 b, b, %27, %33, 0xf6;\nlop3.b32 b, b, %28, %33, 0xf6;\n"
               "lop3.b32 b, b, %29, %33, 0xf6;\nlop3.b32 b, b, %30, %33, 0xf6;\nlop3.b32 b, b, %31, %33, 0xf6;\n"
               "and.b32 b, b, %34;\nsetp.eq.u32 p, b, 0;\nvote.sync.all.pred p, p, 0xffffffff;\n@p bra.uni LD;\n"
               "nanosleep.u32 50;\nadd.u32 c, c, 1;\nsetp.lt.u32 q, c, 1000000;\n@q bra.uni LW;\ntrap;\nLD:\n}"
               : "=&r"(v[0]), "=&r"(v[1]), "=&r"(v[2]), "=&r"(v[3]), "=&r"(v[4]), "=&r"(v[5]), "=&r"(v[6]), "=&r"(v[7]), "=&r"(v[8]), "=&r"(v[9]), "=&r"(v[10]), "=&r"(v[11]), "=&r"(v[12]), "=&r"(v[13]), "=&r"(v[14]), "=&r"(v[15]), "=&r"(v[16]), "=&r"(v[17]), "=&r"(v[18]), "=&r"(v[19]), "=&r"(v[20]), "=&r"(v[21]), "=&r"(v[22]), "=&r"(v[23]), "=&r"(v[24]), "=&r"(v[25]), "=&r"(v[26]), "=&r"(v[27]), "=&r"(v[28]), "=&r"(v[29]), "=&r"(v[30]), "=&r"(v[31])
               : "l"(p), "r"(tag), "r"(mask) : "memory");
}
__device__ __forceinline__ void poll16(uint32_t (&v)[16], const void* p, uint32_t tag, uint32_t mask) {
  asm volatile("{\n.reg .pred p, q;\n.reg .u32 c, b;\n.reg .b64 x, y;\n.reg .b128 z;\nmov.u32 c, 0;\nLW:\n"
               "ld.relaxed.gpu.global.u32 %0, [%16+0];\n"
               "ld.relaxed.gpu.global.u32 %1, [%16+4096];\n"
               "ld.relaxed.gpu.global.u32 %2, [%16+8192];\n"
               "ld.relaxed.gpu.global.u32 %3, [%16+12288];\n"
               "ld.relaxed.gpu.global.u32 %4, [%16+16384];\n"
               "ld.relaxed.gpu.global.u32 %5, [%16+20480];\n"
               "ld.relaxed.gpu.global.u32 %6, [%16+24576];\n"
               "ld.relaxed.gpu.global.u32 %7, [%16+28672];\n"
               "ld.relaxed.gpu.global.u32 %8, [%16+32768];\n"
               "ld.relaxed.gpu.global.u32 %9, [%16+36864];\n"
               "ld.relaxed.gpu.global.u32 %10, [%16+40960];\n"
               "ld.relaxed.gpu.global.u32 %11, [%16+45056];\n"
               "ld.relaxed.gpu.global.u32 %12, [%16+49152];\n"
               "ld.relaxed.gpu.global.u32 %13, [%16+53248];\n"
               "ld.relaxed.gpu.global.u32 %14, [%16+57344];\n"
               "ld.relaxed.gpu.global.u32 %15, [%16+61440];\n"
               "xor.b32 b, %0, %17;\n"
               "lop3.b32 b, b, %1, %17, 0xf6;\nlop3.b32 b, b, %2, %17, 0xf6;\nlop3.b32 b, b, %3, %17, 0xf6;\nlop3.b32 b, b, %4, %17, 0xf6;\n"
               "lop3.b32 b, b, %5, %17, 0xf6;\nlop3.b32 b, b, %6, %17, 0xf6;\nlop3.b32 b, b, %7, %17, 0xf6;\nlop3.b32 b, b, %8, %17, 0xf6;\n"
               "lop3.b32 b, b, %9, %17, 0xf6;\nlop3.b32 b, b, %10, %17, 0xf6;\nlop3.b32 b, b, %11, %17, 0xf6;\nlop3.b32 b, b, %12, %17, 0xf6;\n"
               "lop3.b32 b, b, %13, %17, 0xf6;\nlop3.b32 b, b, %14, %17, 0xf6;\nlop3.b32 b, b, %15, %17, 0xf6;\n"
               "and.b32 b, b, %18;\nsetp.eq.u32 p, b, 0;\nvote.sync.all.pred p, p, 0xffffffff;\n@p bra.uni LD;\n"
               "nanosleep.u32 200;\nadd.u32 c, c, 1;\nsetp.lt.u32 q, c, 1000000;\n@q bra.uni LW;\ntrap;\nLD:\n}"
               : "=&r"(v[0]), "=&r"(v[1]), "=&r"(v[2]), "=&r"(v[3]), "=&r"(v[4]), "=&r"(v[5]), "=&r"(v[6]), "=&r"(v[7]), "=&r"(v[8]), "=&r"(v[9]), "=&r"(v[10]), "=&r"(v[11]), "=&r"(v[12]), "=&r"(v[13]), "=&r"(v[14]), "=&r"(v[15])
               : "l"(p), "r"(tag), "r"(mask) : "memory");
}
__device__ __forceinline__ void poll_keys(uint32_t (&v)[16], const void* p, uint32_t tag, uint32_t mask) {
  asm volatile("{\n.reg .pred p, q;\n.reg .u32 c, b;\n.reg .b64 x, y;\n.reg .b128 z;\nmov.u32 c, 0;\nLW:\n"
               "ld.relaxed.gpu.global.v2.b64 {x, y}, [%16+0];\nmov.b64 {%0,%1}, x;\nmov.b64 {%2,%3}, y;\n"
               "ld.relaxed.gpu.global.v2.b64 {x, y}, [%16+4096];\nmov.b64 {%4,%5}, x;\nmov.b64 {%6,%7}, y;\n"
               "ld.relaxed.gpu.global.v2.b64 {x, y}, [%16+8192];\nmov.b64 {%8,%9}, x;\nmov.b64 {%10,%11}, y;\n"
               "ld.relaxed.gpu.global.v2.b64 {x, y}, [%16+12288];\nmov.b64 {%12,%13}, x;\nmov.b64 {%14,%15}, y;\n"
               "xor.b32 b, %0, %17;\n"
               "lop3.b32 b, b, %2, %17, 0xf6;\nlop3.b32 b, b, %4, %17, 0xf6;\nlop3.b32 b, b, %6, %17, 0xf6;\nlop3.b32 b, b, %8, %17, 0xf6;\n"
               "lop3.b32 b, b, %10, %17, 0xf6;\nlop3.b32 b, b, %12, %17, 0xf6;\nlop3.b32 b, b, %14, %17, 0xf6;\n"
               "and.b32 b, b, %18;\nsetp.eq.u32 p, b, 0;\nvote.sync.all.pred p, p, 0xffffffff;\n@p bra.uni LD;\n"
               "nanosleep.u32 20;\nadd.u32 c, c, 1;\nsetp.lt.u32 q, c, 1000000;\n@q bra.uni LW;\ntrap;\nLD:\n}"
               : "=&r"(v[0]), "=&r"(v[1]), "=&r"(v[2]), "=&r"(v[3]), "=&r"(v[4]), "=&r"(v[5]), "=&r"(v[6]), "=&r"(v[7]), "=&r"(v[8]), "=&r"(v[9]), "=&r"(v[10]), "=&r"(v[11]), "=&r"(v[12]), "=&r"(v[13]), "=&r"(v[14]), "=&r"(v[15])
               : "l"(p), "r"(tag), "r"(mask) : "memory");
}
__device__ __forceinline__ void poll_z(uint32_t (&v)[16], const void* p, uint32_t tag, uint32_t mask) {
  asm volatile("{\n.reg .pred p, q;\n.reg .u32 c, b;\n.reg .b64 x, y;\n.reg .b128 z;\nmov.u32 c, 0;\nLW:\n"
               "ld.relaxed.gpu.global.v4.u32 {%0,%1,%2,%3}, [%16+0];\n"
               "ld.relaxed.gpu.global.v4.u32 {%4,%5,%6,%7}, [%16+4096];\n"
               "ld.relaxed.gpu.global.v4.u32 {%8,%9,%10,%11}, [%16+8192];\n"
               "ld.relaxed.gpu.global.v4.u32 {%12,%13,%14,%15}, [%16+12288];\n"
               "xor.b32 b, %0, %17;\n"
               "lop3.b32 b, b, %1, %17, 0xf6;\nlop3.b32 b, b, %2, %17, 0xf6;\nlop3.b32 b, b, %3, %17, 0xf6;\nlop3.b32 b, b, %4, %17, 0xf6;\n"
               "lop3.b32 b, b, %5, %17, 0xf6;\nlop3.b32 b, b, %6, %17, 0xf6;\nlop3.b32 b, b, %7, %17, 0xf6;\nlop3.b32 b, b, %8, %17, 0xf6;\n"
               "lop3.b32 b, b, %9, %17, 0xf6;\nlop3.b32 b, b, %10, %17, 0xf6;\nlop3.b32 b, b, %11, %17, 0xf6;\nlop3.b32 b, b, %12, %17, 0xf6;\n"
               "lop3.b32 b, b, %13, %17, 0xf6;\nlop3.b32 b, b, %14, %17, 0xf6;\nlop3.b32 b, b, %15, %17, 0xf6;\n"
               "and.b32 b, b, %18;\nsetp.eq.u32 p, b, 0;\nvote.sync.all.pred p, p, 0xffffffff;\n@p bra.uni LD;\n"
               "nanosleep.u32 300;\nadd.u32 c, c, 1;\nsetp.lt.u32 q, c, 1000000;\n@q bra.uni LW;\ntrap;\nLD:\n}"
               : "=&r"(v[0]), "=&r"(v[1]), "=&r"(v[2]), "=&r"(v[3]), "=&r"(v[4]), "=&r"(v[5]), "=&r"(v[6]), "=&r"(v[7]), "=&r"(v[8]), "=&r"(v[9]), "=&r"(v[10]), "=&r"(v[11]), "=&r"(v[12]), "=&r"(v[13]), "=&r"(v[14]), "=&r"(v[15])
               : "l"(p), "r"(tag), "r"(mask) : "memory");
}
__device__ __forceinline__ void poll_kvp(uint32_t (&v)[16], const void* p, uint32_t tag, uint32_t mask) {
  asm volatile("{\n.reg .pred p, q;\n.reg .u32 c, b;\n.reg .b64 x, y;\n.reg .b128 z;\nmov.u32 c, 0;\nLW:\n"
               "ld.relaxed.gpu.global.b128 z, [%16+0];\nmov.b128 {x, y}, z;\nmov.b64 {%0,%1}, x;\nmov.b64 {%2,%3}, y;\n"
               "ld.relaxed.gpu.global.b128 z, [%16+8192];\nmov.b128 {x, y}, z;\nmov.b64 {%4,%5}, x;\nmov.b64 {%6,%7}, y;\n"
               "ld.relaxed.gpu.global.b128 z, [%16+16384];\nmov.b128 {x, y}, z;\nmov.b64 {%8,%9}, x;\nmov.b64 {%10,%11}, y;\n"
               "ld.relaxed.gpu.global.b128 z, [%16+24576];\nmov.b128 {x, y}, z;\nmov.b64 {%12,%13}, x;\nmov.b64 {%14,%15}, y;\n"
               "xor.b32 b, %0, %17;\n"
               "lop3.b32 b, b, %4, %17, 0xf6;\nlop3.b32 b, b, %8, %17, 0xf6;\nlop3.b32 b, b, %12, %17, 0xf6;\n"
               "and.b32 b, b, %18;\nsetp.eq.u32 p, b, 0;\nvote.sync.all.pred p, p, 0xffffffff;\n@p bra.uni LD;\n"
               "nanosleep.u32 50;\nadd.u32 c, c, 1;\nsetp.lt.u32 q, c, 1000000;\n@q bra.uni LW;\ntrap;\nLD:\n}"
               : "=&r"(v[0]), "=&r"(v[1]), "=&r"(v[2]), "=&r"(v[3]), "=&r"(v[4]), "=&r"(v[5]), "=&r"(v[6]), "=&r"(v[7]), "=&r"(v[8]), "=&r"(v[9]), "=&r"(v[10]), "=&r"(v[11]), "=&r"(v[12]), "=&r"(v[13]), "=&r"(v[14]), "=&r"(v[15])
               : "l"(p), "r"(tag), "r"(mask) : "memory");
}

__device__ __align__(1024) __nv_bfloat16 g_o[2048 * 1024];
__device__ __align__(128) uint2 g_keys[2048];
__device__ __align__(128) uint32_t g_csum[18 * 1024];
__device__ __align__(128) uint32_t g_z[16 * 1024];
__device__ __align__(128) uint4 g_kvp[128 * 512];
__device__ __align__(128) uint4 g_kv[8 * 512];
__device__ __align__(128) uint4 g_h[112 * 32];
__device__ __align__(128) uint32_t g_yp[128 * 512];
__device__ __align__(128) uint2 g_sel[32 * 16];
enum { H_CS = 0, H_KVP = 8, H_KV = 16, H_H = 24, H_Y = 32, H_O = 40, H_Z = 56 };
__device__ __align__(128) uint32_t g_sig[64 * 32];
__device__ uint32_t g_epoch;

constexpr uint32_t RING = 1024, SLOT = 32768, SMEM_BYTES = 232448;
constexpr int NST = 5, HST = 7;
constexpr uint32_t STG = RING + 163840, AUX = RING + 196608, FR = RING + 212992, MISC = RING + 229376;
constexpr uint32_t B_FULL = MISC, B_EMPTY = MISC + 56, B_XS = MISC + 112, B_SEL = MISC + 144, B_WK = MISC + 160, B_CSDN = MISC + 168,
                   B_FR = MISC + 176, B_FE = MISC + 200, B_DR = MISC + 224, B_CSV = MISC + 248,
                   B_DND = MISC + 256, B_XRES = MISC + 264, B_PFREE = MISC + 280, B_SFREE = MISC + 288, B_KVL = MISC + 296, B_HL = MISC + 304, B_HOK = MISC + 312, B_HGO = MISC + 320, B_L4 = MISC + 328, NBAR = 42;
constexpr uint32_t S_EPOCH = MISC + 352, S_NCAND = MISC + 356, S_SEL = MISC + 368, S_WMAX = MISC + 432,
                   S_KSTAT = MISC + 512, S_CSK = MISC + 1536, S_CSV = MISC + 2048, S_CSQ = MISC + 2560, S_ONES = MISC + 512;
constexpr uint32_t KVB = FR, HOP = FR + 10240, GR = FR - 8192;
enum { NB_Z = 0, NB_KV = 1, NB_VQ = 2, NB_WG0 = 3, NB_FDONE = 4, NB_PK = 5, NB_KVB = 6, NB_WG1 = 7, NB_WG2 = 8, NB_CSQ = 9,
       NB_Y = 10, NB_ST = 11, NB_OWN0 = 12, NB_OWN1 = 13, NB_Q0 = 14, NB_H1 = 15 };

#define XS_FLY 2
#define FFN_GAP 400
#define PF_GAP 200
#define PF_WAIT 1000
#define GPCMAP 0x75143620u
#define KV_SPEC 200
#define HAND_K 5
#define PHI_CUT 11
#define SIG_EARLY 50
#define WK_AT 0x3210
#define XS_AT 0
#define XS_GAP 0
#define H_DELAY 0
#define KPF 1
#define ST_AFTER 5
#define ST_GAP 100
#define ST_ROWS 32
#define REL0 1
#define SIG1 0
constexpr uint64_t EVICT_FIRST = 0x12f0000000000000ull;
constexpr float LOG2E = 1.4426950408889634f, LN2 = 0.6931471805599453f;

#define ELECT "{\n.reg .pred p;\nelect.sync _|p, 0xffffffff;\n"
#define TMA2D "cp.async.bulk.tensor.2d.shared::cluster.global.mbarrier::complete_tx::bytes"
#define TMA3D "cp.async.bulk.tensor.3d.shared::cluster.global.mbarrier::complete_tx::bytes"
__device__ __forceinline__ void e_expect(uint32_t b, uint32_t n) {
  asm volatile(ELECT "@p mbarrier.arrive.expect_tx.shared::cta.b64 _, [%0], %1;\n}" ::"r"(b), "r"(n) : "memory");
}
__device__ __forceinline__ void e_arrive(uint32_t b) { asm volatile(ELECT "@p mbarrier.arrive.shared::cta.b64 _, [%0];\n}" ::"r"(b) : "memory"); }
__device__ __forceinline__ void e_tma2d(uint32_t dst, const CUtensorMap* m, int c0, int c1, uint32_t bar) {
  asm volatile(ELECT "@p " TMA2D " [%0], [%1, {%3, %4}], [%2];\n}" ::"r"(dst), "l"(m), "r"(bar), "r"(c0), "r"(c1) : "memory");
}
__device__ __forceinline__ void e_tma2d_ef(uint32_t dst, const CUtensorMap* m, int c0, int c1, uint32_t bar, uint64_t pol) {
  asm volatile(ELECT "@p " TMA2D ".L2::cache_hint [%0], [%1, {%3, %4}], [%2], %5;\n}" ::"r"(dst), "l"(m), "r"(bar), "r"(c0), "r"(c1), "l"(pol) : "memory");
}
__device__ __forceinline__ void e_tma3d(uint32_t dst, const CUtensorMap* m, int c1, int c2, uint32_t bar) {
  asm volatile(ELECT "@p " TMA3D " [%0], [%1, {0, %3, %4}], [%2];\n}" ::"r"(dst), "l"(m), "r"(bar), "r"(c1), "r"(c2) : "memory");
}
__device__ __forceinline__ void e_store2d(const CUtensorMap* m, int c0, int c1, uint32_t src) {
  asm volatile(ELECT "@p cp.async.bulk.tensor.2d.global.shared::cta.bulk_group [%0, {%2, %3}], [%1];\n}" ::"l"(m), "r"(src), "r"(c0), "r"(c1) : "memory");
}
__device__ __forceinline__ void e_tma3d_ef(uint32_t dst, const CUtensorMap* m, int c0, int c1, uint32_t bar, uint64_t pol) {
  asm volatile(ELECT "@p " TMA3D ".L2::cache_hint [%0], [%1, {%3, %4, 0}], [%2], %5;\n}" ::"r"(dst), "l"(m), "r"(bar), "r"(c0), "r"(c1), "l"(pol) : "memory");
}
__device__ __forceinline__ void e_load(uint32_t dst, const void* src, uint32_t n, uint32_t bar) {
  asm volatile(ELECT "@p cp.async.bulk.shared::cluster.global.mbarrier::complete_tx::bytes [%0], [%1], %2, [%3];\n}" ::"r"(dst), "l"(src), "r"(n), "r"(bar) : "memory");
}
__device__ __forceinline__ void e_pfmap(const CUtensorMap* m) { asm volatile(ELECT "@p prefetch.tensormap [%0];\n}" ::"l"(m) : "memory"); }
__device__ __forceinline__ void bulk_wait_read() { asm volatile("cp.async.bulk.commit_group;\ncp.async.bulk.wait_group.read 0;" ::: "memory"); }
__device__ __forceinline__ void e_signal(int word, int bit) {
  asm volatile(ELECT "@p red.relaxed.gpu.global.xor.b32 [%0], %1;\n}" ::"l"(g_sig + word * 32), "r"(1u << bit) : "memory");
}
__device__ __forceinline__ void await(int word, uint32_t mask, uint32_t ep) {
  uint32_t f[1];
  poll1f(f, g_sig + word * 32, 0u - (ep & 1u), mask);
}

__device__ __forceinline__ void mbar_arrive(uint32_t b) { asm volatile("mbarrier.arrive.shared::cta.b64 _, [%0];" ::"r"(b) : "memory"); }
__device__ __forceinline__ void mbar_wait(uint32_t b, uint32_t ph) {
  asm volatile("{\n.reg .pred p, q;\n.reg .u32 c;\nmov.u32 c, 0;\nLW:\nmbarrier.try_wait.parity.shared::cta.b64 p, [%0], %1;\n@p bra LD;\n"
               "add.u32 c, c, 1;\nsetp.lt.u32 q, c, 100000;\n@q bra LW;\ntrap;\nLD:\n}" ::"r"(b), "r"(ph) : "memory");
}
#define WAIT01 "{\n.reg .pred p, q;\n.reg .u32 c;\nmov.u32 c, 0;\nLW:\nmbarrier.try_wait.parity.shared::cta.b64 p, [%0], %1;\n@p bra LD;\n" \
               "add.u32 c, c, 1;\nsetp.lt.u32 q, c, 100000;\n@q bra LW;\ntrap;\nLD:\nelect.sync _|p, 0xffffffff;\n"
__device__ __forceinline__ void refill_wx(uint32_t eb, uint32_t ph, uint32_t fb, uint32_t bytes, uint32_t dw, const CUtensorMap* mw, int k0, int c,
                                          uint32_t dx, const CUtensorMap* mx, int row, uint32_t xb) {
  asm volatile(WAIT01 "@p " TMA3D " [%4], [%5, {0, %6, %7}], [%2];\n@p " TMA2D " [%8], [%9, {%6, %10}], [%11];\n"
               "@p mbarrier.arrive.expect_tx.shared::cta.b64 _, [%2], %3;\n}"
               ::"r"(eb), "r"(ph), "r"(fb), "r"(bytes), "r"(dw), "l"(mw), "r"(k0), "r"(c), "r"(dx), "l"(mx), "r"(row), "r"(xb) : "memory");
}
__device__ __forceinline__ void refill_w(uint32_t eb, uint32_t ph, uint32_t fb, uint32_t bytes, uint32_t dw, const CUtensorMap* mw, int k0, int c) {
  asm volatile(WAIT01 "@p " TMA3D " [%4], [%5, {0, %6, %7}], [%2];\n@p mbarrier.arrive.expect_tx.shared::cta.b64 _, [%2], %3;\n}"
               ::"r"(eb), "r"(ph), "r"(fb), "r"(bytes), "r"(dw), "l"(mw), "r"(k0), "r"(c) : "memory");
}
__device__ __forceinline__ void refill_x(uint32_t eb, uint32_t ph, uint32_t fb, uint32_t dx, const CUtensorMap* mx, int k0, int row) {
  asm volatile(WAIT01 "@p " TMA2D " [%3], [%4, {%5, %6}], [%2];\n}" ::"r"(eb), "r"(ph), "r"(fb), "r"(dx), "l"(mx), "r"(k0), "r"(row) : "memory");
}
__device__ __forceinline__ void refill_g(uint32_t eb, uint32_t ph, uint32_t fb, uint32_t dw, const CUtensorMap* mw, int c0, int k0) {
  asm volatile(WAIT01 "@p " TMA3D ".L2::cache_hint [%3], [%4, {%5, %6, 0}], [%2], %7;\n@p mbarrier.arrive.expect_tx.shared::cta.b64 _, [%2], 8192;\n}"
               ::"r"(eb), "r"(ph), "r"(fb), "r"(dw), "l"(mw), "r"(c0), "r"(k0), "l"(EVICT_FIRST) : "memory");
}
__device__ __forceinline__ void nb_sync(int id, int n) { asm volatile("bar.sync %0, %1;" ::"r"(id), "r"(n) : "memory"); }
__device__ __forceinline__ void nb_arrive(int id, int n) { asm volatile("bar.arrive %0, %1;" ::"r"(id), "r"(n) : "memory"); }
__device__ __forceinline__ void wg_fence() { asm volatile("wgmma.fence.sync.aligned;" ::: "memory"); }
__device__ __forceinline__ void wg_commit() { asm volatile("wgmma.commit_group.sync.aligned;" ::: "memory"); }
template <int N> __device__ __forceinline__ void wg_wait() { asm volatile("wgmma.wait_group.sync.aligned %0;" ::"n"(N) : "memory"); }
template <int N> __device__ __forceinline__ void reg_fence(float (&a)[N]) {
#pragma unroll
  for (int i = 0; i < N; i++) asm volatile("" : "+f"(a[i])::"memory");
}
template <int N> __device__ __forceinline__ void reg_zero(float (&a)[N]) {
#pragma unroll
  for (int i = 0; i < N; i++) a[i] = 0.f;
}
__device__ __forceinline__ constexpr uint64_t mkdesc(uint32_t addr, uint32_t lbo, uint32_t sbo, uint32_t swz) {
  return (uint64_t)(addr >> 4) | ((uint64_t)(lbo >> 4) << 16) | ((uint64_t)(sbo >> 4) << 32) | ((uint64_t)swz << 62);
}
__device__ __forceinline__ void fence_async_smem() { asm volatile("fence.proxy.async.shared::cta;" ::: "memory"); }
__device__ __forceinline__ void st_relaxed(uint32_t* p, uint32_t v) { asm volatile("st.relaxed.gpu.global.u32 [%0], %1;" ::"l"(p), "r"(v) : "memory"); }
__device__ __forceinline__ uint32_t ld_relaxed(const uint32_t* p) { uint32_t v; asm volatile("ld.relaxed.gpu.global.u32 %0, [%1];" : "=r"(v) : "l"(p) : "memory"); return v; }
__device__ __forceinline__ void st_unit(uint4* p, uint32_t a, uint32_t b, uint32_t c, uint32_t d, uint32_t par) {
  asm volatile("{\n.reg .b64 x, y;\n.reg .b128 z;\nmov.b64 x, {%1,%2};\nmov.b64 y, {%3,%4};\nmov.b128 z, {x, y};\nst.relaxed.gpu.global.b128 [%0], z;\n}"
               ::"l"(p), "r"((a & ~1u) | par), "r"(b), "r"(c), "r"(d) : "memory");
}
__device__ __forceinline__ uint4 lds128(uint32_t a) { uint4 v; asm volatile("ld.shared.v4.u32 {%0,%1,%2,%3}, [%4];" : "=r"(v.x), "=r"(v.y), "=r"(v.z), "=r"(v.w) : "r"(a)); return v; }
__device__ __forceinline__ float4 lds128f(uint32_t a) { float4 v; asm volatile("ld.shared.v4.f32 {%0,%1,%2,%3}, [%4];" : "=f"(v.x), "=f"(v.y), "=f"(v.z), "=f"(v.w) : "r"(a)); return v; }
__device__ __forceinline__ float4 lds128v(uint32_t a) { float4 v; asm volatile("ld.volatile.shared.v4.f32 {%0,%1,%2,%3}, [%4];" : "=f"(v.x), "=f"(v.y), "=f"(v.z), "=f"(v.w) : "r"(a) : "memory"); return v; }
__device__ __forceinline__ float lds32v(uint32_t a) { float v; asm volatile("ld.volatile.shared.f32 %0, [%1];" : "=f"(v) : "r"(a) : "memory"); return v; }
__device__ __forceinline__ float2 lds64f(uint32_t a) { float2 v; asm volatile("ld.shared.v2.f32 {%0,%1}, [%2];" : "=f"(v.x), "=f"(v.y) : "r"(a)); return v; }
__device__ __forceinline__ uint32_t lds32(uint32_t a) { uint32_t v; asm volatile("ld.shared.u32 %0, [%1];" : "=r"(v) : "r"(a)); return v; }
__device__ __forceinline__ void sts128(uint32_t a, uint32_t x, uint32_t y, uint32_t z, uint32_t w) { asm volatile("st.shared.v4.u32 [%0], {%1,%2,%3,%4};" ::"r"(a), "r"(x), "r"(y), "r"(z), "r"(w) : "memory"); }
__device__ __forceinline__ void sts128f(uint32_t a, float x, float y, float z, float w) { asm volatile("st.shared.v4.f32 [%0], {%1,%2,%3,%4};" ::"r"(a), "f"(x), "f"(y), "f"(z), "f"(w) : "memory"); }
__device__ __forceinline__ void sts64(uint32_t a, uint32_t x, uint32_t y) { asm volatile("st.shared.v2.u32 [%0], {%1,%2};" ::"r"(a), "r"(x), "r"(y) : "memory"); }
__device__ __forceinline__ void sts32(uint32_t a, uint32_t x) { asm volatile("st.shared.u32 [%0], %1;" ::"r"(a), "r"(x) : "memory"); }
__device__ __forceinline__ void stsm4(uint32_t a, uint32_t r0, uint32_t r1, uint32_t r2, uint32_t r3) {
  asm volatile("stmatrix.sync.aligned.m8n8.x4.shared.b16 [%0], {%1,%2,%3,%4};" ::"r"(a), "r"(r0), "r"(r1), "r"(r2), "r"(r3) : "memory");
}
__device__ __forceinline__ uint4 ldsm4(uint32_t a) {
  uint4 v; asm volatile("ldmatrix.sync.aligned.m8n8.x4.shared.b16 {%0,%1,%2,%3}, [%4];" : "=r"(v.x), "=r"(v.y), "=r"(v.z), "=r"(v.w) : "r"(a) : "memory"); return v;
}
__device__ __forceinline__ uint32_t pack(float lo, float hi) { uint32_t r; asm("cvt.rn.bf16x2.f32 %0, %1, %2;" : "=r"(r) : "f"(hi), "f"(lo)); return r; }
__device__ __forceinline__ float bf_lo(uint32_t w) { return __uint_as_float(w << 16); }
__device__ __forceinline__ float bf_hi(uint32_t w) { return __uint_as_float(w & 0xffff0000u); }
__device__ __forceinline__ float bf_round(float x) { return bf_lo(pack(x, x)); }
__device__ __forceinline__ float ex2(float x) { float v; asm("ex2.approx.ftz.f32 %0, %1;" : "=f"(v) : "f"(x)); return v; }
__device__ __forceinline__ float rcp(float x) { float v; asm("rcp.approx.ftz.f32 %0, %1;" : "=f"(v) : "f"(x)); return v; }
__device__ __forceinline__ float addsat(float a, float b) { float v; asm("add.sat.f32 %0, %1, %2;" : "=f"(v) : "f"(a), "f"(b)); return v; }
__device__ __forceinline__ float phi2(float a) { return fmaf(fmaxf(a, 0.f), LN2, addsat(ex2(a), 1e-6f)); }
__device__ __forceinline__ uint32_t phi_pack(float u0, float u1, float rl, uint32_t sd2) {
  uint32_t r;
  asm("{\n.reg .b32 m;\ncvt.rn.relu.bf16x2.f32 m, %2, %1;\nfma.rn.bf16x2 %0, %3, %4, m;\n}"
      : "=r"(r) : "f"(u0), "f"(u1), "r"(pack(addsat(ex2(u0 * rl), 1e-6f), addsat(ex2(u1 * rl), 1e-6f))), "r"(sd2));
  return r;
}
__device__ __forceinline__ uint32_t sub2(uint32_t a, uint32_t b) { uint32_t r; asm("sub.rn.bf16x2 %0, %1, %2;" : "=r"(r) : "r"(a), "r"(b)); return r; }
__device__ __forceinline__ float key_score(uint32_t key) { uint32_t u = key >> 16; u = (u & 0x8000u) ? (u & 0x7fffu) : (~u & 0xffffu); return __uint_as_float(u << 16); }
__device__ __forceinline__ int key_token(uint32_t key) { return 2047 - (int)((key >> 5) & 2047u); }
__device__ __forceinline__ uint32_t bsel(uint32_t a, uint32_t b, uint32_t m) { uint32_t r; asm("lop3.b32 %0, %1, %2, %3, 0xd8;" : "=r"(r) : "r"(a), "r"(b), "r"(m)); return r; }
__device__ __forceinline__ uint32_t prmt(uint32_t a, uint32_t b, uint32_t c) { uint32_t r; asm("prmt.b32 %0, %1, %2, %3;" : "=r"(r) : "r"(a), "r"(b), "r"(c)); return r; }
__device__ __forceinline__ uint32_t tagf(float v, uint32_t par) { return (__float_as_uint(v) & ~1u) | par; }
__device__ __forceinline__ float xred(float a, float b, bool up, int o) { return (up ? b : a) + __shfl_xor_sync(0xffffffffu, up ? a : b, o); }

#define STAMP(id)
#define STAMP_IF(c, id)
#define STAMP2(i)
#define LITE 1
#define LITE_MASK 0ull

template <bool TRANS, int NK = 16>
__device__ __forceinline__ void mainloop(float (&a0)[64], float (&a1)[64], int s, int ph, int handoff, int xpair, bool leader) {
  uint32_t prev = 0;
#pragma unroll 1
  for (int kt = 0; kt < NK; kt++) {
    const bool xr = !TRANS && (kt >> 1) == xpair;
    mbar_wait(B_FULL + 8 * s, ph);
    const uint64_t dw = mkdesc(RING, 8192, 1024, 1) + s * (SLOT >> 4), dx = mkdesc(0, 16, 1024, 1) + (xr ? (STG >> 4) + (kt & 1) * 1024 : ((RING + 16384) >> 4) + s * (SLOT >> 4));
    if (xr) mbar_wait(B_XRES + 8 * (kt & 1), 0);
    wg_fence();
#pragma unroll
    for (int j = 0; j < 4; j++) {
      if (TRANS) {
        wgmma_n128_ss<1, 0>(a0, dw + j * 128, dx + j * 2, 1);
        wgmma_n128_ss<1, 0>(a1, dw + j * 128 + 512, dx + j * 2, 1);
      } else {
        wgmma_n128_ss<0, 1>(a0, dx + j * 2, dw + j * 128, 1);
        wgmma_n128_ss<0, 1>(a1, dx + j * 2 + 512, dw + j * 128, 1);
      }
    }
    wg_commit();
    if (handoff && kt == 15) nb_arrive(handoff, 256);
    wg_wait<1>();
    if (prev && leader) mbar_arrive(prev);
    prev = B_EMPTY + 8 * s;
    if (++s == NST) { s = 0; ph ^= 1; }
  }
  if (NK < 16) return;
  wg_wait<0>();
  if (leader) mbar_arrive(prev);
  reg_fence(a0);
  reg_fence(a1);
}

__device__ __forceinline__ int out_kblock(int r, int tn) {
  const int q = r - 2, half = q >= 7, pi = q - 7 * half;
  return r < 2 ? 2 * tn + r : 2 * ((pi + (pi >= (tn & 3))) ^ (tn & 4)) + half;
}

struct Params {
  const char *x, *w_r, *wg, *wu, *wd;
  CUtensorMap m_wqkv, m_x, m_xs, m_o, m_os, m_os2, m_wo, m_gu, m_down, m_out;
};

template <bool BY_SMID>
__global__ void __launch_bounds__(512, 1) fused_kernel(const __grid_constant__ Params mp) {
  extern __shared__ __align__(1024) uint8_t smem_raw[];
#define CK(i)
  CK(0);
  const int tid = threadIdx.x, lane = tid & 31;
  const int w = __shfl_sync(0xffffffffu, tid >> 5, 0);
  int bid = blockIdx.x;
  if (BY_SMID) {
    uint32_t sm;
    asm volatile("mov.u32 %0, %%smid;" : "=r"(sm));
    const uint32_t p = sm >> 1, q = ((p - 32) * 37) >> 8;
    const uint32_t gpc = p < 32 ? p & 7 : p < 60 ? p - 31 - 7 * q : 0, tpc = p < 32 ? p >> 3 : p < 60 ? 4 + q : p - 58;
    bid = (p >> 1) == 30 ? 128 + ((0x9cu >> (2 * (sm & 3))) & 3) : ((GPCMAP >> (4 * gpc)) & 7) * 16 + tpc * 2 + (sm & 1);
  }
  const int tn = (bid & 3) + 4 * (bid >> 6), tm = (bid >> 2) & 15;

  CK(1);
  if (w == 0) {
#pragma unroll 1
    for (int s = 0; s < NST; s++) {
      asm volatile(ELECT "@p mbarrier.init.shared::cta.b64 [%0], 1;\n}" ::"r"(B_FULL + 8 * s) : "memory");
      if (bid < 128) {
        e_expect(B_FULL + 8 * s, 32768);
        e_tma2d(RING + s * SLOT + 16384, &mp.m_x, s * 64, tm * 128, B_FULL + 8 * s);
        e_tma3d(RING + s * SLOT, &mp.m_wqkv, s * 64, 16 + 2 * tn, B_FULL + 8 * s);
      }
      if (s == 0) CK(2);
    }
  }
  if (w == 1) e_pfmap(&mp.m_wqkv);
  if (w == 2) e_pfmap(&mp.m_xs);
  if (w >= 4) {
#pragma unroll 1
    for (uint32_t b = MISC + 8 * (w + 1); b < MISC + 8 * NBAR; b += 96)
      asm volatile(ELECT "@p mbarrier.init.shared::cta.b64 [%0], %1;\n}" ::"r"(b), "r"(b == B_CSDN ? 4 : 1) : "memory");
    if (w == 15) sts32(S_NCAND, 0);
  }
  CK(3);
  asm volatile("fence.mbarrier_init.release.cluster;" ::: "memory");
  __syncthreads();

  if (bid >= 128) {
    const int h0 = bid == 128 ? 14 : bid - 129, hs = bid == 128 ? 1 : 3, h1 = bid == 128 ? 16 : 14;
    if (w == 12) {
      int s = 0, ph = 1;
#pragma unroll 1
      for (int h = h0; h < h1; h += hs) {
        const int c = 2 * h + (h & 8) * 2;
        if (h == 14) mbar_wait(B_SEL, 0);
        if (H_DELAY && h < 3) __nanosleep(H_DELAY);
#pragma unroll 1
        for (int kt = 0; kt < 16; kt += 2) {
          mbar_wait(B_EMPTY + 8 * s, ph);
          e_expect(B_FULL + 8 * s, 32768);
          e_tma3d(RING + s * SLOT, &mp.m_wqkv, kt * 64, c, B_FULL + 8 * s);
          e_tma3d(RING + s * SLOT + 16384, &mp.m_wqkv, kt * 64 + 64, c, B_FULL + 8 * s);
          if (++s == HST) { s = 0; ph ^= 1; }
        }
      }
    } else if (w < 4) {
      const uint32_t par = (ld_relaxed(&g_epoch) + 1) & 1u;
      sts32(S_ONES + tid * 4, 0x3f803f80u);
      fence_async_smem();
      nb_sync(NB_WG0, 128);
      int s = 0, ph = 0;
#pragma unroll 1
      for (int h = h0; h < h1; h += hs) {
        float c[4][4];
#pragma unroll
        for (int q = 0; q < 4; q++) reg_zero(c[q]);
        uint32_t prev = 0;
#pragma unroll 1
        for (int kt = 0; kt < 8; kt++) {
          mbar_wait(B_FULL + 8 * s, ph);
          const uint64_t dw = mkdesc(RING, 8192, 1024, 1) + s * (SLOT >> 4);
          wg_fence();
#pragma unroll
          for (int j = 0; j < 16; j++) wgmma_n8_ss<1, 0>(c[j & 3], dw + (j & 3) * 512 + (j >> 2) * 128, mkdesc(S_ONES, 128, 128, 0), 1);
          wg_commit();
          wg_wait<1>();
          if (prev && tid == 0) mbar_arrive(prev);
          prev = B_EMPTY + 8 * s;
          if (++s == HST) { s = 0; ph ^= 1; }
        }
        wg_wait<0>();
        if (tid == 0) mbar_arrive(prev);
#pragma unroll
        for (int q = 0; q < 4; q++) reg_fence(c[q]);
        const bool u2 = lane & 2, u1 = lane & 1;
        const float lo = u2 ? c[1][0] + c[3][0] : c[0][0] + c[2][0], hi = u2 ? c[1][2] + c[3][2] : c[0][2] + c[2][2];
        st_relaxed(g_csum + h * 128 + (lane & 2) * 32 + w * 16 + (lane & 1) * 8 + (lane >> 2), tagf(u1 ? hi : lo, par));
        STAMP_IF(tid == 0, h >= 8 ? 6 : 30);
      }
    } else if (w < 12 && bid == 128) {
      const int t = tid - 128, j = w - 4;
      const uint32_t ep = ld_relaxed(&g_epoch) + 1;
      uint32_t kk[16];
      poll_keys(kk, g_keys + t * 2, ep, 31u);
      STAMP_IF(t == 0, 42);
      const uint32_t m = __reduce_max_sync(0xffffffffu, max(max(max(kk[0], kk[2]), max(kk[4], kk[6])), max(max(kk[8], kk[10]), max(kk[12], kk[14]))));
      if (lane == 0) sts32(S_WMAX + j * 4, m);
      nb_sync(NB_WG1, 256);
      const uint32_t T = __reduce_min_sync(0xffffffffu, lds32(S_WMAX + (lane & 7) * 4));
      uint32_t cnt = 0;
#pragma unroll
      for (int i = 0; i < 8; i++) cnt += kk[2 * i] >= T;
      if (cnt) {
        uint32_t pos;
        asm volatile("atom.shared.add.u32 %0, [%1], %2;" : "=r"(pos) : "r"(S_NCAND), "r"(cnt * 8) : "memory");
#pragma unroll
        for (int i = 0; i < 8; i++)
          if (kk[2 * i] >= T) { sts64(AUX + pos, kk[2 * i], kk[2 * i + 1]); pos += 8; }
      }
      nb_sync(NB_WG1, 256);
      const uint32_t n8 = lds32(S_NCAND);
#pragma unroll 1
      for (uint32_t i0 = 0; i0 < n8; i0 += 256) {
        const uint32_t i = i0 + (t & ~7);
        const float2 c = lds64f(AUX + i);
        uint32_t rank = 0;
#pragma unroll 4
        for (uint32_t q = (t & 7) * 8; q < n8; q += 64) rank += lds32(AUX + q) > __float_as_uint(c.x);
        rank += __shfl_xor_sync(0xffffffffu, rank, 1);
        rank += __shfl_xor_sync(0xffffffffu, rank, 2);
        rank += __shfl_xor_sync(0xffffffffu, rank, 4);
        if (rank < 8 && i < n8) sts64(S_SEL + rank * 8, __float_as_uint(c.x), __float_as_uint(c.y));
      }
      nb_sync(NB_WG1, 256);
      if (j < 4) {
        const uint4 v = lds128(S_SEL + (lane & 3) * 16);
        asm volatile("{\n.reg .b64 x, y;\nmov.b64 x, {%1,%2};\nmov.b64 y, {%3,%4};\nst.relaxed.gpu.global.v2.b64 [%0], {x, y};\n}"
                     ::"l"(g_sel + (t >> 2) * 16 + (lane & 3) * 2), "r"(v.x), "r"(v.y), "r"(v.z), "r"(v.w) : "memory");
      } else if (j == 4) {
        fence_async_smem();
        e_arrive(B_SEL);
      }
      STAMP_IF(t == 0, 45);
    }
  } else if (w >= 12) {
    asm volatile("setmaxnreg.dec.sync.aligned.u32 32;");
    if (w == 12) {
      int s = 0, ph = 0;
#pragma unroll 1
      for (int it = NST; it < 48; it++) {
        const int c = (it < 32 ? (it & 16) + 16 : 0) + 2 * tn;
        const int k0 = ((it + (it >= 32 && tn < 4 ? 8 : 0)) & 15) * 64;
        const bool xr = (it >> 1) == 20 + (tn & 3);
        if (xr) { mbar_wait(B_SFREE, 0); e_expect(B_XRES + 8 * (it & 1), 16384); }
        refill_wx(B_EMPTY + 8 * s, ph, B_FULL + 8 * s, xr ? 16384 : 32768, RING + s * SLOT, &mp.m_wqkv, k0, c,
                  xr ? STG + (it & 1) * 16384 : RING + s * SLOT + 16384, &mp.m_x, tm * 128, xr ? B_XRES + 8 * (it & 1) : B_FULL + 8 * s);
        if (it >= NST) STAMP2(it - NST);
        if (++s == NST) { s = 0; ph ^= 1; }
      }
#pragma unroll 1
      for (int r = 0; r < 16; r++) {
        const int kb = out_kblock(r, tn);
        refill_w(B_EMPTY + 8 * s, ph, B_FULL + 8 * s, r < 2 ? 16384 : 32768, RING + s * SLOT, &mp.m_wo, kb * 64, 2 * tn);
        if (r < 2 || r == 4) {
          const uint32_t bar = B_DR + (r < 2 ? 16 : 8);
          const int k0 = (bid >> 4) * 448 + 128 + min(r, 2) * 128;
          if (r != 1) e_expect(bar, r ? 8192 : 32768);
          e_tma2d_ef(RING + s * SLOT + 16384, &mp.m_down, (bid & 15) * 64, k0, bar, EVICT_FIRST);
          if (r < 2) e_tma2d_ef(RING + s * SLOT + 24576, &mp.m_down, (bid & 15) * 64, k0 + 64, bar, EVICT_FIRST);
        }
        STAMP2(r + 48 - NST);
        if (++s == NST) { s = 0; ph ^= 1; }
      }
    } else if (w == 13) {
      mbar_wait(B_FULL + 8 * XS_AT, 0);
#pragma unroll 1
      for (int c = 0; c < 5; c++) {
        if (c >= XS_FLY) mbar_wait(B_XS + 8 * (c - XS_FLY), 0);
        if (c == ((WK_AT >> (4 * (tm >> 2))) & 7)) {
          e_expect(B_WK, 16384);
          e_tma3d(FR, &mp.m_wqkv, tm * 64, 16 + 2 * tn, B_WK);
        }
        if (c == 4) break;
        e_expect(B_XS + 8 * c, 8192);
        e_tma2d(STG + c * 8192, &mp.m_xs, c * 256, tm * 128 + tn * 16, B_XS + 8 * c);
        if (XS_GAP && c == 0) __nanosleep(XS_GAP);
      }
      {
        const char* pd = mp.wd + (bid & 15) * 128 + ((bid >> 4) * 448 + lane) * 2048;
        mbar_wait(B_XS + 24, 0);
        __nanosleep(PF_WAIT);
#pragma unroll 1
        for (int i = 0; i < 14; i++, pd += 65536) {
          asm volatile("prefetch.global.L2 [%0];" ::"l"(pd));
          __nanosleep(PF_GAP);
        }
      }
      nb_sync(NB_Z, 160);
      const uint32_t ep = lds32(S_EPOCH);
      {
        float z[4] = {0.f, 0.f, 0.f, 0.f};
        e_signal(H_Z + tn, tm);
        await(H_Z + tn, 0xffffu, ep);
#pragma unroll 1
        for (int i = 0; i < 4; i++) {
          uint32_t p[16];
          poll_z(p, g_z + i * 4096 + tn * 128 + lane * 4, ep, 1u);
#pragma unroll
          for (int q = 0; q < 4; q++) z[q] += (__uint_as_float(p[q]) + __uint_as_float(p[4 + q])) + (__uint_as_float(p[8 + q]) + __uint_as_float(p[12 + q]));
        }
        const uint32_t z01 = pack(z[0], z[1]), z23 = pack(z[2], z[3]);
        if (bid < 112) mbar_wait(B_PFREE, 0);
#pragma unroll
        for (int n = 0; n < 8; n++) sts64(KVB + (lane >> 4) * 5120 + n * 128 + ((((lane >> 1) & 7) ^ n) << 4) + (lane & 1) * 8, z01, z23);
        fence_async_smem();
        nb_arrive(NB_KVB, 320);
        STAMP_IF(lane == 0, 46);
      }
      nb_sync(NB_Q0, 192);
      e_store2d(&mp.m_os, tn * 128, tm * 128, STG);
      nb_sync(NB_OWN0, 160);
      e_store2d(&mp.m_os, tn * 128, tm * 128 + 64, STG + 8192);
      if (!SIG_EARLY) bulk_wait_read(); else if (SIG_EARLY > 1) __nanosleep(SIG_EARLY);
      e_signal(H_O + tm, 2 * tn);
      STAMP_IF(lane == 0, 4);
      nb_sync(NB_H1, 160);
      if (ST_AFTER) mbar_wait(B_L4, 0);
#pragma unroll 1
      for (int i = 0; i < 128; i += ST_ROWS) {
        if (i) __nanosleep(ST_GAP);
        e_store2d(&mp.m_os2, tn * 128 + 64, tm * 128 + i, STG + 16384 + i * 128);
      }
      if (!SIG1) bulk_wait_read();
      e_signal(H_O + tm, 2 * tn + 1);
      if (SIG1) bulk_wait_read();
      STAMP_IF(lane == 0, 5);
      nb_arrive(NB_ST, 288);
    } else if (w == 14) {
      e_pfmap(&mp.m_gu); e_pfmap(&mp.m_o); e_pfmap(&mp.m_os); e_pfmap(&mp.m_os2); e_pfmap(&mp.m_wo); e_pfmap(&mp.m_down); e_pfmap(&mp.m_out);
      const uint32_t ep = ld_relaxed(&g_epoch) + 1;
      nb_sync(NB_FDONE, 416);
      {
        uint32_t c[4];
        poll_quad(c, g_csum + tn * 128 + lane * 4, ep, 1u);
        sts128(S_CSQ + lane * 16, c[0], c[1], c[2], c[3]);
        nb_arrive(NB_CSQ, 160);
        poll_quad(c, g_csum + 1024 + tn * 128 + lane * 4, ep, 1u);
        sts128(S_CSV + lane * 16, c[0], c[1], c[2], c[3]);
        __syncwarp();
        e_arrive(B_CSV);
      }
      {
        mbar_wait(B_WK, 1);
        if (KV_SPEC) __nanosleep(KV_SPEC); else await(H_KV + tn, 0xffffu, ep);
        STAMP_IF(lane == 0, 7);
        if (bid < 112) mbar_wait(B_PFREE, 0);
        STAMP_IF(lane == 0, 23);
        uint32_t bad, ph = 0;
        do {
          e_expect(B_KVL, 8192);
          e_load(KVB + 1024, g_kv + tn * 512, 4096, B_KVL);
          e_load(KVB + 6144, g_kv + tn * 512 + 256, 4096, B_KVL);
          mbar_wait(B_KVL, ph & 1);
          bad = 0;
#pragma unroll
          for (int i = 0; i < 16; i++) bad |= __float_as_uint(lds32v(KVB + 1024 + (i & 8) * 128 + i * 512 + lane * 16)) ^ ep;
          bad = __any_sync(0xffffffffu, bad & 1u);
          if (bad) fence_async_smem();
        } while (bad && ++ph < 100000);
        nb_arrive(NB_KVB, 320);
        STAMP_IF(lane == 0, 24);
      }
      nb_sync(NB_Q0, 192);
      uint32_t ready = 0;
      int s = 0, ph = 1;
#pragma unroll 1
      for (int r = 2; r < 16; r++) {
        const int kb = out_kblock(r, tn);
        if (!((ready >> kb) & 1)) {
          uint32_t f[1];
          poll0(f, g_sig + (H_O + tm) * 32, 0u - (ep & 1u), 1u << kb);
          ready = f[0] ^ ((ep & 1u) - 1u);
        }
        if (r == 4) mbar_wait(B_DND, 0);
        refill_x(B_EMPTY + 8 * s, ph, B_FULL + 8 * s, RING + s * SLOT + 16384, &mp.m_o, kb * 64, tm * 128);
        if (r == ST_AFTER) e_arrive(B_L4);
        STAMP_IF(lane == 0 && r == 2, 2);
        STAMP_IF(lane == 0 && r == 9, 3);
        if (++s == NST) { s = 0; ph ^= 1; }
      }
    } else {
      uint32_t nsm = 132;
      if (BY_SMID) asm volatile("mov.u32 %0, %%nsmid;" : "=r"(nsm));
      asm volatile("{\n.reg .pred q;\nsetp.eq.u32 q, %0, 1156;\n@q bra LOK;\ntrap;\nLOK:\n}" ::"r"((uint32_t)__cvta_generic_to_shared(smem_raw) + nsm));
      const uint32_t ep = ld_relaxed(&g_epoch) + 1;
      mbar_wait(B_CSDN, 0);
#pragma unroll 1
      for (int n = 0; n < 3 && bid < 112; n++) {
        __nanosleep(FFN_GAP);
        e_expect(B_FR + 8 * n, 8192);
        e_tma3d_ef(GR + n * 8192, &mp.m_gu, bid * 32, n * 64, B_FR + 8 * n, EVICT_FIRST);
      }
      if (bid < 112) {
        int s = 0, ph = 0;
#pragma unroll 1
        for (int n = 3; n < 16; n++) {
          refill_g(B_FE + 8 * s, ph, B_FR + 8 * s, GR + s * 8192, &mp.m_gu, bid * 32, n * 64);
          STAMP2(64 + n);
          if (++s == 3) { s = 0; ph ^= 1; }
        }
      }
      if (bid < 112) mbar_wait(B_FE, 1);
      e_expect(B_DR, 16384);
      e_tma2d_ef(AUX, &mp.m_down, (bid & 15) * 64, (bid >> 4) * 448, B_DR, EVICT_FIRST);
      e_tma2d_ef(AUX + 8192, &mp.m_down, (bid & 15) * 64, (bid >> 4) * 448 + 64, B_DR, EVICT_FIRST);
      {
        mbar_wait(B_WK, 1);
        if (bid < 112) mbar_wait(B_HGO, 0);
        await(H_H + (bid >> 4), 0x3fffu, ep);
        uint32_t bad, ph = 0;
        do {
          e_expect(B_HL, 7168);
          e_load(HOP, g_h + (bid >> 4) * 448, 6144, B_HL);
          e_load(S_CSK, g_h + (bid >> 4) * 448 + 384, 1024, B_HL);
          mbar_wait(B_HL, ph & 1);
          bad = 0;
#pragma unroll
          for (int i = 0; i < 14; i++) bad |= __float_as_uint(lds32v((i < 12 ? HOP : S_CSK - 6144) + i * 512 + lane * 16)) ^ ep;
          bad = __any_sync(0xffffffffu, bad & 1u);
          if (bad) fence_async_smem();
        } while (bad && ++ph < 100000);
        e_arrive(B_HOK);
      }
    }
  } else if (w >= 8) {
    asm volatile("setmaxnreg.dec.sync.aligned.u32 56;");
    const int t = tid - 256, ww = w - 8;
    const uint32_t ep = ld_relaxed(&g_epoch) + 1, par = ep & 1u;
    {
      const int r0 = (lane >> 3) + (lane & 4);
      const uint32_t a = FR + (ww >> 1) * 8192 + r0 * 128 + ((((ww & 1) * 4 + (lane & 3)) ^ r0) << 4);
      float c[8];
      reg_zero(c);
      mbar_wait(B_WK, 0);
#pragma unroll 2
      for (int i = 0; i < 8; i++) {
        const uint4 v = lds128(a + i * 1024);
        c[0] += bf_lo(v.x); c[1] += bf_hi(v.x); c[2] += bf_lo(v.y); c[3] += bf_hi(v.y);
        c[4] += bf_lo(v.z); c[5] += bf_hi(v.z); c[6] += bf_lo(v.w); c[7] += bf_hi(v.w);
      }
      const bool u16 = lane & 16, u8 = lane & 8, u4 = lane & 4;
      const float d0 = xred(c[0], c[4], u16, 16), d1 = xred(c[1], c[5], u16, 16), d2 = xred(c[2], c[6], u16, 16), d3 = xred(c[3], c[7], u16, 16);
      fence_async_smem();
      e_arrive(B_CSDN);
      const float sum = xred(xred(d0, d2, u8, 8), xred(d1, d3, u8, 8), u4, 4);
      st_relaxed(g_csum + (2 + tm) * 1024 + tn * 128 + ww * 32 + (lane & 3) * 8 + (lane >> 2), tagf(sum, par));
      STAMP_IF(t == 0, 8);
      nb_sync(NB_WG2, 128);
      if (ww == 0) { e_signal(H_CS + tn, tm); await(H_CS + tn, 0xffffu, ep); }
      nb_sync(NB_WG2, 128);
      uint32_t p[16];
      poll16(p, g_csum + 2048 + tn * 128 + t, par, 1u);
      float tot = 0.f;
#pragma unroll
      for (int i = 0; i < 16; i += 4) tot += (__uint_as_float(p[i]) + __uint_as_float(p[i + 1])) + (__uint_as_float(p[i + 2]) + __uint_as_float(p[i + 3]));
      sts32(S_CSK + t * 4, __float_as_uint(tot));
      nb_arrive(NB_FDONE, 416);
      STAMP_IF(t == 0, 9);
    }
    const int ks = bid >> 4, nt = bid & 15;
    uint32_t sel[2];
    poll_pair(sel, g_sel + (ks * 4 + ww) * 16 + (t >> 4), ep, 31u);
    if ((t & 15) == 0) sts64(S_SEL + (t >> 4) * 8, sel[0], sel[1]);
    if (bid >= 112) {
      nb_sync(NB_WG2, 128);
      if (t == 0) mbar_arrive(B_SEL);
    } else {
      const uint4* xs = reinterpret_cast<const uint4*>(mp.x + key_token(sel[0]) * 2048) + (t & 15);
      const uint32_t xd = AUX + (t & 8) * 128 + (t >> 4) * 128 + (((t ^ (t >> 4)) & 7) << 4), m2 = __byte_perm(sel[1], 0, 0x3232);
      uint4 v[4];
#pragma unroll
      for (int i = 0; i < 4; i++) v[i] = __ldg(xs + i * 16);
      float fg[4];
      reg_zero(fg);
      constexpr uint64_t DA0 = mkdesc(GR, 4096, 512, 2);
      uint64_t da = DA0;
      uint32_t bar = B_FR, ph = 0;
#pragma unroll 1
      for (int b = 0; b < 2; b++) {
        if (b) nb_sync(NB_WG2, 128);
#pragma unroll
        for (int i = 0; i < 4; i++) sts128(xd + i * 2048, sub2(v[i].x, m2), sub2(v[i].y, m2), sub2(v[i].z, m2), sub2(v[i].w, m2));
        fence_async_smem();
        nb_sync(NB_WG2, 128);
        if (!b) {
          if (t == 0) mbar_arrive(B_SEL);
#pragma unroll
          for (int i = 0; i < 4; i++) v[i] = __ldg(xs + 64 + i * 16);
        }
        uint64_t db = mkdesc(AUX, 16, 1024, 1);
#pragma unroll 1
        for (int n = 0; n < 8; n++) {
          mbar_wait(bar, ph);
          wg_fence();
#pragma unroll
          for (int q = 0; q < 4; q++) wgmma_n8_ss<1, 0>(fg, da + q * 64, db + q * 2, 1);
          wg_commit();
          const uint32_t rel = bar + (B_FE - B_FR);
          const bool wrap = bar == B_FR + 16;
          da = wrap ? DA0 : da + 512;
          db += 64;
          bar = wrap ? B_FR : bar + 8;
          ph ^= wrap;
          wg_wait<0>();
          if (t == 0) mbar_arrive(rel);
          if (t == 0 && b && n == 6) mbar_arrive(B_PFREE);
        }
      }
      const uint4 st = lds128(S_SEL + (lane & 3) * 16);
      const float r0 = rcp(bf_lo(st.y)), r1 = rcp(bf_lo(st.w));
      reg_fence(fg);
      const float fa[4] = {fg[0] * r0, fg[1] * r1, fg[2] * r0, fg[3] * r1};
      STAMP_IF(t == 0, 12);
      const bool isup = (ww >> 1) != (mp.wu < mp.wg);
      if (isup) sts128f(HOP + (t & 63) * 16, fa[0], fa[1], fa[2], fa[3]);
      nb_sync(NB_WG2, 128);
      if (!isup) {
        const float4 u = lds128f(HOP + (t & 63) * 16);
        const float uu[4] = {u.x, u.y, u.z, u.w};
        uint32_t hw[2];
#pragma unroll
        for (int i = 0; i < 2; i++)
          hw[i] = pack(fa[2 * i] * rcp(1.f + ex2(-fa[2 * i] * LOG2E)) * uu[2 * i], fa[2 * i + 1] * rcp(1.f + ex2(-fa[2 * i + 1] * LOG2E)) * uu[2 * i + 1]);
        const uint32_t ha = HOP + 1024 + (ww & 1) * 256 + (lane & 15) * 16;
        asm volatile("stmatrix.sync.aligned.m8n8.x2.trans.shared.b16 [%0], {%1,%2};" ::"r"(ha), "r"(hw[0]), "r"(hw[1]) : "memory");
        __syncwarp();
        const int tok = (lane >> 1) & 7, pc = (ww & 1) * 2 + (lane & 1);
        const uint4 hv = lds128(HOP + 1024 + pc * 128 + tok * 16);
        if (lane < 16) st_unit(g_h + bid * 32 + tok * 4 + (pc ^ (tok >> 1)), hv.x, hv.y, hv.z, hv.w, par);
      }
      fence_async_smem();
      nb_sync(NB_WG2, 128);
      if (ww == 0) { e_signal(H_H + bid / 14, bid % 14); e_arrive(B_HGO); }
    }
    mbar_wait(B_HOK, 0);
    STAMP_IF(t == 0, 13);
    float fa[4] = {0.f, 0.f, 0.f, 0.f};
    auto down = [&](uint32_t a, int k0, int nk) {
#pragma unroll
      for (int q = 0; q < nk; q++) wgmma_n8_ss<1, 0>(fa, mkdesc(a + q * 2048, 4096, 1024, 1), mkdesc((k0 < 24 ? HOP : S_CSK - 6144) + ((k0 + q) >> 1) * 512 + (q & 1) * 32, 16, 512, 2), 1);
    };
    mbar_wait(B_DR, 0);
    mbar_wait(B_DR + 16, 0);
    mbar_wait(B_DR + 8, 0);
    wg_fence();
    down(RING + 2 * SLOT + 16384, 24, 4);
    down(RING + 3 * SLOT + 16384, 8, 8);
    down(RING + 4 * SLOT + 16384, 16, 8);
    wg_commit();
    wg_fence();
    down(AUX, 0, 8);
    wg_commit();
    wg_wait<1>();
    if (t == 0) mbar_arrive(B_DND);
    wg_wait<0>();
    reg_fence(fa);
    STAMP_IF(t == 0, 14);
    {
      uint32_t* yp = g_yp + (nt * 8 + ks) * 512 + (lane & 3) * 128 + ww * 16 + (lane >> 2);
#pragma unroll
      for (int i = 0; i < 4; i++) st_relaxed(yp + (i & 1) * 64 + (i >> 1) * 8, tagf(fa[i], par));
    }
    nb_sync(NB_WG2, 128);
    if (ww == 0) e_signal(H_Y + (nt >> 1), (nt & 1) * 8 + ks);
    const uint32_t mykey = lds32(S_SEL + (lane & 7) * 8);
    const uint32_t inmask = __ballot_sync(0xffffffffu, (key_token(mykey) >> 7) == tm) & 0xffu;
    sts128(AUX + t * 16, 0u, 0u, 0u, 0u);
    if (inmask) {
      if (ww == 0) await(H_Y + tn, 0xffffu, ep);
      nb_sync(NB_WG2, 128);
      const float sg = rcp(1.f + ex2(-key_score(mykey) * LOG2E));
#pragma unroll 1
      for (uint32_t mine = __ballot_sync(0xffffffffu, ((inmask >> lane) & 1) && (__popc(inmask & ((1u << lane) - 1)) & 3) == ww); mine; mine &= mine - 1) {
        const int j = __ffs(mine) - 1;
        uint32_t p[32];
        poll8x4(p, g_yp + (tn * 2 + (lane >> 4)) * 4096 + j * 64 + (lane & 15) * 4, par, 1u);
        float y[4];
        const float sj = __shfl_sync(0xffffffffu, sg, j);
#pragma unroll
        for (int i = 0; i < 4; i++)
          y[i] = sj * (((__uint_as_float(p[i]) + __uint_as_float(p[4 + i])) + (__uint_as_float(p[8 + i]) + __uint_as_float(p[12 + i]))) +
                       ((__uint_as_float(p[16 + i]) + __uint_as_float(p[20 + i])) + (__uint_as_float(p[24 + i]) + __uint_as_float(p[28 + i]))));
        asm volatile("st.shared.v2.u32 [%0], {%1,%2};" ::"r"(AUX + (lane >> 4) * 1024 + j * 128 + ((((lane >> 1) & 7) ^ j) << 4) + (lane & 1) * 8),
                     "r"(pack(y[0], y[1])), "r"(pack(y[2], y[3])) : "memory");
      }
    }
    fence_async_smem();
    nb_arrive(NB_ST, 288);
    STAMP_IF(t == 0, 15);
  } else if (w >= 4) {
    asm volatile("setmaxnreg.inc.sync.aligned.u32 208;");
    const int t = tid - 128, ww = w - 4, g = lane >> 2, t4 = lane & 3;
    const bool leader = t == 0;
    const uint32_t ep = ld_relaxed(&g_epoch) + 1, par = ep & 1u;
    {
      const uint4* wp = reinterpret_cast<const uint4*>(mp.w_r) + lane;
      uint4 w0 = __ldg(wp), w1 = __ldg(wp + 32), w2 = __ldg(wp + 64), w3 = __ldg(wp + 96);
      if (leader) sts32(S_EPOCH, ep);
      if (KV_SPEC && t4 == 0) {
        const int grp = (tm & 1) * 2 + ((lane >> 3) & 1), row = ww * 2 + ((lane >> 2) & 1);
        st_unit(g_kv + tn * 512 + ((tm >> 3) * 4 + grp) * 64 + row * 8 + (((tm & 2) * 2 + ((tm >> 1) & 2) + (lane >> 4)) ^ row), 0u, 0u, 0u, 0u, par ^ 1u);
      }
      float s[4] = {0.f, 0.f, 0.f, 0.f}, q[4] = {0.f, 0.f, 0.f, 0.f}, d[4] = {0.f, 0.f, 0.f, 0.f}, wsum = 0.f;
#pragma unroll 1
      for (int c = 0; c < 4; c++) {
        const float wr[8] = {bf_lo(w0.x), bf_hi(w0.x), bf_lo(w0.y), bf_hi(w0.y), bf_lo(w0.z), bf_hi(w0.z), bf_lo(w0.w), bf_hi(w0.w)};
        w0 = w1; w1 = w2; w2 = w3;
        wsum += ((wr[0] + wr[1]) + (wr[2] + wr[3])) + ((wr[4] + wr[5]) + (wr[6] + wr[7]));
        mbar_wait(B_XS + 8 * c, 0);
#pragma unroll
        for (int r = 0; r < 4; r++) {
          const uint4 v = lds128(STG + c * 8192 + (ww * 4 + r) * 512 + lane * 16);
          const uint32_t xw[4] = {v.x, v.y, v.z, v.w};
#pragma unroll
          for (int i = 0; i < 4; i++) {
            const uint32_t dep = __float_as_uint(q[i ? r : (r + 3) & 3]);
            const float lo = __uint_as_float(prmt(xw[i], dep, 0x10ff)), hi = __uint_as_float(prmt(xw[i], dep, 0x32ff));
            s[r] += lo; q[r] = fmaf(lo, lo, q[r]); d[r] = fmaf(lo, wr[2 * i], d[r]);
            s[r] += hi; q[r] = fmaf(hi, hi, q[r]); d[r] = fmaf(hi, wr[2 * i + 1], d[r]);
          }
        }
      }
      STAMP_IF(leader, 16);
      const bool u16 = lane & 16, u8 = lane & 8, u4 = lane & 4, u2 = lane & 2;
      const float s1 = xred(xred(s[0], s[2], u16, 16), xred(s[1], s[3], u16, 16), u8, 8);
      const float q1 = xred(xred(q[0], q[2], u16, 16), xred(q[1], q[3], u16, 16), u8, 8);
      const float d1 = xred(xred(d[0], d[2], u16, 16), xred(d[1], d[3], u16, 16), u8, 8);
      wsum += __shfl_xor_sync(0xffffffffu, wsum, 16);
      wsum += __shfl_xor_sync(0xffffffffu, wsum, 8);
      float tot = xred(xred(s1, d1, u4, 4), xred(q1, wsum, u4, 4), u2, 2);
      tot += __shfl_xor_sync(0xffffffffu, tot, 1);
      const float qq = __shfl_down_sync(0xffffffffu, tot, 2), dd = __shfl_down_sync(0xffffffffu, tot, 4), ws = __shfl_down_sync(0xffffffffu, tot, 6);
      if ((lane & 7) == 0) {
        const float mean = tot * (1.f / 1024.f);
        const float var = fmaxf(fmaf(-mean, mean, qq * (1.f / 1024.f)), 0.f);
        float sd;
        asm("sqrt.approx.ftz.f32 %0, %1;" : "=f"(sd) : "f"(bf_round(bf_round(var) + 1e-5f)));
        const uint32_t ms = pack(sd, mean);
        const int row = tm * 128 + tn * 16 + ww * 4 + (lane >> 3);
        const uint32_t rbits = pack(0.f, fmaf(-bf_hi(ms), ws, dd) * rcp(bf_lo(ms)));
        const uint32_t key = (rbits ^ (((int)rbits >> 31 & 0x7fff0000u) | 0x80000000u)) | ((2047 - row) << 5) | (ep & 31u);
        asm volatile("{\n.reg .b64 x;\nmov.b64 x, {%1,%2};\nst.relaxed.gpu.global.b64 [%0], x;\n}" ::"l"(g_keys + row), "r"(key), "r"(ms) : "memory");
      }
      STAMP_IF(leader, 17);
      __nanosleep(400);
      uint32_t st[2];
      poll_pair(st, g_keys + tm * 128 + t, ep, 31u);
      asm volatile("st.shared.v2.f32 [%0], {%1,%2};" ::"r"(S_KSTAT + t * 8), "f"(bf_hi(st[1])), "f"(rcp(bf_lo(st[1])) * LOG2E) : "memory");
      nb_arrive(NB_FDONE, 416);
      STAMP_IF(leader, 10);
    }
    float a0[64], a1[64];
    reg_zero(a0); reg_zero(a1); reg_fence(a0); reg_fence(a1);
    STAMP_IF(leader, 18);
    nb_sync(NB_KV, 256);
    mainloop<true, 14>(a0, a1, 1, 1, 0, 0, leader);
    {
      auto half = [&](float (&a)[64], int s, int m) {
#pragma unroll
        for (int j = 0; j < 4; j++)
          wgmma_n128_ss<1, 0>(a, mkdesc(RING + s * SLOT + m * 8192 + j * 2048, 8192, 1024, 1), mkdesc(RING + s * SLOT + 16384 + j * 32, 16, 1024, 1), 1);
      };
      auto kvmma = [&](float (&a)[64], float (&c)[32], int m) {
        reg_fence(a);
        uint32_t f[32];
#pragma unroll
        for (int i = 0; i < 32; i++) f[i] = pack(a[2 * i], a[2 * i + 1]);
        reg_zero(c);
        wg_fence();
#pragma unroll
        for (int k = 0; k < 8; k++) {
          wgmma_n64_rs<0>(c, f[4 * k], f[4 * k + 1], f[4 * k + 2], f[4 * k + 3], mkdesc(STG + (k >> 2) * 16384 + m * 8192 + (k & 3) * 32, 16, 1024, 1), k != 0);
          if (m && k == HAND_K) nb_arrive(NB_VQ, 256);
        }
        wg_commit();
      };
      float c0[32], c1[32];
      mbar_wait(B_FULL, 0);
      wg_fence();
      half(a0, 0, 0);
      wg_commit();
      mbar_wait(B_FULL + 8, 0);
      wg_fence();
      half(a0, 1, 0);
      wg_commit();
      wg_wait<2>();
      if (leader) mbar_arrive(B_EMPTY + 32);
      wg_fence();
      half(a1, 0, 1);
      half(a1, 1, 1);
      wg_commit();
      nb_sync(NB_WG0, 256);
      wg_wait<1>();
      kvmma(a0, c0, 0);
      nb_sync(NB_PK, 256);
      wg_wait<1>();
      if (leader) { mbar_arrive(B_EMPTY); mbar_arrive(B_EMPTY + 8); }
      STAMP_IF(leader, 19);
      kvmma(a1, c1, 1);
      const bool hp = ww >> 1;
      float c[4];
      float2 tt[8];
#pragma unroll
      for (int i = 0; i < 8; i++) tt[i] = lds64f(S_CSK + ((i >> 2) * 64 + hp * 32 + (i & 3) * 8 + 2 * t4) * 4);
      mbar_wait(B_CSV, 0);
#pragma unroll
      for (int i = 0; i < 4; i++) c[i] = -__uint_as_float(lds32(S_CSV + ((i >> 1) * 64 + ww * 16 + (i & 1) * 8 + g) * 4));
      wg_wait<0>();
      reg_fence(c0);
      reg_fence(c1);
      if (leader) mbar_arrive(B_SFREE);
      STAMP_IF(leader, 20);
      uint4* pp = g_kvp + (tn * 16 + tm) * 512 + t;
      auto put = [&](int q, const float* d) {
        const float ca = c[q & 2], cb = c[q | 1];
        const float2 ta = tt[2 * q], tb = tt[2 * q + 1];
        st_unit(pp + q * 128, pack(fmaf(ca, ta.x, d[0]), fmaf(ca, ta.y, d[1])), pack(fmaf(cb, ta.x, d[2]), fmaf(cb, ta.y, d[3])),
                pack(fmaf(ca, tb.x, d[4]), fmaf(ca, tb.y, d[5])), pack(fmaf(cb, tb.x, d[6]), fmaf(cb, tb.y, d[7])), par);
      };
      if (!hp) { put(0, c0); put(1, c0 + 8); put(2, c1); put(3, c1 + 8); }
      else { put(0, c0 + 16); put(1, c0 + 24); put(2, c1 + 16); put(3, c1 + 24); }
      STAMP_IF(leader, 47);
      {
        uint32_t p[16];
        nb_sync(NB_WG1, 128);
        if (ww == 0) { e_signal(H_KVP + tn, tm); await(H_KVP + tn, 0xffffu, ep); }
        nb_sync(NB_WG1, 128);
        STAMP_IF(leader, 1);
        poll_kvp(p, g_kvp + (tn * 16 + (lane >> 3) * 4) * 512 + tm * 32 + ww * 8 + (lane & 7), par, 1u);
        float r[8];
#pragma unroll
        for (int i = 0; i < 4; i++) {
          r[2 * i] = (bf_lo(p[i]) + bf_lo(p[4 + i])) + (bf_lo(p[8 + i]) + bf_lo(p[12 + i]));
          r[2 * i + 1] = (bf_hi(p[i]) + bf_hi(p[4 + i])) + (bf_hi(p[8 + i]) + bf_hi(p[12 + i]));
        }
        const bool u16 = lane & 16, u8 = lane & 8;
        const uint32_t wd = pack(xred(xred(r[0], r[4], u16, 16), xred(r[2], r[6], u16, 16), u8, 8), xred(xred(r[1], r[5], u16, 16), xred(r[3], r[7], u16, 16), u8, 8));
        const uint32_t w1 = __shfl_down_sync(0xffffffffu, wd, 1), w2 = __shfl_down_sync(0xffffffffu, wd, 2), w3 = __shfl_down_sync(0xffffffffu, wd, 3);
        const int grp = (tm & 1) * 2 + ((lane >> 3) & 1), row = ww * 2 + ((lane >> 2) & 1);
        if (t4 == 0) st_unit(g_kv + tn * 512 + ((tm >> 3) * 4 + grp) * 64 + row * 8 + (((tm & 2) * 2 + ((tm >> 1) & 2) + (lane >> 4)) ^ row), wd, w1, w2, w3, par);
        nb_sync(NB_WG1, 128);
        if (ww == 0) { if (!KV_SPEC) e_signal(H_KV + tn, tm); e_arrive(B_WK); }
      }
      STAMP_IF(leader, 21);
    }
    const uint32_t sx = lane & 7, sc = lane >> 4;
    const uint32_t sa = STG + (ww * 16 + (lane & 15)) * 128;
    const uint32_t sw[4] = {sa + ((sc ^ sx) << 4), sa + (((2 + sc) ^ sx) << 4), sa + (((4 + sc) ^ sx) << 4), sa + (((6 + sc) ^ sx) << 4)};
    auto residual = [&]() {
      float ka[4], kb[4];
#pragma unroll
      for (int i = 0; i < 4; i++) {
        const float2 st = lds64f(S_KSTAT + ((i >> 1) * 64 + ww * 16 + (i & 1) * 8 + g) * 8);
        const float r = st.y * LN2;
        ka[i] = 1.f + r; kb[i] = -st.x * r;
      }
#pragma unroll
      for (int j = 0; j < 8; j++) {
        if ((j & 3) == 0) mbar_wait(B_XRES + 8 * (j >> 2), 0);
        const uint4 v = ldsm4(sw[j & 3] + (j >> 2) * 16384), u = ldsm4(sw[j & 3] + (j >> 2) * 16384 + 8192);
        const uint32_t vv[4] = {v.x, v.y, v.z, v.w}, uu[4] = {u.x, u.y, u.z, u.w};
#pragma unroll
        for (int i = 0; i < 4; i++) {
          a0[8 * j + 2 * i] = fmaf(bf_lo(vv[i]), ka[i & 1], kb[i & 1]);
          a0[8 * j + 2 * i + 1] = fmaf(bf_hi(vv[i]), ka[i & 1], kb[i & 1]);
          a1[8 * j + 2 * i] = fmaf(bf_lo(uu[i]), ka[2 + (i & 1)], kb[2 + (i & 1)]);
          a1[8 * j + 2 * i + 1] = fmaf(bf_hi(uu[i]), ka[2 + (i & 1)], kb[2 + (i & 1)]);
        }
      }
      reg_fence(a0);
      reg_fence(a1);
      STAMP_IF(leader, 22);
    };
    residual();
    nb_arrive(NB_KVB, 320);
    uint32_t oh[4];
    {
      mbar_wait(B_SEL, 0);
      const int r0 = key_token(lds32(S_SEL + t4 * 16)) - tm * 128, r1 = key_token(lds32(S_SEL + t4 * 16 + 8)) - tm * 128;
#pragma unroll
      for (int i = 0; i < 4; i++) {
        const int row = (i >> 1) * 64 + ww * 16 + (i & 1) * 8 + g;
        oh[i] = (r0 == row ? 0x3f00u : 0u) | (r1 == row ? 0x3f000000u : 0u);
      }
    }
    uint32_t va = RING + 16384 + sc * 8192 + (ww * 16 + (lane & 8)) * 128 + sx * 16 + (lane >> 3) * 4;
    asm volatile("" : "+r"(va));
    {
      auto own = [&](int r) {
        nb_sync(r ? NB_OWN1 : NB_Y, 256);
        mbar_wait(B_FULL + 8 * (3 + r), 1);
        STAMP_IF(leader, 25 + r);
        const uint64_t dw = mkdesc(RING + (3 + r) * SLOT, 8192, 1024, 1), dx = mkdesc(STG + r * 16384, 16, 1024, 1);
        wg_fence();
#pragma unroll
        for (int j = 0; j < 4; j++) {
          wgmma_n128_ss<0, 1>(a0, dx + j * 2, dw + j * 128, 1);
          wgmma_n128_ss<0, 1>(a1, dx + j * 2 + 512, dw + j * 128, 1);
        }
        wg_commit();
      };
      own(0);
      if (REL0) wg_wait<0>();
      if (REL0 && leader) mbar_arrive(B_EMPTY + 24);
      own(1);
      if (!REL0) wg_wait<1>();
      if (!REL0 && leader) mbar_arrive(B_EMPTY + 24);
      auto check = [&](int r, int s) {
          uint32_t bad;
          asm volatile("{\n.reg .u32 a, b, c, d, e, f, g, h;\n.reg .pred p;\n"
                       "ld.shared.u32 a, [%1];\nld.shared.u32 b, [%1+128];\nld.shared.u32 c, [%1+256];\nld.shared.u32 d, [%1+384];\n"
                       "ld.shared.u32 e, [%1+512];\nld.shared.u32 f, [%1+640];\nld.shared.u32 g, [%1+768];\nld.shared.u32 h, [%1+896];\n"
                       "lop3.b32 a, a, b, %2, 0x7e;\nlop3.b32 c, c, d, %2, 0x7e;\nlop3.b32 e, e, f, %2, 0x7e;\nlop3.b32 g, g, h, %2, 0x7e;\n"
                       "lop3.b32 a, a, c, e, 0xfe;\nlop3.b32 a, a, g, 1, 0xa8;\nsetp.ne.u32 p, a, 0;\nvote.sync.any.pred p, p, 0xffffffff;\nselp.u32 %0, 1, 0, p;\n}"
                       : "=r"(bad) : "r"(va + s * SLOT), "r"(par) : "memory");
          if (__builtin_expect(bad, 0)) {
            const uint4* src = reinterpret_cast<const uint4*>(g_o + (tm * 128 + sc * 64 + ww * 16 + (lane & 15)) * 1024 + out_kblock(r, tn) * 64);
#pragma unroll 1
            for (int i = 0; i < 8; i++) {
              uint32_t v[4];
              asm volatile("{\n.reg .b64 x, y;\n.reg .b128 z;\n.reg .pred p, q, h;\n.reg .u32 c, b;\nmov.u32 c, 0;\nsetp.ne.u32 h, %6, 0;\nLW:\n"
                           "ld.relaxed.gpu.global.b128 z, [%4];\nmov.b128 {x, y}, z;\nmov.b64 {%0,%1}, x;\nmov.b64 {%2,%3}, y;\n"
                           "selp.b64 x, y, x, h;\nshr.b64 x, x, %7;\ncvt.u32.u64 b, x;\nand.b32 b, b, 1;\nsetp.eq.u32 p, b, %5;\n"
                           "vote.sync.all.pred p, p, 0xffffffff;\n@p bra.uni LD;\nadd.u32 c, c, 1;\nsetp.lt.u32 q, c, 1000000;\n@q bra.uni LW;\ntrap;\nLD:\n}"
                           : "=&r"(v[0]), "=&r"(v[1]), "=&r"(v[2]), "=&r"(v[3]) : "l"(src + i), "r"(par), "r"(sc), "r"((lane & 8) * 4) : "memory");
              sts128(RING + 16384 + s * SLOT + sc * 8192 + (ww * 16 + (lane & 15)) * 128 + ((i ^ sx) << 4), v[0], v[1], v[2], v[3]);
            }
            fence_async_smem();
            __syncwarp();
          }
      };
      int s = 0, ph = 0;
      uint32_t prev = B_EMPTY + 32;
#pragma unroll 1
      for (int r = 2; r < 12; r++) {
        mbar_wait(B_FULL + 8 * s, ph);
        check(r, s);
        if (!LITE || ((LITE_MASK >> 27) & 1)) STAMP_IF(leader && r == 2, 27);
        const uint64_t dw = mkdesc(RING, 8192, 1024, 1) + s * (SLOT >> 4), dx = mkdesc(RING + 16384, 16, 1024, 1) + s * (SLOT >> 4);
        wg_fence();
#pragma unroll
        for (int j = 0; j < 4; j++) {
          wgmma_n128_ss<0, 1>(a0, dx + j * 2, dw + j * 128, 1);
          wgmma_n128_ss<0, 1>(a1, dx + j * 2 + 512, dw + j * 128, 1);
        }
        wg_commit();
        wg_wait<1>();
        if (leader) mbar_arrive(prev);
        prev = B_EMPTY + 8 * s;
        if (++s == NST) { s = 0; ph ^= 1; }
      }
      auto half = [&](float (&a)[64], int s, int m) {
        const uint64_t dw = mkdesc(RING, 8192, 1024, 1) + s * (SLOT >> 4), dx = mkdesc(RING + 16384 + m * 8192, 16, 1024, 1) + s * (SLOT >> 4);
#pragma unroll
        for (int j = 0; j < 4; j++) wgmma_n128_ss<0, 1>(a, dx + j * 2, dw + j * 128, 1);
      };
      auto store = [&](float (&a)[64], int m, int c) {
#pragma unroll
        for (int i = 0; i < 32; i++) asm volatile("" : "+f"(a[32 * c + i])::"memory");
#pragma unroll
        for (int j = 4 * c; j < 4 * c + 4; j++)
          stsm4(sw[j & 3] + c * 16384 + m * 8192, pack(a[8 * j], a[8 * j + 1]), pack(a[8 * j + 2], a[8 * j + 3]), pack(a[8 * j + 4], a[8 * j + 5]), pack(a[8 * j + 6], a[8 * j + 7]));
        fence_async_smem();
        e_store2d(&mp.m_out, tn * 128 + c * 64, tm * 128 + m * 64 + ww * 16, STG + c * 16384 + m * 8192 + ww * 2048);
      };
#pragma unroll 1
      for (int q = 0; q < 4; q++) {
        mbar_wait(B_FULL + 8 * q, 0);
        check(12 + q, q);
        wg_fence();
        half(a0, q, 0);
        wg_commit();
      }
      nb_sync(NB_ST, 288);
      wg_fence();
      wgmma_n128_rs<1>(a0, oh[0], oh[1], oh[0], oh[1], mkdesc(AUX, 1024, 0, 1), 1);
      wg_commit();
      wg_fence();
      half(a1, 0, 1);
      half(a1, 1, 1);
      wg_commit();
      wg_wait<1>();
      store(a0, 0, 0);
      store(a0, 0, 1);
      wg_fence();
      half(a1, 2, 1);
      half(a1, 3, 1);
      wgmma_n128_rs<1>(a1, oh[2], oh[3], oh[2], oh[3], mkdesc(AUX, 1024, 0, 1), 1);
      wg_commit();
      wg_wait<0>();
      STAMP_IF(leader, 28);
      store(a1, 1, 0);
      store(a1, 1, 1);
    }
    bulk_wait_read();
    if (bid == 0 && leader) st_relaxed(&g_epoch, ep);
    STAMP_IF(leader, 29);
  } else {
    asm volatile("setmaxnreg.inc.sync.aligned.u32 216;");
    const int g = lane >> 2, t4 = lane & 3;
    const bool leader = tid == 0;
    const uint32_t sx = lane & 7, sc = lane >> 4;
    const uint32_t sa = STG + (w * 16 + (lane & 15)) * 128;
    const uint32_t sw[4] = {sa + ((sc ^ sx) << 4), sa + (((2 + sc) ^ sx) << 4), sa + (((4 + sc) ^ sx) << 4), sa + (((6 + sc) ^ sx) << 4)};
    float a0[64], a1[64];
    reg_zero(a0); reg_zero(a1); reg_fence(a0); reg_fence(a1);
    mainloop<true>(a0, a1, 0, 0, NB_KV, 0, leader);
    STAMP_IF(leader, 33);
    {
      nb_sync(NB_FDONE, 416);
      STAMP_IF(leader, 34);
      const uint32_t par = lds32(S_EPOCH) & 1u;
#pragma unroll 1
      for (int m = 0;; m++) {
        const uint32_t ca = S_CSK + (m * 64 + w * 16 + g) * 4;
        const float c[2] = {-lds32v(ca), -lds32v(ca + 32)};
        float z[2] = {0.f, 0.f}, tt[2] = {0.f, 0.f};
        float4 n0, n1;
        if (KPF) { n0 = lds128v(S_KSTAT + 2 * t4 * 8); n1 = lds128v(S_KSTAT + (8 + 2 * t4) * 8); }
#pragma unroll
        for (int j = 0; j < 8; j++) {
          if (!KPF) { n0 = lds128v(S_KSTAT + (j * 16 + 2 * t4) * 8); n1 = lds128v(S_KSTAT + (j * 16 + 8 + 2 * t4) * 8); }
          const float mu[4] = {n0.x, n0.z, n1.x, n1.z}, rl[4] = {n0.y, n0.w, n1.y, n1.w};
          if (KPF && j < 7) { n0 = lds128v(S_KSTAT + (j * 16 + 16 + 2 * t4) * 8); n1 = lds128v(S_KSTAT + (j * 16 + 24 + 2 * t4) * 8); }
          float p[8];
#pragma unroll
          for (int i = 0; i < 8; i++) {
            const int r = (i >> 1) & 1, cc = (i >> 2) * 2 + (i & 1);
            p[i] = phi2(fmaf(c[r], mu[cc], a0[8 * j + i]) * rl[cc]);
            z[r] += p[i];
            p[i] *= rl[cc];
            tt[r] = fmaf(p[i], mu[cc], tt[r]);
          }
          stsm4(sw[j & 3] + (j >> 2) * 16384 + m * 8192, pack(p[0], p[1]), pack(p[2], p[3]), pack(p[4], p[5]), pack(p[6], p[7]));
        }
        const bool u2 = lane & 2, u1 = lane & 1;
        const float v = xred(xred(z[0], tt[0], u2, 2), xred(z[1], tt[1], u2, 2), u1, 1);
        if (u2) sts32(ca + (t4 & 1) * 32, __float_as_uint(v));
        else st_relaxed(g_z + tm * 1024 + tn * 128 + m * 64 + w * 16 + t4 * 8 + g, tagf(v * LOG2E, par));
        if (m) break;
        fence_async_smem();
        nb_arrive(NB_WG0, 256);
#pragma unroll
        for (int i = 0; i < 64; i++) a0[i] = a1[i];
      }
      fence_async_smem();
      nb_arrive(NB_PK, 256);
      nb_arrive(NB_Z, 160);
    }
    STAMP_IF(leader, 35);
    const uint32_t ep = lds32(S_EPOCH);
    uint32_t sd2[4];
    float es[4];
    {
      nb_sync(NB_CSQ, 160);
      float mu[4];
#pragma unroll
      for (int i = 0; i < 4; i++) {
        const float2 st = lds64f(S_KSTAT + ((i >> 1) * 64 + w * 16 + (i & 1) * 8 + g) * 8);
        mu[i] = -st.x;
        const float sd = LOG2E * rcp(st.y);
        sd2[i] = pack(sd, sd);
        es[i] = sd * (1e-6f * LOG2E);
      }
#pragma unroll
      for (int j = 0; j < 16; j++) {
        const float2 c = lds64f(S_CSQ + (j * 8 + 2 * t4) * 4);
        a0[4 * j] = mu[0] * c.x; a0[4 * j + 1] = mu[0] * c.y; a0[4 * j + 2] = mu[1] * c.x; a0[4 * j + 3] = mu[1] * c.y;
        a1[4 * j] = mu[2] * c.x; a1[4 * j + 1] = mu[2] * c.y; a1[4 * j + 2] = mu[3] * c.x; a1[4 * j + 3] = mu[3] * c.y;
      }
      reg_fence(a0); reg_fence(a1);
    }
    STAMP_IF(leader, 40);
    nb_sync(NB_VQ, 256);
    mainloop<false, 13>(a0, a1, 2, 0, 0, 4 + (tn & 3), leader);
    {
      uint32_t f[2][16];
      const uint32_t ra = S_KSTAT + (w * 16 + g) * 8 + 4;
      auto phi = [&](const float (&a)[64], int off, int m, int i0, int i1, uint32_t (&o)[16]) {
        const float r0 = lds32v(ra + m * 512), r1 = lds32v(ra + m * 512 + 64);
#pragma unroll
        for (int i = i0; i < i1; i++) o[i] = phi_pack(a[off + 2 * i], a[off + 2 * i + 1], i & 1 ? r1 : r0, sd2[2 * m + (i & 1)]);
      };
      auto half = [&](float (&a)[64], int s, int m) {
        const bool xr = ((13 + s) >> 1) == 4 + (tn & 3);
        if (!m) {
          mbar_wait(B_FULL + 8 * s, 1);
          if (xr) mbar_wait(B_XRES + 8 * (~s & 1), 0);
          wg_fence();
        }
        const uint64_t dx = mkdesc(m * 8192, 16, 1024, 1) + ((xr ? STG + (~s & 1) * 16384 : RING + s * SLOT + 16384) >> 4);
#pragma unroll
        for (int j = 0; j < 4; j++) wgmma_n128_ss<0, 1>(a, dx + j * 2, mkdesc(RING + s * SLOT + j * 2048, 8192, 1024, 1), 1);
      };
      half(a0, 0, 0);
      wg_commit();
      half(a0, 1, 0);
      wg_commit();
      wg_wait<2>();
      if (leader) mbar_arrive(B_EMPTY + 32);
      half(a0, 2, 0);
      wg_commit();
      wg_fence();
      half(a1, 0, 1);
      half(a1, 1, 1);
      wg_commit();
      wg_wait<1>();
      reg_fence(a0);
      phi(a0, 0, 0, 0, PHI_CUT, f[0]);
      wg_fence();
      half(a1, 2, 1);
      wg_commit();
      phi(a0, 0, 0, PHI_CUT, 16, f[0]);
      nb_sync(NB_KVB, 320);
      wg_wait<0>();
      if (leader) { mbar_arrive(B_EMPTY); mbar_arrive(B_EMPTY + 8); mbar_arrive(B_EMPTY + 16); }
      reg_fence(a1);
      STAMP_IF(leader, 36);
      const uint32_t mk[4] = {t4 == 0, t4 == 1, t4 == 2, t4 == 3};
      uint64_t db = mkdesc(KVB, 16, 1024, 1);
      uint32_t so = 0;
#pragma unroll 1
      for (int j = 0;; j++) {
        float oc[2][2][20];
        auto mma = [&](const uint32_t (&a)[16], float (&o)[2][20]) {
          reg_zero(o[0]); reg_zero(o[1]);
          wg_fence();
          wgmma_n40_rs<0>(o[0], a[0], a[1], a[2], a[3], db, 0);
          wgmma_n40_rs<0>(o[1], a[8], a[9], a[10], a[11], db + 4, 0);
          wgmma_n40_rs<0>(o[0], a[4], a[5], a[6], a[7], db + 2, 1);
          wgmma_n40_rs<0>(o[1], a[12], a[13], a[14], a[15], db + 6, 1);
          wg_commit();
        };
        auto fin = [&](int m, float (&o)[2][20]) {
          const uint32_t m0 = mk[2 * m], m1 = mk[2 * m + 1];
#pragma unroll
          for (int h = 0; h < 2; h++) {
            const float r0 = rcp(o[h][0] + es[2 * m]), r1 = rcp(o[h][2] + es[2 * m + 1]);
            {
#pragma unroll
              for (int q = 0; q < 2; q++)
                stsm4(sw[h * 2 + q] + so + m * 8192,
                      bsel(pack(o[h][4 + 8 * q] * r0, o[h][5 + 8 * q] * r0), ep, m0), bsel(pack(o[h][6 + 8 * q] * r1, o[h][7 + 8 * q] * r1), ep, m1),
                      bsel(pack(o[h][8 + 8 * q] * r0, o[h][9 + 8 * q] * r0), ep, m0), bsel(pack(o[h][10 + 8 * q] * r1, o[h][11 + 8 * q] * r1), ep, m1));
            }
          }
        };
        mma(f[0], oc[0]);
        if (j) nb_arrive(NB_Y, 256);
        phi(a1, 0, 1, 0, 16, f[1]);
        wg_wait<0>();
        reg_fence(oc[0][0]); reg_fence(oc[0][1]);
        mma(f[1], oc[1]);
        fin(0, oc[0]);
        if (j == 0) { fence_async_smem(); nb_arrive(NB_Q0, 192); }
        wg_wait<0>();
        reg_fence(oc[1][0]); reg_fence(oc[1][1]);
        fin(1, oc[1]);
        fence_async_smem();
        if (j) break;
        nb_arrive(NB_OWN0, 160);
        STAMP_IF(leader, 38);
#pragma unroll
        for (int i = 0; i < 32; i++) a1[i] = a1[32 + i];
        phi(a0, 32, 0, 0, 16, f[0]);
        db = mkdesc(KVB + 5120, 16, 1024, 1);
        so = 16384;
      }
      nb_arrive(NB_OWN1, 256);
      nb_arrive(NB_H1, 160);
      STAMP_IF(leader, 39);
    }
  }
}

#undef CK
typedef CUresult (*EncodeFn)(CUtensorMap*, CUtensorMapDataType, cuuint32_t, void*, const cuuint64_t*, const cuuint64_t*, const cuuint32_t*,
                             const cuuint32_t*, CUtensorMapInterleave, CUtensorMapSwizzle, CUtensorMapL2promotion, CUtensorMapFloatOOBfill);

void make_map(EncodeFn enc, CUtensorMap* m, const void* p, int rank, uint64_t d0, uint64_t d1, uint64_t d2, uint64_t s1, uint64_t s2,
              uint32_t b0, uint32_t b1, uint32_t b2, CUtensorMapSwizzle sw) {
  cuuint64_t gd[3] = {d0, d1, d2}, gs[2] = {s1, s2};
  cuuint32_t bd[3] = {b0, b1, b2}, es[3] = {1, 1, 1};
  enc(m, CU_TENSOR_MAP_DATA_TYPE_BFLOAT16, rank, const_cast<void*>(p), gd, gs, bd, es, CU_TENSOR_MAP_INTERLEAVE_NONE, sw,
      CU_TENSOR_MAP_L2_PROMOTION_L2_128B, CU_TENSOR_MAP_FLOAT_OOB_FILL_NONE);
}

}

extern "C" void kernel_launch(void* const* d_in, const int* in_sizes, int n_in, void* d_out, int out_size) {
  (void)in_sizes; (void)n_in; (void)out_size;
  void* fn = nullptr;
  cudaDriverEntryPointQueryResult qr;
  cudaGetDriverEntryPoint("cuTensorMapEncodeTiled", &fn, cudaEnableDefault, &qr);
  EncodeFn enc = (EncodeFn)fn;
  void* o;
  cudaGetSymbolAddress(&o, g_o);
  const CUtensorMapSwizzle S128 = CU_TENSOR_MAP_SWIZZLE_128B, S64 = CU_TENSOR_MAP_SWIZZLE_64B, S0 = CU_TENSOR_MAP_SWIZZLE_NONE;
  Params mp;
  mp.x = (const char*)d_in[0]; mp.w_r = (const char*)d_in[4];
  mp.wg = (const char*)d_in[5]; mp.wu = (const char*)d_in[6]; mp.wd = (const char*)d_in[7];
  make_map(enc, &mp.m_wqkv, d_in[1], 3, 64, 1024, 48, 6144, 128, 64, 64, 2, S128);
  make_map(enc, &mp.m_x, d_in[0], 2, 1024, 2048, 1, 2048, 0, 64, 128, 1, S128);
  make_map(enc, &mp.m_os, o, 2, 1024, 2048, 1, 2048, 0, 64, 64, 1, S128);
  make_map(enc, &mp.m_os2, o, 2, 1024, 2048, 1, 2048, 0, 64, ST_ROWS, 1, S128);
  make_map(enc, &mp.m_o, o, 2, 1024, 2048, 1, 2048, 0, 64, 128, 1, S128);
  make_map(enc, &mp.m_wo, d_in[2], 3, 64, 1024, 16, 2048, 128, 64, 64, 2, S128);
  make_map(enc, &mp.m_xs, d_in[0], 2, 1024, 2048, 1, 2048, 0, 256, 16, 1, S0);
  const char *wg = (const char*)d_in[5], *wu = (const char*)d_in[6];
  make_map(enc, &mp.m_gu, wu < wg ? wu : wg, 3, 3584, 1024, 2, 7168, (uint64_t)(wu < wg ? wg - wu : wu - wg), 32, 64, 2, S64);
  make_map(enc, &mp.m_down, d_in[7], 2, 1024, 3584, 1, 2048, 0, 64, 64, 1, S128);
  make_map(enc, &mp.m_out, d_out, 2, 1024, 2048, 1, 2048, 0, 64, 16, 1, S128);
  int dev = 0, sms = 0;
  cudaGetDevice(&dev);
  cudaDeviceGetAttribute(&sms, cudaDevAttrMultiProcessorCount, dev);
  auto kern = sms == 132 ? fused_kernel<true> : fused_kernel<false>;
  cudaFuncSetAttribute(kern, cudaFuncAttributeMaxDynamicSharedMemorySize, SMEM_BYTES);
  kern<<<132, 512, SMEM_BYTES>>>(mp);
}
```
